```python
import torch

def _softmax(x, axis=-1):
    return torch.softmax(x, dim=axis)

def _gelu(x):
    return torch.nn.functional.gelu(x, approximate='tanh')

def _silu(x):
    return torch.nn.functional.silu(x)

def _sigmoid(x):
    return torch.sigmoid(x)

def _layernorm(x, axis=-1, eps=1e-05):
    m = x.mean(dim=axis, keepdim=True)
    v = x.var(dim=axis, keepdim=True, unbiased=False)
    return (x - m) / torch.sqrt(v + eps)

def _scatter_add(tgt, idx, src, axis=0):
    return tgt.clone().index_add_(axis, idx, src)

def _segment_sum(src, seg, n):
    out = torch.zeros((n,) + src.shape[1:], dtype=src.dtype)
    return out.index_add_(0, seg, src)

def _pad(x, pw):
    flat = tuple((v for pair in reversed(pw) for v in pair))
    return torch.nn.functional.pad(x, flat)
kernel_name = 'adaLN_cond__compressed_kv_cla__moe_arch_mod__prompt'

def setup_inputs():

    _w = lambda a: (lambda t: t.to(torch.bfloat16) if t.is_floating_point() else t)(torch.as_tensor(a))

    def _A_setup():
        B, H, Sq, Sk, D, M = (1, 32, 2048, 2048, 128, 512)
        Dc = 4 * D
        return {'x': _w((lambda *s: torch.randn(*s, dtype=torch.bfloat16) * 0.1)(B, Sq, M)), 'c_kv': _w((lambda *s: torch.randn(*s, dtype=torch.bfloat16) * 3.2)(B, Sk, Dc)), 'w_q': _w((lambda *s: torch.randn(*s, dtype=torch.bfloat16) * 0.8)(M, H, D) * M ** (-0.5)), 'w_uk': _w((lambda *s: torch.randn(*s, dtype=torch.bfloat16) * 0.8)(Dc, H, D) * Dc ** (-0.5)), 'w_uv': _w((lambda *s: torch.randn(*s, dtype=torch.bfloat16) * 3.2)(Dc, H, D) * Dc ** (-0.5)), 'w_o': _w((lambda *s: torch.randn(*s, dtype=torch.bfloat16) * 3.2)(H, D, M) * (H * D) ** (-0.5))}
    _A_in = _A_setup()

    def _B_setup():
        B, S, D, F, C = (1, 2048, 512, 1792, 1)
        return {'x': _w((lambda *s: torch.randn(*s, dtype=torch.bfloat16) * 0.1)(B, S, D)), 'w_r': _w((lambda *s: torch.randn(*s, dtype=torch.bfloat16) * 3.2)(D)), 'w_gate': _w((lambda *s: torch.randn(*s, dtype=torch.bfloat16) * 3.2)(D, F)), 'w_up': _w((lambda *s: torch.randn(*s, dtype=torch.bfloat16) * 3.2)(D, F)), 'w_down': _w((lambda *s: torch.randn(*s, dtype=torch.bfloat16) * 3.2)(F, D))}
    _B_in = _B_setup()
    return {'A_x': _A_in['x'], 'A_c_kv': _A_in['c_kv'], 'A_w_q': _A_in['w_q'], 'A_w_uk': _A_in['w_uk'], 'A_w_uv': _A_in['w_uv'], 'A_w_o': _A_in['w_o'], 'B_x': _B_in['x'], 'B_w_r': _B_in['w_r'], 'B_w_gate': _B_in['w_gate'], 'B_w_up': _B_in['w_up'], 'B_w_down': _B_in['w_down'], 'c': _w((lambda *s: torch.randn(*s, dtype=torch.bfloat16) * 0.2)(1, 512) * 8.0), 'w_mod': _w((lambda *s: torch.randn(*s, dtype=torch.bfloat16) * 0.2)(512, 6 * 512) * 512 ** (-0.5) * 8.0)}

def reference(A_x, A_c_kv, A_w_q, A_w_uk, A_w_uv, A_w_o, B_x, B_w_r, B_w_gate, B_w_up, B_w_down, c, w_mod):

    def _A_ref(x, c_kv, w_q, w_uk, w_uv, w_o):
        B, Sq, M = (x.shape[0], x.shape[1], x.shape[2])
        Sk = c_kv.shape[1]
        H, D = (w_q.shape[1], w_q.shape[2])
        q = torch.einsum('bqm,mhd->bhqd', x, w_q)
        k = torch.einsum('bkc,chd->bhkd', c_kv, w_uk)
        v = torch.einsum('bkc,chd->bhkd', c_kv, w_uv)
        scores = torch.einsum('bhqd,bhkd->bhqk', q, k) * D ** (-0.5)
        off = Sk - Sq
        qi = torch.arange(Sq)[:, None]
        kj = torch.arange(Sk)[None, :]
        cmask = kj <= qi + off
        scores = torch.where(cmask[None, None], scores, -1000000000.0)
        p = _softmax(scores, axis=-1)
        ctx = torch.einsum('bhqk,bhkd->bhqd', p, v)
        return torch.einsum('bhqd,hdm->bqm', ctx, w_o)

    def _B_ref(x, w_r, w_gate, w_up, w_down):
        B, S, D = x.shape
        C = 1
        r = x @ w_r
        idx = torch.argsort(-r, axis=-1)[:, :C]
        idx_e = (lambda x, n, axis: torch.repeat_interleave(x, n, dim=axis))(idx.reshape(B, C, 1), D, axis=2)
        x_sel = (lambda x, i, axis: torch.take_along_dim(x, i, dim=axis))(x, idx_e, axis=1)
        g = _silu(x_sel @ w_gate)
        u = x_sel @ w_up
        y = g * u @ w_down
        r_sel = _sigmoid((lambda x, i, axis: torch.take_along_dim(x, i, dim=axis))(r, idx, axis=1))
        y = y * r_sel.reshape(B, C, 1)
        b_off = (torch.arange(B) * S).reshape(B, 1)
        flat_idx = (idx + b_off).reshape(B * C)
        zero = (x * 0.0).reshape(B * S, D)
        upd = _scatter_add(zero, flat_idx, y.reshape(B * C, D), axis=0)
        return x + upd.reshape(B, S, D)
    x = A_x
    mod = (_silu(c) @ w_mod).reshape(c.shape[0], 6, 1, -1)
    sa, ca, ga, sb, cb, gb = (mod[:, 0].clone(), mod[:, 1].clone(), mod[:, 2].clone(), mod[:, 3].clone(), mod[:, 4].clone(), mod[:, 5].clone())
    h = _layernorm(x, axis=-1) * (1 + ca) + sa
    x = x + ga * _A_ref(h, A_c_kv, A_w_q, A_w_uk, A_w_uv, A_w_o)
    h = _layernorm(x, axis=-1) * (1 + cb) + sb
    x = x + gb * _B_ref(h, B_w_r, B_w_gate, B_w_up, B_w_down)
    return x
```

```cpp
#include <cuda_runtime.h>
#include <cuda_bf16.h>
#include <cuda.h>
#include <stdint.h>
#include <string.h>
#include <math.h>

namespace {

constexpr int SEQ = 2048, DM = 512, NH = 32, DH = 128, FF = 1792;
constexpr int NCTA = 128, NGRID = 132;

__device__ __nv_bfloat16 g_kvc[192 * SEQ * 64];
__device__ __nv_bfloat16 g_h1[SEQ * DM];
__device__ __nv_bfloat16 g_part[32 * SEQ * 64];
__device__ __align__(16) __nv_bfloat16 g_mod[6 * DM];
constexpr int C_MOD = 0, C_MOD2 = 16, C_H1 = 32, C_KV = 64, C_CTX = 128, C_PART = 384, C_END = C_PART + 32 * 32;
__device__ unsigned int g_cnt[C_END];
__device__ unsigned int g_epoch;
__device__ __align__(16) uint2 g_keys[128];
__device__ __align__(16) uint2 g_row[128][2][DM / 2];
__device__ __align__(16) uint2 g_yll[FF / 16][DM];

#define DBG(i)
#define DBGP(i)

__device__ __forceinline__ uint32_t smem_u32(const void* p) { return (uint32_t)__cvta_generic_to_shared(p); }
__device__ __forceinline__ uint32_t clk32() { uint32_t c; asm volatile("mov.u32 %0, %%clock;" : "=r"(c)); return c; }
__device__ __forceinline__ void mbar_arrive(uint32_t bar) { asm volatile("mbarrier.arrive.shared::cta.b64 _, [%0];" :: "r"(bar) : "memory"); }
__device__ __forceinline__ uint32_t mapa(uint32_t addr, uint32_t cta) { uint32_t r; asm("mapa.shared::cluster.u32 %0, %1, %2;" : "=r"(r) : "r"(addr), "r"(cta)); return r; }
__device__ __forceinline__ void mbar_arrive_remote_if(uint32_t cluster_addr, bool pred) {
  asm volatile("{\n.reg .pred p;\nsetp.ne.u32 p, %1, 0;\n@p mbarrier.arrive.shared::cluster.b64 _, [%0];\n}" :: "r"(cluster_addr), "r"((uint32_t)pred) : "memory");
}
__device__ __forceinline__ bool mbar_try(uint32_t bar, uint32_t parity) {
  uint32_t done;
  asm volatile("{\n.reg .pred p;\nmbarrier.try_wait.parity.shared::cta.b64 p, [%1], %2;\nselp.u32 %0, 1, 0, p;\n}" : "=r"(done) : "r"(bar), "r"(parity) : "memory");
  return done;
}
#define WAIT_LIM (1 << 14)
__device__ __forceinline__ void mbar_wait(uint32_t bar, uint32_t parity) {
  #pragma unroll 1
  for (int n = 0; n < WAIT_LIM; n++) { if (mbar_try(bar, parity)) break; }
}
__device__ __forceinline__ unsigned int ld_acquire(const unsigned int* p) {
  unsigned int v; asm volatile("ld.acquire.gpu.global.u32 %0, [%1];" : "=r"(v) : "l"(p) : "memory"); return v;
}
__device__ __forceinline__ unsigned int ld_relaxed(const unsigned int* p) {
  unsigned int v; asm volatile("ld.relaxed.gpu.global.u32 %0, [%1];" : "=r"(v) : "l"(p) : "memory"); return v;
}
__device__ __forceinline__ void wait_count(int idx, unsigned int target) {
  #pragma unroll 1
  for (int n = 0; n < 4 * WAIT_LIM; n++) { if ((int)(ld_acquire(&g_cnt[idx]) - target) >= 0) break; }
}
__device__ __forceinline__ void wait_count_lazy(int idx, unsigned int target) {
  #pragma unroll 1
  for (int n = 0; n < WAIT_LIM; n++) { if ((int)(ld_relaxed(&g_cnt[idx]) - target) >= 0) break; __nanosleep(100); }
  ld_acquire(&g_cnt[idx]);
}
__device__ __forceinline__ uint4 ld_tagged2(const void* p) {
  uint4 v;
  asm volatile("{\n.reg .b64 a, b;\nld.relaxed.gpu.global.v2.u64 {a, b}, [%4];\nmov.b64 {%0, %1}, a;\nmov.b64 {%2, %3}, b;\n}"
    : "=r"(v.x), "=r"(v.y), "=r"(v.z), "=r"(v.w) : "l"(p) : "memory");
  return v;
}
__device__ __forceinline__ uint2 ld_tagged(const void* p) {
  uint2 v; asm volatile("{\n.reg .b64 a;\nld.relaxed.gpu.global.u64 a, [%2];\nmov.b64 {%0, %1}, a;\n}" : "=r"(v.x), "=r"(v.y) : "l"(p) : "memory"); return v;
}
__device__ __forceinline__ void st_tagged2(void* p, uint32_t a, uint32_t b, uint32_t tag) {
  asm volatile("{\n.reg .b64 a, b;\nmov.b64 a, {%1, %3};\nmov.b64 b, {%2, %3};\nst.relaxed.gpu.global.v2.u64 [%0], {a, b};\n}" :: "l"(p), "r"(a), "r"(b), "r"(tag) : "memory");
}
__device__ __forceinline__ void st_tagged(void* p, uint32_t a, uint32_t tag) {
  asm volatile("{\n.reg .b64 a;\nmov.b64 a, {%1, %2};\nst.relaxed.gpu.global.u64 [%0], a;\n}" :: "l"(p), "r"(a), "r"(tag) : "memory");
}
__device__ __forceinline__ void stg_v4(void* p, uint32_t a, uint32_t b, uint32_t c, uint32_t d) {
  asm volatile("st.global.v4.u32 [%0], {%1, %2, %3, %4};" :: "l"(p), "r"(a), "r"(b), "r"(c), "r"(d) : "memory");
}
__device__ __forceinline__ uint4 lds_v4(uint32_t addr) {
  uint4 v; asm volatile("ld.shared.v4.u32 {%0, %1, %2, %3}, [%4];" : "=r"(v.x), "=r"(v.y), "=r"(v.z), "=r"(v.w) : "r"(addr) : "memory"); return v;
}
__device__ __forceinline__ uint32_t lds_u32(uint32_t addr) { uint32_t v; asm volatile("ld.shared.u32 %0, [%1];" : "=r"(v) : "r"(addr) : "memory"); return v; }
__device__ __forceinline__ void sts_v4(uint32_t addr, uint32_t a, uint32_t b, uint32_t c, uint32_t d) {
  asm volatile("st.shared.v4.u32 [%0], {%1, %2, %3, %4};" :: "r"(addr), "r"(a), "r"(b), "r"(c), "r"(d) : "memory");
}
#define ELECT "{\n.reg .pred p;\nelect.sync _|p, 0xffffffff;\n@p "
__device__ __forceinline__ void w_mbar_init(uint32_t bar, uint32_t cnt) { asm volatile(ELECT "mbarrier.init.shared::cta.b64 [%0], %1;\n}" :: "r"(bar), "r"(cnt) : "memory"); }
__device__ __forceinline__ void w_expect_tx(uint32_t bar, uint32_t bytes) { asm volatile(ELECT "mbarrier.arrive.expect_tx.shared::cta.b64 _, [%0], %1;\n}" :: "r"(bar), "r"(bytes) : "memory"); }
__device__ __forceinline__ void w_arrive(uint32_t bar) { asm volatile(ELECT "mbarrier.arrive.shared::cta.b64 _, [%0];\n}" :: "r"(bar) : "memory"); }
__device__ __forceinline__ void tma_load_2d(uint32_t dst, const CUtensorMap* tm, uint32_t bar, int c0, int c1) {
  asm volatile(ELECT "cp.async.bulk.tensor.2d.shared::cluster.global.mbarrier::complete_tx::bytes [%0], [%1, {%3, %4}], [%2];\n}"
    :: "r"(dst), "l"(tm), "r"(bar), "r"(c0), "r"(c1) : "memory");
}
__device__ __forceinline__ void tma_load_2d_mc(uint32_t dst, const CUtensorMap* tm, uint32_t bar, int c0, int c1) {
  asm volatile(ELECT "cp.async.bulk.tensor.2d.shared::cluster.global.mbarrier::complete_tx::bytes.multicast::cluster [%0], [%1, {%3, %4}], [%2], %5;\n}"
    :: "r"(dst), "l"(tm), "r"(bar), "r"(c0), "r"(c1), "h"((uint16_t)3) : "memory");
}
__device__ __forceinline__ void tma_load_3d_mc(uint32_t dst, const CUtensorMap* tm, uint32_t bar, int c0, int c1, int c2) {
  asm volatile(ELECT "cp.async.bulk.tensor.3d.shared::cluster.global.mbarrier::complete_tx::bytes.multicast::cluster [%0], [%1, {%3, %4, %5}], [%2], %6;\n}"
    :: "r"(dst), "l"(tm), "r"(bar), "r"(c0), "r"(c1), "r"(c2), "h"((uint16_t)3) : "memory");
}
__device__ __forceinline__ void bulk_load(uint32_t dst, const void* src, uint32_t bytes, uint32_t bar) {
  asm volatile(ELECT "cp.async.bulk.shared::cluster.global.mbarrier::complete_tx::bytes [%0], [%1], %2, [%3];\n}" :: "r"(dst), "l"(src), "r"(bytes), "r"(bar) : "memory");
}
__device__ __forceinline__ void tma_prefetch_2d(const CUtensorMap* tm, int c0, int c1) {
  asm volatile(ELECT "cp.async.bulk.prefetch.tensor.2d.L2.global [%0, {%1, %2}];\n}" :: "l"(tm), "r"(c0), "r"(c1) : "memory");
}
__device__ __forceinline__ void tma_prefetch_3d(const CUtensorMap* tm, int c0, int c1, int c2) {
  asm volatile(ELECT "cp.async.bulk.prefetch.tensor.3d.L2.global [%0, {%1, %2, %3}];\n}" :: "l"(tm), "r"(c0), "r"(c1), "r"(c2) : "memory");
}
__device__ __forceinline__ void bulk_prefetch(const void* p, uint32_t bytes) {
  asm volatile(ELECT "cp.async.bulk.prefetch.L2.global [%0], %1;\n}" :: "l"(p), "r"(bytes) : "memory");
}
__device__ __forceinline__ void tma_store_3d(const CUtensorMap* tm, uint32_t src, int c0, int c1, int c2) {
  asm volatile("cp.async.bulk.tensor.3d.global.shared::cta.bulk_group [%0, {%2, %3, %4}], [%1];"
    :: "l"(tm), "r"(src), "r"(c0), "r"(c1), "r"(c2) : "memory");
}
__device__ __forceinline__ void red_relaxed(int idx) { asm volatile("red.relaxed.gpu.global.add.u32 [%0], 1;" :: "l"(&g_cnt[idx]) : "memory"); }
__device__ __forceinline__ void red_release(int idx) { asm volatile("red.release.gpu.global.add.u32 [%0], 1;" :: "l"(&g_cnt[idx]) : "memory"); }
__device__ __forceinline__ void prefetch_tmap(const CUtensorMap* tm) { asm volatile("prefetch.tensormap [%0];" :: "l"(tm) : "memory"); }
__device__ __forceinline__ void bulk_commit() { asm volatile("cp.async.bulk.commit_group;" ::: "memory"); }
template<int N> __device__ __forceinline__ void bulk_wait() { asm volatile("cp.async.bulk.wait_group %0;" :: "n"(N) : "memory"); }
__device__ __forceinline__ void bar_sync(int id, int n) { asm volatile("bar.sync %0, %1;" :: "r"(id), "r"(n) : "memory"); }
__device__ __forceinline__ void bar_arrive(int id, int n) { asm volatile("bar.arrive %0, %1;" :: "r"(id), "r"(n) : "memory"); }
__device__ __forceinline__ void fence_async_smem() { asm volatile("fence.proxy.async.shared::cta;" ::: "memory"); }
__device__ __forceinline__ void fence_async_global() { asm volatile("fence.proxy.async.global;" ::: "memory"); }
__device__ __forceinline__ void fence_mbar_init() { asm volatile("fence.mbarrier_init.release.cluster;" ::: "memory"); }
__device__ __forceinline__ void cluster_arrive() { asm volatile("barrier.cluster.arrive.relaxed.aligned;" ::: "memory"); }
__device__ __forceinline__ void cluster_wait() { asm volatile("barrier.cluster.wait.aligned;" ::: "memory"); }
__device__ __forceinline__ uint32_t cluster_ctarank() { uint32_t r; asm volatile("mov.u32 %0, %%cluster_ctarank;" : "=r"(r)); return r; }
__device__ __forceinline__ void wgmma_fence() { asm volatile("wgmma.fence.sync.aligned;" ::: "memory"); }
__device__ __forceinline__ void wgmma_commit() { asm volatile("wgmma.commit_group.sync.aligned;" ::: "memory"); }
template<int N> __device__ __forceinline__ void wgmma_wait() { asm volatile("wgmma.wait_group.sync.aligned %0;" :: "n"(N) : "memory"); }
__device__ __forceinline__ float ex2(float x) { float y; asm("ex2.approx.ftz.f32 %0, %1;" : "=f"(y) : "f"(x)); return y; }
__device__ __forceinline__ float rcp_fast(float x) { float y; asm("rcp.approx.ftz.f32 %0, %1;" : "=f"(y) : "f"(x)); return y; }
__device__ __forceinline__ uint32_t pack_bf16(float lo, float hi) { uint32_t r; asm("cvt.rn.bf16x2.f32 %0, %1, %2;" : "=r"(r) : "f"(hi), "f"(lo)); return r; }
__device__ __forceinline__ float rbf(float x) { return __uint_as_float(pack_bf16(0.f, x)); }
__device__ __forceinline__ float bf_lo(uint32_t v) { return __uint_as_float(v << 16); }
__device__ __forceinline__ float bf_hi(uint32_t v) { return __uint_as_float(v & 0xffff0000u); }
__device__ __forceinline__ uint32_t add2(uint32_t a, uint32_t b) { uint32_t r; asm("add.rn.bf16x2 %0, %1, %2;" : "=r"(r) : "r"(a), "r"(b)); return r; }
__device__ __forceinline__ uint32_t fma2(uint32_t a, uint32_t b, uint32_t c) { uint32_t r; asm("fma.rn.bf16x2 %0, %1, %2, %3;" : "=r"(r) : "r"(a), "r"(b), "r"(c)); return r; }
__device__ __forceinline__ void prefetch_l2(const void* p) { asm volatile("prefetch.global.L2 [%0];" :: "l"(p) : "memory"); }
__device__ __forceinline__ void stsm_x4(uint32_t addr, uint32_t r0, uint32_t r1, uint32_t r2, uint32_t r3) {
  asm volatile("stmatrix.sync.aligned.m8n8.x4.shared.b16 [%0], {%1, %2, %3, %4};" :: "r"(addr), "r"(r0), "r"(r1), "r"(r2), "r"(r3) : "memory");
}
template<int N> __device__ __forceinline__ void fence_regs(float (&a)[N]) {
  #pragma unroll
  for (int i = 0; i < N; i++) asm volatile("" : "+f"(a[i]) :: "memory");
}
template<int N> __device__ __forceinline__ void fence_regs_u(uint32_t (&a)[N]) {
  #pragma unroll
  for (int i = 0; i < N; i++) asm volatile("" : "+r"(a[i]) :: "memory");
}
__device__ __forceinline__ uint32_t desc_lo(uint32_t addr, uint32_t lbo) { return ((addr & 0x3FFFF) >> 4) | ((lbo >> 4) << 16); }

template<int TB, int OA, int OB> __device__ __forceinline__ void wgmma_ss_n128(float (&d)[64], uint32_t da, uint32_t db, int sd) {
  asm volatile("{\n.reg .pred p;\n.reg .b32 ta, tb;\n.reg .b64 da, db;\nsetp.ne.b32 p, %66, 0;\nadd.u32 ta, %64, %68;\nadd.u32 tb, %65, %69;\nmov.b64 da, {ta, 0x40000040};\nmov.b64 db, {tb, 0x40000040};\n"
    "wgmma.mma_async.sync.aligned.m64n128k16.f32.bf16.bf16 "
    "{%0, %1, %2, %3, %4, %5, %6, %7, %8, %9, %10, %11, %12, %13, %14, %15, %16, %17, %18, %19, %20, %21, %22, %23, %24, %25, %26, %27, %28, %29, %30, %31, %32, %33, %34, %35, %36, %37, %38, %39, %40, %41, %42, %43, %44, %45, %46, %47, %48, %49, %50, %51, %52, %53, %54, %55, %56, %57, %58, %59, %60, %61, %62, %63}, da, db, p, 1, 1, 0, %67;\n}\n"
    : "+f"(d[0]), "+f"(d[1]), "+f"(d[2]), "+f"(d[3]), "+f"(d[4]), "+f"(d[5]), "+f"(d[6]), "+f"(d[7]), "+f"(d[8]), "+f"(d[9]), "+f"(d[10]), "+f"(d[11]), "+f"(d[12]), "+f"(d[13]), "+f"(d[14]), "+f"(d[15]), "+f"(d[16]), "+f"(d[17]), "+f"(d[18]), "+f"(d[19]), "+f"(d[20]), "+f"(d[21]), "+f"(d[22]), "+f"(d[23]), "+f"(d[24]), "+f"(d[25]), "+f"(d[26]), "+f"(d[27]), "+f"(d[28]), "+f"(d[29]), "+f"(d[30]), "+f"(d[31]), "+f"(d[32]), "+f"(d[33]), "+f"(d[34]), "+f"(d[35]), "+f"(d[36]), "+f"(d[37]), "+f"(d[38]), "+f"(d[39]), "+f"(d[40]), "+f"(d[41]), "+f"(d[42]), "+f"(d[43]), "+f"(d[44]), "+f"(d[45]), "+f"(d[46]), "+f"(d[47]), "+f"(d[48]), "+f"(d[49]), "+f"(d[50]), "+f"(d[51]), "+f"(d[52]), "+f"(d[53]), "+f"(d[54]), "+f"(d[55]), "+f"(d[56]), "+f"(d[57]), "+f"(d[58]), "+f"(d[59]), "+f"(d[60]), "+f"(d[61]), "+f"(d[62]), "+f"(d[63])
    : "r"(da), "r"(db), "r"(sd), "n"(TB), "n"(OA), "n"(OB));
}
template<int TB, int OB> __device__ __forceinline__ void wgmma_rs_n128(float (&d)[64], uint32_t a0, uint32_t a1, uint32_t a2, uint32_t a3, uint32_t db, int sd) {
  asm volatile("{\n.reg .pred p;\n.reg .b32 tb;\n.reg .b64 db;\nsetp.ne.b32 p, %69, 0;\nadd.u32 tb, %68, %71;\nmov.b64 db, {tb, 0x40000040};\n"
    "wgmma.mma_async.sync.aligned.m64n128k16.f32.bf16.bf16 "
    "{%0, %1, %2, %3, %4, %5, %6, %7, %8, %9, %10, %11, %12, %13, %14, %15, %16, %17, %18, %19, %20, %21, %22, %23, %24, %25, %26, %27, %28, %29, %30, %31, %32, %33, %34, %35, %36, %37, %38, %39, %40, %41, %42, %43, %44, %45, %46, %47, %48, %49, %50, %51, %52, %53, %54, %55, %56, %57, %58, %59, %60, %61, %62, %63}, {%64,%65,%66,%67}, db, p, 1, 1, %70;\n}\n"
    : "+f"(d[0]), "+f"(d[1]), "+f"(d[2]), "+f"(d[3]), "+f"(d[4]), "+f"(d[5]), "+f"(d[6]), "+f"(d[7]), "+f"(d[8]), "+f"(d[9]), "+f"(d[10]), "+f"(d[11]), "+f"(d[12]), "+f"(d[13]), "+f"(d[14]), "+f"(d[15]), "+f"(d[16]), "+f"(d[17]), "+f"(d[18]), "+f"(d[19]), "+f"(d[20]), "+f"(d[21]), "+f"(d[22]), "+f"(d[23]), "+f"(d[24]), "+f"(d[25]), "+f"(d[26]), "+f"(d[27]), "+f"(d[28]), "+f"(d[29]), "+f"(d[30]), "+f"(d[31]), "+f"(d[32]), "+f"(d[33]), "+f"(d[34]), "+f"(d[35]), "+f"(d[36]), "+f"(d[37]), "+f"(d[38]), "+f"(d[39]), "+f"(d[40]), "+f"(d[41]), "+f"(d[42]), "+f"(d[43]), "+f"(d[44]), "+f"(d[45]), "+f"(d[46]), "+f"(d[47]), "+f"(d[48]), "+f"(d[49]), "+f"(d[50]), "+f"(d[51]), "+f"(d[52]), "+f"(d[53]), "+f"(d[54]), "+f"(d[55]), "+f"(d[56]), "+f"(d[57]), "+f"(d[58]), "+f"(d[59]), "+f"(d[60]), "+f"(d[61]), "+f"(d[62]), "+f"(d[63])
    : "r"(a0), "r"(a1), "r"(a2), "r"(a3), "r"(db), "r"(sd), "n"(TB), "n"(OB));
}
template<int TB, int OA, int OB> __device__ __forceinline__ void wgmma_ss_n256(float (&d)[128], uint32_t da, uint32_t db, int sd) {
  asm volatile("{\n.reg .pred p;\n.reg .b32 ta, tb;\n.reg .b64 da, db;\nsetp.ne.b32 p, %130, 0;\nadd.u32 ta, %128, %132;\nadd.u32 tb, %129, %133;\nmov.b64 da, {ta, 0x40000040};\nmov.b64 db, {tb, 0x40000040};\n"
    "wgmma.mma_async.sync.aligned.m64n256k16.f32.bf16.bf16 "
    "{%0, %1, %2, %3, %4, %5, %6, %7, %8, %9, %10, %11, %12, %13, %14, %15, %16, %17, %18, %19, %20, %21, %22, %23, %24, %25, %26, %27, %28, %29, %30, %31, %32, %33, %34, %35, %36, %37, %38, %39, %40, %41, %42, %43, %44, %45, %46, %47, %48, %49, %50, %51, %52, %53, %54, %55, %56, %57, %58, %59, %60, %61, %62, %63, %64, %65, %66, %67, %68, %69, %70, %71, %72, %73, %74, %75, %76, %77, %78, %79, %80, %81, %82, %83, %84, %85, %86, %87, %88, %89, %90, %91, %92, %93, %94, %95, %96, %97, %98, %99, %100, %101, %102, %103, %104, %105, %106, %107, %108, %109, %110, %111, %112, %113, %114, %115, %116, %117, %118, %119, %120, %121, %122, %123, %124, %125, %126, %127}, da, db, p, 1, 1, 0, %131;\n}\n"
    : "+f"(d[0]), "+f"(d[1]), "+f"(d[2]), "+f"(d[3]), "+f"(d[4]), "+f"(d[5]), "+f"(d[6]), "+f"(d[7]), "+f"(d[8]), "+f"(d[9]), "+f"(d[10]), "+f"(d[11]), "+f"(d[12]), "+f"(d[13]), "+f"(d[14]), "+f"(d[15]), "+f"(d[16]), "+f"(d[17]), "+f"(d[18]), "+f"(d[19]), "+f"(d[20]), "+f"(d[21]), "+f"(d[22]), "+f"(d[23]), "+f"(d[24]), "+f"(d[25]), "+f"(d[26]), "+f"(d[27]), "+f"(d[28]), "+f"(d[29]), "+f"(d[30]), "+f"(d[31]), "+f"(d[32]), "+f"(d[33]), "+f"(d[34]), "+f"(d[35]), "+f"(d[36]), "+f"(d[37]), "+f"(d[38]), "+f"(d[39]), "+f"(d[40]), "+f"(d[41]), "+f"(d[42]), "+f"(d[43]), "+f"(d[44]), "+f"(d[45]), "+f"(d[46]), "+f"(d[47]), "+f"(d[48]), "+f"(d[49]), "+f"(d[50]), "+f"(d[51]), "+f"(d[52]), "+f"(d[53]), "+f"(d[54]), "+f"(d[55]), "+f"(d[56]), "+f"(d[57]), "+f"(d[58]), "+f"(d[59]), "+f"(d[60]), "+f"(d[61]), "+f"(d[62]), "+f"(d[63]), "+f"(d[64]), "+f"(d[65]), "+f"(d[66]), "+f"(d[67]), "+f"(d[68]), "+f"(d[69]), "+f"(d[70]), "+f"(d[71]), "+f"(d[72]), "+f"(d[73]), "+f"(d[74]), "+f"(d[75]), "+f"(d[76]), "+f"(d[77]), "+f"(d[78]), "+f"(d[79]), "+f"(d[80]), "+f"(d[81]), "+f"(d[82]), "+f"(d[83]), "+f"(d[84]), "+f"(d[85]), "+f"(d[86]), "+f"(d[87]), "+f"(d[88]), "+f"(d[89]), "+f"(d[90]), "+f"(d[91]), "+f"(d[92]), "+f"(d[93]), "+f"(d[94]), "+f"(d[95]), "+f"(d[96]), "+f"(d[97]), "+f"(d[98]), "+f"(d[99]), "+f"(d[100]), "+f"(d[101]), "+f"(d[102]), "+f"(d[103]), "+f"(d[104]), "+f"(d[105]), "+f"(d[106]), "+f"(d[107]), "+f"(d[108]), "+f"(d[109]), "+f"(d[110]), "+f"(d[111]), "+f"(d[112]), "+f"(d[113]), "+f"(d[114]), "+f"(d[115]), "+f"(d[116]), "+f"(d[117]), "+f"(d[118]), "+f"(d[119]), "+f"(d[120]), "+f"(d[121]), "+f"(d[122]), "+f"(d[123]), "+f"(d[124]), "+f"(d[125]), "+f"(d[126]), "+f"(d[127])
    : "r"(da), "r"(db), "r"(sd), "n"(TB), "n"(OA), "n"(OB));
}
template<int TB, int OA, int OB> __device__ __forceinline__ void wgmma_ss_n64_lo(float (&d)[64], uint32_t da, uint32_t db, int sd) {
  asm volatile("{\n.reg .pred p;\n.reg .b32 ta, tb;\n.reg .b64 da, db;\nsetp.ne.b32 p, %34, 0;\nadd.u32 ta, %32, %36;\nadd.u32 tb, %33, %37;\nmov.b64 da, {ta, 0x40000040};\nmov.b64 db, {tb, 0x40000040};\n"
    "wgmma.mma_async.sync.aligned.m64n64k16.f32.bf16.bf16 "
    "{%0, %1, %2, %3, %4, %5, %6, %7, %8, %9, %10, %11, %12, %13, %14, %15, %16, %17, %18, %19, %20, %21, %22, %23, %24, %25, %26, %27, %28, %29, %30, %31}, da, db, p, 1, 1, 0, %35;\n}\n"
    : "+f"(d[0]), "+f"(d[1]), "+f"(d[2]), "+f"(d[3]), "+f"(d[4]), "+f"(d[5]), "+f"(d[6]), "+f"(d[7]), "+f"(d[8]), "+f"(d[9]), "+f"(d[10]), "+f"(d[11]), "+f"(d[12]), "+f"(d[13]), "+f"(d[14]), "+f"(d[15]), "+f"(d[16]), "+f"(d[17]), "+f"(d[18]), "+f"(d[19]), "+f"(d[20]), "+f"(d[21]), "+f"(d[22]), "+f"(d[23]), "+f"(d[24]), "+f"(d[25]), "+f"(d[26]), "+f"(d[27]), "+f"(d[28]), "+f"(d[29]), "+f"(d[30]), "+f"(d[31])
    : "r"(da), "r"(db), "r"(sd), "n"(TB), "n"(OA), "n"(OB));
}
template<int OA> __device__ __forceinline__ void kblock_n128(float (&d)[64], uint32_t da, uint32_t db, int sd) {
  wgmma_ss_n128<1, OA, 0>(d, da, db, sd); wgmma_ss_n128<1, OA + 2, 128>(d, da, db, 1); wgmma_ss_n128<1, OA + 4, 256>(d, da, db, 1); wgmma_ss_n128<1, OA + 6, 384>(d, da, db, 1);
}
template<int OA> __device__ __forceinline__ void kblock_n256(float (&d)[128], uint32_t da, uint32_t db, int sd) {
  wgmma_ss_n256<1, OA, 0>(d, da, db, sd); wgmma_ss_n256<1, OA + 2, 128>(d, da, db, 1); wgmma_ss_n256<1, OA + 4, 256>(d, da, db, 1); wgmma_ss_n256<1, OA + 6, 384>(d, da, db, 1);
}

__device__ __forceinline__ float quad_sum(float v) {
  v += __shfl_xor_sync(0xffffffff, v, 1);
  v += __shfl_xor_sync(0xffffffff, v, 2);
  return v;
}
__device__ __forceinline__ void unpack8(const uint4& v, float* f) {
  f[0] = bf_lo(v.x); f[1] = bf_hi(v.x); f[2] = bf_lo(v.y); f[3] = bf_hi(v.y);
  f[4] = bf_lo(v.z); f[5] = bf_hi(v.z); f[6] = bf_lo(v.w); f[7] = bf_hi(v.w);
}
struct Row { uint32_t v[8]; };
template<class F> __device__ __forceinline__ Row load_row(const __nv_bfloat16* p, int lane, F ld) {
  const uint4 a = ld(reinterpret_cast<const uint4*>(p) + lane), b = ld(reinterpret_cast<const uint4*>(p) + 32 + lane);
  return Row{{a.x, a.y, a.z, a.w, b.x, b.y, b.z, b.w}};
}
__device__ __forceinline__ Row ldg_row(const __nv_bfloat16* p, int lane) { return load_row(p, lane, [](const uint4* q) { return __ldg(q); }); }
__device__ __forceinline__ Row ldca_row(const __nv_bfloat16* p, int lane) { return load_row(p, lane, [](const uint4* q) { return __ldca(q); }); }
__device__ __forceinline__ Row lds_row(uint32_t addr, int lane) {
  const uint4 a = lds_v4(addr + lane * 16), b = lds_v4(addr + 512 + lane * 16);
  return Row{{a.x, a.y, a.z, a.w, b.x, b.y, b.z, b.w}};
}
__device__ __forceinline__ void store_row(__nv_bfloat16* p, int lane, const Row& r) {
  stg_v4(p + lane * 8, r.v[0], r.v[1], r.v[2], r.v[3]); stg_v4(p + 256 + lane * 8, r.v[4], r.v[5], r.v[6], r.v[7]);
}
__device__ __forceinline__ Row fma_row(const Row& a, const Row& b, const Row& c) {
  Row r;
  #pragma unroll
  for (int i = 0; i < 8; i++) r.v[i] = fma2(a.v[i], b.v[i], c.v[i]);
  return r;
}
__device__ __forceinline__ Row one_plus(const Row& a) {
  Row r;
  #pragma unroll
  for (int i = 0; i < 8; i++) r.v[i] = add2(a.v[i], 0x3f803f80u);
  return r;
}
__device__ __forceinline__ void layer_norm2(const Row (&x)[2], Row (&n)[2]) {
  float d[2][16], s[4];
  #pragma unroll
  for (int r = 0; r < 2; r++) {
    const float c = bf_lo(__shfl_sync(0xffffffff, x[r].v[0], 0));
    float s1 = 0.f, s2 = 0.f;
    #pragma unroll
    for (int i = 0; i < 16; i++) { d[r][i] = ((i & 1) ? bf_hi(x[r].v[i >> 1]) : bf_lo(x[r].v[i >> 1])) - c; s1 += d[r][i]; s2 = fmaf(d[r][i], d[r][i], s2); }
    s[2*r] = s1; s[2*r+1] = s2;
  }
  #pragma unroll
  for (int o = 16; o > 0; o >>= 1) {
    #pragma unroll
    for (int k = 0; k < 4; k++) s[k] += __shfl_xor_sync(0xffffffff, s[k], o);
  }
  #pragma unroll
  for (int r = 0; r < 2; r++) {
    const float m = s[2*r] * (1.f / DM), rstd = rsqrtf(fmaxf(fmaf(-m, m, s[2*r+1] * (1.f / DM)), 0.f) + 1e-5f), o = -m * rstd;
    #pragma unroll
    for (int i = 0; i < 8; i++) n[r].v[i] = pack_bf16(fmaf(d[r][2*i], rstd, o), fmaf(d[r][2*i+1], rstd, o));
  }
}

constexpr int SM_Q = 6 * 32768, SM_BAR = 7 * 32768, SM_MAIL = SM_BAR + 640, SM_RED = SM_MAIL + 128, SM_H2 = SM_RED + 1024, SM_KEY = SM_H2 + 1024, SMEM = SM_KEY + 128;
constexpr int B_AF = 0, B_RF = 64, B_WF = 112, B_WE = 160, B_RE = 208, B_PUB = 256, B_RDY = 496;
__device__ __forceinline__ uint32_t k_addrA(int kb) { return ((0x6310u >> ((kb >> 1) * 4)) & 15u) * 32768u + (kb & 1) * 16384u; }
__device__ __forceinline__ uint32_t k_addrW(int s) { return ((0x254u >> ((s >> 1) * 4)) & 15u) * 32768u + (s & 1) * 16384u; }

constexpr int MAX_ITEMS = 6;
struct Sched {
  uint8_t khead[NGRID / 2][4];
  uint8_t nitems[NGRID / 2];
  uint8_t item[NGRID / 2][MAX_ITEMS];
  uint8_t otask[NGRID / 2];
  uint8_t ohead[NGRID / 2][8];
};

__device__ __forceinline__ int ring_add(int e, int n) { e += n; return e >= 12 ? e - 12 : e; }
__device__ __forceinline__ int ring_slot(int e) { return e >= 6 ? e - 6 : e; }
__device__ __forceinline__ void ring_wait_full(uint32_t bars, int e) { mbar_wait(bars + B_RF + 8 * ring_slot(e), e >= 6); }

struct Ctx {
  uint32_t base, bars;
  uint32_t rel;
  int w, wtid, tmask, nev;
};
__device__ __forceinline__ void slot_release(const Ctx& x, int s, bool twice) {
  mbar_arrive_remote_if(x.rel + B_RE + 8 * s, (x.wtid & 31) == 0 && (twice || x.wtid == 32 || x.wtid == 64));
}
__device__ __forceinline__ void ring_release(const Ctx& x, int e, bool twice) { slot_release(x, ring_slot(e), twice); }
__device__ __forceinline__ void publish(Ctx& x, int idx) {
  const uint32_t n = x.w * 15 + x.nev;
  if (x.wtid == 0) asm volatile("st.shared.u32 [%0], %1;" :: "r"(x.base + SM_MAIL + 4 * n), "r"(idx) : "memory");
  __syncwarp();
  if ((x.wtid & 31) == 0) mbar_arrive(x.bars + B_PUB + 8 * n);
  x.nev++;
}

template<int KK = 0> __device__ __forceinline__ void issue_qk(float (&S)[64], uint32_t dq, uint32_t dk) {
  constexpr int off = (KK >> 2) * 1024 + (KK & 3) * 2;
  wgmma_ss_n128<0, off, off>(S, dq, dk, KK > 0);
  if constexpr (KK < 7) issue_qk<KK + 1>(S, dq, dk);
}
template<int KK = 0> __device__ __forceinline__ void issue_qk_half(float (&S)[64], uint32_t dq, uint32_t dk) {
  constexpr int off = (KK >> 2) * 1024 + (KK & 3) * 2;
  wgmma_ss_n64_lo<0, off, off + 512>(S, dq, dk, KK > 0);
  if constexpr (KK < 7) issue_qk_half<KK + 1>(S, dq, dk);
}
template<int NK, int KK = 0>
__device__ __forceinline__ void issue_pv(float (&O)[64], uint32_t (&P)[32], uint32_t dv, int accumulate) {
  wgmma_rs_n128<1, (KK + 8 - NK) * 128>(O, P[4*KK], P[4*KK+1], P[4*KK+2], P[4*KK+3], dv, accumulate);
  if constexpr (KK + 1 < NK) issue_pv<NK, KK + 1>(O, P, dv, 1);
}
template<int K0, int K1>
__device__ __forceinline__ void exp_pack(const float (&S)[64], uint32_t (&D)[32], float& s0, float& s1) {
  #pragma unroll
  for (int k = K0; k < K1; k++) {
    const float e0 = ex2(S[2*k]), e1 = ex2(S[2*k+1]);
    D[k] = pack_bf16(e0, e1);
    if (k & 1) s1 += e0 + e1; else s0 += e0 + e1;
  }
}
__device__ __forceinline__ void exp_pack_diag(const float (&S)[64], uint32_t (&D)[32], int t, float& s0, float& s1) {
  #pragma unroll
  for (int k = 0; k < 16; k++) {
    const int c = 8 * (k >> 1) - 8 * (k & 1);
    const float e0 = ex2((c <= t) ? S[2*k] : -INFINITY), e1 = ex2((c + 1 <= t) ? S[2*k+1] : -INFINITY);
    D[k] = pack_bf16(e0, e1);
    if (k & 1) s1 += e0 + e1; else s0 += e0 + e1;
  }
}
constexpr float SUM_HI = 1.8446744073709552e19f;
constexpr float SUM_LO = 5.421010862427522e-20f;

__device__ __forceinline__ void classic_tile(const float (&S)[64], uint32_t (&P)[32], bool fresh, bool half, int tmask, float& mc0, float& mc1,
                                             float& l0, float& l1, float& s0, float& s1, float& sc0, float& sc1) {
  float4 t[16];
  #pragma unroll
  for (int j = 0; j < 16; j++) t[j] = make_float4(S[4*j], S[4*j+1], S[4*j+2], S[4*j+3]);
  float mx0 = -INFINITY, mx1 = -INFINITY;
  #pragma unroll 1
  for (int j = 0; j < 16; j++) {
    float4 v = t[j];
    const int lim = !fresh ? 1000 : j < 8 ? tmask - 8 * j : half ? -1000 : 1000;
    v.x = 0 <= lim ? v.x : -INFINITY; v.y = 1 <= lim ? v.y : -INFINITY; v.z = -8 <= lim ? v.z : -INFINITY; v.w = -7 <= lim ? v.w : -INFINITY;
    t[j] = v;
    mx0 = fmaxf(mx0, fmaxf(v.x, v.y)); mx1 = fmaxf(mx1, fmaxf(v.z, v.w));
  }
  mx0 = fmaxf(mx0, __shfl_xor_sync(0xffffffff, mx0, 1));
  mx1 = fmaxf(mx1, __shfl_xor_sync(0xffffffff, mx1, 1));
  mx0 = fmaxf(mx0, __shfl_xor_sync(0xffffffff, mx0, 2));
  mx1 = fmaxf(mx1, __shfl_xor_sync(0xffffffff, mx1, 2));
  const float n0 = fresh ? -mx0 : fminf(mc0, -mx0), n1 = fresh ? -mx1 : fminf(mc1, -mx1);
  sc0 = ex2(n0 - mc0); sc1 = ex2(n1 - mc1);
  mc0 = n0; mc1 = n1;
  s0 = 0.f; s1 = 0.f;
  #pragma unroll 1
  for (int j = 0; j < 16; j++) {
    const float4 v = t[j];
    const float e0 = ex2(v.x + n0), e1 = ex2(v.y + n0), e2 = ex2(v.z + n1), e3 = ex2(v.w + n1);
    s0 += e0 + e1; s1 += e2 + e3;
    t[j].x = __uint_as_float(pack_bf16(e0, e1)); t[j].y = __uint_as_float(pack_bf16(e2, e3));
  }
  #pragma unroll
  for (int j = 0; j < 16; j++) { P[2*j] = __float_as_uint(t[j].x); P[2*j+1] = __float_as_uint(t[j].y); }
  if (!fresh) { l0 *= sc0; l1 *= sc1; }
}
__device__ __forceinline__ void pack_tile(const float (&A)[64], uint32_t (&D)[32], float f0, float f1) {
  #pragma unroll
  for (int j = 0; j < 16; j++) {
    D[8 * (j >> 2) + (j & 3)] = pack_bf16(A[4*j] * f0, A[4*j+1] * f0);
    D[8 * (j >> 2) + 4 + (j & 3)] = pack_bf16(A[4*j+2] * f1, A[4*j+3] * f1);
  }
}
__device__ __forceinline__ void store_tile(__nv_bfloat16* p, const uint32_t (&D)[32]) {
  #pragma unroll
  for (int i = 0; i < 8; i++) stg_v4(p + (i >> 2) * (SEQ * 64) + ((i >> 1) & 1) * 32 + (i & 1) * 8 * 64, D[4*i], D[4*i+1], D[4*i+2], D[4*i+3]);
}

enum : int { PV_ACC = 0, PV_ZERO = 1, PV_HALF = 2, PV_NONE = 3 };
struct Att {
  float l0, l1, mc0, mc1;
  uint32_t classic;
};
__device__ __forceinline__ void store_ctx(Ctx& x, int code, const uint32_t (&D)[32]) {
  const int item = code >> 2, lane = x.wtid & 31;
  const int row = (item & 7) * 256 + (code & 3) * 64 + (x.wtid >> 5) * 16 + (lane >> 2);
  store_tile(g_kvc + ((size_t)(128 + (item >> 3) * 2) * SEQ + row) * 64 + (lane & 3) * 8, D);
  publish(x, C_CTX + item);
}

__device__ __forceinline__ void q_proj(Ctx& x, int& e, float (&S)[64], bool isY, bool dbg = false) {
  bar_sync(1 + x.w, 256);
  if (dbg) DBG(80);
  if (isY) bar_arrive(1 + (x.w ^ 1), 256);
  #pragma unroll 1
  for (int kb = 0; kb < 8; kb++) {
    ring_wait_full(x.bars, e);
    if (dbg) DBG(81 + kb);
    const uint32_t ent = x.base + ring_slot(e) * 32768;
    const uint32_t da = desc_lo(ent + x.w * 8192, 16), dw = desc_lo(ent + 16384, 8192);
    wgmma_fence();
    kblock_n128<0>(S, da, dw, kb != 0);
    wgmma_commit();
    if (kb == 7 && !isY) bar_arrive(1 + (x.w ^ 1), 256);
    if (kb > 0) { wgmma_wait<1>(); ring_release(x, ring_add(e, 11), false); }
    e = ring_add(e, 1);
  }
  wgmma_wait<0>();
  fence_regs(S);
  if (dbg) DBG(89);
  ring_release(x, ring_add(e, 11), false);
  const int lane = x.wtid & 31, g = lane >> 2;
  const uint32_t qa = x.base + SM_Q + x.w * 8192 + ((x.wtid >> 5) * 16 + g) * 128;
  #pragma unroll
  for (int i = 0; i < 8; i++) {
    const int j = 4 * (i >> 1), o = 2 * (i & 1);
    sts_v4(qa + (i >> 2) * 16384 + (i & 1) * 1024 + (((((i >> 1) & 1) * 4 + (lane & 3)) ^ g) << 4),
           pack_bf16(S[4*j+o], S[4*j+o+1]), pack_bf16(S[4*j+4+o], S[4*j+5+o]), pack_bf16(S[4*j+8+o], S[4*j+9+o]), pack_bf16(S[4*j+12+o], S[4*j+13+o]));
  }
  fence_async_smem();
  if (dbg) DBG(90);
  ring_wait_full(x.bars, ring_add(e, isY ? 0 : 2));
  ring_wait_full(x.bars, ring_add(e, 1));
}

template<int KIND>
__device__ __forceinline__ void slot(Ctx& x, Att& a, int& e, float (&S)[64], float (&O)[64], uint32_t (&Pn)[32], uint32_t (&Po)[32],
                                     bool more, bool isY, bool half, int pv, int pend) {
  const int w = x.w;
  const bool skip = KIND == 0 && !isY;
  const int en = ring_add(e, skip ? 4 : 2), sn = ring_slot(en), sv = ring_slot(e) + 1, sk = skip ? ring_slot(ring_add(e, 2)) : sv - 1;
  const uint32_t dq = desc_lo(x.base + SM_Q + w * 8192, 16), dk = desc_lo(x.base, 16) + sk * 2048, dv = desc_lo(x.base, 16384) + sv * 2048;
  bar_sync(1 + w, 256);
  if (KIND == 2) {
    wgmma_fence();
    issue_qk(S, dq, dk); wgmma_commit();
    issue_pv<8>(O, Po, dv, 1); wgmma_commit();
  } else if (KIND == 1) {
    if (half) { wgmma_fence(); issue_qk(S, dq, dk); wgmma_commit(); issue_pv<4>(O, Po, dv, 0); wgmma_commit(); }
    else      { wgmma_fence(); issue_qk(S, dq, dk); wgmma_commit(); issue_pv<8>(O, Po, dv, 0); wgmma_commit(); }
  } else if (half) {
    if (pv == PV_NONE) { wgmma_fence(); issue_qk_half(S, dq, dk); wgmma_commit(); wgmma_commit(); }
    else               { wgmma_fence(); issue_qk_half(S, dq, dk); wgmma_commit(); issue_pv<8>(O, Po, dv, pv == PV_ACC); wgmma_commit(); }
  } else {
    if (pv == PV_NONE)      { wgmma_fence(); issue_qk(S, dq, dk); wgmma_commit(); wgmma_commit(); }
    else if (pv == PV_HALF) { wgmma_fence(); issue_qk(S, dq, dk); wgmma_commit(); issue_pv<4>(O, Po, dv, 0); wgmma_commit(); }
    else                    { wgmma_fence(); issue_qk(S, dq, dk); wgmma_commit(); issue_pv<8>(O, Po, dv, pv == PV_ACC); wgmma_commit(); }
  }
  bar_arrive(1 + (w ^ 1), 256);
  float i0 = 0.f, i1 = 0.f;
  if (KIND == 1 && pend >= 0) store_ctx(x, pend, Pn);
  if (KIND == 0) { i0 = rcp_fast(quad_sum(a.l0)); i1 = rcp_fast(quad_sum(a.l1)); }
  wgmma_wait<1>();
  fence_regs(S);
  fence_regs_u(Pn);
  slot_release(x, sk, KIND == 0 && isY);
  float s0 = 0.f, s1 = 0.f;
  if (KIND == 0) {
    a.l0 = 0.f; a.l1 = 0.f; a.mc0 = 0.f; a.mc1 = 0.f;
    exp_pack_diag(S, Pn, x.tmask, s0, s1);
    if (!half) exp_pack<16, 32>(S, Pn, s0, s1);
    const float q0 = quad_sum(s0), q1 = quad_sum(s1);
    a.classic = __any_sync(0xffffffff, !(s0 <= SUM_HI && s1 <= SUM_HI && q0 >= SUM_LO && q1 >= SUM_LO)) ? 1u : 0u;
  } else {
    exp_pack<0, 32>(S, Pn, s0, s1);
    a.classic = __any_sync(0xffffffff, a.classic || !(s0 <= SUM_HI && s1 <= SUM_HI)) ? 1u : 0u;
  }
  fence_regs_u(Pn);
  mbar_wait(x.bars + B_RF + 8 * sn, en >= 6);
  if (more) mbar_wait(x.bars + B_RF + 8 * sn + 8, en >= 6);
  wgmma_wait<0>();
  fence_regs(O);
  fence_regs_u(Po);
  slot_release(x, sv, KIND == 1 && isY);
  if (__builtin_expect(a.classic, 0)) {
    float sc0, sc1;
    classic_tile(S, Pn, KIND == 0, half, x.tmask, a.mc0, a.mc1, a.l0, a.l1, s0, s1, sc0, sc1);
    if (KIND != 0) {
      #pragma unroll
      for (int j = 0; j < 16; j++) { O[4*j] *= sc0; O[4*j+1] *= sc0; O[4*j+2] *= sc1; O[4*j+3] *= sc1; }
    }
  }
  a.l0 += s0; a.l1 += s1;
  if (KIND == 0) pack_tile(O, Po, i0, i1);
  e = en;
}

__device__ __forceinline__ void attention(Ctx& x, int& e, const uint8_t* items, int nitems, int rank) {
  float S[64], O[64]; uint32_t PA[32], PB[32];
  Att a;
  a.l0 = 1.f; a.l1 = 1.f; a.mc0 = 0.f; a.mc1 = 0.f; a.classic = 0;
  int pv = PV_NONE, cur = -1;
#define DBGS()
  #pragma unroll 1
  for (int it = 0; it < nitems; it++) {
    const int item = items[it];
    const bool isY = (it & 1) == x.w, half = isY == (rank != 0);
    const int prev = cur;
    cur = item * 4 + (isY ? 3 - rank : rank);
    int rem = 2 * (item & 7) + (isY ? 1 : 0);
    DBG(16 + it);
    q_proj(x, e, S, isY);
    DBGS();
    slot<0>(x, a, e, S, O, PA, PB, rem > 0, isY, half, pv, -1);
    if (rem > 0) {
      pv = PV_ACC;
      rem--;
      DBGS();
      slot<1>(x, a, e, S, O, PB, PA, rem > 0, isY, half, 0, prev);
      #pragma unroll 1
      while (rem > 0) {
        DBGS();
        slot<2>(x, a, e, S, O, PA, PB, rem > 1, false, false, 0, -1);
        if (rem == 1) break;
        rem -= 2;
        DBGS();
        slot<2>(x, a, e, S, O, PB, PA, rem > 0, false, false, 0, -1);
      }
    } else {
      pv = half ? PV_HALF : PV_ZERO;
      if (prev >= 0) store_ctx(x, prev, PB);
    }
    if (!isY) {
      #pragma unroll
      for (int i = 0; i < 32; i++) PB[i] = PA[i];
    }
  }
  DBGS();
  const uint32_t dv = desc_lo(x.base + ring_slot(e) * 32768, 16384);
  bar_sync(1 + x.w, 256);
  if (pv == PV_HALF) { wgmma_fence(); issue_pv<4>(O, PB, dv, 0); wgmma_commit(); }
  else { wgmma_fence(); issue_pv<8>(O, PB, dv, pv == PV_ACC); wgmma_commit(); }
  if ((nitems & 1) == x.w) bar_arrive(1 + (x.w ^ 1), 256);
  const float i0 = rcp_fast(quad_sum(a.l0)), i1 = rcp_fast(quad_sum(a.l1));
  ring_wait_full(x.bars, ring_add(e, 1));
  wgmma_wait<0>();
  fence_regs(O);
  fence_regs_u(PB);
  ring_release(x, e, false);
  pack_tile(O, PB, i0, i1);
  store_ctx(x, cur, PB);
  e = ring_add(e, 1);
}

#define LN_AT 3
__device__ __forceinline__ void mod_cta(uint8_t* smem, const __nv_bfloat16* cvec, const __nv_bfloat16* w_mod) {
  const int ct = threadIdx.x - 128, cw = ct >> 5, lane = ct & 31;
  const uint32_t cv = __ldg(reinterpret_cast<const uint32_t*>(cvec + cw * 64) + lane);
  const uint32_t sv = pack_bf16(__fdividef(bf_lo(cv), 1.f + __expf(-bf_lo(cv))), __fdividef(bf_hi(cv), 1.f + __expf(-bf_hi(cv))));
  float* red = reinterpret_cast<float*>(smem);
  #pragma unroll 1
  for (int rd = 0; rd < 3; rd++) {
    const int col0 = rd * 1024 + (blockIdx.x - NCTA) * 256;
    const uint4* wp = reinterpret_cast<const uint4*>(w_mod + (size_t)(cw * 64) * 3072 + col0) + lane;
    float am[8] = {0, 0, 0, 0, 0, 0, 0, 0};
    #pragma unroll 1
    for (int rb = 0; rb < 4; rb++) {
      uint4 wv[16];
      #pragma unroll
      for (int r = 0; r < 16; r++) wv[r] = __ldg(wp + (rb * 16 + r) * (3072 / 8));
      #pragma unroll
      for (int r = 0; r < 16; r++) {
        float f[8]; unpack8(wv[r], f);
        const uint32_t s2 = __shfl_sync(0xffffffff, sv, rb * 8 + (r >> 1));
        const float s1 = (r & 1) ? bf_hi(s2) : bf_lo(s2);
        #pragma unroll
        for (int j = 0; j < 8; j++) am[j] = fmaf(s1, f[j], am[j]);
      }
    }
    reinterpret_cast<float4*>(red + rd * 2048 + cw * 256)[lane * 2] = make_float4(am[0], am[1], am[2], am[3]);
    reinterpret_cast<float4*>(red + rd * 2048 + cw * 256)[lane * 2 + 1] = make_float4(am[4], am[5], am[6], am[7]);
    bar_sync(1, 256);
    float v = 0.f;
    #pragma unroll
    for (int i = 0; i < 8; i++) v += red[rd * 2048 + i * 256 + ct];
    g_mod[col0 + ct] = __float2bfloat16(v);
    bar_sync(1, 256);
    if (ct == 0) red_release(rd == 0 ? C_MOD : C_MOD2);
  }
}

__global__ void __cluster_dims__(2, 1, 1) __launch_bounds__(384, 1)
k_fused(const __grid_constant__ CUtensorMap tmC, const __grid_constant__ CUtensorMap tmH, const __grid_constant__ CUtensorMap tmWq,
        const __grid_constant__ CUtensorMap tmWk, const __grid_constant__ CUtensorMap tmWv, const __grid_constant__ CUtensorMap tmKV,
        const __grid_constant__ CUtensorMap tmWo, const __grid_constant__ CUtensorMap tmPart, const __grid_constant__ CUtensorMap tmWg,
        const __grid_constant__ CUtensorMap tmWu, const __grid_constant__ Sched sched,
        const __nv_bfloat16* __restrict__ xin, const __nv_bfloat16* __restrict__ ckv, const __nv_bfloat16* __restrict__ w_uk,
        const __nv_bfloat16* __restrict__ cvec, const __nv_bfloat16* __restrict__ w_mod,
        const __nv_bfloat16* __restrict__ w_r, const __nv_bfloat16* __restrict__ w_gate, const __nv_bfloat16* __restrict__ w_up,
        const __nv_bfloat16* __restrict__ w_down, __nv_bfloat16* __restrict__ out) {
  extern __shared__ __align__(1024) uint8_t smem_raw[];
  const uint32_t base = smem_u32(smem_raw), bars = base + SM_BAR;
  const int warp = __shfl_sync(0xffffffff, threadIdx.x >> 5, 0), wg = warp >> 2;
  const int rank = cluster_ctarank(), p = blockIdx.x >> 1;
  const int mt = (p & 7) * 2 + rank;
  const bool spare = blockIdx.x >= NCTA;
  if (!spare) {
    if (warp == 0) prefetch_tmap(&tmC);
    if (warp == 1) prefetch_tmap(&tmWk);
    if (warp == 10) bulk_prefetch(ckv + (size_t)(mt * 128 + (p >> 3) * 16) * DM, 16384);
    if (warp == 11) { const __nv_bfloat16* q = w_uk + (size_t)(mt * 32 + (threadIdx.x & 31)) * (NH * DH) + sched.khead[p][0] * 128; prefetch_l2(q); prefetch_l2(q + 64); }
    if (warp < 10) {
      #pragma unroll 1
      for (int t = warp * 8; t < warp * 8 + 8; t++)
        w_mbar_init(bars + 8 * t, t < B_WE / 8 ? 1 : t < B_RE / 8 ? 2 : t < B_RDY / 8 ? 4 : 1);
      fence_mbar_init();
    }
    cluster_arrive();
  }
  const int nitems = sched.nitems[p];
  const int ot = sched.otask[p], m = (ot & 7) * 2 + rank, grp = m * 8 + (ot >> 3);

  if (wg == 0) {
    asm volatile("setmaxnreg.dec.sync.aligned.u32 24;");
    if (spare) return;
    const int lane = threadIdx.x & 31;
    const unsigned int tag = ld_relaxed(&g_epoch) + 1;
    if (warp == 0) {
      #pragma unroll 1
      for (int kb = 0; kb < 8; kb++) {
        w_expect_tx(bars + B_AF + 8 * kb, 16384);
        tma_load_2d(base + k_addrA(kb), &tmC, bars + B_AF + 8 * kb, kb * 64, mt * 128);
        if (kb == 0) cluster_wait();
        if (kb < 6) {
          w_expect_tx(bars + B_WF + 8 * kb, 16384);
          tma_load_2d_mc(base + k_addrW(kb) + rank * 8192, &tmWk, bars + B_WF + 8 * kb, sched.khead[p][0] * 128 + rank * 64, kb * 64);
        }
      }
    } else cluster_wait();
    if (warp == 0) {
      {
        int s = 0, ph = 0;
        tma_prefetch_2d(&tmWv, sched.khead[p][0] * 128 + rank * 64, (p & 7) * 64);
        #pragma unroll 1
        for (int g = 6; g < 64; g++) {
          const int u = g >> 3, kb = g & 7;
          if (kb == 0 && u < 7) tma_prefetch_2d((u & 1) ? &tmWk : &tmWv, sched.khead[p][(u + 1) >> 1] * 128 + rank * 64, (p & 7) * 64);
          mbar_wait(bars + B_WE + 8 * s, ph);
          w_expect_tx(bars + B_WF + 8 * s, 16384);
          tma_load_2d_mc(base + k_addrW(s) + rank * 8192, (u & 1) ? &tmWv : &tmWk, bars + B_WF + 8 * s, sched.khead[p][u >> 1] * 128 + rank * 64, kb * 64);
          if (++s == 6) { s = 0; ph ^= 1; }
        }
      }
      int s = 0, ph = 0;
      auto next_entry = [&](bool load) {
        mbar_wait(bars + B_RE + 8 * s, ph);
        if (load) w_expect_tx(bars + B_RF + 8 * s, 32768); else w_arrive(bars + B_RF + 8 * s);
      };
      auto advance = [&]() { if (++s == 6) { s = 0; ph ^= 1; } };
      int vrow = -1;
      #pragma unroll 1
      for (int i = 0; i < nitems; i++) {
        const int item = sched.item[p][i], h = item >> 3, j = item & 7;
        const int row0 = j * 256 + ((i & 1) ? rank : 3 - rank) * 64, row1 = j * 256 + ((i & 1) ? 3 - rank : rank) * 64;
        mbar_wait(bars + B_RDY + 8 * (1 + i), 0);
        fence_async_global();
        #pragma unroll 1
        for (int kb = 0; kb < 8; kb++) {
          next_entry(true);
          if (i == 2) DBGP(kb);
          tma_load_2d_mc(base + s * 32768 + 16384 + rank * 8192, &tmWq, bars + B_RF + 8 * s, h * 128 + rank * 64, kb * 64);
          tma_load_2d(base + s * 32768, &tmH, bars + B_RF + 8 * s, kb * 64, row0);
          tma_load_2d(base + s * 32768 + 8192, &tmH, bars + B_RF + 8 * s, kb * 64, row1);
          advance();
        }
        #pragma unroll 1
        for (int n = 2 * j + 1; n >= 0; n--) {
          const int krow = (h * 2 + rank) * SEQ + n * 128;
          next_entry(true);
          if (i == 2 && n >= 2 * j) DBGP(8 + 2 * (2 * j + 1 - n));
          tma_load_2d_mc(base + s * 32768 + rank * 16384, &tmKV, bars + B_RF + 8 * s, 0, krow);
          advance();
          next_entry(vrow >= 0);
          if (i == 2 && n >= 2 * j) DBGP(9 + 2 * (2 * j + 1 - n));
          if (vrow >= 0) tma_load_2d_mc(base + s * 32768 + rank * 16384, &tmKV, bars + B_RF + 8 * s, 0, vrow);
          advance();
          vrow = krow + 64 * SEQ;
        }
      }
      next_entry(true);
      tma_load_2d_mc(base + s * 32768 + rank * 16384, &tmKV, bars + B_RF + 8 * s, 0, vrow);
      advance();
      const int oj = ot & 7, oc = ((ot >> 3) & 1) * 4 + rank * 2;
      #pragma unroll 1
      for (int i = 0; i < 8; i++) {
        const int h = sched.ohead[p][i];
        next_entry(true);
        tma_load_3d_mc(base + s * 32768 + rank * 16384, &tmWo, bars + B_RF + 8 * s, 0, h * 128, oc);
        advance();
        mbar_wait(bars + B_RDY + 8 * (8 + i), 0);
        fence_async_global();
        next_entry(true);
        tma_load_2d(base + s * 32768, &tmKV, bars + B_RF + 8 * s, 0, (128 + h * 2) * SEQ + oj * 256 + rank * 128);
        tma_load_2d(base + s * 32768 + 16384, &tmKV, bars + B_RF + 8 * s, 0, (129 + h * 2) * SEQ + oj * 256 + rank * 128);
        advance();
        next_entry(true);
        tma_load_3d_mc(base + s * 32768 + rank * 16384, &tmWo, bars + B_RF + 8 * s, 0, h * 128 + 64, oc);
        advance();
      }
      const int f0 = (blockIdx.x < FF / 16 ? blockIdx.x : 0) * 16;
      next_entry(true);
      #pragma unroll 1
      for (int k = 0; k < 4; k++) tma_load_2d(base + s * 32768 + k * 8192, (k & 2) ? &tmWu : &tmWg, bars + B_RF + 8 * s, f0, (k & 1) * 256);
      advance();
      next_entry(true);
      bulk_load(base + s * 32768, w_down + (size_t)f0 * DM, 16384, bars + B_RF + 8 * s);
      bulk_load(base + s * 32768 + 16384, xin + (size_t)grp * 16 * DM, 16384, bars + B_RF + 8 * s);
      advance();
      mbar_wait(bars + B_RE + 8 * s, ph);
      w_expect_tx(bars + B_RF + 8 * s, 5120);
      bulk_load(base + s * 32768, g_mod + 2 * DM, 4096, bars + B_RF + 8 * s);
      bulk_load(base + s * 32768 + 4096, w_r, 1024, bars + B_RF + 8 * s);
    } else if (warp < 3) {
      const int w = warp - 1, n1 = w * 15 + 4 + w + nitems;
      if (lane == 0) {
        #pragma unroll 1
        for (int n = w * 15; n < n1 + 2; n++) {
          #pragma unroll 1
          for (int k = 0; k < 8 * WAIT_LIM; k++) { if (mbar_try(bars + B_PUB + 8 * n, 0)) break; }
          const uint32_t msg = lds_u32(base + SM_MAIL + 4 * n);
          if (n < n1) {
            fence_async_global();
            if (msg < (unsigned)C_END) red_release(msg);
          } else {
            tma_store_3d(&tmPart, base + (msg & 0x3c000), 0, m * 128 + 64 * w, (ot >> 4) * 8 + ((ot >> 3) & 1) * 4 + 2 * (n - n1));
            bulk_commit();
          }
        }
        bulk_wait<0>();
        red_relaxed(C_PART + (m * 2 + w) * 32);
      }
      __syncwarp();
    } else {
      wait_count_lazy(C_MOD, 4 * tag);
      w_arrive(bars + B_RDY);
      #pragma unroll 1
      for (int i = 0; i < nitems; i++) {
        const int item = sched.item[p][i];
        tma_prefetch_2d(&tmWq, (item >> 3) * 128 + rank * 64, (p & 7) * 64);
        wait_count_lazy(C_H1 + (item & 7), 16 * tag);
        wait_count_lazy(C_KV + (item >> 3), 32 * tag);
        w_arrive(bars + B_RDY + 8 * (1 + i));
      }
      wait_count_lazy(C_MOD2, 8 * tag);
      #pragma unroll 1
      for (int i = 0; i < 8; i++) {
        wait_count_lazy(C_CTX + sched.ohead[p][i] * 8 + (ot & 7), 4 * tag);
        w_arrive(bars + B_RDY + 8 * (8 + i));
        if (i == 5) { for (int k = 0; k < 2; k++) tma_prefetch_3d(&tmWo, 0, sched.ohead[p][ot & 7] * 128 + k * 64, ((ot >> 3) & 1) * 4 + rank * 2); }
      }
      bulk_prefetch(xin + (size_t)grp * 16 * DM, 16 * DM * 2);
      bulk_prefetch(w_gate + (size_t)blockIdx.x * (DM * FF / NCTA), DM * FF / NCTA * 2);
      bulk_prefetch(w_up + (size_t)blockIdx.x * (DM * FF / NCTA), DM * FF / NCTA * 2);
      bulk_prefetch(w_down + (size_t)blockIdx.x * (DM * FF / NCTA), DM * FF / NCTA * 2);
      wait_count(C_PART + (m * 2 + (ot >> 5)) * 32, 8 * tag);
      w_arrive(bars + B_RDY + 8 * 7);
      DBGP(12);
      uint32_t have = 0;
      #pragma unroll 1
      for (int n = 0; n < WAIT_LIM; n++) {
        const uint4 k0 = ld_tagged2(&g_keys[lane * 4]), k1 = ld_tagged2(&g_keys[lane * 4 + 2]);
        const bool all = __all_sync(0xffffffff, k0.y == tag && k0.w == tag && k1.y == tag && k1.w == tag);
        const uint32_t kn = __reduce_max_sync(0xffffffff, max(max(k0.y == tag ? k0.x : 0u, k0.w == tag ? k0.z : 0u), max(k1.y == tag ? k1.x : 0u, k1.w == tag ? k1.z : 0u)));
        if (kn != have) {
          const uint2* rp = &g_row[((0xffffu - kn) >> 4) & 127][0][lane * 2];
          uint4 hv[4];
          #pragma unroll
          for (int i = 0; i < 4; i++) hv[i] = ld_tagged2(rp + i * 64);
          bool ok = true;
          #pragma unroll
          for (int i = 0; i < 4; i++) { ok = ok && hv[i].y == tag && hv[i].w == tag; reinterpret_cast<uint2*>(smem_raw + SM_H2)[i * 32 + lane] = make_uint2(hv[i].x, hv[i].z); }
          have = __all_sync(0xffffffff, ok) ? kn : 0;
        }
        if (all && kn == have) break;
      }
      if (lane == 0) { *reinterpret_cast<uint32_t*>(smem_raw + SM_KEY + 32) = have; if (blockIdx.x == 0) g_epoch = tag; }
      __syncwarp();
      w_arrive(bars + B_RDY + 8 * 16);
      DBGP(13);
    }
    {
      const int col = blockIdx.x * 4 + (lane & 1) * 2, src = threadIdx.x >> 1;
      uint4 ya, yb = make_uint4(0, tag, 0, tag);
      #pragma unroll 1
      for (int n = 0; n < WAIT_LIM; n++) {
        ya = ld_tagged2(&g_yll[src][col]);
        if (src + 64 < FF / 16) yb = ld_tagged2(&g_yll[src + 64][col]);
        if (n == 0) mbar_wait(bars + B_RDY + 8 * 16, 0);
        if (__all_sync(0xffffffff, ya.y == tag && ya.w == tag && yb.y == tag && yb.w == tag)) break;
      }
      float y0 = __uint_as_float(ya.x) + __uint_as_float(yb.x), y1 = __uint_as_float(ya.z) + __uint_as_float(yb.z);
      #pragma unroll
      for (int o = 2; o < 32; o <<= 1) { y0 += __shfl_xor_sync(0xffffffff, y0, o); y1 += __shfl_xor_sync(0xffffffff, y1, o); }
      float2* s_y = reinterpret_cast<float2*>(smem_raw + SM_KEY + 64);
      if (lane < 2) s_y[warp * 2 + lane] = make_float2(y0, y1);
      const uint32_t gbest = lds_u32(base + SM_KEY + 32);
      const int row = (int)(0xffffu - (gbest & 0xffffu)) & (SEQ - 1);
      uint2 xx = make_uint2(0, 0);
      if (warp == 3) {
        #pragma unroll 1
        for (int n = 0; n < WAIT_LIM; n++) { xx = ld_tagged(&g_row[row >> 4][1][col >> 1]); if (xx.y == tag) break; }
      }
      bar_sync(6, 128);
      if (warp == 3 && lane < 2) {
        y0 = 0.f; y1 = 0.f;
        #pragma unroll
        for (int i = 0; i < 4; i++) { const float2 v = s_y[i * 2 + lane]; y0 += v.x; y1 += v.y; }
        const uint32_t sb16 = gbest & 0xffff0000u, hh = lds_u32(base + SM_H2 + col * 2), gbf = __ldcg(reinterpret_cast<const uint32_t*>(g_mod + 5 * DM + col));
        const float rsel = __uint_as_float((sb16 & 0x80000000u) ? (sb16 & 0x7fffffffu) : (~sb16 & 0xffff0000u));
        const float rs = rbf(__fdividef(1.f, 1.f + __expf(-rsel)));
        const float o0 = bf_lo(xx.x) + rbf(bf_lo(gbf) * rbf(bf_lo(hh) + rbf(rbf(y0) * rs)));
        const float o1 = bf_hi(xx.x) + rbf(bf_hi(gbf) * rbf(bf_hi(hh) + rbf(rbf(y1) * rs)));
        *reinterpret_cast<uint32_t*>(out + (size_t)row * DM + col) = pack_bf16(o0, o1);
      }
      DBGP(14);
    }
    __syncwarp();
    cluster_arrive();
    cluster_wait();
  } else {
    asm volatile("setmaxnreg.inc.sync.aligned.u32 240;");
    if (spare) { mod_cta(smem_raw, cvec, w_mod); return; }
    Ctx x;
    x.w = wg - 1; x.wtid = threadIdx.x & 127; x.base = base; x.bars = bars; x.nev = 0;
    const int w = x.w, wtid = x.wtid, warp4 = warp & 3, lane = threadIdx.x & 31;
    x.rel = mapa(bars, (warp4 & 1) ^ 1);
    x.tmask = 16 * warp4 + (lane >> 2) - 2 * (lane & 3);
    cluster_wait();
    DBG(1);
    {
      Row xn[2][2];
      const int lrow = blockIdx.x * 16 + warp4 * 4;
      if (w == 1) {
        bar_arrive(1, 256);
        mbar_wait(bars + B_WF, 0);
        Row xr[2][2];
        #pragma unroll
        for (int r = 0; r < 4; r++) xr[r >> 1][r & 1] = ldg_row(xin + (size_t)(lrow + r) * DM, lane);
        #pragma unroll 1
        for (int k = 0; k < 2; k++) {
          xn[0][0] = xn[1][0]; xn[0][1] = xn[1][1];
          layer_norm2(xr[0], xn[1]);
          xr[0][0] = xr[1][0]; xr[0][1] = xr[1][1];
        }
      }
      DBG(2);
      float acc0[64], acc1[64];
      const float sc = w == 0 ? 0.08838834764831845f * 1.4426950408889634f : 1.f;
      int s = 2 * w, ph = w;
      #pragma unroll 1
      for (int u = w; u < 8; u += 2) {
        bar_sync(1 + w, 256);
        DBG(4 + (u >> 1) * 3);
        int ps = 0;
        #pragma unroll 1
        for (int kb = 0; kb < 8; kb++) {
          if (u < 2) mbar_wait(bars + B_AF + 8 * kb, 0);
          mbar_wait(bars + B_WF + 8 * s, ph);
          const uint32_t da = desc_lo(base + k_addrA(kb), 16), dw = desc_lo(base + k_addrW(s), 8192);
          wgmma_fence();
          kblock_n128<0>(acc0, da, dw, kb != 0);
          kblock_n128<512>(acc1, da, dw, kb != 0);
          wgmma_commit();
          if (kb == 7) bar_arrive(1 + (w ^ 1), 256);
          if (kb > 0) {
            wgmma_wait<1>();
            mbar_arrive_remote_if(x.rel + B_WE + 8 * ps, wtid == 32 || wtid == 64);
            if (u == 7 && !(kb & 1)) {
              ring_release(x, kb == 2 ? 0 : kb - 3, false);
              if (kb > 2) ring_release(x, kb - 2, false);
            }
          }
          ps = s;
          if (++s == 6) { s = 0; ph ^= 1; }
        }
        wgmma_wait<0>();
        fence_regs(acc0); fence_regs(acc1);
        DBG(5 + (u >> 1) * 3);
        mbar_arrive_remote_if(x.rel + B_WE + 8 * ps, wtid == 32 || wtid == 64);
        if (u == 6) { for (int k = 0; k < 5; k++) ring_release(x, k, false); }
        if (u >= 6) ring_release(x, 5, false);
        s += 2; ph ^= 1; if (s >= 6) { s -= 6; ph ^= 1; }
        if (u == LN_AT) {
          mbar_wait(bars + B_RDY, 0);
          const Row sa = ldca_row(g_mod, lane), ca1 = one_plus(ldca_row(g_mod + DM, lane));
          #pragma unroll
          for (int r = 0; r < 4; r++) store_row(g_h1 + (size_t)(lrow + r) * DM, lane, fma_row(xn[r >> 1][r & 1], ca1, sa));
          publish(x, C_H1 + (blockIdx.x >> 4));
        }
        const int h = sched.khead[p][u >> 1];
        __nv_bfloat16* dst = g_kvc + ((size_t)(w * 64 + h * 2) * SEQ + mt * 128 + warp4 * 16 + (lane >> 2)) * 64 + (lane & 3) * 8;
        uint32_t D[32];
        pack_tile(acc0, D, sc, sc); store_tile(dst + 64 * 64, D);
        pack_tile(acc1, D, sc, sc); store_tile(dst, D);
        publish(x, C_KV + h);
        DBG(6 + (u >> 1) * 3);
      }
    }
    int e = 0;
    attention(x, e, sched.item[p], nitems, rank);
    DBG(100);
    const int cw = w * 4 + warp4, ct = threadIdx.x - 128;
    const int row0 = grp * 16 + cw * 2;
    const bool moe_cta = blockIdx.x < FF / 16;
    const unsigned int tag = ld_relaxed(&g_epoch) + 1;
    {
      float acc[128];
      #pragma unroll 1
      for (int i = 0; i < 8; i++) {
        const int ea = ring_add(e, 1), eb = ring_add(e, 2);
        const uint32_t da = desc_lo(base + ring_slot(ea) * 32768 + w * 8192, 16);
        ring_wait_full(bars, e);
        ring_wait_full(bars, ea);
        uint32_t db = desc_lo(base + ring_slot(e) * 32768, 8192);
        wgmma_fence();
        kblock_n256<0>(acc, da, db, i != 0);
        wgmma_commit();
        if (i > 0) { wgmma_wait<1>(); ring_release(x, ring_add(e, 10), false); ring_release(x, ring_add(e, 11), false); }
        ring_wait_full(bars, eb);
        db = desc_lo(base + ring_slot(eb) * 32768, 8192);
        wgmma_fence();
        kblock_n256<1024>(acc, da, db, 1);
        wgmma_commit();
        wgmma_wait<1>();
        ring_release(x, e, false);
        e = ring_add(e, 3);
      }
      const int es = ring_add(e, 9);
      if (w == 1) mbar_wait(bars + B_RE + 8 * ring_slot(es), es < 6);
      wgmma_wait<0>();
      fence_regs(acc);
      DBG(101);
      __syncwarp();
      cluster_arrive();
      const uint32_t stg = base + (w == 0 ? SM_Q : ring_slot(es) * 32768);
      const int srow = 16 * warp4 + (lane & 7) + 8 * ((lane >> 3) & 1);
      const uint32_t sb = stg + srow * 128, swz = (((lane >> 4) ^ (srow & 7)) << 4);
      #pragma unroll
      for (int c = 0; c < 2; c++) {
        #pragma unroll
        for (int j = 16 * c; j < 16 * c + 16; j += 2)
          stsm_x4(sb + (j >> 3) * 8192 + (((j & 7) << 4) ^ swz),
                  pack_bf16(acc[4*j+0], acc[4*j+1]), pack_bf16(acc[4*j+2], acc[4*j+3]), pack_bf16(acc[4*j+4], acc[4*j+5]), pack_bf16(acc[4*j+6], acc[4*j+7]));
        fence_async_smem();
        publish(x, stg - base + c * 16384);
      }
      DBG(102);
    }
    const uint32_t sW = base + ring_slot(e) * 32768, sD = base + ring_slot(ring_add(e, 1)) * 32768, sM = base + ring_slot(ring_add(e, 2)) * 32768;
    ring_wait_full(bars, e); ring_wait_full(bars, ring_add(e, 1)); ring_wait_full(bars, ring_add(e, 2));
    Row x1[2];
    #pragma unroll
    for (int r = 0; r < 2; r++) x1[r] = lds_row(sD + 16384 + (cw * 2 + r) * 1024, lane);
    const Row ga = lds_row(sM, lane), sb = lds_row(sM + 1024, lane), cb1 = one_plus(lds_row(sM + 2048, lane)), gb = lds_row(sM + 3072, lane), wr = lds_row(sM + 4096, lane);
    uint4 wgv[4], wuv[4]; uint32_t wdv[16];
    #pragma unroll
    for (int r = 0; r < 4; r++) { wgv[r] = lds_v4(sW + r * 4096 + ct * 16); wuv[r] = lds_v4(sW + 16384 + r * 4096 + ct * 16); }
    #pragma unroll
    for (int r = 0; r < 16; r++) wdv[r] = lds_u32(sD + r * 1024 + ct * 4);
    DBG(103);
    mbar_wait(bars + B_RDY + 8 * 7, 0);
    DBG(104);
    Row h2[2];
    uint32_t key[2];
    {
      uint4 pv[2][4][2];
      const uint4* pp = reinterpret_cast<const uint4*>(g_part + ((size_t)(lane >> 3) * SEQ + row0) * 64) + (lane & 7);
      #pragma unroll
      for (int r = 0; r < 2; r++)
        #pragma unroll
        for (int q = 0; q < 8; q++) pv[r][q >> 1][q & 1] = __ldcg(pp + (size_t)q * (4 * SEQ * 8) + r * 8);
      #pragma unroll
      for (int r = 0; r < 2; r++) {
        Row av;
        #pragma unroll
        for (int i = 0; i < 2; i++) {
          av.v[4*i]   = add2(add2(pv[r][0][i].x, pv[r][1][i].x), add2(pv[r][2][i].x, pv[r][3][i].x));
          av.v[4*i+1] = add2(add2(pv[r][0][i].y, pv[r][1][i].y), add2(pv[r][2][i].y, pv[r][3][i].y));
          av.v[4*i+2] = add2(add2(pv[r][0][i].z, pv[r][1][i].z), add2(pv[r][2][i].z, pv[r][3][i].z));
          av.v[4*i+3] = add2(add2(pv[r][0][i].w, pv[r][1][i].w), add2(pv[r][2][i].w, pv[r][3][i].w));
        }
        x1[r] = fma_row(ga, av, x1[r]);
      }
      layer_norm2(x1, h2);
      float sc[2] = {0.f, 0.f};
      #pragma unroll
      for (int r = 0; r < 2; r++) {
        h2[r] = fma_row(h2[r], cb1, sb);
        #pragma unroll
        for (int i = 0; i < 8; i++) sc[r] = fmaf(bf_hi(h2[r].v[i]), bf_hi(wr.v[i]), fmaf(bf_lo(h2[r].v[i]), bf_lo(wr.v[i]), sc[r]));
      }
      #pragma unroll
      for (int o = 16; o > 0; o >>= 1) { sc[0] += __shfl_xor_sync(0xffffffff, sc[0], o); sc[1] += __shfl_xor_sync(0xffffffff, sc[1], o); }
      #pragma unroll
      for (int r = 0; r < 2; r++) {
        const uint32_t rb = pack_bf16(0.f, sc[r]);
        key[r] = (((rb & 0x80000000u) ? ~rb : (rb | 0x80000000u)) & 0xffff0000u) | (0xffffu - (uint32_t)(row0 + r));
      }
    }
    DBG(105);
    float* s_red = reinterpret_cast<float*>(smem_raw + SM_RED);
    uint32_t* s_key = reinterpret_cast<uint32_t*>(smem_raw + SM_KEY);
    const int rb = key[1] > key[0];
    const uint32_t wbest = rb ? key[1] : key[0];
    if (lane == 0) s_key[cw] = wbest;
    bar_sync(5, 256);
    const uint32_t cbest = __reduce_max_sync(0xffffffff, s_key[lane & 7]);
    Row ob, hb, xb;
    #pragma unroll
    for (int i = 0; i < 8; i++) { hb.v[i] = rb ? h2[1].v[i] : h2[0].v[i]; xb.v[i] = rb ? x1[1].v[i] : x1[0].v[i]; }
    if (wbest == cbest) {
      if (lane == 0) st_tagged(&g_keys[grp], cbest, tag);
      #pragma unroll
      for (int i = 0; i < 4; i++) st_tagged2(&g_row[grp][0][(i >> 1) * 128 + lane * 4 + (i & 1) * 2], hb.v[2*i], hb.v[2*i+1], tag);
      #pragma unroll
      for (int i = 0; i < 4; i++) st_tagged2(&g_row[grp][1][(i >> 1) * 128 + lane * 4 + (i & 1) * 2], xb.v[2*i], xb.v[2*i+1], tag);
    }
    DBG(106);
    #pragma unroll
    for (int i = 0; i < 8; i++) { ob.v[i] = fma2(gb.v[i], rb ? h2[0].v[i] : h2[1].v[i], rb ? x1[0].v[i] : x1[1].v[i]); }
    store_row(out + (size_t)(row0 + 1 - rb) * DM, lane, ob);
    ob = fma_row(gb, hb, xb);
    if (wbest != cbest) store_row(out + (size_t)(row0 + rb) * DM, lane, ob);
    mbar_wait(bars + B_RDY + 8 * 16, 0);
    DBG(107);
    if (moe_cta) {
      float hs[4];
      #pragma unroll
      for (int r = 0; r < 4; r++) hs[r] = __bfloat162float(reinterpret_cast<const __nv_bfloat16*>(smem_raw + SM_H2)[(ct >> 1) + 128 * r]);
      float ag[8] = {0, 0, 0, 0, 0, 0, 0, 0}, au[8] = {0, 0, 0, 0, 0, 0, 0, 0};
      #pragma unroll
      for (int r = 0; r < 4; r++) {
        float fg[8], fu[8]; unpack8(wgv[r], fg); unpack8(wuv[r], fu);
        #pragma unroll
        for (int j = 0; j < 8; j++) { ag[j] = fmaf(hs[r], fg[j], ag[j]); au[j] = fmaf(hs[r], fu[j], au[j]); }
      }
      #pragma unroll
      for (int j = 0; j < 8; j++) { const bool hi = lane & 16; ag[j] = (hi ? au[j] : ag[j]) + __shfl_xor_sync(0xffffffff, hi ? ag[j] : au[j], 16); }
      #pragma unroll
      for (int j = 0; j < 4; j++) { const bool hi = lane & 8; ag[j] = (hi ? ag[j+4] : ag[j]) + __shfl_xor_sync(0xffffffff, hi ? ag[j] : ag[j+4], 8); }
      #pragma unroll
      for (int j = 0; j < 2; j++) { const bool hi = lane & 4; ag[j] = (hi ? ag[j+2] : ag[j]) + __shfl_xor_sync(0xffffffff, hi ? ag[j] : ag[j+2], 4); }
      { const bool hi = lane & 2; ag[0] = (hi ? ag[1] : ag[0]) + __shfl_xor_sync(0xffffffff, hi ? ag[0] : ag[1], 2); }
      s_red[cw * 32 + (lane & 16) + (lane & 1) * 8 + ((lane >> 1) & 7)] = ag[0];
      bar_sync(5, 256);
      float g = 0.f;
      #pragma unroll
      for (int i = 0; i < 8; i++) g += s_red[i * 32 + lane];
      g = rbf(g);
      const float u = __shfl_down_sync(0xffffffff, g, 16);
      const float act = rbf(rbf(__fdividef(g, 1.f + __expf(-g))) * u);
      float y0 = 0.f, y1 = 0.f;
      #pragma unroll
      for (int r = 0; r < 16; r++) { const float av = __shfl_sync(0xffffffff, act, r); y0 = fmaf(av, bf_lo(wdv[r]), y0); y1 = fmaf(av, bf_hi(wdv[r]), y1); }
      st_tagged2(&g_yll[blockIdx.x][2 * ct], __float_as_uint(y0), __float_as_uint(y1), tag);
    }
    DBG(108);
    if (wbest == cbest && wbest != s_key[8]) store_row(out + (size_t)(row0 + rb) * DM, lane, ob);
    DBG(109);
    __syncwarp();
    cluster_wait();
  }
}

typedef CUresult (*EncodeFn)(CUtensorMap*, CUtensorMapDataType, cuuint32_t, void*, const cuuint64_t*, const cuuint64_t*, const cuuint32_t*,
                             const cuuint32_t*, CUtensorMapInterleave, CUtensorMapSwizzle, CUtensorMapL2promotion, CUtensorMapFloatOOBfill);

struct HostState {
  bool ready = false;
  EncodeFn encode = nullptr;
  CUtensorMap tmC, tmH, tmWq, tmWk, tmWv, tmKV, tmWo, tmPart, tmWg, tmWu;
  Sched sched;
};

void make_map(EncodeFn enc, CUtensorMap* m, const void* ptr, int rank, const cuuint64_t* dims, const cuuint64_t* strides, const cuuint32_t* box, bool swizzle = true) {
  const cuuint32_t es[3] = {1, 1, 1};
  enc(m, CU_TENSOR_MAP_DATA_TYPE_BFLOAT16, rank, const_cast<void*>(ptr), dims, strides, box, es, CU_TENSOR_MAP_INTERLEAVE_NONE,
      swizzle ? CU_TENSOR_MAP_SWIZZLE_128B : CU_TENSOR_MAP_SWIZZLE_NONE, swizzle ? CU_TENSOR_MAP_L2_PROMOTION_L2_128B : CU_TENSOR_MAP_L2_PROMOTION_NONE, CU_TENSOR_MAP_FLOAT_OOB_FILL_NONE);
}
void make_2d(EncodeFn enc, CUtensorMap* m, const void* ptr, int rows, int cols, int box_rows) {
  const cuuint64_t dims[2] = {(cuuint64_t)cols, (cuuint64_t)rows}, strides[1] = {(cuuint64_t)cols * 2};
  const cuuint32_t box[2] = {64, (cuuint32_t)box_rows};
  make_map(enc, m, ptr, 2, dims, strides, box);
}
void make_3d(EncodeFn enc, CUtensorMap* m, const void* ptr, int rows, int chunks, size_t row_stride, size_t chunk_stride) {
  const cuuint64_t dims[3] = {64, (cuuint64_t)rows, (cuuint64_t)chunks}, strides[2] = {row_stride, chunk_stride};
  const cuuint32_t box[3] = {64, 64, 2};
  make_map(enc, m, ptr, 3, dims, strides, box);
}

void make_ffn(EncodeFn enc, CUtensorMap* m, const void* ptr) {
  const cuuint64_t dims[2] = {(cuuint64_t)FF, (cuuint64_t)DM}, strides[1] = {(cuuint64_t)FF * 2};
  const cuuint32_t box[2] = {16, 256};
  make_map(enc, m, ptr, 2, dims, strides, box, false);
}

#define KORDER 2, 3, 0, 1
void build_sched(Sched& s) {
  memset(&s, 0, sizeof(s));
  const int korder[4] = {KORDER};
  for (int p = 0; p < NCTA / 2; p++) {
    const int hh = p >> 3, a = p & 7, b = (a + 4) & 7;
    for (int k = 0; k < 4; k++) s.khead[p][k] = (uint8_t)(korder[k] * 8 + hh);
    const int js[4] = {a, b, 7 - a, 7 - b};
    s.nitems[p] = 4;
    for (int r = 0; r < 4; r++) s.item[p][r] = (uint8_t)((r * 8 + hh) * 8 + js[r]);
    const int kq = p >> 4;
    s.otask[p] = (uint8_t)(p & 63);
    for (int k = 0; k < 8; k++) s.ohead[p][k] = (uint8_t)((k >> 1) * 8 + kq * 2 + (k & 1));
  }
}

}

extern "C" void kernel_launch(void* const* d_in, const int* in_sizes, int n_in, void* d_out, int out_size) {
  (void)in_sizes; (void)n_in; (void)out_size;
  const __nv_bfloat16* x     = (const __nv_bfloat16*)d_in[0];
  const __nv_bfloat16* ckv   = (const __nv_bfloat16*)d_in[1];
  const __nv_bfloat16* w_q   = (const __nv_bfloat16*)d_in[2];
  const __nv_bfloat16* w_uk  = (const __nv_bfloat16*)d_in[3];
  const __nv_bfloat16* w_uv  = (const __nv_bfloat16*)d_in[4];
  const __nv_bfloat16* w_o   = (const __nv_bfloat16*)d_in[5];
  const __nv_bfloat16* w_r   = (const __nv_bfloat16*)d_in[7];
  const __nv_bfloat16* w_g   = (const __nv_bfloat16*)d_in[8];
  const __nv_bfloat16* w_u   = (const __nv_bfloat16*)d_in[9];
  const __nv_bfloat16* w_d   = (const __nv_bfloat16*)d_in[10];
  const __nv_bfloat16* cvec  = (const __nv_bfloat16*)d_in[11];
  const __nv_bfloat16* w_mod = (const __nv_bfloat16*)d_in[12];
  __nv_bfloat16* out = (__nv_bfloat16*)d_out;

  static HostState st;
  if (!st.ready) {
    void* fn = nullptr; cudaDriverEntryPointQueryResult qr;
    cudaGetDriverEntryPoint("cuTensorMapEncodeTiled", &fn, cudaEnableDefault, &qr);
    st.encode = (EncodeFn)fn;
    cudaFuncSetAttribute(k_fused, cudaFuncAttributeMaxDynamicSharedMemorySize, SMEM);
    build_sched(st.sched);
    void *p_kvc, *p_h1, *p_part;
    cudaGetSymbolAddress(&p_kvc, g_kvc); cudaGetSymbolAddress(&p_h1, g_h1); cudaGetSymbolAddress(&p_part, g_part);
    make_2d(st.encode, &st.tmH, p_h1, SEQ, DM, 64);
    make_2d(st.encode, &st.tmKV, p_kvc, 192 * SEQ, 64, 128);
    make_3d(st.encode, &st.tmPart, p_part, SEQ, 32, 128, (size_t)SEQ * 128);
    st.ready = true;
  }
  make_2d(st.encode, &st.tmC, ckv, SEQ, DM, 128);
  make_2d(st.encode, &st.tmWq, w_q, DM, NH * DH, 64);
  make_2d(st.encode, &st.tmWk, w_uk, DM, NH * DH, 64);
  make_2d(st.encode, &st.tmWv, w_uv, DM, NH * DH, 64);
  make_3d(st.encode, &st.tmWo, w_o, NH * DH, DM / 64, (size_t)DM * 2, 128);
  make_ffn(st.encode, &st.tmWg, w_g);
  make_ffn(st.encode, &st.tmWu, w_u);

  k_fused<<<NGRID, 384, SMEM, cudaStreamPerThread>>>(st.tmC, st.tmH, st.tmWq, st.tmWk, st.tmWv, st.tmKV, st.tmWo, st.tmPart, st.tmWg, st.tmWu, st.sched,
                                                     x, ckv, w_uk, cvec, w_mod, w_r, w_g, w_u, w_d, out);
}
```

```cpp
#include <cuda_runtime.h>
#include <cuda_bf16.h>
#include <cuda.h>
#include <stdint.h>
#include <string.h>
#include <math.h>

namespace {

constexpr int SEQ = 2048, DM = 512, NH = 32, DH = 128, FF = 1792;
constexpr int NCTA = 128, NGRID = 132;

__device__ __nv_bfloat16 g_kvc[192 * SEQ * 64];
__device__ __nv_bfloat16 g_h1[SEQ * DM];
__device__ __nv_bfloat16 g_part[32 * SEQ * 64];
__device__ __align__(16) __nv_bfloat16 g_mod[6 * DM];
constexpr int C_MOD = 0, C_MOD2 = 16, C_H1 = 32, C_KV = 64, C_CTX = 128, C_END = 384;
__device__ unsigned int g_cnt[C_END];
__device__ unsigned int g_epoch;
__device__ __align__(128) unsigned int g_pflag[32][32];
__device__ __align__(128) uint2 g_keys[128][4];
__device__ __align__(16) uint2 g_row[128][2][DM / 2];
__device__ __align__(16) uint2 g_yll[FF / 16][DM];

#define DBG(i)
#define DBGP(i)

__device__ __forceinline__ uint32_t smem_u32(const void* p) { return (uint32_t)__cvta_generic_to_shared(p); }
__device__ __forceinline__ int wg_tid() { int t; asm volatile("mov.u32 %0, %%tid.x;" : "=r"(t)); return t & 127; }
__device__ __forceinline__ uint32_t clk32() { uint32_t c; asm volatile("mov.u32 %0, %%clock;" : "=r"(c)); return c; }
__device__ __forceinline__ void mbar_arrive(uint32_t bar) { asm volatile("mbarrier.arrive.shared::cta.b64 _, [%0];" :: "r"(bar) : "memory"); }
__device__ __forceinline__ uint32_t mapa(uint32_t addr, uint32_t cta) { uint32_t r; asm("mapa.shared::cluster.u32 %0, %1, %2;" : "=r"(r) : "r"(addr), "r"(cta)); return r; }
__device__ __forceinline__ void mbar_arrive_remote_if(uint32_t cluster_addr, bool pred) {
  asm volatile("{\n.reg .pred p;\nsetp.ne.u32 p, %1, 0;\n@p mbarrier.arrive.shared::cluster.b64 _, [%0];\n}" :: "r"(cluster_addr), "r"((uint32_t)pred) : "memory");
}
__device__ __forceinline__ bool mbar_try(uint32_t bar, uint32_t parity) {
  uint32_t done;
  asm volatile("{\n.reg .pred p;\nmbarrier.try_wait.parity.shared::cta.b64 p, [%1], %2;\nselp.u32 %0, 1, 0, p;\n}" : "=r"(done) : "r"(bar), "r"(parity) : "memory");
  return done;
}
#define WAIT_LIM (1 << 14)
__device__ __forceinline__ void mbar_wait(uint32_t bar, uint32_t parity) {
  #pragma unroll 1
  for (int n = 0; n < WAIT_LIM; n++) { if (mbar_try(bar, parity)) break; }
}
__device__ __forceinline__ unsigned int ld_acquire(const unsigned int* p) {
  unsigned int v; asm volatile("ld.acquire.gpu.global.u32 %0, [%1];" : "=r"(v) : "l"(p) : "memory"); return v;
}
__device__ __forceinline__ unsigned int ld_relaxed(const unsigned int* p) {
  unsigned int v; asm volatile("ld.relaxed.gpu.global.u32 %0, [%1];" : "=r"(v) : "l"(p) : "memory"); return v;
}
__device__ __forceinline__ void wait_count_lazy(int idx, unsigned int target) {
  #pragma unroll 1
  for (int n = 0; n < WAIT_LIM; n++) { if ((int)(ld_relaxed(&g_cnt[idx]) - target) >= 0) break; __nanosleep(100); }
  ld_acquire(&g_cnt[idx]);
}
__device__ __forceinline__ uint4 ld_tagged2(const void* p) {
  uint4 v;
  asm volatile("{\n.reg .b64 a, b;\nld.relaxed.gpu.global.v2.u64 {a, b}, [%4];\nmov.b64 {%0, %1}, a;\nmov.b64 {%2, %3}, b;\n}"
    : "=r"(v.x), "=r"(v.y), "=r"(v.z), "=r"(v.w) : "l"(p) : "memory");
  return v;
}
__device__ __forceinline__ uint2 ld_tagged(const void* p) {
  uint2 v; asm volatile("{\n.reg .b64 a;\nld.relaxed.gpu.global.u64 a, [%2];\nmov.b64 {%0, %1}, a;\n}" : "=r"(v.x), "=r"(v.y) : "l"(p) : "memory"); return v;
}
__device__ __forceinline__ void st_tagged2(void* p, uint32_t a, uint32_t b, uint32_t tag) {
  asm volatile("{\n.reg .b64 a, b;\nmov.b64 a, {%1, %3};\nmov.b64 b, {%2, %3};\nst.relaxed.gpu.global.v2.u64 [%0], {a, b};\n}" :: "l"(p), "r"(a), "r"(b), "r"(tag) : "memory");
}
__device__ __forceinline__ void st_tagged(void* p, uint32_t a, uint32_t tag) {
  asm volatile("{\n.reg .b64 a;\nmov.b64 a, {%1, %2};\nst.relaxed.gpu.global.u64 [%0], a;\n}" :: "l"(p), "r"(a), "r"(tag) : "memory");
}
__device__ __forceinline__ void stg_v4(void* p, uint32_t a, uint32_t b, uint32_t c, uint32_t d) {
  asm volatile("st.global.v4.u32 [%0], {%1, %2, %3, %4};" :: "l"(p), "r"(a), "r"(b), "r"(c), "r"(d) : "memory");
}
__device__ __forceinline__ uint4 lds_v4(uint32_t addr) {
  uint4 v; asm volatile("ld.shared.v4.u32 {%0, %1, %2, %3}, [%4];" : "=r"(v.x), "=r"(v.y), "=r"(v.z), "=r"(v.w) : "r"(addr) : "memory"); return v;
}
__device__ __forceinline__ uint32_t lds_u32(uint32_t addr) { uint32_t v; asm volatile("ld.shared.u32 %0, [%1];" : "=r"(v) : "r"(addr) : "memory"); return v; }
__device__ __forceinline__ void sts_v4(uint32_t addr, uint32_t a, uint32_t b, uint32_t c, uint32_t d) {
  asm volatile("st.shared.v4.u32 [%0], {%1, %2, %3, %4};" :: "r"(addr), "r"(a), "r"(b), "r"(c), "r"(d) : "memory");
}
#define ELECT "{\n.reg .pred p;\nelect.sync _|p, 0xffffffff;\n@p "
__device__ __forceinline__ void w_mbar_init(uint32_t bar, uint32_t cnt) { asm volatile(ELECT "mbarrier.init.shared::cta.b64 [%0], %1;\n}" :: "r"(bar), "r"(cnt) : "memory"); }
__device__ __forceinline__ void w_expect_tx(uint32_t bar, uint32_t bytes) { asm volatile(ELECT "mbarrier.arrive.expect_tx.shared::cta.b64 _, [%0], %1;\n}" :: "r"(bar), "r"(bytes) : "memory"); }
__device__ __forceinline__ void w_arrive(uint32_t bar) { asm volatile(ELECT "mbarrier.arrive.shared::cta.b64 _, [%0];\n}" :: "r"(bar) : "memory"); }
__device__ __forceinline__ void tma_load_2d(uint32_t dst, const CUtensorMap* tm, uint32_t bar, int c0, int c1) {
  asm volatile(ELECT "cp.async.bulk.tensor.2d.shared::cluster.global.mbarrier::complete_tx::bytes [%0], [%1, {%3, %4}], [%2];\n}"
    :: "r"(dst), "l"(tm), "r"(bar), "r"(c0), "r"(c1) : "memory");
}
__device__ __forceinline__ void tma_load_2d_mc(uint32_t dst, const CUtensorMap* tm, uint32_t bar, int c0, int c1) {
  asm volatile(ELECT "cp.async.bulk.tensor.2d.shared::cluster.global.mbarrier::complete_tx::bytes.multicast::cluster [%0], [%1, {%3, %4}], [%2], %5;\n}"
    :: "r"(dst), "l"(tm), "r"(bar), "r"(c0), "r"(c1), "h"((uint16_t)3) : "memory");
}
__device__ __forceinline__ void tma_load_3d(uint32_t dst, const CUtensorMap* tm, uint32_t bar, int c0, int c1, int c2) {
  asm volatile(ELECT "cp.async.bulk.tensor.3d.shared::cluster.global.mbarrier::complete_tx::bytes [%0], [%1, {%3, %4, %5}], [%2];\n}"
    :: "r"(dst), "l"(tm), "r"(bar), "r"(c0), "r"(c1), "r"(c2) : "memory");
}
__device__ __forceinline__ void tma_load_3d_mc(uint32_t dst, const CUtensorMap* tm, uint32_t bar, int c0, int c1, int c2) {
  asm volatile(ELECT "cp.async.bulk.tensor.3d.shared::cluster.global.mbarrier::complete_tx::bytes.multicast::cluster [%0], [%1, {%3, %4, %5}], [%2], %6;\n}"
    :: "r"(dst), "l"(tm), "r"(bar), "r"(c0), "r"(c1), "r"(c2), "h"((uint16_t)3) : "memory");
}
__device__ __forceinline__ void bulk_load(uint32_t dst, const void* src, uint32_t bytes, uint32_t bar) {
  asm volatile(ELECT "cp.async.bulk.shared::cluster.global.mbarrier::complete_tx::bytes [%0], [%1], %2, [%3];\n}" :: "r"(dst), "l"(src), "r"(bytes), "r"(bar) : "memory");
}
__device__ __forceinline__ void tma_prefetch_2d(const CUtensorMap* tm, int c0, int c1) {
  asm volatile(ELECT "cp.async.bulk.prefetch.tensor.2d.L2.global [%0, {%1, %2}];\n}" :: "l"(tm), "r"(c0), "r"(c1) : "memory");
}
__device__ __forceinline__ void tma_prefetch_3d(const CUtensorMap* tm, int c0, int c1, int c2) {
  asm volatile(ELECT "cp.async.bulk.prefetch.tensor.3d.L2.global [%0, {%1, %2, %3}];\n}" :: "l"(tm), "r"(c0), "r"(c1), "r"(c2) : "memory");
}
__device__ __forceinline__ void bulk_prefetch(const void* p, uint32_t bytes) {
  asm volatile(ELECT "cp.async.bulk.prefetch.L2.global [%0], %1;\n}" :: "l"(p), "r"(bytes) : "memory");
}
__device__ __forceinline__ void tma_store_3d(const CUtensorMap* tm, uint32_t src, int c0, int c1, int c2) {
  asm volatile("cp.async.bulk.tensor.3d.global.shared::cta.bulk_group [%0, {%2, %3, %4}], [%1];"
    :: "l"(tm), "r"(src), "r"(c0), "r"(c1), "r"(c2) : "memory");
}
__device__ __forceinline__ void st_release(unsigned int* p, unsigned int v) { asm volatile("st.release.gpu.global.u32 [%0], %1;" :: "l"(p), "r"(v) : "memory"); }
__device__ __forceinline__ void red_release(int idx) { asm volatile("red.release.gpu.global.add.u32 [%0], 1;" :: "l"(&g_cnt[idx]) : "memory"); }
__device__ __forceinline__ void prefetch_tmap(const CUtensorMap* tm) { asm volatile("prefetch.tensormap [%0];" :: "l"(tm) : "memory"); }
__device__ __forceinline__ void bulk_commit() { asm volatile("cp.async.bulk.commit_group;" ::: "memory"); }
template<int N> __device__ __forceinline__ void bulk_wait() { asm volatile("cp.async.bulk.wait_group %0;" :: "n"(N) : "memory"); }
__device__ __forceinline__ void bar_sync(int id, int n) { asm volatile("bar.sync %0, %1;" :: "r"(id), "r"(n) : "memory"); }
__device__ __forceinline__ void bar_arrive(int id, int n) { asm volatile("bar.arrive %0, %1;" :: "r"(id), "r"(n) : "memory"); }
__device__ __forceinline__ void fence_async_smem() { asm volatile("fence.proxy.async.shared::cta;" ::: "memory"); }
__device__ __forceinline__ void fence_async_global() { asm volatile("fence.proxy.async.global;" ::: "memory"); }
__device__ __forceinline__ void fence_mbar_init() { asm volatile("fence.mbarrier_init.release.cluster;" ::: "memory"); }
__device__ __forceinline__ void cluster_arrive() { asm volatile("barrier.cluster.arrive.relaxed.aligned;" ::: "memory"); }
__device__ __forceinline__ void cluster_wait() { asm volatile("barrier.cluster.wait.aligned;" ::: "memory"); }
__device__ __forceinline__ uint32_t cluster_ctarank() { uint32_t r; asm volatile("mov.u32 %0, %%cluster_ctarank;" : "=r"(r)); return r; }
__device__ __forceinline__ void wgmma_fence() { asm volatile("wgmma.fence.sync.aligned;" ::: "memory"); }
__device__ __forceinline__ void wgmma_commit() { asm volatile("wgmma.commit_group.sync.aligned;" ::: "memory"); }
template<int N> __device__ __forceinline__ void wgmma_wait() { asm volatile("wgmma.wait_group.sync.aligned %0;" :: "n"(N) : "memory"); }
__device__ __forceinline__ float ex2(float x) { float y; asm("ex2.approx.ftz.f32 %0, %1;" : "=f"(y) : "f"(x)); return y; }
__device__ __forceinline__ float rcp_fast(float x) { float y; asm("rcp.approx.ftz.f32 %0, %1;" : "=f"(y) : "f"(x)); return y; }
__device__ __forceinline__ uint32_t pack_bf16(float lo, float hi) { uint32_t r; asm("cvt.rn.bf16x2.f32 %0, %1, %2;" : "=r"(r) : "f"(hi), "f"(lo)); return r; }
__device__ __forceinline__ float rbf(float x) { return __uint_as_float(pack_bf16(0.f, x)); }
__device__ __forceinline__ float bf_lo(uint32_t v) { return __uint_as_float(v << 16); }
__device__ __forceinline__ float bf_hi(uint32_t v) { return __uint_as_float(v & 0xffff0000u); }
__device__ __forceinline__ uint32_t add2(uint32_t a, uint32_t b) { uint32_t r; asm("add.rn.bf16x2 %0, %1, %2;" : "=r"(r) : "r"(a), "r"(b)); return r; }
__device__ __forceinline__ uint32_t fma2(uint32_t a, uint32_t b, uint32_t c) { uint32_t r; asm("fma.rn.bf16x2 %0, %1, %2, %3;" : "=r"(r) : "r"(a), "r"(b), "r"(c)); return r; }
__device__ __forceinline__ void prefetch_l2(const void* p) { asm volatile("prefetch.global.L2 [%0];" :: "l"(p) : "memory"); }
__device__ __forceinline__ void stsm_x4(uint32_t addr, uint32_t r0, uint32_t r1, uint32_t r2, uint32_t r3) {
  asm volatile("stmatrix.sync.aligned.m8n8.x4.shared.b16 [%0], {%1, %2, %3, %4};" :: "r"(addr), "r"(r0), "r"(r1), "r"(r2), "r"(r3) : "memory");
}
template<int N> __device__ __forceinline__ void fence_regs(float (&a)[N]) {
  #pragma unroll
  for (int i = 0; i < N; i++) asm volatile("" : "+f"(a[i]) :: "memory");
}
template<int N> __device__ __forceinline__ void fence_regs_u(uint32_t (&a)[N]) {
  #pragma unroll
  for (int i = 0; i < N; i++) asm volatile("" : "+r"(a[i]) :: "memory");
}
__device__ __forceinline__ uint32_t desc_lo(uint32_t addr, uint32_t lbo) { return ((addr & 0x3FFFF) >> 4) | ((lbo >> 4) << 16); }

template<int TB, int OA, int OB> __device__ __forceinline__ void wgmma_ss_n128(float (&d)[64], uint32_t da, uint32_t db, int sd) {
  asm volatile("{\n.reg .pred p;\n.reg .b32 ta, tb;\n.reg .b64 da, db;\nsetp.ne.b32 p, %66, 0;\nadd.u32 ta, %64, %68;\nadd.u32 tb, %65, %69;\nmov.b64 da, {ta, 0x40000040};\nmov.b64 db, {tb, 0x40000040};\n"
    "wgmma.mma_async.sync.aligned.m64n128k16.f32.bf16.bf16 "
    "{%0, %1, %2, %3, %4, %5, %6, %7, %8, %9, %10, %11, %12, %13, %14, %15, %16, %17, %18, %19, %20, %21, %22, %23, %24, %25, %26, %27, %28, %29, %30, %31, %32, %33, %34, %35, %36, %37, %38, %39, %40, %41, %42, %43, %44, %45, %46, %47, %48, %49, %50, %51, %52, %53, %54, %55, %56, %57, %58, %59, %60, %61, %62, %63}, da, db, p, 1, 1, 0, %67;\n}\n"
    : "+f"(d[0]), "+f"(d[1]), "+f"(d[2]), "+f"(d[3]), "+f"(d[4]), "+f"(d[5]), "+f"(d[6]), "+f"(d[7]), "+f"(d[8]), "+f"(d[9]), "+f"(d[10]), "+f"(d[11]), "+f"(d[12]), "+f"(d[13]), "+f"(d[14]), "+f"(d[15]), "+f"(d[16]), "+f"(d[17]), "+f"(d[18]), "+f"(d[19]), "+f"(d[20]), "+f"(d[21]), "+f"(d[22]), "+f"(d[23]), "+f"(d[24]), "+f"(d[25]), "+f"(d[26]), "+f"(d[27]), "+f"(d[28]), "+f"(d[29]), "+f"(d[30]), "+f"(d[31]), "+f"(d[32]), "+f"(d[33]), "+f"(d[34]), "+f"(d[35]), "+f"(d[36]), "+f"(d[37]), "+f"(d[38]), "+f"(d[39]), "+f"(d[40]), "+f"(d[41]), "+f"(d[42]), "+f"(d[43]), "+f"(d[44]), "+f"(d[45]), "+f"(d[46]), "+f"(d[47]), "+f"(d[48]), "+f"(d[49]), "+f"(d[50]), "+f"(d[51]), "+f"(d[52]), "+f"(d[53]), "+f"(d[54]), "+f"(d[55]), "+f"(d[56]), "+f"(d[57]), "+f"(d[58]), "+f"(d[59]), "+f"(d[60]), "+f"(d[61]), "+f"(d[62]), "+f"(d[63])
    : "r"(da), "r"(db), "r"(sd), "n"(TB), "n"(OA), "n"(OB));
}
template<int TB, int OB> __device__ __forceinline__ void wgmma_rs_n128(float (&d)[64], uint32_t a0, uint32_t a1, uint32_t a2, uint32_t a3, uint32_t db, int sd) {
  asm volatile("{\n.reg .pred p;\n.reg .b32 tb;\n.reg .b64 db;\nsetp.ne.b32 p, %69, 0;\nadd.u32 tb, %68, %71;\nmov.b64 db, {tb, 0x40000040};\n"
    "wgmma.mma_async.sync.aligned.m64n128k16.f32.bf16.bf16 "
    "{%0, %1, %2, %3, %4, %5, %6, %7, %8, %9, %10, %11, %12, %13, %14, %15, %16, %17, %18, %19, %20, %21, %22, %23, %24, %25, %26, %27, %28, %29, %30, %31, %32, %33, %34, %35, %36, %37, %38, %39, %40, %41, %42, %43, %44, %45, %46, %47, %48, %49, %50, %51, %52, %53, %54, %55, %56, %57, %58, %59, %60, %61, %62, %63}, {%64,%65,%66,%67}, db, p, 1, 1, %70;\n}\n"
    : "+f"(d[0]), "+f"(d[1]), "+f"(d[2]), "+f"(d[3]), "+f"(d[4]), "+f"(d[5]), "+f"(d[6]), "+f"(d[7]), "+f"(d[8]), "+f"(d[9]), "+f"(d[10]), "+f"(d[11]), "+f"(d[12]), "+f"(d[13]), "+f"(d[14]), "+f"(d[15]), "+f"(d[16]), "+f"(d[17]), "+f"(d[18]), "+f"(d[19]), "+f"(d[20]), "+f"(d[21]), "+f"(d[22]), "+f"(d[23]), "+f"(d[24]), "+f"(d[25]), "+f"(d[26]), "+f"(d[27]), "+f"(d[28]), "+f"(d[29]), "+f"(d[30]), "+f"(d[31]), "+f"(d[32]), "+f"(d[33]), "+f"(d[34]), "+f"(d[35]), "+f"(d[36]), "+f"(d[37]), "+f"(d[38]), "+f"(d[39]), "+f"(d[40]), "+f"(d[41]), "+f"(d[42]), "+f"(d[43]), "+f"(d[44]), "+f"(d[45]), "+f"(d[46]), "+f"(d[47]), "+f"(d[48]), "+f"(d[49]), "+f"(d[50]), "+f"(d[51]), "+f"(d[52]), "+f"(d[53]), "+f"(d[54]), "+f"(d[55]), "+f"(d[56]), "+f"(d[57]), "+f"(d[58]), "+f"(d[59]), "+f"(d[60]), "+f"(d[61]), "+f"(d[62]), "+f"(d[63])
    : "r"(a0), "r"(a1), "r"(a2), "r"(a3), "r"(db), "r"(sd), "n"(TB), "n"(OB));
}
template<int TB, int OA, int OB> __device__ __forceinline__ void wgmma_ss_n64_lo(float (&d)[64], uint32_t da, uint32_t db, int sd) {
  asm volatile("{\n.reg .pred p;\n.reg .b32 ta, tb;\n.reg .b64 da, db;\nsetp.ne.b32 p, %34, 0;\nadd.u32 ta, %32, %36;\nadd.u32 tb, %33, %37;\nmov.b64 da, {ta, 0x40000040};\nmov.b64 db, {tb, 0x40000040};\n"
    "wgmma.mma_async.sync.aligned.m64n64k16.f32.bf16.bf16 "
    "{%0, %1, %2, %3, %4, %5, %6, %7, %8, %9, %10, %11, %12, %13, %14, %15, %16, %17, %18, %19, %20, %21, %22, %23, %24, %25, %26, %27, %28, %29, %30, %31}, da, db, p, 1, 1, 0, %35;\n}\n"
    : "+f"(d[0]), "+f"(d[1]), "+f"(d[2]), "+f"(d[3]), "+f"(d[4]), "+f"(d[5]), "+f"(d[6]), "+f"(d[7]), "+f"(d[8]), "+f"(d[9]), "+f"(d[10]), "+f"(d[11]), "+f"(d[12]), "+f"(d[13]), "+f"(d[14]), "+f"(d[15]), "+f"(d[16]), "+f"(d[17]), "+f"(d[18]), "+f"(d[19]), "+f"(d[20]), "+f"(d[21]), "+f"(d[22]), "+f"(d[23]), "+f"(d[24]), "+f"(d[25]), "+f"(d[26]), "+f"(d[27]), "+f"(d[28]), "+f"(d[29]), "+f"(d[30]), "+f"(d[31])
    : "r"(da), "r"(db), "r"(sd), "n"(TB), "n"(OA), "n"(OB));
}
template<int OA, int OB = 0> __device__ __forceinline__ void kblock_n128(float (&d)[64], uint32_t da, uint32_t db, int sd) {
  wgmma_ss_n128<1, OA, OB>(d, da, db, sd); wgmma_ss_n128<1, OA + 2, OB + 128>(d, da, db, 1);
  wgmma_ss_n128<1, OA + 4, OB + 256>(d, da, db, 1); wgmma_ss_n128<1, OA + 6, OB + 384>(d, da, db, 1);
}

__device__ __forceinline__ float quad_sum(float v) {
  v += __shfl_xor_sync(0xffffffff, v, 1);
  v += __shfl_xor_sync(0xffffffff, v, 2);
  return v;
}
__device__ __forceinline__ void unpack8(const uint4& v, float* f) {
  f[0] = bf_lo(v.x); f[1] = bf_hi(v.x); f[2] = bf_lo(v.y); f[3] = bf_hi(v.y);
  f[4] = bf_lo(v.z); f[5] = bf_hi(v.z); f[6] = bf_lo(v.w); f[7] = bf_hi(v.w);
}
struct Row { uint32_t v[8]; };
template<class F> __device__ __forceinline__ Row load_row(const __nv_bfloat16* p, int lane, F ld) {
  const uint4 a = ld(reinterpret_cast<const uint4*>(p) + lane), b = ld(reinterpret_cast<const uint4*>(p) + 32 + lane);
  return Row{{a.x, a.y, a.z, a.w, b.x, b.y, b.z, b.w}};
}
__device__ __forceinline__ Row ldg_row(const __nv_bfloat16* p, int lane) { return load_row(p, lane, [](const uint4* q) { return __ldg(q); }); }
__device__ __forceinline__ Row ldca_row(const __nv_bfloat16* p, int lane) { return load_row(p, lane, [](const uint4* q) { return __ldca(q); }); }
__device__ __forceinline__ Row lds_row(uint32_t addr, int lane) {
  const uint4 a = lds_v4(addr + lane * 16), b = lds_v4(addr + 512 + lane * 16);
  return Row{{a.x, a.y, a.z, a.w, b.x, b.y, b.z, b.w}};
}
__device__ __forceinline__ void store_row(__nv_bfloat16* p, int lane, const Row& r) {
  stg_v4(p + lane * 8, r.v[0], r.v[1], r.v[2], r.v[3]); stg_v4(p + 256 + lane * 8, r.v[4], r.v[5], r.v[6], r.v[7]);
}
__device__ __forceinline__ Row fma_row(const Row& a, const Row& b, const Row& c) {
  Row r;
  #pragma unroll
  for (int i = 0; i < 8; i++) r.v[i] = fma2(a.v[i], b.v[i], c.v[i]);
  return r;
}
__device__ __forceinline__ Row one_plus(const Row& a) {
  Row r;
  #pragma unroll
  for (int i = 0; i < 8; i++) r.v[i] = add2(a.v[i], 0x3f803f80u);
  return r;
}
__device__ __forceinline__ void layer_norm2(const Row (&x)[2], Row (&n)[2]) {
  float d[2][16], s[4];
  #pragma unroll
  for (int r = 0; r < 2; r++) {
    const float c = bf_lo(__shfl_sync(0xffffffff, x[r].v[0], 0));
    float s1 = 0.f, s2 = 0.f;
    #pragma unroll
    for (int i = 0; i < 16; i++) { d[r][i] = ((i & 1) ? bf_hi(x[r].v[i >> 1]) : bf_lo(x[r].v[i >> 1])) - c; s1 += d[r][i]; s2 = fmaf(d[r][i], d[r][i], s2); }
    s[2*r] = s1; s[2*r+1] = s2;
  }
  #pragma unroll
  for (int o = 16; o > 0; o >>= 1) {
    #pragma unroll
    for (int k = 0; k < 4; k++) s[k] += __shfl_xor_sync(0xffffffff, s[k], o);
  }
  #pragma unroll
  for (int r = 0; r < 2; r++) {
    const float m = s[2*r] * (1.f / DM), rstd = rsqrtf(fmaxf(fmaf(-m, m, s[2*r+1] * (1.f / DM)), 0.f) + 1e-5f), o = -m * rstd;
    #pragma unroll
    for (int i = 0; i < 8; i++) n[r].v[i] = pack_bf16(fmaf(d[r][2*i], rstd, o), fmaf(d[r][2*i+1], rstd, o));
  }
}

constexpr int SM_Q = 6 * 32768, SM_BAR = 7 * 32768, SM_MAIL = SM_BAR + 640, SM_RED = SM_MAIL + 128, SM_H2 = SM_RED + 1024, SM_KEY = SM_H2 + 1024, SMEM = SM_KEY + 128;
constexpr int B_AF = 0, B_RF = 64, B_WF = 112, B_WE = 160, B_RE = 208, B_PUB = 256, B_RDY = 496;
__device__ __forceinline__ uint32_t k_addrA(int kb) { return ((0x6310u >> ((kb >> 1) * 4)) & 15u) * 32768u + (kb & 1) * 16384u; }
__device__ __forceinline__ uint32_t k_addrW(int s) { return ((0x254u >> ((s >> 1) * 4)) & 15u) * 32768u + (s & 1) * 16384u; }

constexpr int MAX_ITEMS = 6;
struct Sched {
  uint8_t khead[NGRID / 2][4];
  uint8_t nitems[NGRID / 2];
  uint8_t item[NGRID / 2][MAX_ITEMS];
  uint8_t otask[NGRID / 2];
  uint8_t ohead[NGRID / 2][8];
};

__device__ __forceinline__ int ring_add(int e, int n) { e += n; return e >= 12 ? e - 12 : e; }
__device__ __forceinline__ int ring_slot(int e) { return e >= 6 ? e - 6 : e; }
__device__ __forceinline__ void ring_wait_full(uint32_t bars, int e) { mbar_wait(bars + B_RF + 8 * ring_slot(e), e >= 6); }

struct Ctx {
  uint32_t base, bars;
  uint32_t rel;
  bool rel1;
  int w, nev;
};
__device__ __forceinline__ void slot_release(const Ctx& x, int s, bool twice) {
  mbar_arrive_remote_if(x.rel + B_RE + 8 * s, twice ? (wg_tid() & 31) == 0 : x.rel1);
}
__device__ __forceinline__ void ring_release(const Ctx& x, int e, bool twice) { slot_release(x, ring_slot(e), twice); }
__device__ __forceinline__ void publish(Ctx& x, int idx) {
  const uint32_t n = x.w * 15 + x.nev;
  const int t = wg_tid();
  if (t == 0) asm volatile("st.shared.u32 [%0], %1;" :: "r"(x.base + SM_MAIL + 4 * n), "r"(idx) : "memory");
  __syncwarp();
  if ((t & 31) == 0) mbar_arrive(x.bars + B_PUB + 8 * n);
  x.nev++;
}

template<int KK = 0> __device__ __forceinline__ void issue_qk(float (&S)[64], uint32_t dq, uint32_t dk) {
  constexpr int off = (KK >> 2) * 1024 + (KK & 3) * 2;
  wgmma_ss_n128<0, off, off>(S, dq, dk, KK > 0);
  if constexpr (KK < 7) issue_qk<KK + 1>(S, dq, dk);
}
template<int KK = 0> __device__ __forceinline__ void issue_qk_half(float (&S)[64], uint32_t dq, uint32_t dk) {
  constexpr int off = (KK >> 2) * 1024 + (KK & 3) * 2;
  wgmma_ss_n64_lo<0, off, off + 512>(S, dq, dk, KK > 0);
  if constexpr (KK < 7) issue_qk_half<KK + 1>(S, dq, dk);
}
template<int NK, int KK = 0>
__device__ __forceinline__ void issue_pv(float (&O)[64], uint32_t (&P)[32], uint32_t dv, int accumulate) {
  wgmma_rs_n128<1, (KK + 8 - NK) * 128>(O, P[4*KK], P[4*KK+1], P[4*KK+2], P[4*KK+3], dv, accumulate);
  if constexpr (KK + 1 < NK) issue_pv<NK, KK + 1>(O, P, dv, 1);
}
template<int K0, int K1>
__device__ __forceinline__ void exp_pack(const float (&S)[64], uint32_t (&D)[32], float& s0, float& s1) {
  #pragma unroll
  for (int k = K0; k < K1; k++) {
    const float e0 = ex2(S[2*k]), e1 = ex2(S[2*k+1]);
    D[k] = pack_bf16(e0, e1);
    if (k & 1) s1 += e0 + e1; else s0 += e0 + e1;
  }
}
__device__ __forceinline__ int diag_limit() { const int t = wg_tid(); return 16 * (t >> 5) + ((t & 31) >> 2) - 2 * (t & 3); }
__device__ __forceinline__ void exp_pack_diag(const float (&S)[64], uint32_t (&D)[32], int t, float& s0, float& s1) {
  #pragma unroll
  for (int k = 0; k < 16; k++) {
    const int c = 8 * (k >> 1) - 8 * (k & 1);
    const float e0 = ex2((c <= t) ? S[2*k] : -INFINITY), e1 = ex2((c + 1 <= t) ? S[2*k+1] : -INFINITY);
    D[k] = pack_bf16(e0, e1);
    if (k & 1) s1 += e0 + e1; else s0 += e0 + e1;
  }
}
constexpr float SUM_HI = 1.8446744073709552e19f;
constexpr float SUM_LO = 5.421010862427522e-20f;

__device__ __forceinline__ void classic_tile(const float (&S)[64], uint32_t (&P)[32], bool fresh, bool half, bool was_classic, volatile float* mc,
                                             float& l0, float& l1, float& s0, float& s1, float& sc0, float& sc1) {
  const int tmask = diag_limit();
  float4 t[16];
  #pragma unroll
  for (int j = 0; j < 16; j++) t[j] = make_float4(S[4*j], S[4*j+1], S[4*j+2], S[4*j+3]);
  float mx0 = -INFINITY, mx1 = -INFINITY;
  #pragma unroll 1
  for (int j = 0; j < 16; j++) {
    float4 v = t[j];
    const int lim = !fresh ? 1000 : j < 8 ? tmask - 8 * j : half ? -1000 : 1000;
    v.x = 0 <= lim ? v.x : -INFINITY; v.y = 1 <= lim ? v.y : -INFINITY; v.z = -8 <= lim ? v.z : -INFINITY; v.w = -7 <= lim ? v.w : -INFINITY;
    t[j] = v;
    mx0 = fmaxf(mx0, fmaxf(v.x, v.y)); mx1 = fmaxf(mx1, fmaxf(v.z, v.w));
  }
  mx0 = fmaxf(mx0, __shfl_xor_sync(0xffffffff, mx0, 1));
  mx1 = fmaxf(mx1, __shfl_xor_sync(0xffffffff, mx1, 1));
  mx0 = fmaxf(mx0, __shfl_xor_sync(0xffffffff, mx0, 2));
  mx1 = fmaxf(mx1, __shfl_xor_sync(0xffffffff, mx1, 2));
  const float mc0 = was_classic ? mc[0] : 0.f, mc1 = was_classic ? mc[1] : 0.f;
  const float n0 = fresh ? -mx0 : fminf(mc0, -mx0), n1 = fresh ? -mx1 : fminf(mc1, -mx1);
  sc0 = ex2(n0 - mc0); sc1 = ex2(n1 - mc1);
  mc[0] = n0; mc[1] = n1;
  s0 = 0.f; s1 = 0.f;
  #pragma unroll 1
  for (int j = 0; j < 16; j++) {
    const float4 v = t[j];
    const float e0 = ex2(v.x + n0), e1 = ex2(v.y + n0), e2 = ex2(v.z + n1), e3 = ex2(v.w + n1);
    s0 += e0 + e1; s1 += e2 + e3;
    t[j].x = __uint_as_float(pack_bf16(e0, e1)); t[j].y = __uint_as_float(pack_bf16(e2, e3));
  }
  #pragma unroll
  for (int j = 0; j < 16; j++) { P[2*j] = __float_as_uint(t[j].x); P[2*j+1] = __float_as_uint(t[j].y); }
  if (!fresh) { l0 *= sc0; l1 *= sc1; }
}
__device__ __forceinline__ void pack_tile(const float (&A)[64], uint32_t (&D)[32], float f0, float f1) {
  #pragma unroll
  for (int j = 0; j < 16; j++) {
    D[8 * (j >> 2) + (j & 3)] = pack_bf16(A[4*j] * f0, A[4*j+1] * f0);
    D[8 * (j >> 2) + 4 + (j & 3)] = pack_bf16(A[4*j+2] * f1, A[4*j+3] * f1);
  }
}
__device__ __forceinline__ void store_tile(__nv_bfloat16* p, const uint32_t (&D)[32]) {
  #pragma unroll
  for (int i = 0; i < 8; i++) stg_v4(p + (i >> 2) * (SEQ * 64) + ((i >> 1) & 1) * 32 + (i & 1) * 8 * 64, D[4*i], D[4*i+1], D[4*i+2], D[4*i+3]);
}

enum : int { PV_ACC = 0, PV_ZERO = 1, PV_HALF = 2, PV_NONE = 3 };
struct Att {
  float l0, l1;
  bool classic;
  volatile float* mc;
};
__device__ __forceinline__ void store_ctx(Ctx& x, int code, const uint32_t (&D)[32]) {
  const int item = code >> 2, t = wg_tid(), lane = t & 31;
  const int row = (item & 7) * 256 + (code & 3) * 64 + (t >> 5) * 16 + (lane >> 2);
  store_tile(g_kvc + ((size_t)(128 + (item >> 3) * 2) * SEQ + row) * 64 + (lane & 3) * 8, D);
  publish(x, C_CTX + item);
}

__device__ __forceinline__ void q_proj(Ctx& x, int& e, float (&S)[64], bool isY, bool dbg = false) {
  bar_sync(1 + x.w, 256);
  if (dbg) DBG(80);
  if (isY) bar_arrive(1 + (x.w ^ 1), 256);
  #pragma unroll 1
  for (int kb = 0; kb < 8; kb++) {
    ring_wait_full(x.bars, e);
    if (dbg) DBG(81 + kb);
    const uint32_t ent = x.base + ring_slot(e) * 32768;
    const uint32_t da = desc_lo(ent + x.w * 8192, 16), dw = desc_lo(ent + 16384, 8192);
    wgmma_fence();
    kblock_n128<0>(S, da, dw, kb != 0);
    wgmma_commit();
    if (kb == 7 && !isY) bar_arrive(1 + (x.w ^ 1), 256);
    if (kb > 0) { wgmma_wait<1>(); ring_release(x, ring_add(e, 11), false); }
    e = ring_add(e, 1);
  }
  wgmma_wait<0>();
  fence_regs(S);
  if (dbg) DBG(89);
  ring_release(x, ring_add(e, 11), false);
  const int t = wg_tid(), lane = t & 31, g = lane >> 2;
  const uint32_t qa = x.base + SM_Q + x.w * 8192 + ((t >> 5) * 16 + g) * 128;
  #pragma unroll
  for (int i = 0; i < 8; i++) {
    const int j = 4 * (i >> 1), o = 2 * (i & 1);
    sts_v4(qa + (i >> 2) * 16384 + (i & 1) * 1024 + (((((i >> 1) & 1) * 4 + (lane & 3)) ^ g) << 4),
           pack_bf16(S[4*j+o], S[4*j+o+1]), pack_bf16(S[4*j+4+o], S[4*j+5+o]), pack_bf16(S[4*j+8+o], S[4*j+9+o]), pack_bf16(S[4*j+12+o], S[4*j+13+o]));
  }
  fence_async_smem();
  if (dbg) DBG(90);
  ring_wait_full(x.bars, ring_add(e, isY ? 0 : 2));
  ring_wait_full(x.bars, ring_add(e, 1));
}

template<int KIND>
__device__ __forceinline__ void slot(Ctx& x, Att& a, int& e, float (&S)[64], float (&O)[64], uint32_t (&Pn)[32], uint32_t (&Po)[32],
                                     bool more, bool isY, bool half, int pv, int pend) {
  const int w = x.w;
  const bool skip = KIND == 0 && !isY;
  const int en = ring_add(e, skip ? 4 : 2), sn = ring_slot(en), sv = ring_slot(e) + 1, sk = skip ? ring_slot(ring_add(e, 2)) : sv - 1;
  const uint32_t dq = desc_lo(x.base + SM_Q + w * 8192, 16), dk = desc_lo(x.base, 16) + sk * 2048, dv = desc_lo(x.base, 16384) + sv * 2048;
  bar_sync(1 + w, 256);
  if (KIND == 2) {
    wgmma_fence();
    issue_qk(S, dq, dk); wgmma_commit();
    issue_pv<8>(O, Po, dv, 1); wgmma_commit();
  } else if (KIND == 1) {
    if (half) { wgmma_fence(); issue_qk(S, dq, dk); wgmma_commit(); issue_pv<4>(O, Po, dv, 0); wgmma_commit(); }
    else      { wgmma_fence(); issue_qk(S, dq, dk); wgmma_commit(); issue_pv<8>(O, Po, dv, 0); wgmma_commit(); }
  } else if (half) {
    if (pv == PV_NONE) { wgmma_fence(); issue_qk_half(S, dq, dk); wgmma_commit(); wgmma_commit(); }
    else               { wgmma_fence(); issue_qk_half(S, dq, dk); wgmma_commit(); issue_pv<8>(O, Po, dv, pv == PV_ACC); wgmma_commit(); }
  } else {
    if (pv == PV_NONE)      { wgmma_fence(); issue_qk(S, dq, dk); wgmma_commit(); wgmma_commit(); }
    else if (pv == PV_HALF) { wgmma_fence(); issue_qk(S, dq, dk); wgmma_commit(); issue_pv<4>(O, Po, dv, 0); wgmma_commit(); }
    else                    { wgmma_fence(); issue_qk(S, dq, dk); wgmma_commit(); issue_pv<8>(O, Po, dv, pv == PV_ACC); wgmma_commit(); }
  }
  bar_arrive(1 + (w ^ 1), 256);
  float i0 = 0.f, i1 = 0.f;
  if (KIND == 1 && pend >= 0) store_ctx(x, pend, Pn);
  if (KIND == 0) { i0 = rcp_fast(quad_sum(a.l0)); i1 = rcp_fast(quad_sum(a.l1)); }
  wgmma_wait<1>();
  fence_regs(S);
  fence_regs_u(Pn);
  slot_release(x, sk, KIND == 0 && isY);
  float s0 = 0.f, s1 = 0.f;
  const bool was_classic = KIND != 0 && a.classic;
  if (KIND == 0) {
    a.l0 = 0.f; a.l1 = 0.f;
    if (!half) exp_pack<16, 32>(S, Pn, s0, s1);
    exp_pack_diag(S, Pn, diag_limit(), s0, s1);
    const float q0 = quad_sum(s0), q1 = quad_sum(s1);
    a.classic = __any_sync(0xffffffff, !(s0 <= SUM_HI && s1 <= SUM_HI && q0 >= SUM_LO && q1 >= SUM_LO));
  } else {
    exp_pack<0, 32>(S, Pn, s0, s1);
    a.classic = __any_sync(0xffffffff, a.classic || !(s0 <= SUM_HI && s1 <= SUM_HI));
  }
  fence_regs_u(Pn);
  mbar_wait(x.bars + B_RF + 8 * sn, en >= 6);
  if (more) mbar_wait(x.bars + B_RF + 8 * sn + 8, en >= 6);
  wgmma_wait<0>();
  fence_regs(O);
  fence_regs_u(Po);
  slot_release(x, sv, KIND == 1 && isY);
  if (__builtin_expect(a.classic, 0)) {
    float sc0, sc1;
    classic_tile(S, Pn, KIND == 0, half, was_classic, a.mc, a.l0, a.l1, s0, s1, sc0, sc1);
    if (KIND != 0) {
      #pragma unroll
      for (int j = 0; j < 16; j++) { O[4*j] *= sc0; O[4*j+1] *= sc0; O[4*j+2] *= sc1; O[4*j+3] *= sc1; }
    }
  }
  a.l0 += s0; a.l1 += s1;
  if (KIND == 0) pack_tile(O, Po, i0, i1);
  e = en;
}

__device__ __forceinline__ void attention(Ctx& x, int& e, const uint8_t* items, int nitems, int rank) {
  float S[64], O[64]; uint32_t PA[32], PB[32];
  Att a;
  volatile float mc[2];
  a.l0 = 1.f; a.l1 = 1.f; a.classic = false; a.mc = mc;
  int pv = PV_NONE, cur = -1;
#define DBGS()
  #pragma unroll 1
  for (int it = 0; it < nitems; it++) {
    const int item = items[it];
    const bool isY = (it & 1) == x.w, half = isY == (rank != 0);
    const int prev = cur;
    cur = item * 4 + (isY ? 3 - rank : rank);
    int rem = 2 * (item & 7) + (isY ? 1 : 0);
    DBG(16 + it);
    q_proj(x, e, S, isY);
    DBGS();
    slot<0>(x, a, e, S, O, PA, PB, rem > 0, isY, half, pv, -1);
    if (rem > 0) {
      pv = PV_ACC;
      rem--;
      DBGS();
      slot<1>(x, a, e, S, O, PB, PA, rem > 0, isY, half, 0, prev);
      #pragma unroll 1
      while (rem > 0) {
        DBGS();
        slot<2>(x, a, e, S, O, PA, PB, rem > 1, false, false, 0, -1);
        if (rem == 1) break;
        rem -= 2;
        DBGS();
        slot<2>(x, a, e, S, O, PB, PA, rem > 0, false, false, 0, -1);
      }
    } else {
      pv = half ? PV_HALF : PV_ZERO;
      if (prev >= 0) store_ctx(x, prev, PB);
    }
    if (!isY) {
      #pragma unroll
      for (int i = 0; i < 32; i++) PB[i] = PA[i];
    }
  }
  DBGS();
  const uint32_t dv = desc_lo(x.base + ring_slot(e) * 32768, 16384);
  bar_sync(1 + x.w, 256);
  if (pv == PV_HALF) { wgmma_fence(); issue_pv<4>(O, PB, dv, 0); wgmma_commit(); }
  else { wgmma_fence(); issue_pv<8>(O, PB, dv, pv == PV_ACC); wgmma_commit(); }
  if ((nitems & 1) == x.w) bar_arrive(1 + (x.w ^ 1), 256);
  const float i0 = rcp_fast(quad_sum(a.l0)), i1 = rcp_fast(quad_sum(a.l1));
  ring_wait_full(x.bars, ring_add(e, 1));
  wgmma_wait<0>();
  fence_regs(O);
  fence_regs_u(PB);
  ring_release(x, e, false);
  pack_tile(O, PB, i0, i1);
  store_ctx(x, cur, PB);
  e = ring_add(e, 1);
}

#define LN_AT 3
__device__ __forceinline__ void mod_cta(uint8_t* smem, const __nv_bfloat16* cvec, const __nv_bfloat16* w_mod) {
  const int ct = threadIdx.x - 128, cw = ct >> 5, lane = ct & 31;
  const uint32_t cv = __ldg(reinterpret_cast<const uint32_t*>(cvec + cw * 64) + lane);
  const uint32_t sv = pack_bf16(__fdividef(bf_lo(cv), 1.f + __expf(-bf_lo(cv))), __fdividef(bf_hi(cv), 1.f + __expf(-bf_hi(cv))));
  float* red = reinterpret_cast<float*>(smem);
  #pragma unroll 1
  for (int rd = 0; rd < 3; rd++) {
    const int col0 = rd * 1024 + (blockIdx.x - NCTA) * 256;
    const uint4* wp = reinterpret_cast<const uint4*>(w_mod + (size_t)(cw * 64) * 3072 + col0) + lane;
    float am[8] = {0, 0, 0, 0, 0, 0, 0, 0};
    #pragma unroll 1
    for (int rb = 0; rb < 4; rb++) {
      uint4 wv[16];
      #pragma unroll
      for (int r = 0; r < 16; r++) wv[r] = __ldg(wp + (rb * 16 + r) * (3072 / 8));
      #pragma unroll
      for (int r = 0; r < 16; r++) {
        float f[8]; unpack8(wv[r], f);
        const uint32_t s2 = __shfl_sync(0xffffffff, sv, rb * 8 + (r >> 1));
        const float s1 = (r & 1) ? bf_hi(s2) : bf_lo(s2);
        #pragma unroll
        for (int j = 0; j < 8; j++) am[j] = fmaf(s1, f[j], am[j]);
      }
    }
    reinterpret_cast<float4*>(red + rd * 2048 + cw * 256)[lane * 2] = make_float4(am[0], am[1], am[2], am[3]);
    reinterpret_cast<float4*>(red + rd * 2048 + cw * 256)[lane * 2 + 1] = make_float4(am[4], am[5], am[6], am[7]);
    bar_sync(1, 256);
    float v = 0.f;
    #pragma unroll
    for (int i = 0; i < 8; i++) v += red[rd * 2048 + i * 256 + ct];
    g_mod[col0 + ct] = __float2bfloat16(v);
    bar_sync(1, 256);
    if (ct == 0) red_release(rd == 0 ? C_MOD : C_MOD2);
  }
}

__global__ void __cluster_dims__(2, 1, 1) __launch_bounds__(384, 1)
k_fused(const __grid_constant__ CUtensorMap tmC, const __grid_constant__ CUtensorMap tmH, const __grid_constant__ CUtensorMap tmWq,
        const __grid_constant__ CUtensorMap tmWk, const __grid_constant__ CUtensorMap tmWv, const __grid_constant__ CUtensorMap tmKV,
        const __grid_constant__ CUtensorMap tmWo, const __grid_constant__ CUtensorMap tmPart, const __grid_constant__ CUtensorMap tmWg,
        const __grid_constant__ CUtensorMap tmWu, const __grid_constant__ CUtensorMap tmPl, const __grid_constant__ Sched sched,
        const __nv_bfloat16* __restrict__ xin, const __nv_bfloat16* __restrict__ ckv, const __nv_bfloat16* __restrict__ w_uk,
        const __nv_bfloat16* __restrict__ cvec, const __nv_bfloat16* __restrict__ w_mod,
        const __nv_bfloat16* __restrict__ w_r, const __nv_bfloat16* __restrict__ w_gate, const __nv_bfloat16* __restrict__ w_up,
        const __nv_bfloat16* __restrict__ w_down, __nv_bfloat16* __restrict__ out) {
  extern __shared__ __align__(1024) uint8_t smem_raw[];
  const uint32_t base = smem_u32(smem_raw), bars = base + SM_BAR;
  const int warp = __shfl_sync(0xffffffff, threadIdx.x >> 5, 0), wg = warp >> 2;
  const int rank = cluster_ctarank(), p = blockIdx.x >> 1;
  const int mt = (p & 7) * 2 + rank;
  const bool spare = blockIdx.x >= NCTA;
  if (!spare) {
    if (warp == 0) prefetch_tmap(&tmC);
    if (warp == 1) prefetch_tmap(&tmWk);
    if (warp == 10) bulk_prefetch(ckv + (size_t)(mt * 128 + (p >> 3) * 16) * DM, 16384);
    if (warp == 11) { const __nv_bfloat16* q = w_uk + (size_t)(mt * 32 + (threadIdx.x & 31)) * (NH * DH) + sched.khead[p][0] * 128; prefetch_l2(q); prefetch_l2(q + 64); }
    if (warp < 10) {
      #pragma unroll 1
      for (int t = warp * 8; t < warp * 8 + 8; t++)
        w_mbar_init(bars + 8 * t, t < B_WE / 8 ? 1 : t < B_RE / 8 ? 2 : t < B_RDY / 8 ? 4 : 1);
      fence_mbar_init();
    }
    cluster_arrive();
  }
  const int nitems = sched.nitems[p];
  const int ot = sched.otask[p], m = (ot & 7) * 2 + rank, grp = m * 8 + (ot >> 3);

  if (wg == 0) {
    asm volatile("setmaxnreg.dec.sync.aligned.u32 24;");
    if (spare) return;
    const int lane = threadIdx.x & 31;
    const unsigned int tag = ld_relaxed(&g_epoch) + 1;
    if (warp == 0) {
      #pragma unroll 1
      for (int kb = 0; kb < 8; kb++) {
        w_expect_tx(bars + B_AF + 8 * kb, 16384);
        tma_load_2d(base + k_addrA(kb), &tmC, bars + B_AF + 8 * kb, kb * 64, mt * 128);
        if (kb == 0) cluster_wait();
        if (kb < 6) {
          w_expect_tx(bars + B_WF + 8 * kb, 16384);
          tma_load_2d_mc(base + k_addrW(kb) + rank * 8192, &tmWk, bars + B_WF + 8 * kb, sched.khead[p][0] * 128 + rank * 64, kb * 64);
        }
      }
    } else cluster_wait();
    if (warp == 0) {
      {
        int s = 0, ph = 0;
        tma_prefetch_2d(&tmWv, sched.khead[p][0] * 128 + rank * 64, (p & 7) * 64);
        #pragma unroll 1
        for (int g = 6; g < 64; g++) {
          const int u = g >> 3, kb = g & 7;
          if (kb == 0 && u < 7) tma_prefetch_2d((u & 1) ? &tmWk : &tmWv, sched.khead[p][(u + 1) >> 1] * 128 + rank * 64, (p & 7) * 64);
          mbar_wait(bars + B_WE + 8 * s, ph);
          w_expect_tx(bars + B_WF + 8 * s, 16384);
          tma_load_2d_mc(base + k_addrW(s) + rank * 8192, (u & 1) ? &tmWv : &tmWk, bars + B_WF + 8 * s, sched.khead[p][u >> 1] * 128 + rank * 64, kb * 64);
          if (++s == 6) { s = 0; ph ^= 1; }
        }
      }
      int s = 0, ph = 0;
      auto next_entry = [&](bool load) {
        mbar_wait(bars + B_RE + 8 * s, ph);
        if (load) w_expect_tx(bars + B_RF + 8 * s, 32768); else w_arrive(bars + B_RF + 8 * s);
      };
      auto advance = [&]() { if (++s == 6) { s = 0; ph ^= 1; } };
      int vrow = -1;
      #pragma unroll 1
      for (int i = 0; i < nitems; i++) {
        const int item = sched.item[p][i], h = item >> 3, j = item & 7;
        const int row0 = j * 256 + ((i & 1) ? rank : 3 - rank) * 64, row1 = j * 256 + ((i & 1) ? 3 - rank : rank) * 64;
        mbar_wait(bars + B_RDY + 8 * (1 + i), 0);
        fence_async_global();
        #pragma unroll 1
        for (int kb = 0; kb < 8; kb++) {
          next_entry(true);
          if (i == 2) DBGP(kb);
          tma_load_2d_mc(base + s * 32768 + 16384 + rank * 8192, &tmWq, bars + B_RF + 8 * s, h * 128 + rank * 64, kb * 64);
          tma_load_2d(base + s * 32768, &tmH, bars + B_RF + 8 * s, kb * 64, row0);
          tma_load_2d(base + s * 32768 + 8192, &tmH, bars + B_RF + 8 * s, kb * 64, row1);
          advance();
        }
        #pragma unroll 1
        for (int n = 2 * j + 1; n >= 0; n--) {
          const int krow = (h * 2 + rank) * SEQ + n * 128;
          next_entry(true);
          if (i == 2 && n >= 2 * j) DBGP(8 + 2 * (2 * j + 1 - n));
          tma_load_2d_mc(base + s * 32768 + rank * 16384, &tmKV, bars + B_RF + 8 * s, 0, krow);
          advance();
          next_entry(vrow >= 0);
          if (i == 2 && n >= 2 * j) DBGP(9 + 2 * (2 * j + 1 - n));
          if (vrow >= 0) tma_load_2d_mc(base + s * 32768 + rank * 16384, &tmKV, bars + B_RF + 8 * s, 0, vrow);
          advance();
          vrow = krow + 64 * SEQ;
        }
      }
      next_entry(true);
      tma_load_2d_mc(base + s * 32768 + rank * 16384, &tmKV, bars + B_RF + 8 * s, 0, vrow);
      advance();
      const int oj = ot & 7, oc = ((ot >> 3) & 1) * 4 + rank * 2;
      #pragma unroll 1
      for (int i = 0; i < 8; i++) {
        const int h = sched.ohead[p][i];
        next_entry(true);
        tma_load_3d_mc(base + s * 32768 + rank * 16384, &tmWo, bars + B_RF + 8 * s, 0, h * 128, oc);
        advance();
        mbar_wait(bars + B_RDY + 8 * (8 + i), 0);
        fence_async_global();
        next_entry(true);
        tma_load_2d(base + s * 32768, &tmKV, bars + B_RF + 8 * s, 0, (128 + h * 2) * SEQ + oj * 256 + rank * 128);
        tma_load_2d(base + s * 32768 + 16384, &tmKV, bars + B_RF + 8 * s, 0, (129 + h * 2) * SEQ + oj * 256 + rank * 128);
        advance();
        next_entry(true);
        tma_load_3d_mc(base + s * 32768 + rank * 16384, &tmWo, bars + B_RF + 8 * s, 0, h * 128 + 64, oc);
        advance();
      }
      const int f0 = (blockIdx.x < FF / 16 ? blockIdx.x : 0) * 16;
      next_entry(true);
      #pragma unroll 1
      for (int k = 0; k < 4; k++) tma_load_2d(base + s * 32768 + k * 8192, (k & 2) ? &tmWu : &tmWg, bars + B_RF + 8 * s, f0, (k & 1) * 256);
      advance();
      next_entry(true);
      bulk_load(base + s * 32768, w_down + (size_t)f0 * DM, 16384, bars + B_RF + 8 * s);
      bulk_load(base + s * 32768 + 16384, xin + (size_t)grp * 16 * DM, 16384, bars + B_RF + 8 * s);
      advance();
      w_expect_tx(bars + B_RDY + 8 * 7, 65536);
      mbar_wait(bars + B_PUB + 8 * (4 + nitems + 1), 0);
      mbar_wait(bars + B_PUB + 8 * (15 + 5 + nitems + 1), 0);
      uint32_t todo = 0xff;
      #pragma unroll 1
      for (int n = 0; n < WAIT_LIM && todo; n++) {
        uint32_t now = __ballot_sync(0xffffffff, ld_acquire(&g_pflag[m * 2 + (ot >> 5)][lane & 7]) == tag) & todo;
        todo &= ~now;
        fence_async_global();
        #pragma unroll 1
        for (; now; now &= now - 1) {
          const int q = __ffs(now) - 1, sl = s + 1 + (q >> 2);
          tma_load_3d(base + (sl >= 6 ? sl - 6 : sl) * 32768 + (q & 3) * 8192, &tmPl, bars + B_RDY + 8 * 7, 0, grp * 16, q * 4);
        }
      }
      DBGP(11);
    } else if (warp < 3) {
      const int w = warp - 1, n1 = w * 15 + 4 + w + nitems;
      if (lane == 0) {
        #pragma unroll 1
        for (int n = w * 15; n < n1 + 2; n++) {
          #pragma unroll 1
          for (int k = 0; k < 8 * WAIT_LIM; k++) { if (mbar_try(bars + B_PUB + 8 * n, 0)) break; }
          const uint32_t msg = lds_u32(base + SM_MAIL + 4 * n);
          if (n < n1) {
            fence_async_global();
            if (msg < (unsigned)C_END) red_release(msg);
          } else {
            tma_store_3d(&tmPart, base + (msg & 0x3c000), 0, m * 128 + 64 * w, (ot >> 4) * 8 + ((ot >> 3) & 1) * 4 + 2 * (n - n1));
            bulk_commit();
          }
        }
        bulk_wait<0>();
        fence_async_global();
        st_release(&g_pflag[m * 2 + w][ot >> 3], tag);
      }
      __syncwarp();
    } else {
      wait_count_lazy(C_MOD, 4 * tag);
      w_arrive(bars + B_RDY);
      #pragma unroll 1
      for (int i = 0; i < nitems; i++) {
        const int item = sched.item[p][i];
        tma_prefetch_2d(&tmWq, (item >> 3) * 128 + rank * 64, (p & 7) * 64);
        wait_count_lazy(C_H1 + (item & 7), 16 * tag);
        wait_count_lazy(C_KV + (item >> 3), 32 * tag);
        w_arrive(bars + B_RDY + 8 * (1 + i));
      }
      wait_count_lazy(C_MOD2, 8 * tag);
      #pragma unroll 1
      for (int i = 0; i < 8; i++) {
        wait_count_lazy(C_CTX + sched.ohead[p][i] * 8 + (ot & 7), 4 * tag);
        w_arrive(bars + B_RDY + 8 * (8 + i));
        if (i == 5) { for (int k = 0; k < 2; k++) tma_prefetch_3d(&tmWo, 0, sched.ohead[p][ot & 7] * 128 + k * 64, ((ot >> 3) & 1) * 4 + rank * 2); }
      }
      bulk_prefetch(xin + (size_t)grp * 16 * DM, 16 * DM * 2);
      bulk_prefetch(w_gate + (size_t)blockIdx.x * (DM * FF / NCTA), DM * FF / NCTA * 2);
      bulk_prefetch(w_up + (size_t)blockIdx.x * (DM * FF / NCTA), DM * FF / NCTA * 2);
      bulk_prefetch(w_down + (size_t)blockIdx.x * (DM * FF / NCTA), DM * FF / NCTA * 2);
    }
    bar_sync(6, 128);
    asm volatile("setmaxnreg.inc.sync.aligned.u32 88;");
    {
      const int col = blockIdx.x * 4 + (lane & 1) * 2, src = threadIdx.x >> 1;
      uint32_t gbest = 0, hh = 0, gbf = 0;
      uint2 xx = make_uint2(0, 0);
      if (warp == 3) {
        gbf = __ldcg(reinterpret_cast<const uint32_t*>(g_mod + 5 * DM + col));
        uint4 hv[4];
        #pragma unroll 1
        for (int n = 0; n < WAIT_LIM; n++) {
          uint2 k[4];
          #pragma unroll
          for (int i = 0; i < 4; i++) k[i] = ld_tagged(&g_keys[i * 32 + lane][0]);
          bool ok = gbest != 0;
          if (ok) {
            const int g = ((0xffffu - gbest) >> 4) & 127;
            #pragma unroll
            for (int i = 0; i < 4; i++) hv[i] = ld_tagged2(&g_row[g][0][i * 64 + lane * 2]);
            xx = ld_tagged(&g_row[g][1][col >> 1]);
            #pragma unroll
            for (int i = 0; i < 4; i++) ok = ok && hv[i].y == tag && hv[i].w == tag;
            ok = ok && xx.y == tag;
          }
          uint32_t kn = 0;
          #pragma unroll
          for (int i = 0; i < 4; i++) { ok = ok && k[i].y == tag; kn = max(kn, k[i].y == tag ? k[i].x : 0u); }
          kn = __reduce_max_sync(0xffffffff, kn);
          if (__all_sync(0xffffffff, ok && kn == gbest)) break;
          gbest = kn;
        }
        #pragma unroll
        for (int i = 0; i < 4; i++) reinterpret_cast<uint2*>(smem_raw + SM_H2)[i * 32 + lane] = make_uint2(hv[i].x, hv[i].z);
        if (lane == 0) *reinterpret_cast<uint32_t*>(smem_raw + SM_KEY + 32) = gbest;
        __syncwarp();
        w_arrive(bars + B_RDY + 8 * 16);
        if (blockIdx.x == 0 && lane == 0) g_epoch = tag;
        hh = lds_u32(base + SM_H2 + col * 2);
        DBGP(13);
      }
      const uint32_t sb16 = gbest & 0xffff0000u;
      const float rsel = __uint_as_float((sb16 & 0x80000000u) ? (sb16 & 0x7fffffffu) : (~sb16 & 0xffff0000u));
      const float rs = rbf(__fdividef(1.f, 1.f + __expf(-rsel)));
      uint4 ya, yb = make_uint4(0, tag, 0, tag);
      #pragma unroll 1
      for (int n = 0; n < WAIT_LIM; n++) {
        ya = ld_tagged2(&g_yll[src][col]);
        if (src + 64 < FF / 16) yb = ld_tagged2(&g_yll[src + 64][col]);
        if (n == 0) mbar_wait(bars + B_RDY + 8 * 16, 0);
        if (__all_sync(0xffffffff, ya.y == tag && ya.w == tag && yb.y == tag && yb.w == tag)) break;
      }
      float y0 = __uint_as_float(ya.x) + __uint_as_float(yb.x), y1 = __uint_as_float(ya.z) + __uint_as_float(yb.z);
      #pragma unroll
      for (int o = 2; o < 32; o <<= 1) { y0 += __shfl_xor_sync(0xffffffff, y0, o); y1 += __shfl_xor_sync(0xffffffff, y1, o); }
      float2* s_y = reinterpret_cast<float2*>(smem_raw + SM_KEY + 64);
      if (lane < 2) s_y[warp * 2 + lane] = make_float2(y0, y1);
      bar_sync(6, 128);
      if (warp == 3 && lane < 2) {
        #pragma unroll
        for (int i = 0; i < 3; i++) { const float2 v = s_y[i * 2 + lane]; y0 += v.x; y1 += v.y; }
        const float o0 = bf_lo(xx.x) + rbf(bf_lo(gbf) * rbf(bf_lo(hh) + rbf(rbf(y0) * rs)));
        const float o1 = bf_hi(xx.x) + rbf(bf_hi(gbf) * rbf(bf_hi(hh) + rbf(rbf(y1) * rs)));
        *reinterpret_cast<uint32_t*>(out + (size_t)((0xffffu - gbest) & (SEQ - 1)) * DM + col) = pack_bf16(o0, o1);
      }
      DBGP(14);
    }
    __syncwarp();
    cluster_arrive();
    cluster_wait();
  } else {
    asm volatile("setmaxnreg.inc.sync.aligned.u32 240;");
    if (spare) { mod_cta(smem_raw, cvec, w_mod); return; }
    Ctx x;
    x.w = wg - 1; x.base = base; x.bars = bars; x.nev = 0;
    const int w = x.w, warp4 = warp & 3;
    x.rel = mapa(bars, (warp4 & 1) ^ 1);
    x.rel1 = (threadIdx.x & 127) == 32 || (threadIdx.x & 127) == 64;
    cluster_wait();
    DBG(1);
    {
      const int lane = wg_tid() & 31;
      Row xn[2][2];
      const int lrow = blockIdx.x * 16 + warp4 * 4;
      if (w == 1) {
        bar_arrive(1, 256);
        mbar_wait(bars + B_WF, 0);
        Row xr[2][2];
        #pragma unroll
        for (int r = 0; r < 4; r++) xr[r >> 1][r & 1] = ldg_row(xin + (size_t)(lrow + r) * DM, lane);
        #pragma unroll 1
        for (int k = 0; k < 2; k++) {
          xn[0][0] = xn[1][0]; xn[0][1] = xn[1][1];
          layer_norm2(xr[0], xn[1]);
          xr[0][0] = xr[1][0]; xr[0][1] = xr[1][1];
        }
      }
      DBG(2);
      float acc0[64], acc1[64];
      const float sc = w == 0 ? 0.08838834764831845f * 1.4426950408889634f : 1.f;
      int s = 2 * w, ph = w;
      #pragma unroll 1
      for (int u = w; u < 8; u += 2) {
        bar_sync(1 + w, 256);
        DBG(4 + (u >> 1) * 3);
        int ps = 0;
        #pragma unroll 1
        for (int kb = 0; kb < 8; kb++) {
          if (u < 2) mbar_wait(bars + B_AF + 8 * kb, 0);
          mbar_wait(bars + B_WF + 8 * s, ph);
          const uint32_t da = desc_lo(base + k_addrA(kb), 16), dw = desc_lo(base + k_addrW(s), 8192);
          wgmma_fence();
          kblock_n128<0>(acc0, da, dw, kb != 0);
          kblock_n128<512>(acc1, da, dw, kb != 0);
          wgmma_commit();
          if (kb == 7) bar_arrive(1 + (w ^ 1), 256);
          if (kb > 0) {
            wgmma_wait<1>();
            mbar_arrive_remote_if(x.rel + B_WE + 8 * ps, x.rel1);
            if (u == 7 && !(kb & 1)) {
              ring_release(x, kb == 2 ? 0 : kb - 3, false);
              if (kb > 2) ring_release(x, kb - 2, false);
            }
          }
          ps = s;
          if (++s == 6) { s = 0; ph ^= 1; }
        }
        wgmma_wait<0>();
        fence_regs(acc0); fence_regs(acc1);
        DBG(5 + (u >> 1) * 3);
        mbar_arrive_remote_if(x.rel + B_WE + 8 * ps, x.rel1);
        if (u == 6) { for (int k = 0; k < 5; k++) ring_release(x, k, false); }
        if (u >= 6) ring_release(x, 5, false);
        s += 2; ph ^= 1; if (s >= 6) { s -= 6; ph ^= 1; }
        if (u == LN_AT) {
          mbar_wait(bars + B_RDY, 0);
          const Row sa = ldca_row(g_mod, lane), ca1 = one_plus(ldca_row(g_mod + DM, lane));
          #pragma unroll
          for (int r = 0; r < 4; r++) store_row(g_h1 + (size_t)(lrow + r) * DM, lane, fma_row(xn[r >> 1][r & 1], ca1, sa));
          publish(x, C_H1 + (blockIdx.x >> 4));
        }
        const int h = sched.khead[p][u >> 1];
        __nv_bfloat16* dst = g_kvc + ((size_t)(w * 64 + h * 2) * SEQ + mt * 128 + warp4 * 16 + (lane >> 2)) * 64 + (lane & 3) * 8;
        uint32_t D[32];
        pack_tile(acc0, D, sc, sc); store_tile(dst + 64 * 64, D);
        pack_tile(acc1, D, sc, sc); store_tile(dst, D);
        publish(x, C_KV + h);
        DBG(6 + (u >> 1) * 3);
      }
    }
    int e = 0;
    attention(x, e, sched.item[p], nitems, rank);
    DBG(100);
    const int lane = wg_tid() & 31, cw = w * 4 + warp4, ct = cw * 32 + lane;
    const int row0 = grp * 16 + cw * 2;
    const bool moe_cta = blockIdx.x < FF / 16;
    const unsigned int tag = ld_relaxed(&g_epoch) + 1;
    asm volatile("setmaxnreg.dec.sync.aligned.u32 208;");
    Row ga, sb, cb1, gb, wr;
    {
      float accA[64], accB[64];
      #pragma unroll 1
      for (int i = 0; i < 7; i++) {
        const int ea = ring_add(e, 1), eb = ring_add(e, 2);
        const uint32_t da = desc_lo(base + ring_slot(ea) * 32768 + w * 8192, 16);
        ring_wait_full(bars, e);
        ring_wait_full(bars, ea);
        uint32_t db = desc_lo(base + ring_slot(e) * 32768, 8192);
        wgmma_fence();
        kblock_n128<0>(accA, da, db, i != 0); kblock_n128<0, 1024>(accB, da, db, i != 0);
        wgmma_commit();
        if (i > 0) { wgmma_wait<1>(); ring_release(x, ring_add(e, 10), false); ring_release(x, ring_add(e, 11), false); }
        ring_wait_full(bars, eb);
        db = desc_lo(base + ring_slot(eb) * 32768, 8192);
        wgmma_fence();
        kblock_n128<1024>(accA, da, db, 1); kblock_n128<1024, 1024>(accB, da, db, 1);
        wgmma_commit();
        wgmma_wait<1>();
        ring_release(x, e, false);
        e = ring_add(e, 3);
      }
      const int ea = ring_add(e, 1), eb = ring_add(e, 2), es = ring_add(e, 11);
      const uint32_t da = desc_lo(base + ring_slot(ea) * 32768 + w * 8192, 16);
      const uint32_t db0 = desc_lo(base + ring_slot(e) * 32768, 8192), db1 = desc_lo(base + ring_slot(eb) * 32768, 8192);
      ring_wait_full(bars, e);
      ring_wait_full(bars, ea);
      ring_wait_full(bars, eb);
      wgmma_fence();
      kblock_n128<0>(accA, da, db0, 1); kblock_n128<1024>(accA, da, db1, 1);
      wgmma_commit();
      kblock_n128<0, 1024>(accB, da, db0, 1); kblock_n128<1024, 1024>(accB, da, db1, 1);
      wgmma_commit();
      wgmma_wait<2>();
      ring_release(x, ring_add(e, 10), false); ring_release(x, es, false);
      __syncwarp();
      cluster_arrive();
      ga = ldca_row(g_mod + 2 * DM, lane); sb = ldca_row(g_mod + 3 * DM, lane); cb1 = ldca_row(g_mod + 4 * DM, lane); gb = ldca_row(g_mod + 5 * DM, lane);
      wr = ldg_row(w_r, lane);
      e = ring_add(e, 3);
      const int srow = 16 * warp4 + (lane & 7) + 8 * ((lane >> 3) & 1);
      const uint32_t swz = (((lane >> 4) ^ (srow & 7)) << 4);
      auto stage = [&](const float (&acc)[64], uint32_t off) {
        #pragma unroll
        for (int j = 0; j < 16; j += 2)
          stsm_x4(base + off + srow * 128 + (j >> 3) * 8192 + (((j & 7) << 4) ^ swz),
                  pack_bf16(acc[4*j+0], acc[4*j+1]), pack_bf16(acc[4*j+2], acc[4*j+3]), pack_bf16(acc[4*j+4], acc[4*j+5]), pack_bf16(acc[4*j+6], acc[4*j+7]));
        fence_async_smem();
        publish(x, off);
      };
      wgmma_wait<1>();
      fence_regs(accA);
      stage(accA, SM_Q + w * 16384);
      mbar_wait(bars + B_RE + 8 * ring_slot(es), es < 6);
      wgmma_wait<0>();
      fence_regs(accB);
      DBG(101);
      stage(accB, ring_slot(es) * 32768 + w * 16384);
      DBG(102);
    }
    const uint32_t sW = base + ring_slot(e) * 32768, sD = base + ring_slot(ring_add(e, 1)) * 32768;
    ring_wait_full(bars, e); ring_wait_full(bars, ring_add(e, 1));
    Row x1[2];
    #pragma unroll
    for (int r = 0; r < 2; r++) x1[r] = lds_row(sD + 16384 + (cw * 2 + r) * 1024, lane);
    cb1 = one_plus(cb1);
    uint4 wgv[4], wuv[4]; uint32_t wdv[16];
    #pragma unroll
    for (int r = 0; r < 4; r++) { wgv[r] = lds_v4(sW + r * 4096 + ct * 16); wuv[r] = lds_v4(sW + 16384 + r * 4096 + ct * 16); }
    #pragma unroll
    for (int r = 0; r < 16; r++) wdv[r] = lds_u32(sD + r * 1024 + ct * 4);
    DBG(103);
    mbar_wait(bars + B_RDY + 8 * 7, 0);
    DBG(104);
    Row h2[2];
    uint32_t key[2];
    {
      uint4 pv[2][4][2];
      const uint32_t po = base + (lane >> 3) * 2048 + cw * 256 + (lane & 7) * 16;
      const uint32_t pa[2] = {po + ring_slot(ring_add(e, 3)) * 32768, po + ring_slot(ring_add(e, 4)) * 32768};
      #pragma unroll
      for (int r = 0; r < 2; r++)
        #pragma unroll
        for (int q = 0; q < 8; q++) pv[r][q >> 1][q & 1] = lds_v4(pa[q >> 2] + (q & 3) * 8192 + r * 128);
      #pragma unroll
      for (int r = 0; r < 2; r++) {
        Row av;
        #pragma unroll
        for (int i = 0; i < 2; i++) {
          av.v[4*i]   = add2(add2(pv[r][0][i].x, pv[r][1][i].x), add2(pv[r][2][i].x, pv[r][3][i].x));
          av.v[4*i+1] = add2(add2(pv[r][0][i].y, pv[r][1][i].y), add2(pv[r][2][i].y, pv[r][3][i].y));
          av.v[4*i+2] = add2(add2(pv[r][0][i].z, pv[r][1][i].z), add2(pv[r][2][i].z, pv[r][3][i].z));
          av.v[4*i+3] = add2(add2(pv[r][0][i].w, pv[r][1][i].w), add2(pv[r][2][i].w, pv[r][3][i].w));
        }
        x1[r] = fma_row(ga, av, x1[r]);
      }
      layer_norm2(x1, h2);
      float sc[2] = {0.f, 0.f};
      #pragma unroll
      for (int r = 0; r < 2; r++) {
        h2[r] = fma_row(h2[r], cb1, sb);
        #pragma unroll
        for (int i = 0; i < 8; i++) sc[r] = fmaf(bf_hi(h2[r].v[i]), bf_hi(wr.v[i]), fmaf(bf_lo(h2[r].v[i]), bf_lo(wr.v[i]), sc[r]));
      }
      #pragma unroll
      for (int o = 16; o > 0; o >>= 1) { sc[0] += __shfl_xor_sync(0xffffffff, sc[0], o); sc[1] += __shfl_xor_sync(0xffffffff, sc[1], o); }
      #pragma unroll
      for (int r = 0; r < 2; r++) {
        const uint32_t rb = pack_bf16(0.f, sc[r]);
        key[r] = (((rb & 0x80000000u) ? ~rb : (rb | 0x80000000u)) & 0xffff0000u) | (0xffffu - (uint32_t)(row0 + r));
      }
    }
    DBG(105);
    float* s_red = reinterpret_cast<float*>(smem_raw + SM_RED);
    uint32_t* s_key = reinterpret_cast<uint32_t*>(smem_raw + SM_KEY);
    const int rb = key[1] > key[0];
    const uint32_t wbest = rb ? key[1] : key[0];
    if (lane == 0) s_key[cw] = wbest;
    bar_sync(5, 256);
    const uint32_t cbest = __reduce_max_sync(0xffffffff, s_key[lane & 7]);
    Row ob, hb, xb;
    #pragma unroll
    for (int i = 0; i < 8; i++) { hb.v[i] = rb ? h2[1].v[i] : h2[0].v[i]; xb.v[i] = rb ? x1[1].v[i] : x1[0].v[i]; }
    if (wbest == cbest) {
      if (lane == 0) st_tagged(&g_keys[grp][0], cbest, tag);
      #pragma unroll
      for (int i = 0; i < 4; i++) st_tagged2(&g_row[grp][0][(i >> 1) * 128 + lane * 4 + (i & 1) * 2], hb.v[2*i], hb.v[2*i+1], tag);
      #pragma unroll
      for (int i = 0; i < 4; i++) st_tagged2(&g_row[grp][1][(i >> 1) * 128 + lane * 4 + (i & 1) * 2], xb.v[2*i], xb.v[2*i+1], tag);
    }
    DBG(106);
    #pragma unroll
    for (int i = 0; i < 8; i++) { ob.v[i] = fma2(gb.v[i], rb ? h2[0].v[i] : h2[1].v[i], rb ? x1[0].v[i] : x1[1].v[i]); }
    store_row(out + (size_t)(row0 + 1 - rb) * DM, lane, ob);
    ob = fma_row(gb, hb, xb);
    if (wbest != cbest) store_row(out + (size_t)(row0 + rb) * DM, lane, ob);
    mbar_wait(bars + B_RDY + 8 * 16, 0);
    DBG(107);
    if (moe_cta) {
      float hs[4];
      #pragma unroll
      for (int r = 0; r < 4; r++) hs[r] = __bfloat162float(reinterpret_cast<const __nv_bfloat16*>(smem_raw + SM_H2)[(ct >> 1) + 128 * r]);
      float ag[8] = {0, 0, 0, 0, 0, 0, 0, 0}, au[8] = {0, 0, 0, 0, 0, 0, 0, 0};
      #pragma unroll
      for (int r = 0; r < 4; r++) {
        float fg[8], fu[8]; unpack8(wgv[r], fg); unpack8(wuv[r], fu);
        #pragma unroll
        for (int j = 0; j < 8; j++) { ag[j] = fmaf(hs[r], fg[j], ag[j]); au[j] = fmaf(hs[r], fu[j], au[j]); }
      }
      #pragma unroll
      for (int j = 0; j < 8; j++) { const bool hi = lane & 16; ag[j] = (hi ? au[j] : ag[j]) + __shfl_xor_sync(0xffffffff, hi ? ag[j] : au[j], 16); }
      #pragma unroll
      for (int j = 0; j < 4; j++) { const bool hi = lane & 8; ag[j] = (hi ? ag[j+4] : ag[j]) + __shfl_xor_sync(0xffffffff, hi ? ag[j] : ag[j+4], 8); }
      #pragma unroll
      for (int j = 0; j < 2; j++) { const bool hi = lane & 4; ag[j] = (hi ? ag[j+2] : ag[j]) + __shfl_xor_sync(0xffffffff, hi ? ag[j] : ag[j+2], 4); }
      { const bool hi = lane & 2; ag[0] = (hi ? ag[1] : ag[0]) + __shfl_xor_sync(0xffffffff, hi ? ag[0] : ag[1], 2); }
      s_red[cw * 32 + (lane & 16) + (lane & 1) * 8 + ((lane >> 1) & 7)] = ag[0];
      bar_sync(5, 256);
      float g = 0.f;
      #pragma unroll
      for (int i = 0; i < 8; i++) g += s_red[i * 32 + lane];
      g = rbf(g);
      const float u = __shfl_down_sync(0xffffffff, g, 16);
      const float act = rbf(rbf(__fdividef(g, 1.f + __expf(-g))) * u);
      float y0 = 0.f, y1 = 0.f;
      #pragma unroll
      for (int r = 0; r < 16; r++) { const float av = __shfl_sync(0xffffffff, act, r); y0 = fmaf(av, bf_lo(wdv[r]), y0); y1 = fmaf(av, bf_hi(wdv[r]), y1); }
      st_tagged2(&g_yll[blockIdx.x][2 * ct], __float_as_uint(y0), __float_as_uint(y1), tag);
    }
    DBG(108);
    if (wbest == cbest && wbest != s_key[8]) store_row(out + (size_t)(row0 + rb) * DM, lane, ob);
    DBG(109);
    __syncwarp();
    cluster_wait();
  }
}

typedef CUresult (*EncodeFn)(CUtensorMap*, CUtensorMapDataType, cuuint32_t, void*, const cuuint64_t*, const cuuint64_t*, const cuuint32_t*,
                             const cuuint32_t*, CUtensorMapInterleave, CUtensorMapSwizzle, CUtensorMapL2promotion, CUtensorMapFloatOOBfill);

struct HostState {
  bool ready = false;
  EncodeFn encode = nullptr;
  CUtensorMap tmC, tmH, tmWq, tmWk, tmWv, tmKV, tmWo, tmPart, tmWg, tmWu, tmPl;
  Sched sched;
};

void make_map(EncodeFn enc, CUtensorMap* m, const void* ptr, int rank, const cuuint64_t* dims, const cuuint64_t* strides, const cuuint32_t* box, bool swizzle = true) {
  const cuuint32_t es[3] = {1, 1, 1};
  enc(m, CU_TENSOR_MAP_DATA_TYPE_BFLOAT16, rank, const_cast<void*>(ptr), dims, strides, box, es, CU_TENSOR_MAP_INTERLEAVE_NONE,
      swizzle ? CU_TENSOR_MAP_SWIZZLE_128B : CU_TENSOR_MAP_SWIZZLE_NONE, swizzle ? CU_TENSOR_MAP_L2_PROMOTION_L2_128B : CU_TENSOR_MAP_L2_PROMOTION_NONE, CU_TENSOR_MAP_FLOAT_OOB_FILL_NONE);
}
void make_2d(EncodeFn enc, CUtensorMap* m, const void* ptr, int rows, int cols, int box_rows) {
  const cuuint64_t dims[2] = {(cuuint64_t)cols, (cuuint64_t)rows}, strides[1] = {(cuuint64_t)cols * 2};
  const cuuint32_t box[2] = {64, (cuuint32_t)box_rows};
  make_map(enc, m, ptr, 2, dims, strides, box);
}
void make_3d(EncodeFn enc, CUtensorMap* m, const void* ptr, int rows, int chunks, size_t row_stride, size_t chunk_stride) {
  const cuuint64_t dims[3] = {64, (cuuint64_t)rows, (cuuint64_t)chunks}, strides[2] = {row_stride, chunk_stride};
  const cuuint32_t box[3] = {64, 64, 2};
  make_map(enc, m, ptr, 3, dims, strides, box);
}

void make_ffn(EncodeFn enc, CUtensorMap* m, const void* ptr) {
  const cuuint64_t dims[2] = {(cuuint64_t)FF, (cuuint64_t)DM}, strides[1] = {(cuuint64_t)FF * 2};
  const cuuint32_t box[2] = {16, 256};
  make_map(enc, m, ptr, 2, dims, strides, box, false);
}

#define KORDER 2, 3, 0, 1
void build_sched(Sched& s) {
  memset(&s, 0, sizeof(s));
  const int korder[4] = {KORDER};
  for (int p = 0; p < NCTA / 2; p++) {
    const int hh = p >> 3, a = p & 7, b = (a + 4) & 7;
    for (int k = 0; k < 4; k++) s.khead[p][k] = (uint8_t)(korder[k] * 8 + hh);
    const int js[4] = {a, b, 7 - a, 7 - b};
    s.nitems[p] = 4;
    for (int r = 0; r < 4; r++) s.item[p][r] = (uint8_t)((r * 8 + hh) * 8 + js[r]);
    const int kq = p >> 4;
    s.otask[p] = (uint8_t)(p & 63);
    for (int k = 0; k < 8; k++) s.ohead[p][k] = (uint8_t)((k >> 1) * 8 + kq * 2 + (k & 1));
  }
}

}

extern "C" void kernel_launch(void* const* d_in, const int* in_sizes, int n_in, void* d_out, int out_size) {
  (void)in_sizes; (void)n_in; (void)out_size;
  const __nv_bfloat16* x     = (const __nv_bfloat16*)d_in[0];
  const __nv_bfloat16* ckv   = (const __nv_bfloat16*)d_in[1];
  const __nv_bfloat16* w_q   = (const __nv_bfloat16*)d_in[2];
  const __nv_bfloat16* w_uk  = (const __nv_bfloat16*)d_in[3];
  const __nv_bfloat16* w_uv  = (const __nv_bfloat16*)d_in[4];
  const __nv_bfloat16* w_o   = (const __nv_bfloat16*)d_in[5];
  const __nv_bfloat16* w_r   = (const __nv_bfloat16*)d_in[7];
  const __nv_bfloat16* w_g   = (const __nv_bfloat16*)d_in[8];
  const __nv_bfloat16* w_u   = (const __nv_bfloat16*)d_in[9];
  const __nv_bfloat16* w_d   = (const __nv_bfloat16*)d_in[10];
  const __nv_bfloat16* cvec  = (const __nv_bfloat16*)d_in[11];
  const __nv_bfloat16* w_mod = (const __nv_bfloat16*)d_in[12];
  __nv_bfloat16* out = (__nv_bfloat16*)d_out;

  static HostState st;
  if (!st.ready) {
    void* fn = nullptr; cudaDriverEntryPointQueryResult qr;
    cudaGetDriverEntryPoint("cuTensorMapEncodeTiled", &fn, cudaEnableDefault, &qr);
    st.encode = (EncodeFn)fn;
    cudaFuncSetAttribute(k_fused, cudaFuncAttributeMaxDynamicSharedMemorySize, SMEM);
    build_sched(st.sched);
    void *p_kvc, *p_h1, *p_part;
    cudaGetSymbolAddress(&p_kvc, g_kvc); cudaGetSymbolAddress(&p_h1, g_h1); cudaGetSymbolAddress(&p_part, g_part);
    make_2d(st.encode, &st.tmH, p_h1, SEQ, DM, 64);
    make_2d(st.encode, &st.tmKV, p_kvc, 192 * SEQ, 64, 128);
    make_3d(st.encode, &st.tmPart, p_part, SEQ, 32, 128, (size_t)SEQ * 128);
    { const cuuint64_t dims[3] = {64, (cuuint64_t)SEQ, 32}, strides[2] = {128, (cuuint64_t)SEQ * 128}; const cuuint32_t box[3] = {64, 16, 4};
      make_map(st.encode, &st.tmPl, p_part, 3, dims, strides, box, false); }
    st.ready = true;
  }
  make_2d(st.encode, &st.tmC, ckv, SEQ, DM, 128);
  make_2d(st.encode, &st.tmWq, w_q, DM, NH * DH, 64);
  make_2d(st.encode, &st.tmWk, w_uk, DM, NH * DH, 64);
  make_2d(st.encode, &st.tmWv, w_uv, DM, NH * DH, 64);
  make_3d(st.encode, &st.tmWo, w_o, NH * DH, DM / 64, (size_t)DM * 2, 128);
  make_ffn(st.encode, &st.tmWg, w_g);
  make_ffn(st.encode, &st.tmWu, w_u);

  k_fused<<<NGRID, 384, SMEM, cudaStreamPerThread>>>(st.tmC, st.tmH, st.tmWq, st.tmWk, st.tmWv, st.tmKV, st.tmWo, st.tmPart, st.tmWg, st.tmWu, st.tmPl, st.sched,
                                                     x, ckv, w_uk, cvec, w_mod, w_r, w_g, w_u, w_d, out);
}
```

```cpp
#include <cuda_runtime.h>
#include <cuda_bf16.h>
#include <cuda.h>
#include <stdint.h>
#include <string.h>
#include <math.h>

namespace {

constexpr int SEQ = 2048, DM = 512, NH = 32, DH = 128, FF = 1792;
constexpr int NCTA = 128, NGRID = 132;

__device__ __nv_bfloat16 g_kvc[192 * SEQ * 64];
__device__ __nv_bfloat16 g_h1[SEQ * DM];
__device__ __nv_bfloat16 g_part[32 * SEQ * 64];
__device__ __align__(16) __nv_bfloat16 g_mod[6 * DM];
constexpr int C_MOD = 0, C_MOD2 = 16, C_H1 = 32, C_KV = 64, C_CTX = 128, C_END = 384;
__device__ unsigned int g_cnt[C_END];
__device__ unsigned int g_epoch;
__device__ __align__(128) unsigned int g_pflag[32][32];
__device__ __align__(128) uint2 g_keys[128][4];
__device__ __align__(16) uint2 g_row[128][2][DM / 2];
__device__ __align__(16) uint2 g_yll[FF / 16][DM];

#define DBG(i)
#define DBGP(i)

__device__ __forceinline__ uint32_t smem_u32(const void* p) { return (uint32_t)__cvta_generic_to_shared(p); }
__device__ __forceinline__ int wg_tid() { int t; asm volatile("mov.u32 %0, %%tid.x;" : "=r"(t)); return t & 127; }
__device__ __forceinline__ uint32_t clk32() { uint32_t c; asm volatile("mov.u32 %0, %%clock;" : "=r"(c)); return c; }
__device__ __forceinline__ void mbar_arrive(uint32_t bar) { asm volatile("mbarrier.arrive.shared::cta.b64 _, [%0];" :: "r"(bar) : "memory"); }
__device__ __forceinline__ uint32_t mapa(uint32_t addr, uint32_t cta) { uint32_t r; asm("mapa.shared::cluster.u32 %0, %1, %2;" : "=r"(r) : "r"(addr), "r"(cta)); return r; }
__device__ __forceinline__ void mbar_arrive_remote_if(uint32_t cluster_addr, bool pred) {
  asm volatile("{\n.reg .pred p;\nsetp.ne.u32 p, %1, 0;\n@p mbarrier.arrive.shared::cluster.b64 _, [%0];\n}" :: "r"(cluster_addr), "r"((uint32_t)pred) : "memory");
}
__device__ __forceinline__ bool mbar_try(uint32_t bar, uint32_t parity) {
  uint32_t done;
  asm volatile("{\n.reg .pred p;\nmbarrier.try_wait.parity.shared::cta.b64 p, [%1], %2;\nselp.u32 %0, 1, 0, p;\n}" : "=r"(done) : "r"(bar), "r"(parity) : "memory");
  return done;
}
#define WAIT_LIM (1 << 14)
__device__ __forceinline__ void mbar_wait(uint32_t bar, uint32_t parity) {
  #pragma unroll 1
  for (int n = 0; n < WAIT_LIM; n++) { if (mbar_try(bar, parity)) break; }
}
__device__ __forceinline__ unsigned int ld_acquire(const unsigned int* p) {
  unsigned int v; asm volatile("ld.acquire.gpu.global.u32 %0, [%1];" : "=r"(v) : "l"(p) : "memory"); return v;
}
__device__ __forceinline__ unsigned int ld_relaxed(const unsigned int* p) {
  unsigned int v; asm volatile("ld.relaxed.gpu.global.u32 %0, [%1];" : "=r"(v) : "l"(p) : "memory"); return v;
}
__device__ __forceinline__ void wait_count_lazy(int idx, unsigned int target) {
  #pragma unroll 1
  for (int n = 0; n < WAIT_LIM; n++) { if ((int)(ld_relaxed(&g_cnt[idx]) - target) >= 0) break; __nanosleep(100); }
  ld_acquire(&g_cnt[idx]);
}
__device__ __forceinline__ uint4 ld_tagged2(const void* p) {
  uint4 v;
  asm volatile("{\n.reg .b64 a, b;\nld.relaxed.gpu.global.v2.u64 {a, b}, [%4];\nmov.b64 {%0, %1}, a;\nmov.b64 {%2, %3}, b;\n}"
    : "=r"(v.x), "=r"(v.y), "=r"(v.z), "=r"(v.w) : "l"(p) : "memory");
  return v;
}
__device__ __forceinline__ uint2 ld_tagged(const void* p) {
  uint2 v; asm volatile("{\n.reg .b64 a;\nld.relaxed.gpu.global.u64 a, [%2];\nmov.b64 {%0, %1}, a;\n}" : "=r"(v.x), "=r"(v.y) : "l"(p) : "memory"); return v;
}
__device__ __forceinline__ void st_tagged2(void* p, uint32_t a, uint32_t b, uint32_t tag) {
  asm volatile("{\n.reg .b64 a, b;\nmov.b64 a, {%1, %3};\nmov.b64 b, {%2, %3};\nst.relaxed.gpu.global.v2.u64 [%0], {a, b};\n}" :: "l"(p), "r"(a), "r"(b), "r"(tag) : "memory");
}
__device__ __forceinline__ void st_tagged(void* p, uint32_t a, uint32_t tag) {
  asm volatile("{\n.reg .b64 a;\nmov.b64 a, {%1, %2};\nst.relaxed.gpu.global.u64 [%0], a;\n}" :: "l"(p), "r"(a), "r"(tag) : "memory");
}
__device__ __forceinline__ void stg_v4(void* p, uint32_t a, uint32_t b, uint32_t c, uint32_t d) {
  asm volatile("st.global.v4.u32 [%0], {%1, %2, %3, %4};" :: "l"(p), "r"(a), "r"(b), "r"(c), "r"(d) : "memory");
}
__device__ __forceinline__ uint4 lds_v4(uint32_t addr) {
  uint4 v; asm volatile("ld.shared.v4.u32 {%0, %1, %2, %3}, [%4];" : "=r"(v.x), "=r"(v.y), "=r"(v.z), "=r"(v.w) : "r"(addr) : "memory"); return v;
}
__device__ __forceinline__ uint32_t lds_u32(uint32_t addr) { uint32_t v; asm volatile("ld.shared.u32 %0, [%1];" : "=r"(v) : "r"(addr) : "memory"); return v; }
__device__ __forceinline__ void sts_v4(uint32_t addr, uint32_t a, uint32_t b, uint32_t c, uint32_t d) {
  asm volatile("st.shared.v4.u32 [%0], {%1, %2, %3, %4};" :: "r"(addr), "r"(a), "r"(b), "r"(c), "r"(d) : "memory");
}
#define ELECT "{\n.reg .pred p;\nelect.sync _|p, 0xffffffff;\n@p "
__device__ __forceinline__ void w_mbar_init(uint32_t bar, uint32_t cnt) { asm volatile(ELECT "mbarrier.init.shared::cta.b64 [%0], %1;\n}" :: "r"(bar), "r"(cnt) : "memory"); }
__device__ __forceinline__ void w_expect_tx(uint32_t bar, uint32_t bytes) { asm volatile(ELECT "mbarrier.arrive.expect_tx.shared::cta.b64 _, [%0], %1;\n}" :: "r"(bar), "r"(bytes) : "memory"); }
__device__ __forceinline__ void w_arrive(uint32_t bar) { asm volatile(ELECT "mbarrier.arrive.shared::cta.b64 _, [%0];\n}" :: "r"(bar) : "memory"); }
__device__ __forceinline__ void tma_load_2d(uint32_t dst, const CUtensorMap* tm, uint32_t bar, int c0, int c1) {
  asm volatile(ELECT "cp.async.bulk.tensor.2d.shared::cluster.global.mbarrier::complete_tx::bytes [%0], [%1, {%3, %4}], [%2];\n}"
    :: "r"(dst), "l"(tm), "r"(bar), "r"(c0), "r"(c1) : "memory");
}
__device__ __forceinline__ void tma_load_2d_mc(uint32_t dst, const CUtensorMap* tm, uint32_t bar, int c0, int c1) {
  asm volatile(ELECT "cp.async.bulk.tensor.2d.shared::cluster.global.mbarrier::complete_tx::bytes.multicast::cluster [%0], [%1, {%3, %4}], [%2], %5;\n}"
    :: "r"(dst), "l"(tm), "r"(bar), "r"(c0), "r"(c1), "h"((uint16_t)3) : "memory");
}
__device__ __forceinline__ void tma_load_3d(uint32_t dst, const CUtensorMap* tm, uint32_t bar, int c0, int c1, int c2) {
  asm volatile(ELECT "cp.async.bulk.tensor.3d.shared::cluster.global.mbarrier::complete_tx::bytes [%0], [%1, {%3, %4, %5}], [%2];\n}"
    :: "r"(dst), "l"(tm), "r"(bar), "r"(c0), "r"(c1), "r"(c2) : "memory");
}
__device__ __forceinline__ void tma_load_3d_mc(uint32_t dst, const CUtensorMap* tm, uint32_t bar, int c0, int c1, int c2) {
  asm volatile(ELECT "cp.async.bulk.tensor.3d.shared::cluster.global.mbarrier::complete_tx::bytes.multicast::cluster [%0], [%1, {%3, %4, %5}], [%2], %6;\n}"
    :: "r"(dst), "l"(tm), "r"(bar), "r"(c0), "r"(c1), "r"(c2), "h"((uint16_t)3) : "memory");
}
__device__ __forceinline__ void bulk_load(uint32_t dst, const void* src, uint32_t bytes, uint32_t bar) {
  asm volatile(ELECT "cp.async.bulk.shared::cluster.global.mbarrier::complete_tx::bytes [%0], [%1], %2, [%3];\n}" :: "r"(dst), "l"(src), "r"(bytes), "r"(bar) : "memory");
}
__device__ __forceinline__ void tma_prefetch_2d(const CUtensorMap* tm, int c0, int c1) {
  asm volatile(ELECT "cp.async.bulk.prefetch.tensor.2d.L2.global [%0, {%1, %2}];\n}" :: "l"(tm), "r"(c0), "r"(c1) : "memory");
}
__device__ __forceinline__ void tma_prefetch_3d(const CUtensorMap* tm, int c0, int c1, int c2) {
  asm volatile(ELECT "cp.async.bulk.prefetch.tensor.3d.L2.global [%0, {%1, %2, %3}];\n}" :: "l"(tm), "r"(c0), "r"(c1), "r"(c2) : "memory");
}
__device__ __forceinline__ void bulk_prefetch(const void* p, uint32_t bytes) {
  asm volatile(ELECT "cp.async.bulk.prefetch.L2.global [%0], %1;\n}" :: "l"(p), "r"(bytes) : "memory");
}
__device__ __forceinline__ void tma_store_3d(const CUtensorMap* tm, uint32_t src, int c0, int c1, int c2) {
  asm volatile("cp.async.bulk.tensor.3d.global.shared::cta.bulk_group [%0, {%2, %3, %4}], [%1];"
    :: "l"(tm), "r"(src), "r"(c0), "r"(c1), "r"(c2) : "memory");
}
__device__ __forceinline__ void st_release(unsigned int* p, unsigned int v) { asm volatile("st.release.gpu.global.u32 [%0], %1;" :: "l"(p), "r"(v) : "memory"); }
__device__ __forceinline__ void red_release(int idx) { asm volatile("red.release.gpu.global.add.u32 [%0], 1;" :: "l"(&g_cnt[idx]) : "memory"); }
__device__ __forceinline__ void prefetch_tmap(const CUtensorMap* tm) { asm volatile("prefetch.tensormap [%0];" :: "l"(tm) : "memory"); }
__device__ __forceinline__ void bulk_commit() { asm volatile("cp.async.bulk.commit_group;" ::: "memory"); }
template<int N> __device__ __forceinline__ void bulk_wait() { asm volatile("cp.async.bulk.wait_group %0;" :: "n"(N) : "memory"); }
__device__ __forceinline__ void bar_sync(int id, int n) { asm volatile("bar.sync %0, %1;" :: "r"(id), "r"(n) : "memory"); }
__device__ __forceinline__ void bar_arrive(int id, int n) { asm volatile("bar.arrive %0, %1;" :: "r"(id), "r"(n) : "memory"); }
__device__ __forceinline__ void fence_async_smem() { asm volatile("fence.proxy.async.shared::cta;" ::: "memory"); }
__device__ __forceinline__ void fence_async_global() { asm volatile("fence.proxy.async.global;" ::: "memory"); }
__device__ __forceinline__ void fence_mbar_init() { asm volatile("fence.mbarrier_init.release.cluster;" ::: "memory"); }
__device__ __forceinline__ void cluster_arrive() { asm volatile("barrier.cluster.arrive.relaxed.aligned;" ::: "memory"); }
__device__ __forceinline__ void cluster_wait() { asm volatile("barrier.cluster.wait.aligned;" ::: "memory"); }
__device__ __forceinline__ uint32_t cluster_ctarank() { uint32_t r; asm volatile("mov.u32 %0, %%cluster_ctarank;" : "=r"(r)); return r; }
__device__ __forceinline__ void wgmma_fence() { asm volatile("wgmma.fence.sync.aligned;" ::: "memory"); }
__device__ __forceinline__ void wgmma_commit() { asm volatile("wgmma.commit_group.sync.aligned;" ::: "memory"); }
template<int N> __device__ __forceinline__ void wgmma_wait() { asm volatile("wgmma.wait_group.sync.aligned %0;" :: "n"(N) : "memory"); }
__device__ __forceinline__ float ex2(float x) { float y; asm("ex2.approx.ftz.f32 %0, %1;" : "=f"(y) : "f"(x)); return y; }
__device__ __forceinline__ float rcp_fast(float x) { float y; asm("rcp.approx.ftz.f32 %0, %1;" : "=f"(y) : "f"(x)); return y; }
__device__ __forceinline__ uint32_t pack_bf16(float lo, float hi) { uint32_t r; asm("cvt.rn.bf16x2.f32 %0, %1, %2;" : "=r"(r) : "f"(hi), "f"(lo)); return r; }
__device__ __forceinline__ float rbf(float x) { return __uint_as_float(pack_bf16(0.f, x)); }
__device__ __forceinline__ float bf_lo(uint32_t v) { return __uint_as_float(v << 16); }
__device__ __forceinline__ float bf_hi(uint32_t v) { return __uint_as_float(v & 0xffff0000u); }
__device__ __forceinline__ uint32_t add2(uint32_t a, uint32_t b) { uint32_t r; asm("add.rn.bf16x2 %0, %1, %2;" : "=r"(r) : "r"(a), "r"(b)); return r; }
__device__ __forceinline__ uint32_t fma2(uint32_t a, uint32_t b, uint32_t c) { uint32_t r; asm("fma.rn.bf16x2 %0, %1, %2, %3;" : "=r"(r) : "r"(a), "r"(b), "r"(c)); return r; }
__device__ __forceinline__ void prefetch_l2(const void* p) { asm volatile("prefetch.global.L2 [%0];" :: "l"(p) : "memory"); }
__device__ __forceinline__ void stsm_x4(uint32_t addr, uint32_t r0, uint32_t r1, uint32_t r2, uint32_t r3) {
  asm volatile("stmatrix.sync.aligned.m8n8.x4.shared.b16 [%0], {%1, %2, %3, %4};" :: "r"(addr), "r"(r0), "r"(r1), "r"(r2), "r"(r3) : "memory");
}
template<int N> __device__ __forceinline__ void fence_regs(float (&a)[N]) {
  #pragma unroll
  for (int i = 0; i < N; i++) asm volatile("" : "+f"(a[i]) :: "memory");
}
template<int N> __device__ __forceinline__ void fence_regs_u(uint32_t (&a)[N]) {
  #pragma unroll
  for (int i = 0; i < N; i++) asm volatile("" : "+r"(a[i]) :: "memory");
}
__device__ __forceinline__ uint32_t desc_lo(uint32_t addr, uint32_t lbo) { return ((addr & 0x3FFFF) >> 4) | ((lbo >> 4) << 16); }

template<int TB, int OA, int OB> __device__ __forceinline__ void wgmma_ss_n128(float (&d)[64], uint32_t da, uint32_t db, int sd) {
  asm volatile("{\n.reg .pred p;\n.reg .b32 ta, tb;\n.reg .b64 da, db;\nsetp.ne.b32 p, %66, 0;\nadd.u32 ta, %64, %68;\nadd.u32 tb, %65, %69;\nmov.b64 da, {ta, 0x40000040};\nmov.b64 db, {tb, 0x40000040};\n"
    "wgmma.mma_async.sync.aligned.m64n128k16.f32.bf16.bf16 "
    "{%0, %1, %2, %3, %4, %5, %6, %7, %8, %9, %10, %11, %12, %13, %14, %15, %16, %17, %18, %19, %20, %21, %22, %23, %24, %25, %26, %27, %28, %29, %30, %31, %32, %33, %34, %35, %36, %37, %38, %39, %40, %41, %42, %43, %44, %45, %46, %47, %48, %49, %50, %51, %52, %53, %54, %55, %56, %57, %58, %59, %60, %61, %62, %63}, da, db, p, 1, 1, 0, %67;\n}\n"
    : "+f"(d[0]), "+f"(d[1]), "+f"(d[2]), "+f"(d[3]), "+f"(d[4]), "+f"(d[5]), "+f"(d[6]), "+f"(d[7]), "+f"(d[8]), "+f"(d[9]), "+f"(d[10]), "+f"(d[11]), "+f"(d[12]), "+f"(d[13]), "+f"(d[14]), "+f"(d[15]), "+f"(d[16]), "+f"(d[17]), "+f"(d[18]), "+f"(d[19]), "+f"(d[20]), "+f"(d[21]), "+f"(d[22]), "+f"(d[23]), "+f"(d[24]), "+f"(d[25]), "+f"(d[26]), "+f"(d[27]), "+f"(d[28]), "+f"(d[29]), "+f"(d[30]), "+f"(d[31]), "+f"(d[32]), "+f"(d[33]), "+f"(d[34]), "+f"(d[35]), "+f"(d[36]), "+f"(d[37]), "+f"(d[38]), "+f"(d[39]), "+f"(d[40]), "+f"(d[41]), "+f"(d[42]), "+f"(d[43]), "+f"(d[44]), "+f"(d[45]), "+f"(d[46]), "+f"(d[47]), "+f"(d[48]), "+f"(d[49]), "+f"(d[50]), "+f"(d[51]), "+f"(d[52]), "+f"(d[53]), "+f"(d[54]), "+f"(d[55]), "+f"(d[56]), "+f"(d[57]), "+f"(d[58]), "+f"(d[59]), "+f"(d[60]), "+f"(d[61]), "+f"(d[62]), "+f"(d[63])
    : "r"(da), "r"(db), "r"(sd), "n"(TB), "n"(OA), "n"(OB));
}
template<int TB, int OB> __device__ __forceinline__ void wgmma_rs_n128(float (&d)[64], uint32_t a0, uint32_t a1, uint32_t a2, uint32_t a3, uint32_t db, int sd) {
  asm volatile("{\n.reg .pred p;\n.reg .b32 tb;\n.reg .b64 db;\nsetp.ne.b32 p, %69, 0;\nadd.u32 tb, %68, %71;\nmov.b64 db, {tb, 0x40000040};\n"
    "wgmma.mma_async.sync.aligned.m64n128k16.f32.bf16.bf16 "
    "{%0, %1, %2, %3, %4, %5, %6, %7, %8, %9, %10, %11, %12, %13, %14, %15, %16, %17, %18, %19, %20, %21, %22, %23, %24, %25, %26, %27, %28, %29, %30, %31, %32, %33, %34, %35, %36, %37, %38, %39, %40, %41, %42, %43, %44, %45, %46, %47, %48, %49, %50, %51, %52, %53, %54, %55, %56, %57, %58, %59, %60, %61, %62, %63}, {%64,%65,%66,%67}, db, p, 1, 1, %70;\n}\n"
    : "+f"(d[0]), "+f"(d[1]), "+f"(d[2]), "+f"(d[3]), "+f"(d[4]), "+f"(d[5]), "+f"(d[6]), "+f"(d[7]), "+f"(d[8]), "+f"(d[9]), "+f"(d[10]), "+f"(d[11]), "+f"(d[12]), "+f"(d[13]), "+f"(d[14]), "+f"(d[15]), "+f"(d[16]), "+f"(d[17]), "+f"(d[18]), "+f"(d[19]), "+f"(d[20]), "+f"(d[21]), "+f"(d[22]), "+f"(d[23]), "+f"(d[24]), "+f"(d[25]), "+f"(d[26]), "+f"(d[27]), "+f"(d[28]), "+f"(d[29]), "+f"(d[30]), "+f"(d[31]), "+f"(d[32]), "+f"(d[33]), "+f"(d[34]), "+f"(d[35]), "+f"(d[36]), "+f"(d[37]), "+f"(d[38]), "+f"(d[39]), "+f"(d[40]), "+f"(d[41]), "+f"(d[42]), "+f"(d[43]), "+f"(d[44]), "+f"(d[45]), "+f"(d[46]), "+f"(d[47]), "+f"(d[48]), "+f"(d[49]), "+f"(d[50]), "+f"(d[51]), "+f"(d[52]), "+f"(d[53]), "+f"(d[54]), "+f"(d[55]), "+f"(d[56]), "+f"(d[57]), "+f"(d[58]), "+f"(d[59]), "+f"(d[60]), "+f"(d[61]), "+f"(d[62]), "+f"(d[63])
    : "r"(a0), "r"(a1), "r"(a2), "r"(a3), "r"(db), "r"(sd), "n"(TB), "n"(OB));
}
template<int TB, int OA, int OB> __device__ __forceinline__ void wgmma_ss_n64(float (&d)[32], uint32_t da, uint32_t db, int sd) {
  asm volatile("{\n.reg .pred p;\n.reg .b32 ta, tb;\n.reg .b64 da, db;\nsetp.ne.b32 p, %34, 0;\nadd.u32 ta, %32, %36;\nadd.u32 tb, %33, %37;\nmov.b64 da, {ta, 0x40000040};\nmov.b64 db, {tb, 0x40000040};\n"
    "wgmma.mma_async.sync.aligned.m64n64k16.f32.bf16.bf16 "
    "{%0, %1, %2, %3, %4, %5, %6, %7, %8, %9, %10, %11, %12, %13, %14, %15, %16, %17, %18, %19, %20, %21, %22, %23, %24, %25, %26, %27, %28, %29, %30, %31}, da, db, p, 1, 1, 0, %35;\n}\n"
    : "+f"(d[0]), "+f"(d[1]), "+f"(d[2]), "+f"(d[3]), "+f"(d[4]), "+f"(d[5]), "+f"(d[6]), "+f"(d[7]), "+f"(d[8]), "+f"(d[9]), "+f"(d[10]), "+f"(d[11]), "+f"(d[12]), "+f"(d[13]), "+f"(d[14]), "+f"(d[15]), "+f"(d[16]), "+f"(d[17]), "+f"(d[18]), "+f"(d[19]), "+f"(d[20]), "+f"(d[21]), "+f"(d[22]), "+f"(d[23]), "+f"(d[24]), "+f"(d[25]), "+f"(d[26]), "+f"(d[27]), "+f"(d[28]), "+f"(d[29]), "+f"(d[30]), "+f"(d[31])
    : "r"(da), "r"(db), "r"(sd), "n"(TB), "n"(OA), "n"(OB));
}
template<int TB, int OA, int OB> __device__ __forceinline__ void wgmma_ss_n128_new(float (&d)[64], uint32_t da, uint32_t db) {
  asm volatile("{\n.reg .pred p;\n.reg .b32 ta, tb;\n.reg .b64 da, db;\nsetp.ne.b32 p, %66, 0;\nadd.u32 ta, %64, %68;\nadd.u32 tb, %65, %69;\nmov.b64 da, {ta, 0x40000040};\nmov.b64 db, {tb, 0x40000040};\n"
    "wgmma.mma_async.sync.aligned.m64n128k16.f32.bf16.bf16 "
    "{%0, %1, %2, %3, %4, %5, %6, %7, %8, %9, %10, %11, %12, %13, %14, %15, %16, %17, %18, %19, %20, %21, %22, %23, %24, %25, %26, %27, %28, %29, %30, %31, %32, %33, %34, %35, %36, %37, %38, %39, %40, %41, %42, %43, %44, %45, %46, %47, %48, %49, %50, %51, %52, %53, %54, %55, %56, %57, %58, %59, %60, %61, %62, %63}, da, db, p, 1, 1, 0, %67;\n}\n"
    : "=f"(d[0]), "=f"(d[1]), "=f"(d[2]), "=f"(d[3]), "=f"(d[4]), "=f"(d[5]), "=f"(d[6]), "=f"(d[7]), "=f"(d[8]), "=f"(d[9]), "=f"(d[10]), "=f"(d[11]), "=f"(d[12]), "=f"(d[13]), "=f"(d[14]), "=f"(d[15]), "=f"(d[16]), "=f"(d[17]), "=f"(d[18]), "=f"(d[19]), "=f"(d[20]), "=f"(d[21]), "=f"(d[22]), "=f"(d[23]), "=f"(d[24]), "=f"(d[25]), "=f"(d[26]), "=f"(d[27]), "=f"(d[28]), "=f"(d[29]), "=f"(d[30]), "=f"(d[31]), "=f"(d[32]), "=f"(d[33]), "=f"(d[34]), "=f"(d[35]), "=f"(d[36]), "=f"(d[37]), "=f"(d[38]), "=f"(d[39]), "=f"(d[40]), "=f"(d[41]), "=f"(d[42]), "=f"(d[43]), "=f"(d[44]), "=f"(d[45]), "=f"(d[46]), "=f"(d[47]), "=f"(d[48]), "=f"(d[49]), "=f"(d[50]), "=f"(d[51]), "=f"(d[52]), "=f"(d[53]), "=f"(d[54]), "=f"(d[55]), "=f"(d[56]), "=f"(d[57]), "=f"(d[58]), "=f"(d[59]), "=f"(d[60]), "=f"(d[61]), "=f"(d[62]), "=f"(d[63])
    : "r"(da), "r"(db), "n"(0), "n"(TB), "n"(OA), "n"(OB));
}
template<int TB, int OA, int OB> __device__ __forceinline__ void wgmma_ss_n64_new(float (&d)[32], uint32_t da, uint32_t db) {
  asm volatile("{\n.reg .pred p;\n.reg .b32 ta, tb;\n.reg .b64 da, db;\nsetp.ne.b32 p, %34, 0;\nadd.u32 ta, %32, %36;\nadd.u32 tb, %33, %37;\nmov.b64 da, {ta, 0x40000040};\nmov.b64 db, {tb, 0x40000040};\n"
    "wgmma.mma_async.sync.aligned.m64n64k16.f32.bf16.bf16 "
    "{%0, %1, %2, %3, %4, %5, %6, %7, %8, %9, %10, %11, %12, %13, %14, %15, %16, %17, %18, %19, %20, %21, %22, %23, %24, %25, %26, %27, %28, %29, %30, %31}, da, db, p, 1, 1, 0, %35;\n}\n"
    : "=f"(d[0]), "=f"(d[1]), "=f"(d[2]), "=f"(d[3]), "=f"(d[4]), "=f"(d[5]), "=f"(d[6]), "=f"(d[7]), "=f"(d[8]), "=f"(d[9]), "=f"(d[10]), "=f"(d[11]), "=f"(d[12]), "=f"(d[13]), "=f"(d[14]), "=f"(d[15]), "=f"(d[16]), "=f"(d[17]), "=f"(d[18]), "=f"(d[19]), "=f"(d[20]), "=f"(d[21]), "=f"(d[22]), "=f"(d[23]), "=f"(d[24]), "=f"(d[25]), "=f"(d[26]), "=f"(d[27]), "=f"(d[28]), "=f"(d[29]), "=f"(d[30]), "=f"(d[31])
    : "r"(da), "r"(db), "n"(0), "n"(TB), "n"(OA), "n"(OB));
}
template<int OA, int OB = 0> __device__ __forceinline__ void kblock_n128(float (&d)[64], uint32_t da, uint32_t db, int sd) {
  wgmma_ss_n128<1, OA, OB>(d, da, db, sd); wgmma_ss_n128<1, OA + 2, OB + 128>(d, da, db, 1);
  wgmma_ss_n128<1, OA + 4, OB + 256>(d, da, db, 1); wgmma_ss_n128<1, OA + 6, OB + 384>(d, da, db, 1);
}

__device__ __forceinline__ float quad_sum(float v) {
  v += __shfl_xor_sync(0xffffffff, v, 1);
  v += __shfl_xor_sync(0xffffffff, v, 2);
  return v;
}
__device__ __forceinline__ void unpack8(const uint4& v, float* f) {
  f[0] = bf_lo(v.x); f[1] = bf_hi(v.x); f[2] = bf_lo(v.y); f[3] = bf_hi(v.y);
  f[4] = bf_lo(v.z); f[5] = bf_hi(v.z); f[6] = bf_lo(v.w); f[7] = bf_hi(v.w);
}
struct Row { uint32_t v[8]; };
template<class F> __device__ __forceinline__ Row load_row(const __nv_bfloat16* p, int lane, F ld) {
  const uint4 a = ld(reinterpret_cast<const uint4*>(p) + lane), b = ld(reinterpret_cast<const uint4*>(p) + 32 + lane);
  return Row{{a.x, a.y, a.z, a.w, b.x, b.y, b.z, b.w}};
}
__device__ __forceinline__ Row ldg_row(const __nv_bfloat16* p, int lane) { return load_row(p, lane, [](const uint4* q) { return __ldg(q); }); }
__device__ __forceinline__ Row ldca_row(const __nv_bfloat16* p, int lane) { return load_row(p, lane, [](const uint4* q) { return __ldca(q); }); }
__device__ __forceinline__ Row lds_row(uint32_t addr, int lane) {
  const uint4 a = lds_v4(addr + lane * 16), b = lds_v4(addr + 512 + lane * 16);
  return Row{{a.x, a.y, a.z, a.w, b.x, b.y, b.z, b.w}};
}
__device__ __forceinline__ void store_row(__nv_bfloat16* p, int lane, const Row& r) {
  stg_v4(p + lane * 8, r.v[0], r.v[1], r.v[2], r.v[3]); stg_v4(p + 256 + lane * 8, r.v[4], r.v[5], r.v[6], r.v[7]);
}
__device__ __forceinline__ Row fma_row(const Row& a, const Row& b, const Row& c) {
  Row r;
  #pragma unroll
  for (int i = 0; i < 8; i++) r.v[i] = fma2(a.v[i], b.v[i], c.v[i]);
  return r;
}
__device__ __forceinline__ Row one_plus(const Row& a) {
  Row r;
  #pragma unroll
  for (int i = 0; i < 8; i++) r.v[i] = add2(a.v[i], 0x3f803f80u);
  return r;
}
__device__ __forceinline__ void layer_norm2(const Row (&x)[2], Row (&n)[2]) {
  float d[2][16], s[4];
  #pragma unroll
  for (int r = 0; r < 2; r++) {
    const float c = bf_lo(__shfl_sync(0xffffffff, x[r].v[0], 0));
    float s1 = 0.f, s2 = 0.f;
    #pragma unroll
    for (int i = 0; i < 16; i++) { d[r][i] = ((i & 1) ? bf_hi(x[r].v[i >> 1]) : bf_lo(x[r].v[i >> 1])) - c; s1 += d[r][i]; s2 = fmaf(d[r][i], d[r][i], s2); }
    s[2*r] = s1; s[2*r+1] = s2;
  }
  #pragma unroll
  for (int o = 16; o > 0; o >>= 1) {
    #pragma unroll
    for (int k = 0; k < 4; k++) s[k] += __shfl_xor_sync(0xffffffff, s[k], o);
  }
  #pragma unroll
  for (int r = 0; r < 2; r++) {
    const float m = s[2*r] * (1.f / DM), rstd = rsqrtf(fmaxf(fmaf(-m, m, s[2*r+1] * (1.f / DM)), 0.f) + 1e-5f), o = -m * rstd;
    #pragma unroll
    for (int i = 0; i < 8; i++) n[r].v[i] = pack_bf16(fmaf(d[r][2*i], rstd, o), fmaf(d[r][2*i+1], rstd, o));
  }
}

constexpr int SM_Q = 6 * 32768, SM_BAR = 7 * 32768, SM_MAIL = SM_BAR + 640, SM_RED = SM_MAIL + 128, SM_H2 = SM_RED + 1024, SM_KEY = SM_H2 + 1024, SMEM = SM_KEY + 128;
constexpr int B_AF = 0, B_WF = 64, B_RF = 112, B_WE = 168, B_RE = 216, B_PUB = 272, B_RDY = 496;
constexpr int NPUB = 14;
__device__ __forceinline__ uint32_t k_addrA(int kb) { return ((0x6310u >> ((kb >> 1) * 4)) & 15u) * 32768u + (kb & 1) * 16384u; }
__device__ __forceinline__ uint32_t k_addrW(int s) { return ((0x254u >> ((s >> 1) * 4)) & 15u) * 32768u + (s & 1) * 16384u; }

#define KORDER 0x2301
constexpr int KHEAD0 = ((KORDER >> 12) & 3) * 8;
constexpr int MAX_ITEMS = 6;
struct Sched {
  __nv_bfloat16 *kvc, *h1;
  uint8_t khead[NGRID / 2][4];
  uint8_t nitems[NGRID / 2];
  uint8_t item[NGRID / 2][MAX_ITEMS];
  uint8_t otask[NGRID / 2];
  uint8_t ohead[NGRID / 2][8];
};

__device__ __forceinline__ int ring_add(int e, int n) { e += n; return e >= 12 ? e - 12 : e; }
__device__ __forceinline__ int ring_slot(int e) { return e >= 6 ? e - 6 : e; }
__device__ __forceinline__ void ring_wait_full(uint32_t bars, int e) { mbar_wait(bars + B_RF + 8 * ring_slot(e), e >= 6); }

__device__ __forceinline__ uint32_t o_table(int e) {
  uint32_t t = 6u << 16;
  #pragma unroll
  for (int q = 0; q < 6; q++) { const int f = ring_add(e, q); t |= (uint32_t)(f >= 6 ? f + 2 : f) << (4 * (q < 4 ? q : q + 1)); }
  return t;
}
__device__ __forceinline__ uint32_t o_entry(uint32_t tab, int k) { const int pass = (k * 37) >> 8; return ((tab >> (4 * (k - 7 * pass))) & 15u) ^ ((pass & 1) << 3); }
__device__ __forceinline__ void o_wait_full(uint32_t bars, uint32_t v) { mbar_wait(bars + B_RF + 8 * (v & 7), v >> 3); }

struct Ctx {
  uint32_t base, bars;
  uint32_t rel;
  bool rel1;
  int w, nev;
  const Sched* sched;
};
__device__ __forceinline__ void slot_release(const Ctx& x, int s, bool twice) {
  mbar_arrive_remote_if(x.rel + B_RE + 8 * s, twice ? (wg_tid() & 31) == 0 : x.rel1);
}
__device__ __forceinline__ void ring_release(const Ctx& x, int e, bool twice) { slot_release(x, ring_slot(e), twice); }
__device__ __forceinline__ void publish(Ctx& x, int idx) {
  const uint32_t n = x.w * NPUB + x.nev;
  const int t = wg_tid();
  if (t == 0) asm volatile("st.shared.u32 [%0], %1;" :: "r"(x.base + SM_MAIL + 4 * n), "r"(idx) : "memory");
  __syncwarp();
  if ((t & 31) == 0) mbar_arrive(x.bars + B_PUB + 8 * n);
  x.nev++;
}

template<int KK = 0> __device__ __forceinline__ void issue_qk(float (&S)[64], uint32_t dq, uint32_t dk) {
  constexpr int off = (KK >> 2) * 1024 + (KK & 3) * 2;
  if constexpr (KK == 0) wgmma_ss_n128_new<0, 0, 0>(S, dq, dk); else wgmma_ss_n128<0, off, off>(S, dq, dk, 1);
  if constexpr (KK < 7) issue_qk<KK + 1>(S, dq, dk);
}
template<int KK = 0> __device__ __forceinline__ void issue_qk_half(float (&S)[32], uint32_t dq, uint32_t dk) {
  constexpr int off = (KK >> 2) * 1024 + (KK & 3) * 2;
  if constexpr (KK == 0) wgmma_ss_n64_new<0, 0, 512>(S, dq, dk); else wgmma_ss_n64<0, off, off + 512>(S, dq, dk, 1);
  if constexpr (KK < 7) issue_qk_half<KK + 1>(S, dq, dk);
}
template<int NK, int KK = 0>
__device__ __forceinline__ void issue_pv(float (&O)[64], uint32_t (&P)[32], uint32_t dv, int accumulate) {
  wgmma_rs_n128<1, (KK + 8 - NK) * 128>(O, P[4*KK], P[4*KK+1], P[4*KK+2], P[4*KK+3], dv, accumulate);
  if constexpr (KK + 1 < NK) issue_pv<NK, KK + 1>(O, P, dv, 1);
}
template<int K0, int K1>
__device__ __forceinline__ void exp_pack(const float (&S)[64], uint32_t (&D)[32], float& s0, float& s1) {
  #pragma unroll
  for (int k = K0; k < K1; k++) {
    const float e0 = ex2(S[2*k]), e1 = ex2(S[2*k+1]);
    D[k] = pack_bf16(e0, e1);
    if (k & 1) s1 += e0 + e1; else s0 += e0 + e1;
  }
}
__device__ __forceinline__ int q_row(int t) { return 16 * (t >> 5) + ((t >> 1) & 6) + ((t >> 4) & 1); }
__device__ __forceinline__ int diag_limit() { const int t = wg_tid(); return q_row(t) - 2 * (t & 3); }
__device__ __forceinline__ void exp_pack_diag(const float (&S)[64], uint32_t (&D)[32], int t, float& s0, float& s1) {
  #pragma unroll
  for (int k = 0; k < 16; k++) {
    const int c = 8 * (k >> 1) - 8 * (k & 1);
    const float e0 = ex2((c <= t) ? S[2*k] : -INFINITY), e1 = ex2((c + 1 <= t) ? S[2*k+1] : -INFINITY);
    D[k] = pack_bf16(e0, e1);
    if (k & 1) s1 += e0 + e1; else s0 += e0 + e1;
  }
}
constexpr float SUM_HI = 1.8446744073709552e19f;
constexpr float SUM_LO = 5.421010862427522e-20f;

__device__ __forceinline__ void classic_tile(const float (&S)[64], uint32_t (&P)[32], bool fresh, bool half, bool was_classic, volatile float* mc,
                                             float& l0, float& l1, float& s0, float& s1, float& sc0, float& sc1) {
  const int tmask = diag_limit();
  float4 t[16];
  #pragma unroll
  for (int j = 0; j < 16; j++) t[j] = make_float4(S[4*j], S[4*j+1], S[4*j+2], S[4*j+3]);
  float mx0 = -INFINITY, mx1 = -INFINITY;
  #pragma unroll 1
  for (int j = 0; j < 16; j++) {
    float4 v = t[j];
    const int lim = !fresh ? 1000 : j < 8 ? tmask - 8 * j : half ? -1000 : 1000;
    v.x = 0 <= lim ? v.x : -INFINITY; v.y = 1 <= lim ? v.y : -INFINITY; v.z = -8 <= lim ? v.z : -INFINITY; v.w = -7 <= lim ? v.w : -INFINITY;
    t[j] = v;
    mx0 = fmaxf(mx0, fmaxf(v.x, v.y)); mx1 = fmaxf(mx1, fmaxf(v.z, v.w));
  }
  mx0 = fmaxf(mx0, __shfl_xor_sync(0xffffffff, mx0, 1));
  mx1 = fmaxf(mx1, __shfl_xor_sync(0xffffffff, mx1, 1));
  mx0 = fmaxf(mx0, __shfl_xor_sync(0xffffffff, mx0, 2));
  mx1 = fmaxf(mx1, __shfl_xor_sync(0xffffffff, mx1, 2));
  const float mc0 = was_classic ? mc[0] : 0.f, mc1 = was_classic ? mc[1] : 0.f;
  const float n0 = fresh ? -mx0 : fminf(mc0, -mx0), n1 = fresh ? -mx1 : fminf(mc1, -mx1);
  sc0 = ex2(n0 - mc0); sc1 = ex2(n1 - mc1);
  mc[0] = n0; mc[1] = n1;
  s0 = 0.f; s1 = 0.f;
  #pragma unroll 1
  for (int j = 0; j < 16; j++) {
    const float4 v = t[j];
    const float e0 = ex2(v.x + n0), e1 = ex2(v.y + n0), e2 = ex2(v.z + n1), e3 = ex2(v.w + n1);
    s0 += e0 + e1; s1 += e2 + e3;
    reinterpret_cast<uint2*>(t)[j] = make_uint2(pack_bf16(e0, e1), pack_bf16(e2, e3));
  }
  #pragma unroll
  for (int j = 0; j < 8; j++) { P[4*j] = __float_as_uint(t[j].x); P[4*j+1] = __float_as_uint(t[j].y); P[4*j+2] = __float_as_uint(t[j].z); P[4*j+3] = __float_as_uint(t[j].w); }
  if (!fresh) { l0 *= sc0; l1 *= sc1; }
}
__device__ __forceinline__ void pack_tile(const float (&A)[64], uint32_t (&D)[32], float f0, float f1) {
  #pragma unroll
  for (int j = 0; j < 16; j++) {
    D[8 * (j >> 2) + (j & 3)] = pack_bf16(A[4*j] * f0, A[4*j+1] * f0);
    D[8 * (j >> 2) + 4 + (j & 3)] = pack_bf16(A[4*j+2] * f1, A[4*j+3] * f1);
  }
}
__device__ __forceinline__ void store_tile(__nv_bfloat16* p, const uint32_t (&D)[32]) {
  #pragma unroll
  for (int i = 0; i < 8; i++) stg_v4(p + (i >> 2) * (SEQ * 64) + ((i >> 1) & 1) * 32 + (i & 1) * 8 * 64, D[4*i], D[4*i+1], D[4*i+2], D[4*i+3]);
}

enum : int { PV_ACC = 0, PV_ZERO = 1, PV_HALF = 2, PV_NONE = 3 };
struct Att {
  float l0, l1, i0, i1;
  bool classic;
  volatile float* mc;
};
__device__ __forceinline__ void store_ctx(Ctx& x, int code, const uint32_t (&D)[32]) {
  const int item = code >> 2, t = wg_tid(), lane = t & 31;
  const int row = (item & 7) * 256 + (code & 3) * 64 + q_row(t);
  store_tile(x.sched->kvc + ((size_t)(128 + (item >> 3) * 2) * SEQ + row) * 64 + (lane & 3) * 8, D);
  publish(x, C_CTX + item);
}

#define G_DEEP 0
#define MERGE1 1
#define NO_CLASSIC 0
__device__ __forceinline__ void q_proj(Ctx& x, int& e, bool isY, bool dbg = false) {
  float S[64];
  bar_sync(1 + x.w, 256);
  if (dbg) DBG(80);
  if (isY) bar_arrive(1 + (x.w ^ 1), 256);
  #pragma unroll 1
  for (int kb = 0; kb < 8; kb++) {
    ring_wait_full(x.bars, e);
    if (dbg) DBG(81 + kb);
    const uint32_t ent = x.base + ring_slot(e) * 32768;
    const uint32_t da = desc_lo(ent + x.w * 8192, 16), dw = desc_lo(ent + 16384, 8192);
    wgmma_fence();
    kblock_n128<0>(S, da, dw, kb != 0);
    wgmma_commit();
    if (kb == 7 && !isY) bar_arrive(1 + (x.w ^ 1), 256);
    if (kb > 0) { wgmma_wait<1>(); ring_release(x, ring_add(e, 11), false); }
    e = ring_add(e, 1);
  }
  wgmma_wait<0>();
  fence_regs(S);
  if (dbg) DBG(89);
  ring_release(x, ring_add(e, 11), false);
  const int t = wg_tid(), lane = t & 31, g = (lane >> 3) + (lane & 4);
  const uint32_t qa = x.base + SM_Q + x.w * 8192 + ((t >> 5) * 16 + g) * 128;
  #pragma unroll
  for (int i = 0; i < 8; i++) {
    const int j = 4 * (i >> 1), o = 2 * (i & 1);
    sts_v4(qa + (i >> 2) * 16384 + (i & 1) * 1024 + (((((i >> 1) & 1) * 4 + (lane & 3)) ^ g) << 4),
           pack_bf16(S[4*j+o], S[4*j+o+1]), pack_bf16(S[4*j+4+o], S[4*j+5+o]), pack_bf16(S[4*j+8+o], S[4*j+9+o]), pack_bf16(S[4*j+12+o], S[4*j+13+o]));
  }
  fence_async_smem();
  if (dbg) DBG(90);
  ring_wait_full(x.bars, ring_add(e, isY ? 0 : 2));
  ring_wait_full(x.bars, ring_add(e, 1));
}

template<int KIND>
__device__ __forceinline__ void slot(Ctx& x, Att& a, int& e, float (&O)[64], uint32_t (&Pn)[32], uint32_t (&Po)[32],
                                     bool more, bool isY, bool half, int pv, int pend) {
  float S[64];
  const int w = x.w;
  const bool skip = KIND == 0 && !isY;
  const int en = ring_add(e, skip ? 4 : 2), sn = ring_slot(en), sv = ring_slot(e) + 1, sk = skip ? ring_slot(ring_add(e, 2)) : sv - 1;
  const uint32_t dq = desc_lo(x.base + SM_Q + w * 8192, 16), dk = desc_lo(x.base, 16) + sk * 2048, dv = desc_lo(x.base, 16384) + sv * 2048;
  bar_sync(1 + w, 256);
  if (KIND == 2) {
    wgmma_fence();
    issue_qk(S, dq, dk); wgmma_commit();
    issue_pv<8>(O, Po, dv, 1); wgmma_commit();
    bar_arrive(1 + (w ^ 1), 256);
    wgmma_wait<1>();
  } else if (KIND == 0 && half) {
    float T[32];
    wgmma_fence(); issue_qk_half(T, dq, dk); wgmma_commit();
    a.i0 = rcp_fast(quad_sum(a.l0)); a.i1 = rcp_fast(quad_sum(a.l1));
    if (pv == PV_NONE) { wgmma_fence(); wgmma_commit(); }
    else               { wgmma_fence(); issue_pv<8>(O, Po, dv, pv == PV_ACC); wgmma_commit(); }
    bar_arrive(1 + (w ^ 1), 256);
    wgmma_wait<1>();
    fence_regs(T);
    #pragma unroll
    for (int i = 0; i < 32; i++) { S[i] = T[i]; asm volatile("" : "=f"(S[32 + i])); }
  } else {
    wgmma_fence(); issue_qk(S, dq, dk); wgmma_commit();
    if (KIND == 1 && pend >= 0) { bar_arrive(1 + (w ^ 1), 256); pack_tile(O, Pn, a.i0, a.i1); store_ctx(x, pend, Pn); }
    if (KIND == 0) { a.i0 = rcp_fast(quad_sum(a.l0)); a.i1 = rcp_fast(quad_sum(a.l1)); }
    if (KIND == 0 && pv == PV_NONE) { wgmma_fence(); wgmma_commit(); }
    else if (pv == PV_HALF)         { wgmma_fence(); issue_pv<4>(O, Po, dv, 0); wgmma_commit(); }
    else                            { wgmma_fence(); issue_pv<8>(O, Po, dv, pv == PV_ACC); wgmma_commit(); }
    if (KIND == 0 || pend < 0) bar_arrive(1 + (w ^ 1), 256);
    wgmma_wait<1>();
  }
  fence_regs(S);
  fence_regs_u(Pn);
  slot_release(x, sk, KIND == 0 && isY);
  float s0 = 0.f, s1 = 0.f;
  const bool was_classic = KIND != 0 && a.classic;
  if (KIND == 0) {
    a.l0 = 0.f; a.l1 = 0.f;
    if (!half) exp_pack<16, 32>(S, Pn, s0, s1);
    else {
      #pragma unroll
      for (int i = 16; i < 32; i++) asm volatile("" : "=r"(Pn[i]));
    }
    exp_pack_diag(S, Pn, diag_limit(), s0, s1);
    uint32_t b0 = __ballot_sync(0xffffffff, s0 >= SUM_LO), b1 = __ballot_sync(0xffffffff, s1 >= SUM_LO);
    b0 |= b0 >> 1; b0 |= b0 >> 2; b1 |= b1 >> 1; b1 |= b1 >> 2;
    a.classic = __any_sync(0xffffffff, !(s0 <= SUM_HI && s1 <= SUM_HI)) || (b0 & b1 & 0x11111111u) != 0x11111111u;
  } else {
    exp_pack<0, 32>(S, Pn, s0, s1);
    a.classic = __any_sync(0xffffffff, a.classic || !(s0 <= SUM_HI && s1 <= SUM_HI));
  }
  fence_regs_u(Pn);
  mbar_wait(x.bars + B_RF + 8 * sn, en >= 6);
  if (more) mbar_wait(x.bars + B_RF + 8 * sn + 8, en >= 6);
  wgmma_wait<0>();
  fence_regs(O);
  fence_regs_u(Po);
  slot_release(x, sv, KIND == 1 && isY && pv != PV_ACC);
  if (!NO_CLASSIC && __builtin_expect(a.classic, 0)) {
    float sc0, sc1;
    classic_tile(S, Pn, KIND == 0, half, was_classic, a.mc, a.l0, a.l1, s0, s1, sc0, sc1);
    if (KIND != 0) {
      #pragma unroll
      for (int j = 0; j < 16; j++) { O[4*j] *= sc0; O[4*j+1] *= sc0; O[4*j+2] *= sc1; O[4*j+3] *= sc1; }
    }
  }
  a.l0 += s0; a.l1 += s1;
  e = en;
}

__device__ __forceinline__ void attention(Ctx& x, int& e, const uint8_t* items, int nitems, int rank) {
  float O[64]; uint32_t PA[32], PB[32];
  Att a;
  volatile float mc[2];
  a.l0 = 1.f; a.l1 = 1.f; a.i0 = 0.f; a.i1 = 0.f; a.classic = false; a.mc = mc;
  int pv = PV_NONE, cur = -1;
#define DBGS()
  #pragma unroll 1
  for (int it = 0; ; it++) {
    const bool isY = (it & 1) == x.w;
    int pend = cur;
    if (it < nitems) {
      const int item = items[it];
      const bool half = isY == (rank != 0);
      cur = item * 4 + (isY ? 3 - rank : rank);
      int rem = 2 * (item & 7) + (isY ? 1 : 0);
      DBG(16 + it);
      q_proj(x, e, isY);
      DBGS();
      slot<0>(x, a, e, O, PA, PB, rem > 0, isY, half, pv, -1);
      pv = half ? PV_HALF : PV_ZERO;
      #pragma unroll 1
      while (rem > 0) {
        DBGS();
        slot<1>(x, a, e, O, PB, PA, rem > 1, isY, false, pv, pend);
        pv = PV_ACC; pend = -1;
        if (rem == 1) break;
        rem -= 2;
        DBGS();
        slot<2>(x, a, e, O, PA, PB, rem > 0, false, false, 0, -1);
      }
    } else {
      DBGS();
      slot_release(x, 6, false);
      const uint32_t dv = desc_lo(x.base + ring_slot(e) * 32768, 16384);
      bar_sync(1 + x.w, 256);
      if (pv == PV_HALF) { wgmma_fence(); issue_pv<4>(O, PB, dv, 0); wgmma_commit(); }
      else { wgmma_fence(); issue_pv<8>(O, PB, dv, pv == PV_ACC); wgmma_commit(); }
      if (isY) bar_arrive(1 + (x.w ^ 1), 256);
      a.i0 = rcp_fast(quad_sum(a.l0)); a.i1 = rcp_fast(quad_sum(a.l1));
      ring_wait_full(x.bars, ring_add(e, 1));
      wgmma_wait<0>();
      fence_regs(O);
      fence_regs_u(PB);
      ring_release(x, e, false);
      e = ring_add(e, 1);
    }
    if (pend >= 0) { pack_tile(O, PB, a.i0, a.i1); store_ctx(x, pend, PB); }
    if (it == nitems) break;
    if (!isY) {
      #pragma unroll
      for (int i = 0; i < 32; i++) asm volatile("mov.b32 %0, %1;" : "=r"(PB[i]) : "r"(PA[i]));
    }
  }
}

#define LN_AT 3
#define X_AT 6
#define PF0 0
#define PF_AT 5
#define PF_N 4
#define PF_MOE 3
__device__ __forceinline__ void mod_cta(uint8_t* smem, const __nv_bfloat16* cvec, const __nv_bfloat16* w_mod) {
  const int ct = threadIdx.x - 128, cw = ct >> 5, lane = ct & 31;
  const uint32_t cv = __ldg(reinterpret_cast<const uint32_t*>(cvec + cw * 64) + lane);
  const uint32_t sv = pack_bf16(__fdividef(bf_lo(cv), 1.f + __expf(-bf_lo(cv))), __fdividef(bf_hi(cv), 1.f + __expf(-bf_hi(cv))));
  float* red = reinterpret_cast<float*>(smem);
  #pragma unroll 1
  for (int rd = 0; rd < 3; rd++) {
    const int col0 = rd * 1024 + (blockIdx.x - NCTA) * 256;
    const uint4* wp = reinterpret_cast<const uint4*>(w_mod + (size_t)(cw * 64) * 3072 + col0) + lane;
    float am[8] = {0, 0, 0, 0, 0, 0, 0, 0};
    DBG(1 + rd * 8);
    #pragma unroll 1
    for (int rb = 0; rb < 4; rb++) {
      uint4 wv[16];
      #pragma unroll
      for (int r = 0; r < 16; r++) wv[r] = __ldg(wp + (rb * 16 + r) * (3072 / 8));
      #pragma unroll 1
      for (int k = 0; k < 4; k++) {
        #pragma unroll
        for (int r = 0; r < 4; r++) {
          float f[8]; unpack8(wv[r], f);
          const uint32_t s2 = __shfl_sync(0xffffffff, sv, rb * 8 + k * 2 + (r >> 1));
          const float s1 = (r & 1) ? bf_hi(s2) : bf_lo(s2);
          #pragma unroll
          for (int j = 0; j < 8; j++) am[j] = fmaf(s1, f[j], am[j]);
        }
        #pragma unroll
        for (int r = 0; r < 12; r++) wv[r] = wv[r + 4];
      }
      DBG(2 + rb + rd * 8);
    }
    reinterpret_cast<float4*>(red + rd * 2048 + cw * 256)[lane * 2] = make_float4(am[0], am[1], am[2], am[3]);
    reinterpret_cast<float4*>(red + rd * 2048 + cw * 256)[lane * 2 + 1] = make_float4(am[4], am[5], am[6], am[7]);
    bar_sync(1, 256);
    float v = 0.f;
    #pragma unroll
    for (int i = 0; i < 8; i++) v += red[rd * 2048 + i * 256 + ct];
    g_mod[col0 + ct] = __float2bfloat16(v);
    bar_sync(1, 256);
    DBG(6 + rd * 8);
    if (ct == 0) red_release(rd == 0 ? C_MOD : C_MOD2);
    bar_sync(1, 256);
    DBG(7 + rd * 8);
  }
}

__global__ void __cluster_dims__(2, 1, 1) __launch_bounds__(384, 1)
k_fused(const __grid_constant__ CUtensorMap tmC, const __grid_constant__ CUtensorMap tmH, const __grid_constant__ CUtensorMap tmWq,
        const __grid_constant__ CUtensorMap tmWk, const __grid_constant__ CUtensorMap tmWv, const __grid_constant__ CUtensorMap tmKV,
        const __grid_constant__ CUtensorMap tmWo, const __grid_constant__ CUtensorMap tmPart, const __grid_constant__ CUtensorMap tmWg,
        const __grid_constant__ CUtensorMap tmWu, const __grid_constant__ CUtensorMap tmPl, const __grid_constant__ Sched sched,
        const __nv_bfloat16* __restrict__ xin, const __nv_bfloat16* __restrict__ ckv,
        const __nv_bfloat16* __restrict__ cvec, const __nv_bfloat16* __restrict__ w_mod,
        const __nv_bfloat16* __restrict__ w_r, const __nv_bfloat16* __restrict__ w_gate, const __nv_bfloat16* __restrict__ w_up,
        const __nv_bfloat16* __restrict__ w_down, __nv_bfloat16* __restrict__ out) {
  extern __shared__ __align__(1024) uint8_t smem_raw[];
  const uint32_t base = smem_u32(smem_raw), bars = base + SM_BAR;
  const int warp = __shfl_sync(0xffffffff, threadIdx.x >> 5, 0), wg = warp >> 2;
  const int rank = cluster_ctarank(), p = blockIdx.x >> 1;
  const int mt = (p & 7) * 2 + rank;
  const bool spare = blockIdx.x >= NCTA;
  if (!spare) {
    const int h0 = KHEAD0 + (p >> 3);
    if (warp == 9) prefetch_tmap(&tmWk);
    if (warp == 10 && PF0) bulk_prefetch(ckv + (size_t)(mt * 128 + (p >> 3) * 16) * DM, 16384);
    if (warp <= 8) {
      #pragma unroll 1
      for (int t = 8 - warp; t < 80; t += (warp < 8 ? 8 : 80))
        w_mbar_init(bars + 8 * t, t < B_WE / 8 ? 1 : t < B_RE / 8 ? 2 : t < B_RDY / 8 ? 4 : 1);
      fence_mbar_init();
    }
    cluster_arrive();
    if (wg == 2) bar_arrive(1, 256);
    if (warp == 8) {
      #pragma unroll 1
      for (int kb = 0; kb < 8; kb++) {
        w_expect_tx(bars + B_AF + 8 * kb, 16384);
        tma_load_2d(base + k_addrA(kb), &tmC, bars + B_AF + 8 * kb, kb * 64, mt * 128);
        if (kb == 0) cluster_wait();
        if (kb < 6) {
          w_expect_tx(bars + B_WF + 8 * kb, 16384);
          tma_load_2d_mc(base + k_addrW(kb) + rank * 8192, &tmWk, bars + B_WF + 8 * kb, h0 * 128 + rank * 64, kb * 64);
        }
      }
    }
  }
  const int nitems = sched.nitems[p];
  const int ot = sched.otask[p], m = (ot & 7) * 2 + rank, grp = m * 8 + (ot >> 3);

  if (wg == 0) {
    asm volatile("setmaxnreg.dec.sync.aligned.u32 24;");
    if (spare) return;
    const int lane = threadIdx.x & 31;
    cluster_wait();
    const unsigned int tag = ld_relaxed(&g_epoch) + 1;
    if (warp == 0) {
      {
        int s = 0, ph = 0;
        tma_prefetch_2d(&tmWv, sched.khead[p][0] * 128 + rank * 64, (p & 7) * 64);
        #pragma unroll 1
        for (int g = 6; g < 64; g++) {
          const int u = g >> 3, kb = g & 7;
          if (kb == 0 && u < 7) tma_prefetch_2d((u & 1) ? &tmWk : &tmWv, sched.khead[p][(u + 1) >> 1] * 128 + rank * 64, (p & 7) * 64);
          mbar_wait(bars + B_WE + 8 * s, ph);
          w_expect_tx(bars + B_WF + 8 * s, 16384);
          tma_load_2d_mc(base + k_addrW(s) + rank * 8192, (u & 1) ? &tmWv : &tmWk, bars + B_WF + 8 * s, sched.khead[p][u >> 1] * 128 + rank * 64, kb * 64);
          if (++s == 6) { s = 0; ph ^= 1; }
        }
      }
      int s = 0, ph = 0;
      auto next_entry = [&](bool load) {
        mbar_wait(bars + B_RE + 8 * s, ph);
        if (load) w_expect_tx(bars + B_RF + 8 * s, 32768); else w_arrive(bars + B_RF + 8 * s);
      };
      auto advance = [&]() { if (++s == 6) { s = 0; ph ^= 1; } };
      int vrow = -1;
      #pragma unroll 1
      for (int i = 0; i < nitems; i++) {
        const int item = sched.item[p][i], h = item >> 3, j = item & 7;
        const int row0 = j * 256 + ((i & 1) ? rank : 3 - rank) * 64, row1 = j * 256 + ((i & 1) ? 3 - rank : rank) * 64;
        mbar_wait(bars + B_RDY + 8 * (1 + i), 0);
        fence_async_global();
        #pragma unroll 1
        for (int kb = 0; kb < 8; kb++) {
          next_entry(true);
          if (i == 2) DBGP(kb);
          tma_load_2d_mc(base + s * 32768 + 16384 + rank * 8192, &tmWq, bars + B_RF + 8 * s, h * 128 + rank * 64, kb * 64);
          tma_load_2d(base + s * 32768, &tmH, bars + B_RF + 8 * s, kb * 64, row0);
          tma_load_2d(base + s * 32768 + 8192, &tmH, bars + B_RF + 8 * s, kb * 64, row1);
          advance();
        }
        #pragma unroll 1
        for (int n = 2 * j + 1; n >= 0; n--) {
          const int krow = (h * 2 + rank) * SEQ + n * 128;
          if (i + 1 == nitems && n == min(2 * j + 1, PF_AT)) w_arrive(bars + B_RDY + 8 * 17);
          next_entry(true);
          if (i == 2 && n >= 2 * j) DBGP(8 + 2 * (2 * j + 1 - n));
          tma_load_2d_mc(base + s * 32768 + rank * 16384, &tmKV, bars + B_RF + 8 * s, 0, krow);
          advance();
          next_entry(vrow >= 0);
          if (i == 2 && n >= 2 * j) DBGP(9 + 2 * (2 * j + 1 - n));
          if (vrow >= 0) tma_load_2d_mc(base + s * 32768 + rank * 16384, &tmKV, bars + B_RF + 8 * s, 0, vrow);
          advance();
          vrow = krow + 64 * SEQ;
        }
      }
      next_entry(true);
      tma_load_2d_mc(base + s * 32768 + rank * 16384, &tmKV, bars + B_RF + 8 * s, 0, vrow);
      advance();
      const int oj = ot & 7, oc = ((ot >> 3) & 1) * 4 + rank * 2;
      const uint32_t tab = o_table(s + 6 * ph);
      auto o_next = [&](int k) { const uint32_t v = o_entry(tab, k); s = v & 7; ph = v >> 3; next_entry(true); };
      #pragma unroll 1
      for (int i = 0; i < 8; i++) {
        const int h = sched.ohead[p][i];
        if (i >= PF_MOE && i < PF_MOE + 3)
          bulk_prefetch((i == PF_MOE ? w_gate : i == PF_MOE + 1 ? w_up : w_down) + (size_t)blockIdx.x * (DM * FF / NCTA), DM * FF / NCTA * 2);
        o_next(3 * i);
        tma_load_3d_mc(base + s * 32768 + rank * 16384, &tmWo, bars + B_RF + 8 * s, 0, h * 128, oc);
        mbar_wait(bars + B_RDY + 8 * (8 + i), 0);
        fence_async_global();
        o_next(3 * i + 1);
        tma_load_2d(base + s * 32768, &tmKV, bars + B_RF + 8 * s, 0, (128 + h * 2) * SEQ + oj * 256 + rank * 128);
        tma_load_2d(base + s * 32768 + 16384, &tmKV, bars + B_RF + 8 * s, 0, (129 + h * 2) * SEQ + oj * 256 + rank * 128);
        o_next(3 * i + 2);
        tma_load_3d_mc(base + s * 32768 + rank * 16384, &tmWo, bars + B_RF + 8 * s, 0, h * 128 + 64, oc);
      }
      const int f0 = (blockIdx.x < FF / 16 ? blockIdx.x : 0) * 16;
      o_next(24);
      bulk_load(base + s * 32768, w_down + (size_t)f0 * DM, 16384, bars + B_RF + 8 * s);
      bulk_load(base + s * 32768 + 16384, xin + (size_t)grp * 16 * DM, 16384, bars + B_RF + 8 * s);
      o_next(25);
      #pragma unroll 1
      for (int k = 0; k < 4; k++) tma_load_2d(base + s * 32768 + k * 8192, (k & 2) ? &tmWu : &tmWg, bars + B_RF + 8 * s, f0, (k & 1) * 256);
      w_expect_tx(bars + B_RDY + 8 * 7, 65536);
      mbar_wait(bars + B_PUB + 8 * (5 + nitems + 1), 0);
      mbar_wait(bars + B_PUB + 8 * (NPUB + 5 + nitems + 1), 0);
      uint32_t todo = 0xff;
      #pragma unroll 1
      for (int n = 0; n < WAIT_LIM && todo; n++) {
        uint32_t now = __ballot_sync(0xffffffff, ld_acquire(&g_pflag[m * 2 + (ot >> 5)][lane & 7]) == tag) & todo;
        todo &= ~now;
        fence_async_global();
        #pragma unroll 1
        for (; now; now &= now - 1) {
          const int q = __ffs(now) - 1;
          tma_load_3d(base + ((tab >> (q & 4)) & 7) * 32768 + (q & 3) * 8192, &tmPl, bars + B_RDY + 8 * 7, 0, grp * 16, q * 4);
        }
      }
      DBGP(11);
    } else if (warp < 3) {
      const int w = warp - 1, n1 = w * NPUB + 5 + nitems;
      #pragma unroll 1
      for (int n = w * NPUB; n < n1 + 2; n++) {
        #pragma unroll 1
        for (int k = 0; k < 8 * WAIT_LIM; k++) { if (mbar_try(bars + B_PUB + 8 * n, 0)) break; }
        const uint32_t msg = lds_u32(base + SM_MAIL + 4 * n);
        if (n < n1) {
          fence_async_global();
          if (lane == 0 && msg < (unsigned)C_END) red_release(msg);
        } else if (lane == 0) {
          tma_store_3d(&tmPart, base + (msg & 0x3c000), 0, m * 128 + 64 * w, (ot >> 4) * 8 + ((ot >> 3) & 1) * 4 + 2 * (n - n1));
          bulk_commit();
        }
        __syncwarp();
      }
      bulk_wait<0>();
      fence_async_global();
      if (lane == 0) st_release(&g_pflag[m * 2 + w][ot >> 3], tag);
      __syncwarp();
    } else {
      mbar_wait(bars + B_AF + 8 * X_AT, 0);
      bulk_prefetch(xin + (size_t)blockIdx.x * 16 * DM, 16 * DM * 2);
      wait_count_lazy(C_MOD, 4 * tag);
      DBGP(12);
      w_arrive(bars + B_RDY);
      #pragma unroll 1
      for (int i = 0; i < nitems; i++) {
        const int item = sched.item[p][i];
        tma_prefetch_2d(&tmWq, (item >> 3) * 128 + rank * 64, (p & 7) * 64);
        wait_count_lazy(C_H1 + (item & 7), 32 * tag);
        wait_count_lazy(C_KV + (item >> 3), 32 * tag);
        w_arrive(bars + B_RDY + 8 * (1 + i));
      }
      wait_count_lazy(C_MOD2, 8 * tag);
      #pragma unroll 1
      for (int i = 0; i < 8; i++) {
        wait_count_lazy(C_CTX + sched.ohead[p][i] * 8 + (ot & 7), 4 * tag);
        w_arrive(bars + B_RDY + 8 * (8 + i));
        if (i == PF_N - 1) {
          #pragma unroll 1
          for (int k = 0; k < 8 * WAIT_LIM; k++) { if (mbar_try(bars + B_RDY + 8 * 17, 0)) break; }
          for (int k = 0; k < 2; k++) tma_prefetch_3d(&tmWo, 0, sched.ohead[p][ot & 7] * 128 + k * 64, ((ot >> 3) & 1) * 4 + rank * 2);
          #pragma unroll 1
          for (int k = 0; k < PF_N; k++) bulk_prefetch(sched.kvc + ((size_t)(128 + sched.ohead[p][k] * 2 + ((ot >> 3) & 1)) * SEQ + m * 128) * 64, 16384);
        }
      }
    }
    bar_sync(6, 128);
    asm volatile("setmaxnreg.inc.sync.aligned.u32 88;");
    {
      const int col = blockIdx.x * 4 + (lane & 1) * 2, src = threadIdx.x >> 1;
      uint32_t gbest = 0, hh = 0, gbf = 0;
      uint2 xx = make_uint2(0, 0);
      if (warp == 3) {
        gbf = __ldcg(reinterpret_cast<const uint32_t*>(g_mod + 5 * DM + col));
        uint4 hv[4];
        #pragma unroll 1
        for (int n = 0; n < WAIT_LIM; n++) {
          uint2 k[4];
          #pragma unroll
          for (int i = 0; i < 4; i++) k[i] = ld_tagged(&g_keys[i * 32 + lane][0]);
          bool ok = gbest != 0;
          if (ok) {
            const int g = ((0xffffu - gbest) >> 4) & 127;
            #pragma unroll
            for (int i = 0; i < 4; i++) hv[i] = ld_tagged2(&g_row[g][0][i * 64 + lane * 2]);
            xx = ld_tagged(&g_row[g][1][col >> 1]);
            #pragma unroll
            for (int i = 0; i < 4; i++) ok = ok && hv[i].y == tag && hv[i].w == tag;
            ok = ok && xx.y == tag;
          }
          uint32_t kn = 0;
          #pragma unroll
          for (int i = 0; i < 4; i++) { ok = ok && k[i].y == tag; kn = max(kn, k[i].y == tag ? k[i].x : 0u); }
          kn = __reduce_max_sync(0xffffffff, kn);
          if (__all_sync(0xffffffff, ok && kn == gbest)) break;
          gbest = kn;
        }
        #pragma unroll
        for (int i = 0; i < 4; i++) reinterpret_cast<uint2*>(smem_raw + SM_H2)[i * 32 + lane] = make_uint2(hv[i].x, hv[i].z);
        if (lane == 0) *reinterpret_cast<uint32_t*>(smem_raw + SM_KEY + 32) = gbest;
        __syncwarp();
        w_arrive(bars + B_RDY + 8 * 16);
        if (blockIdx.x == 0 && lane == 0) g_epoch = tag;
        hh = lds_u32(base + SM_H2 + col * 2);
        DBGP(13);
      }
      const uint32_t sb16 = gbest & 0xffff0000u;
      const float rsel = __uint_as_float((sb16 & 0x80000000u) ? (sb16 & 0x7fffffffu) : (~sb16 & 0xffff0000u));
      const float rs = rbf(__fdividef(1.f, 1.f + __expf(-rsel)));
      uint4 ya, yb = make_uint4(0, tag, 0, tag);
      #pragma unroll 1
      for (int n = 0; n < WAIT_LIM; n++) {
        ya = ld_tagged2(&g_yll[src][col]);
        if (src + 64 < FF / 16) yb = ld_tagged2(&g_yll[src + 64][col]);
        if (n == 0) mbar_wait(bars + B_RDY + 8 * 16, 0);
        if (__all_sync(0xffffffff, ya.y == tag && ya.w == tag && yb.y == tag && yb.w == tag)) break;
      }
      float y0 = __uint_as_float(ya.x) + __uint_as_float(yb.x), y1 = __uint_as_float(ya.z) + __uint_as_float(yb.z);
      #pragma unroll
      for (int o = 2; o < 32; o <<= 1) { y0 += __shfl_xor_sync(0xffffffff, y0, o); y1 += __shfl_xor_sync(0xffffffff, y1, o); }
      float2* s_y = reinterpret_cast<float2*>(smem_raw + SM_KEY + 64);
      if (lane < 2) s_y[warp * 2 + lane] = make_float2(y0, y1);
      bar_sync(6, 128);
      if (warp == 3 && lane < 2) {
        #pragma unroll
        for (int i = 0; i < 3; i++) { const float2 v = s_y[i * 2 + lane]; y0 += v.x; y1 += v.y; }
        const float o0 = bf_lo(xx.x) + rbf(bf_lo(gbf) * rbf(bf_lo(hh) + rbf(rbf(y0) * rs)));
        const float o1 = bf_hi(xx.x) + rbf(bf_hi(gbf) * rbf(bf_hi(hh) + rbf(rbf(y1) * rs)));
        *reinterpret_cast<uint32_t*>(out + (size_t)((0xffffu - gbest) & (SEQ - 1)) * DM + col) = pack_bf16(o0, o1);
      }
      DBGP(14);
    }
    __syncwarp();
    cluster_arrive();
    cluster_wait();
  } else {
    asm volatile("setmaxnreg.inc.sync.aligned.u32 240;");
    if (spare) { mod_cta(smem_raw, cvec, w_mod); return; }
    Ctx x;
    x.w = wg - 1; x.base = base; x.bars = bars; x.nev = 0; x.sched = &sched;
    const int w = x.w, warp4 = warp & 3;
    x.rel = mapa(bars, (warp4 & 1) ^ 1);
    x.rel1 = (threadIdx.x & 127) == 32 || (threadIdx.x & 127) == 64;
    if (warp != 8) cluster_wait();
    DBG(1);
    {
      const int lane = wg_tid() & 31;
      Row xn[2];
      float acc0[64], acc1[64];
      const float sc = w == 0 ? 0.08838834764831845f * 1.4426950408889634f : 1.f;
      int s = 2 * w, ph = w;
      #pragma unroll 1
      for (int u = w; u < 8; u += 2) {
        bar_sync(1 + w, 256);
        DBG(4 + (u >> 1) * 3);
        int ps = 0;
        #pragma unroll 1
        for (int kb = 0; kb < 8; kb++) {
          if (u < 2) mbar_wait(bars + B_AF + 8 * kb, 0);
          mbar_wait(bars + B_WF + 8 * s, ph);
          const uint32_t da = desc_lo(base + k_addrA(kb), 16), dw = desc_lo(base + k_addrW(s), 8192);
          wgmma_fence();
          kblock_n128<0>(acc0, da, dw, kb != 0);
          kblock_n128<512>(acc1, da, dw, kb != 0);
          wgmma_commit();
          if (kb == 7) bar_arrive(1 + (w ^ 1), 256);
          if (kb > 0) {
            wgmma_wait<1>();
            mbar_arrive_remote_if(x.rel + B_WE + 8 * ps, x.rel1);
            if (u == 7 && !(kb & 1)) {
              ring_release(x, kb == 2 ? 0 : kb - 3, false);
              if (kb > 2) ring_release(x, kb - 2, false);
            }
          }
          ps = s;
          if (++s == 6) { s = 0; ph ^= 1; }
        }
        Row t[2];
        const int lrow = blockIdx.x * 16 + w * 8 + warp4 * 2;
        if (u == w) { t[0] = ldg_row(xin + (size_t)lrow * DM, lane); t[1] = ldg_row(xin + (size_t)(lrow + 1) * DM, lane); }
        if (u == LN_AT || u == LN_AT + 1) {
          mbar_wait(bars + B_RDY, 0);
          t[0] = ldca_row(g_mod, lane); t[1] = ldca_row(g_mod + DM, lane);
        }
        wgmma_wait<0>();
        fence_regs(acc0); fence_regs(acc1);
        DBG(5 + (u >> 1) * 3);
        mbar_arrive_remote_if(x.rel + B_WE + 8 * ps, x.rel1);
        if (u == 6) { for (int k = 0; k < 5; k++) ring_release(x, k, false); }
        if (u >= 6) ring_release(x, 5, false);
        s += 2; ph ^= 1; if (s >= 6) { s -= 6; ph ^= 1; }
        if (u == w) layer_norm2(t, xn);
        if ((u == LN_AT || u == LN_AT + 1)) {
          #pragma unroll
          for (int r = 0; r < 2; r++) store_row(sched.h1 + (size_t)(lrow + r) * DM, lane, fma_row(xn[r], one_plus(t[1]), t[0]));
        }
        const int h = sched.khead[p][u >> 1];
        __nv_bfloat16* dst = sched.kvc + ((size_t)(w * 64 + h * 2) * SEQ + mt * 128 + warp4 * 16 + (lane >> 2)) * 64 + (lane & 3) * 8;
        uint32_t D[32];
        pack_tile(acc0, D, sc, sc); store_tile(dst + 64 * 64, D);
        pack_tile(acc1, D, sc, sc); store_tile(dst, D);
        if ((u == LN_AT || u == LN_AT + 1)) publish(x, C_H1 + (blockIdx.x >> 4));
        publish(x, C_KV + h);
        DBG(6 + (u >> 1) * 3);
      }
    }
    int e = 0;
    attention(x, e, sched.item[p], nitems, rank);
    DBG(100);
    const int lane = wg_tid() & 31, cw = w * 4 + warp4, ct = cw * 32 + lane;
    const int row0 = grp * 16 + cw * 2;
    const bool moe_cta = blockIdx.x < FF / 16;
    const unsigned int tag = ld_relaxed(&g_epoch) + 1;
    asm volatile("setmaxnreg.dec.sync.aligned.u32 208;");
    const uint32_t tab = o_table(e);
    Row ga, sb, cb1, gb, wr;
    {
      float accA[64], accB[64];
      uint32_t pa = 0, pb = 0;
      #pragma unroll 1
      for (int i = 0; i < 7; i++) {
        const uint32_t e0 = o_entry(tab, 3 * i), ea = o_entry(tab, 3 * i + 1), eb = o_entry(tab, 3 * i + 2);
        const uint32_t da = desc_lo(base + w * 8192, 16) + (ea & 7) * 2048;
        o_wait_full(bars, e0);
        DBG(70 + i);
        o_wait_full(bars, ea);
        DBG(91 + i);
        uint32_t db = desc_lo(base, 8192) + (e0 & 7) * 2048;
        wgmma_fence();
        kblock_n128<0>(accA, da, db, i != 0); kblock_n128<0, 1024>(accB, da, db, i != 0);
        wgmma_commit();
        if (i > 0) { wgmma_wait<1>(); slot_release(x, pa, false); slot_release(x, pb, false); }
        o_wait_full(bars, eb);
        db = desc_lo(base, 8192) + (eb & 7) * 2048;
        wgmma_fence();
        kblock_n128<1024>(accA, da, db, 1); kblock_n128<1024, 1024>(accB, da, db, 1);
        wgmma_commit();
        wgmma_wait<1>();
        slot_release(x, e0 & 7, false);
        pa = ea & 7; pb = eb & 7;
      }
      const uint32_t e0 = o_entry(tab, 21), ea = o_entry(tab, 22), eb = o_entry(tab, 23);
      const uint32_t da = desc_lo(base + w * 8192, 16) + (ea & 7) * 2048;
      const uint32_t db0 = desc_lo(base, 8192) + (e0 & 7) * 2048, db1 = desc_lo(base, 8192) + (eb & 7) * 2048;
      o_wait_full(bars, e0);
      DBG(77);
      o_wait_full(bars, ea);
      o_wait_full(bars, eb);
      DBG(98);
      wgmma_fence();
      kblock_n128<0>(accA, da, db0, 1); kblock_n128<1024>(accA, da, db1, 1);
      wgmma_commit();
      kblock_n128<0, 1024>(accB, da, db0, 1); kblock_n128<1024, 1024>(accB, da, db1, 1);
      wgmma_commit();
      wgmma_wait<2>();
      slot_release(x, pa, false); slot_release(x, pb, false);
      __syncwarp();
      cluster_arrive();
      ga = ldca_row(g_mod + 2 * DM, lane); sb = ldca_row(g_mod + 3 * DM, lane); cb1 = ldca_row(g_mod + 4 * DM, lane); gb = ldca_row(g_mod + 5 * DM, lane);
      wr = ldg_row(w_r, lane);
      const int srow = 16 * warp4 + (lane & 7) + 8 * ((lane >> 3) & 1);
      const uint32_t swz = (((lane >> 4) ^ (srow & 7)) << 4);
      auto stage = [&](const float (&acc)[64], uint32_t off) {
        #pragma unroll
        for (int j = 0; j < 16; j += 2)
          stsm_x4(base + off + srow * 128 + (j >> 3) * 8192 + (((j & 7) << 4) ^ swz),
                  pack_bf16(acc[4*j+0], acc[4*j+1]), pack_bf16(acc[4*j+2], acc[4*j+3]), pack_bf16(acc[4*j+4], acc[4*j+5]), pack_bf16(acc[4*j+6], acc[4*j+7]));
        fence_async_smem();
        publish(x, off);
      };
      mbar_wait(bars + B_RE + 8 * pa, o_entry(tab, 26) >> 3);
      wgmma_wait<1>();
      fence_regs(accA);
      stage(accA, pa * 32768 + w * 16384);
      mbar_wait(bars + B_RE + 8 * pb, o_entry(tab, 27) >> 3);
      wgmma_wait<0>();
      fence_regs(accB);
      DBG(101);
      stage(accB, pb * 32768 + w * 16384);
      DBG(102);
    }
    const uint32_t sD = base + (o_entry(tab, 24) & 7) * 32768, sW = base + (o_entry(tab, 25) & 7) * 32768;
    o_wait_full(bars, o_entry(tab, 24)); o_wait_full(bars, o_entry(tab, 25));
    Row x1[2];
    #pragma unroll
    for (int r = 0; r < 2; r++) x1[r] = lds_row(sD + 16384 + (cw * 2 + r) * 1024, lane);
    cb1 = one_plus(cb1);
    uint4 wgv[4], wuv[4]; uint32_t wdv[16];
    #pragma unroll
    for (int r = 0; r < 4; r++) { wgv[r] = lds_v4(sW + r * 4096 + ct * 16); wuv[r] = lds_v4(sW + 16384 + r * 4096 + ct * 16); }
    #pragma unroll
    for (int r = 0; r < 16; r++) wdv[r] = lds_u32(sD + r * 1024 + ct * 4);
    DBG(103);
    mbar_wait(bars + B_RDY + 8 * 7, 0);
    DBG(104);
    Row h2[2];
    uint32_t key[2];
    {
      uint4 pv[2][4][2];
      const uint32_t po = base + (lane >> 3) * 2048 + cw * 256 + (lane & 7) * 16;
      const uint32_t pa[2] = {po + (tab & 7) * 32768, po + ((tab >> 4) & 7) * 32768};
      #pragma unroll
      for (int r = 0; r < 2; r++)
        #pragma unroll
        for (int q = 0; q < 8; q++) pv[r][q >> 1][q & 1] = lds_v4(pa[q >> 2] + (q & 3) * 8192 + r * 128);
      #pragma unroll
      for (int r = 0; r < 2; r++) {
        Row av;
        #pragma unroll
        for (int i = 0; i < 2; i++) {
          av.v[4*i]   = add2(add2(pv[r][0][i].x, pv[r][1][i].x), add2(pv[r][2][i].x, pv[r][3][i].x));
          av.v[4*i+1] = add2(add2(pv[r][0][i].y, pv[r][1][i].y), add2(pv[r][2][i].y, pv[r][3][i].y));
          av.v[4*i+2] = add2(add2(pv[r][0][i].z, pv[r][1][i].z), add2(pv[r][2][i].z, pv[r][3][i].z));
          av.v[4*i+3] = add2(add2(pv[r][0][i].w, pv[r][1][i].w), add2(pv[r][2][i].w, pv[r][3][i].w));
        }
        x1[r] = fma_row(ga, av, x1[r]);
      }
      layer_norm2(x1, h2);
      float sc[2] = {0.f, 0.f};
      #pragma unroll
      for (int r = 0; r < 2; r++) {
        h2[r] = fma_row(h2[r], cb1, sb);
        #pragma unroll
        for (int i = 0; i < 8; i++) sc[r] = fmaf(bf_hi(h2[r].v[i]), bf_hi(wr.v[i]), fmaf(bf_lo(h2[r].v[i]), bf_lo(wr.v[i]), sc[r]));
      }
      #pragma unroll
      for (int o = 16; o > 0; o >>= 1) { sc[0] += __shfl_xor_sync(0xffffffff, sc[0], o); sc[1] += __shfl_xor_sync(0xffffffff, sc[1], o); }
      #pragma unroll
      for (int r = 0; r < 2; r++) {
        const uint32_t rb = pack_bf16(0.f, sc[r]);
        key[r] = (((rb & 0x80000000u) ? ~rb : (rb | 0x80000000u)) & 0xffff0000u) | (0xffffu - (uint32_t)(row0 + r));
      }
    }
    DBG(105);
    float* s_red = reinterpret_cast<float*>(smem_raw + SM_RED);
    uint32_t* s_key = reinterpret_cast<uint32_t*>(smem_raw + SM_KEY);
    const int rb = key[1] > key[0];
    const uint32_t wbest = rb ? key[1] : key[0];
    if (lane == 0) s_key[cw] = wbest;
    bar_sync(5, 256);
    const uint32_t cbest = __reduce_max_sync(0xffffffff, s_key[lane & 7]);
    Row ob, hb, xb;
    #pragma unroll
    for (int i = 0; i < 8; i++) { hb.v[i] = rb ? h2[1].v[i] : h2[0].v[i]; xb.v[i] = rb ? x1[1].v[i] : x1[0].v[i]; }
    if (wbest == cbest) {
      if (lane == 0) st_tagged(&g_keys[grp][0], cbest, tag);
      #pragma unroll
      for (int i = 0; i < 4; i++) st_tagged2(&g_row[grp][0][(i >> 1) * 128 + lane * 4 + (i & 1) * 2], hb.v[2*i], hb.v[2*i+1], tag);
      #pragma unroll
      for (int i = 0; i < 4; i++) st_tagged2(&g_row[grp][1][(i >> 1) * 128 + lane * 4 + (i & 1) * 2], xb.v[2*i], xb.v[2*i+1], tag);
    }
    DBG(106);
    #pragma unroll
    for (int i = 0; i < 8; i++) { ob.v[i] = fma2(gb.v[i], rb ? h2[0].v[i] : h2[1].v[i], rb ? x1[0].v[i] : x1[1].v[i]); }
    store_row(out + (size_t)(row0 + 1 - rb) * DM, lane, ob);
    ob = fma_row(gb, hb, xb);
    if (wbest != cbest) store_row(out + (size_t)(row0 + rb) * DM, lane, ob);
    mbar_wait(bars + B_RDY + 8 * 16, 0);
    DBG(107);
    if (moe_cta) {
      float hs[4];
      #pragma unroll
      for (int r = 0; r < 4; r++) hs[r] = __bfloat162float(reinterpret_cast<const __nv_bfloat16*>(smem_raw + SM_H2)[(ct >> 1) + 128 * r]);
      float ag[8] = {0, 0, 0, 0, 0, 0, 0, 0}, au[8] = {0, 0, 0, 0, 0, 0, 0, 0};
      #pragma unroll
      for (int r = 0; r < 4; r++) {
        float fg[8], fu[8]; unpack8(wgv[r], fg); unpack8(wuv[r], fu);
        #pragma unroll
        for (int j = 0; j < 8; j++) { ag[j] = fmaf(hs[r], fg[j], ag[j]); au[j] = fmaf(hs[r], fu[j], au[j]); }
      }
      #pragma unroll
      for (int j = 0; j < 8; j++) { const bool hi = lane & 16; ag[j] = (hi ? au[j] : ag[j]) + __shfl_xor_sync(0xffffffff, hi ? ag[j] : au[j], 16); }
      #pragma unroll
      for (int j = 0; j < 4; j++) { const bool hi = lane & 8; ag[j] = (hi ? ag[j+4] : ag[j]) + __shfl_xor_sync(0xffffffff, hi ? ag[j] : ag[j+4], 8); }
      #pragma unroll
      for (int j = 0; j < 2; j++) { const bool hi = lane & 4; ag[j] = (hi ? ag[j+2] : ag[j]) + __shfl_xor_sync(0xffffffff, hi ? ag[j] : ag[j+2], 4); }
      { const bool hi = lane & 2; ag[0] = (hi ? ag[1] : ag[0]) + __shfl_xor_sync(0xffffffff, hi ? ag[0] : ag[1], 2); }
      s_red[cw * 32 + (lane & 16) + (lane & 1) * 8 + ((lane >> 1) & 7)] = ag[0];
      bar_sync(5, 256);
      float g = 0.f;
      #pragma unroll
      for (int i = 0; i < 8; i++) g += s_red[i * 32 + lane];
      g = rbf(g);
      const float u = __shfl_down_sync(0xffffffff, g, 16);
      const float act = rbf(rbf(__fdividef(g, 1.f + __expf(-g))) * u);
      float y0 = 0.f, y1 = 0.f;
      #pragma unroll
      for (int r = 0; r < 16; r++) { const float av = __shfl_sync(0xffffffff, act, r); y0 = fmaf(av, bf_lo(wdv[r]), y0); y1 = fmaf(av, bf_hi(wdv[r]), y1); }
      st_tagged2(&g_yll[blockIdx.x][2 * ct], __float_as_uint(y0), __float_as_uint(y1), tag);
    }
    DBG(108);
    if (wbest == cbest && wbest != s_key[8]) store_row(out + (size_t)(row0 + rb) * DM, lane, ob);
    DBG(109);
    __syncwarp();
    cluster_wait();
  }
}

typedef CUresult (*EncodeFn)(CUtensorMap*, CUtensorMapDataType, cuuint32_t, void*, const cuuint64_t*, const cuuint64_t*, const cuuint32_t*,
                             const cuuint32_t*, CUtensorMapInterleave, CUtensorMapSwizzle, CUtensorMapL2promotion, CUtensorMapFloatOOBfill);

struct HostState {
  bool ready = false;
  EncodeFn encode = nullptr;
  CUtensorMap tmC, tmH, tmWq, tmWk, tmWv, tmKV, tmWo, tmPart, tmWg, tmWu, tmPl;
  Sched sched;
};

void make_map(EncodeFn enc, CUtensorMap* m, const void* ptr, int rank, const cuuint64_t* dims, const cuuint64_t* strides, const cuuint32_t* box, bool swizzle = true) {
  const cuuint32_t es[3] = {1, 1, 1};
  enc(m, CU_TENSOR_MAP_DATA_TYPE_BFLOAT16, rank, const_cast<void*>(ptr), dims, strides, box, es, CU_TENSOR_MAP_INTERLEAVE_NONE,
      swizzle ? CU_TENSOR_MAP_SWIZZLE_128B : CU_TENSOR_MAP_SWIZZLE_NONE, swizzle ? CU_TENSOR_MAP_L2_PROMOTION_L2_128B : CU_TENSOR_MAP_L2_PROMOTION_NONE, CU_TENSOR_MAP_FLOAT_OOB_FILL_NONE);
}
void make_2d(EncodeFn enc, CUtensorMap* m, const void* ptr, int rows, int cols, int box_rows) {
  const cuuint64_t dims[2] = {(cuuint64_t)cols, (cuuint64_t)rows}, strides[1] = {(cuuint64_t)cols * 2};
  const cuuint32_t box[2] = {64, (cuuint32_t)box_rows};
  make_map(enc, m, ptr, 2, dims, strides, box);
}
void make_3d(EncodeFn enc, CUtensorMap* m, const void* ptr, int rows, int chunks, size_t row_stride, size_t chunk_stride) {
  const cuuint64_t dims[3] = {64, (cuuint64_t)rows, (cuuint64_t)chunks}, strides[2] = {row_stride, chunk_stride};
  const cuuint32_t box[3] = {64, 64, 2};
  make_map(enc, m, ptr, 3, dims, strides, box);
}

void make_ffn(EncodeFn enc, CUtensorMap* m, const void* ptr) {
  const cuuint64_t dims[2] = {(cuuint64_t)FF, (cuuint64_t)DM}, strides[1] = {(cuuint64_t)FF * 2};
  const cuuint32_t box[2] = {16, 256};
  make_map(enc, m, ptr, 2, dims, strides, box, false);
}

void build_sched(Sched& s) {
  memset(&s, 0, sizeof(s));
  const int korder[4] = {(KORDER >> 12) & 3, (KORDER >> 8) & 3, (KORDER >> 4) & 3, KORDER & 3};
  for (int p = 0; p < NCTA / 2; p++) {
    const int hh = p >> 3, a = p & 7, b = (a + 4) & 7;
    for (int k = 0; k < 4; k++) s.khead[p][k] = (uint8_t)(korder[k] * 8 + hh);
    const int js[4] = {a, b, 7 - a, 7 - b};
    s.nitems[p] = 4;
    for (int r = 0; r < 4; r++) s.item[p][r] = (uint8_t)((r * 8 + hh) * 8 + js[r]);
    const int kq = p >> 4;
    s.otask[p] = (uint8_t)(p & 63);
    for (int k = 0; k < 8; k++) s.ohead[p][k] = (uint8_t)((k >> 1) * 8 + kq * 2 + (k & 1));
  }
}

}

extern "C" void kernel_launch(void* const* d_in, const int* in_sizes, int n_in, void* d_out, int out_size) {
  (void)in_sizes; (void)n_in; (void)out_size;
  const __nv_bfloat16* x     = (const __nv_bfloat16*)d_in[0];
  const __nv_bfloat16* ckv   = (const __nv_bfloat16*)d_in[1];
  const __nv_bfloat16* w_q   = (const __nv_bfloat16*)d_in[2];
  const __nv_bfloat16* w_uk  = (const __nv_bfloat16*)d_in[3];
  const __nv_bfloat16* w_uv  = (const __nv_bfloat16*)d_in[4];
  const __nv_bfloat16* w_o   = (const __nv_bfloat16*)d_in[5];
  const __nv_bfloat16* w_r   = (const __nv_bfloat16*)d_in[7];
  const __nv_bfloat16* w_g   = (const __nv_bfloat16*)d_in[8];
  const __nv_bfloat16* w_u   = (const __nv_bfloat16*)d_in[9];
  const __nv_bfloat16* w_d   = (const __nv_bfloat16*)d_in[10];
  const __nv_bfloat16* cvec  = (const __nv_bfloat16*)d_in[11];
  const __nv_bfloat16* w_mod = (const __nv_bfloat16*)d_in[12];
  __nv_bfloat16* out = (__nv_bfloat16*)d_out;

  static HostState st;
  if (!st.ready) {
    void* fn = nullptr; cudaDriverEntryPointQueryResult qr;
    cudaGetDriverEntryPoint("cuTensorMapEncodeTiled", &fn, cudaEnableDefault, &qr);
    st.encode = (EncodeFn)fn;
    cudaFuncSetAttribute(k_fused, cudaFuncAttributeMaxDynamicSharedMemorySize, SMEM);
    build_sched(st.sched);
    void *p_kvc, *p_h1, *p_part;
    cudaGetSymbolAddress(&p_kvc, g_kvc); cudaGetSymbolAddress(&p_h1, g_h1); cudaGetSymbolAddress(&p_part, g_part);
    st.sched.kvc = (__nv_bfloat16*)p_kvc; st.sched.h1 = (__nv_bfloat16*)p_h1;
    make_2d(st.encode, &st.tmH, p_h1, SEQ, DM, 64);
    make_2d(st.encode, &st.tmKV, p_kvc, 192 * SEQ, 64, 128);
    make_3d(st.encode, &st.tmPart, p_part, SEQ, 32, 128, (size_t)SEQ * 128);
    { const cuuint64_t dims[3] = {64, (cuuint64_t)SEQ, 32}, strides[2] = {128, (cuuint64_t)SEQ * 128}; const cuuint32_t box[3] = {64, 16, 4};
      make_map(st.encode, &st.tmPl, p_part, 3, dims, strides, box, false); }
    st.ready = true;
  }
  make_2d(st.encode, &st.tmC, ckv, SEQ, DM, 128);
  make_2d(st.encode, &st.tmWq, w_q, DM, NH * DH, 64);
  make_2d(st.encode, &st.tmWk, w_uk, DM, NH * DH, 64);
  make_2d(st.encode, &st.tmWv, w_uv, DM, NH * DH, 64);
  make_3d(st.encode, &st.tmWo, w_o, NH * DH, DM / 64, (size_t)DM * 2, 128);
  make_ffn(st.encode, &st.tmWg, w_g);
  make_ffn(st.encode, &st.tmWu, w_u);

  k_fused<<<NGRID, 384, SMEM, cudaStreamPerThread>>>(st.tmC, st.tmH, st.tmWq, st.tmWk, st.tmWv, st.tmKV, st.tmWo, st.tmPart, st.tmWg, st.tmWu, st.tmPl, st.sched,
                                                     x, ckv, cvec, w_mod, w_r, w_g, w_u, w_d, out);
}
```

```cpp
#include <cuda_runtime.h>
#include <cuda_bf16.h>
#include <cuda.h>
#include <stdint.h>
#include <string.h>
#include <math.h>

namespace {

constexpr int SEQ = 2048, DM = 512, NH = 32, DH = 128, FF = 1792;
constexpr int NCTA = 128, NGRID = 132;

__device__ __nv_bfloat16 g_kvc[192 * SEQ * 64];
__device__ __nv_bfloat16 g_h1[SEQ * DM];
__device__ __nv_bfloat16 g_part[32 * SEQ * 64];
__device__ __align__(16) __nv_bfloat16 g_mod[6 * DM];
constexpr int C_MOD = 0, C_MOD2 = 16, C_H1 = 32, C_KV = 64, C_CTX = 128, C_END = 384;
__device__ unsigned int g_cnt[C_END];
__device__ unsigned int g_epoch;
__device__ __align__(128) unsigned int g_pflag[32][32];
__device__ __align__(128) uint2 g_keys[128][4];
__device__ __align__(16) uint2 g_row[128][2][DM / 2];
__device__ __align__(16) uint2 g_yll[FF / 16][DM];

#define DBG(i)
#define DBGP(i)

__device__ __forceinline__ uint32_t smem_u32(const void* p) { return (uint32_t)__cvta_generic_to_shared(p); }
__device__ __forceinline__ int wg_tid() { int t; asm volatile("mov.u32 %0, %%tid.x;" : "=r"(t)); return t & 127; }
__device__ __forceinline__ uint32_t clk32() { uint32_t c; asm volatile("mov.u32 %0, %%clock;" : "=r"(c)); return c; }
__device__ __forceinline__ void mbar_arrive(uint32_t bar) { asm volatile("mbarrier.arrive.shared::cta.b64 _, [%0];" :: "r"(bar) : "memory"); }
__device__ __forceinline__ uint32_t mapa(uint32_t addr, uint32_t cta) { uint32_t r; asm("mapa.shared::cluster.u32 %0, %1, %2;" : "=r"(r) : "r"(addr), "r"(cta)); return r; }
__device__ __forceinline__ void mbar_arrive_remote_if(uint32_t cluster_addr, bool pred) {
  asm volatile("{\n.reg .pred p;\nsetp.ne.u32 p, %1, 0;\n@p mbarrier.arrive.shared::cluster.b64 _, [%0];\n}" :: "r"(cluster_addr), "r"((uint32_t)pred) : "memory");
}
__device__ __forceinline__ bool mbar_try(uint32_t bar, uint32_t parity) {
  uint32_t done;
  asm volatile("{\n.reg .pred p;\nmbarrier.try_wait.parity.shared::cta.b64 p, [%1], %2;\nselp.u32 %0, 1, 0, p;\n}" : "=r"(done) : "r"(bar), "r"(parity) : "memory");
  return done;
}
#define WAIT_LIM (1 << 14)
__device__ __forceinline__ void mbar_wait(uint32_t bar, uint32_t parity) {
  #pragma unroll 1
  for (int n = 0; n < WAIT_LIM; n++) { if (mbar_try(bar, parity)) break; }
}
__device__ __forceinline__ unsigned int ld_acquire(const unsigned int* p) {
  unsigned int v; asm volatile("ld.acquire.gpu.global.u32 %0, [%1];" : "=r"(v) : "l"(p) : "memory"); return v;
}
__device__ __forceinline__ unsigned int ld_relaxed(const unsigned int* p) {
  unsigned int v; asm volatile("ld.relaxed.gpu.global.u32 %0, [%1];" : "=r"(v) : "l"(p) : "memory"); return v;
}
__device__ __forceinline__ void wait_count_lazy(int idx, unsigned int target) {
  #pragma unroll 1
  for (int n = 0; n < WAIT_LIM; n++) { if ((int)(ld_relaxed(&g_cnt[idx]) - target) >= 0) break; __nanosleep(100); }
  ld_acquire(&g_cnt[idx]);
}
__device__ __forceinline__ uint4 ld_tagged2(const void* p) {
  uint4 v;
  asm volatile("{\n.reg .b64 a, b;\nld.relaxed.gpu.global.v2.u64 {a, b}, [%4];\nmov.b64 {%0, %1}, a;\nmov.b64 {%2, %3}, b;\n}"
    : "=r"(v.x), "=r"(v.y), "=r"(v.z), "=r"(v.w) : "l"(p) : "memory");
  return v;
}
__device__ __forceinline__ uint2 ld_tagged(const void* p) {
  uint2 v; asm volatile("{\n.reg .b64 a;\nld.relaxed.gpu.global.u64 a, [%2];\nmov.b64 {%0, %1}, a;\n}" : "=r"(v.x), "=r"(v.y) : "l"(p) : "memory"); return v;
}
__device__ __forceinline__ void st_tagged2(void* p, uint32_t a, uint32_t b, uint32_t tag) {
  asm volatile("{\n.reg .b64 a, b;\nmov.b64 a, {%1, %3};\nmov.b64 b, {%2, %3};\nst.relaxed.gpu.global.v2.u64 [%0], {a, b};\n}" :: "l"(p), "r"(a), "r"(b), "r"(tag) : "memory");
}
__device__ __forceinline__ void st_tagged(void* p, uint32_t a, uint32_t tag) {
  asm volatile("{\n.reg .b64 a;\nmov.b64 a, {%1, %2};\nst.relaxed.gpu.global.u64 [%0], a;\n}" :: "l"(p), "r"(a), "r"(tag) : "memory");
}
__device__ __forceinline__ void stg_v4(void* p, uint32_t a, uint32_t b, uint32_t c, uint32_t d) {
  asm volatile("st.global.v4.u32 [%0], {%1, %2, %3, %4};" :: "l"(p), "r"(a), "r"(b), "r"(c), "r"(d) : "memory");
}
__device__ __forceinline__ uint4 lds_v4(uint32_t addr) {
  uint4 v; asm volatile("ld.shared.v4.u32 {%0, %1, %2, %3}, [%4];" : "=r"(v.x), "=r"(v.y), "=r"(v.z), "=r"(v.w) : "r"(addr) : "memory"); return v;
}
__device__ __forceinline__ uint32_t lds_u32(uint32_t addr) { uint32_t v; asm volatile("ld.shared.u32 %0, [%1];" : "=r"(v) : "r"(addr) : "memory"); return v; }
__device__ __forceinline__ void sts_v4(uint32_t addr, uint32_t a, uint32_t b, uint32_t c, uint32_t d) {
  asm volatile("st.shared.v4.u32 [%0], {%1, %2, %3, %4};" :: "r"(addr), "r"(a), "r"(b), "r"(c), "r"(d) : "memory");
}
#define ELECT "{\n.reg .pred p;\nelect.sync _|p, 0xffffffff;\n@p "
__device__ __forceinline__ void w_mbar_init(uint32_t bar, uint32_t cnt) { asm volatile(ELECT "mbarrier.init.shared::cta.b64 [%0], %1;\n}" :: "r"(bar), "r"(cnt) : "memory"); }
__device__ __forceinline__ void w_expect_tx(uint32_t bar, uint32_t bytes) { asm volatile(ELECT "mbarrier.arrive.expect_tx.shared::cta.b64 _, [%0], %1;\n}" :: "r"(bar), "r"(bytes) : "memory"); }
__device__ __forceinline__ void w_arrive(uint32_t bar) { asm volatile(ELECT "mbarrier.arrive.shared::cta.b64 _, [%0];\n}" :: "r"(bar) : "memory"); }
__device__ __forceinline__ void tma_load_2d(uint32_t dst, const CUtensorMap* tm, uint32_t bar, int c0, int c1) {
  asm volatile(ELECT "cp.async.bulk.tensor.2d.shared::cluster.global.mbarrier::complete_tx::bytes [%0], [%1, {%3, %4}], [%2];\n}"
    :: "r"(dst), "l"(tm), "r"(bar), "r"(c0), "r"(c1) : "memory");
}
__device__ __forceinline__ void tma_load_2d_mc(uint32_t dst, const CUtensorMap* tm, uint32_t bar, int c0, int c1) {
  asm volatile(ELECT "cp.async.bulk.tensor.2d.shared::cluster.global.mbarrier::complete_tx::bytes.multicast::cluster [%0], [%1, {%3, %4}], [%2], %5;\n}"
    :: "r"(dst), "l"(tm), "r"(bar), "r"(c0), "r"(c1), "h"((uint16_t)3) : "memory");
}
__device__ __forceinline__ void tma_load_3d(uint32_t dst, const CUtensorMap* tm, uint32_t bar, int c0, int c1, int c2) {
  asm volatile(ELECT "cp.async.bulk.tensor.3d.shared::cluster.global.mbarrier::complete_tx::bytes [%0], [%1, {%3, %4, %5}], [%2];\n}"
    :: "r"(dst), "l"(tm), "r"(bar), "r"(c0), "r"(c1), "r"(c2) : "memory");
}
__device__ __forceinline__ void tma_load_3d_mc(uint32_t dst, const CUtensorMap* tm, uint32_t bar, int c0, int c1, int c2) {
  asm volatile(ELECT "cp.async.bulk.tensor.3d.shared::cluster.global.mbarrier::complete_tx::bytes.multicast::cluster [%0], [%1, {%3, %4, %5}], [%2], %6;\n}"
    :: "r"(dst), "l"(tm), "r"(bar), "r"(c0), "r"(c1), "r"(c2), "h"((uint16_t)3) : "memory");
}
__device__ __forceinline__ void bulk_load(uint32_t dst, const void* src, uint32_t bytes, uint32_t bar) {
  asm volatile(ELECT "cp.async.bulk.shared::cluster.global.mbarrier::complete_tx::bytes [%0], [%1], %2, [%3];\n}" :: "r"(dst), "l"(src), "r"(bytes), "r"(bar) : "memory");
}
__device__ __forceinline__ void tma_prefetch_2d(const CUtensorMap* tm, int c0, int c1) {
  asm volatile(ELECT "cp.async.bulk.prefetch.tensor.2d.L2.global [%0, {%1, %2}];\n}" :: "l"(tm), "r"(c0), "r"(c1) : "memory");
}
__device__ __forceinline__ void tma_prefetch_3d(const CUtensorMap* tm, int c0, int c1, int c2) {
  asm volatile(ELECT "cp.async.bulk.prefetch.tensor.3d.L2.global [%0, {%1, %2, %3}];\n}" :: "l"(tm), "r"(c0), "r"(c1), "r"(c2) : "memory");
}
__device__ __forceinline__ void bulk_prefetch(const void* p, uint32_t bytes) {
  asm volatile(ELECT "cp.async.bulk.prefetch.L2.global [%0], %1;\n}" :: "l"(p), "r"(bytes) : "memory");
}
__device__ __forceinline__ void tma_store_3d(const CUtensorMap* tm, uint32_t src, int c0, int c1, int c2) {
  asm volatile("cp.async.bulk.tensor.3d.global.shared::cta.bulk_group [%0, {%2, %3, %4}], [%1];"
    :: "l"(tm), "r"(src), "r"(c0), "r"(c1), "r"(c2) : "memory");
}
__device__ __forceinline__ void st_release(unsigned int* p, unsigned int v) { asm volatile("st.release.gpu.global.u32 [%0], %1;" :: "l"(p), "r"(v) : "memory"); }
__device__ __forceinline__ void red_release(int idx) { asm volatile("red.release.gpu.global.add.u32 [%0], 1;" :: "l"(&g_cnt[idx]) : "memory"); }
__device__ __forceinline__ void prefetch_tmap(const CUtensorMap* tm) { asm volatile("prefetch.tensormap [%0];" :: "l"(tm) : "memory"); }
__device__ __forceinline__ void bulk_commit() { asm volatile("cp.async.bulk.commit_group;" ::: "memory"); }
template<int N> __device__ __forceinline__ void bulk_wait() { asm volatile("cp.async.bulk.wait_group %0;" :: "n"(N) : "memory"); }
__device__ __forceinline__ void bar_sync(int id, int n) { asm volatile("bar.sync %0, %1;" :: "r"(id), "r"(n) : "memory"); }
__device__ __forceinline__ void bar_arrive(int id, int n) { asm volatile("bar.arrive %0, %1;" :: "r"(id), "r"(n) : "memory"); }
__device__ __forceinline__ void fence_async_smem() { asm volatile("fence.proxy.async.shared::cta;" ::: "memory"); }
__device__ __forceinline__ void fence_async_global() { asm volatile("fence.proxy.async.global;" ::: "memory"); }
__device__ __forceinline__ void fence_mbar_init() { asm volatile("fence.mbarrier_init.release.cluster;" ::: "memory"); }
__device__ __forceinline__ void cluster_arrive() { asm volatile("barrier.cluster.arrive.relaxed.aligned;" ::: "memory"); }
__device__ __forceinline__ void cluster_wait() { asm volatile("barrier.cluster.wait.aligned;" ::: "memory"); }
__device__ __forceinline__ uint32_t cluster_ctarank() { uint32_t r; asm volatile("mov.u32 %0, %%cluster_ctarank;" : "=r"(r)); return r; }
__device__ __forceinline__ void wgmma_fence() { asm volatile("wgmma.fence.sync.aligned;" ::: "memory"); }
__device__ __forceinline__ void wgmma_commit() { asm volatile("wgmma.commit_group.sync.aligned;" ::: "memory"); }
template<int N> __device__ __forceinline__ void wgmma_wait() { asm volatile("wgmma.wait_group.sync.aligned %0;" :: "n"(N) : "memory"); }
__device__ __forceinline__ float ex2(float x) { float y; asm("ex2.approx.ftz.f32 %0, %1;" : "=f"(y) : "f"(x)); return y; }
__device__ __forceinline__ float rcp_fast(float x) { float y; asm("rcp.approx.ftz.f32 %0, %1;" : "=f"(y) : "f"(x)); return y; }
__device__ __forceinline__ uint32_t pack_bf16(float lo, float hi) { uint32_t r; asm("cvt.rn.bf16x2.f32 %0, %1, %2;" : "=r"(r) : "f"(hi), "f"(lo)); return r; }
__device__ __forceinline__ float rbf(float x) { return __uint_as_float(pack_bf16(0.f, x)); }
__device__ __forceinline__ float bf_lo(uint32_t v) { return __uint_as_float(v << 16); }
__device__ __forceinline__ float bf_hi(uint32_t v) { return __uint_as_float(v & 0xffff0000u); }
__device__ __forceinline__ uint32_t add2(uint32_t a, uint32_t b) { uint32_t r; asm("add.rn.bf16x2 %0, %1, %2;" : "=r"(r) : "r"(a), "r"(b)); return r; }
__device__ __forceinline__ uint32_t fma2(uint32_t a, uint32_t b, uint32_t c) { uint32_t r; asm("fma.rn.bf16x2 %0, %1, %2, %3;" : "=r"(r) : "r"(a), "r"(b), "r"(c)); return r; }
__device__ __forceinline__ uint4 ldsm_x4_t(uint32_t addr) {
  uint4 v; asm volatile("ldmatrix.sync.aligned.m8n8.x4.trans.shared.b16 {%0, %1, %2, %3}, [%4];" : "=r"(v.x), "=r"(v.y), "=r"(v.z), "=r"(v.w) : "r"(addr) : "memory"); return v;
}
__device__ __forceinline__ void mma16816(float (&c)[4], const uint4& a, uint32_t b0, uint32_t b1) {
  asm("mma.sync.aligned.m16n8k16.row.col.f32.bf16.bf16.f32 {%0, %1, %2, %3}, {%4, %5, %6, %7}, {%8, %9}, {%0, %1, %2, %3};"
    : "+f"(c[0]), "+f"(c[1]), "+f"(c[2]), "+f"(c[3]) : "r"(a.x), "r"(a.y), "r"(a.z), "r"(a.w), "r"(b0), "r"(b1));
}
__device__ __forceinline__ void stsm_x4(uint32_t addr, uint32_t r0, uint32_t r1, uint32_t r2, uint32_t r3) {
  asm volatile("stmatrix.sync.aligned.m8n8.x4.shared.b16 [%0], {%1, %2, %3, %4};" :: "r"(addr), "r"(r0), "r"(r1), "r"(r2), "r"(r3) : "memory");
}
template<int N> __device__ __forceinline__ void fence_regs(float (&a)[N]) {
  #pragma unroll
  for (int i = 0; i < N; i++) asm volatile("" : "+f"(a[i]) :: "memory");
}
template<int N> __device__ __forceinline__ void fence_regs_u(uint32_t (&a)[N]) {
  #pragma unroll
  for (int i = 0; i < N; i++) asm volatile("" : "+r"(a[i]) :: "memory");
}
__device__ __forceinline__ uint32_t desc_lo(uint32_t addr, uint32_t lbo) { return ((addr & 0x3FFFF) >> 4) | ((lbo >> 4) << 16); }

template<int TB, int OA, int OB> __device__ __forceinline__ void wgmma_ss_n128(float (&d)[64], uint32_t da, uint32_t db, int sd) {
  asm volatile("{\n.reg .pred p;\n.reg .b32 ta, tb;\n.reg .b64 da, db;\nsetp.ne.b32 p, %66, 0;\nadd.u32 ta, %64, %68;\nadd.u32 tb, %65, %69;\nmov.b64 da, {ta, 0x40000040};\nmov.b64 db, {tb, 0x40000040};\n"
    "wgmma.mma_async.sync.aligned.m64n128k16.f32.bf16.bf16 "
    "{%0, %1, %2, %3, %4, %5, %6, %7, %8, %9, %10, %11, %12, %13, %14, %15, %16, %17, %18, %19, %20, %21, %22, %23, %24, %25, %26, %27, %28, %29, %30, %31, %32, %33, %34, %35, %36, %37, %38, %39, %40, %41, %42, %43, %44, %45, %46, %47, %48, %49, %50, %51, %52, %53, %54, %55, %56, %57, %58, %59, %60, %61, %62, %63}, da, db, p, 1, 1, 0, %67;\n}\n"
    : "+f"(d[0]), "+f"(d[1]), "+f"(d[2]), "+f"(d[3]), "+f"(d[4]), "+f"(d[5]), "+f"(d[6]), "+f"(d[7]), "+f"(d[8]), "+f"(d[9]), "+f"(d[10]), "+f"(d[11]), "+f"(d[12]), "+f"(d[13]), "+f"(d[14]), "+f"(d[15]), "+f"(d[16]), "+f"(d[17]), "+f"(d[18]), "+f"(d[19]), "+f"(d[20]), "+f"(d[21]), "+f"(d[22]), "+f"(d[23]), "+f"(d[24]), "+f"(d[25]), "+f"(d[26]), "+f"(d[27]), "+f"(d[28]), "+f"(d[29]), "+f"(d[30]), "+f"(d[31]), "+f"(d[32]), "+f"(d[33]), "+f"(d[34]), "+f"(d[35]), "+f"(d[36]), "+f"(d[37]), "+f"(d[38]), "+f"(d[39]), "+f"(d[40]), "+f"(d[41]), "+f"(d[42]), "+f"(d[43]), "+f"(d[44]), "+f"(d[45]), "+f"(d[46]), "+f"(d[47]), "+f"(d[48]), "+f"(d[49]), "+f"(d[50]), "+f"(d[51]), "+f"(d[52]), "+f"(d[53]), "+f"(d[54]), "+f"(d[55]), "+f"(d[56]), "+f"(d[57]), "+f"(d[58]), "+f"(d[59]), "+f"(d[60]), "+f"(d[61]), "+f"(d[62]), "+f"(d[63])
    : "r"(da), "r"(db), "r"(sd), "n"(TB), "n"(OA), "n"(OB));
}
template<int TB, int OB> __device__ __forceinline__ void wgmma_rs_n128(float (&d)[64], uint32_t a0, uint32_t a1, uint32_t a2, uint32_t a3, uint32_t db, int sd) {
  asm volatile("{\n.reg .pred p;\n.reg .b32 tb;\n.reg .b64 db;\nsetp.ne.b32 p, %69, 0;\nadd.u32 tb, %68, %71;\nmov.b64 db, {tb, 0x40000040};\n"
    "wgmma.mma_async.sync.aligned.m64n128k16.f32.bf16.bf16 "
    "{%0, %1, %2, %3, %4, %5, %6, %7, %8, %9, %10, %11, %12, %13, %14, %15, %16, %17, %18, %19, %20, %21, %22, %23, %24, %25, %26, %27, %28, %29, %30, %31, %32, %33, %34, %35, %36, %37, %38, %39, %40, %41, %42, %43, %44, %45, %46, %47, %48, %49, %50, %51, %52, %53, %54, %55, %56, %57, %58, %59, %60, %61, %62, %63}, {%64,%65,%66,%67}, db, p, 1, 1, %70;\n}\n"
    : "+f"(d[0]), "+f"(d[1]), "+f"(d[2]), "+f"(d[3]), "+f"(d[4]), "+f"(d[5]), "+f"(d[6]), "+f"(d[7]), "+f"(d[8]), "+f"(d[9]), "+f"(d[10]), "+f"(d[11]), "+f"(d[12]), "+f"(d[13]), "+f"(d[14]), "+f"(d[15]), "+f"(d[16]), "+f"(d[17]), "+f"(d[18]), "+f"(d[19]), "+f"(d[20]), "+f"(d[21]), "+f"(d[22]), "+f"(d[23]), "+f"(d[24]), "+f"(d[25]), "+f"(d[26]), "+f"(d[27]), "+f"(d[28]), "+f"(d[29]), "+f"(d[30]), "+f"(d[31]), "+f"(d[32]), "+f"(d[33]), "+f"(d[34]), "+f"(d[35]), "+f"(d[36]), "+f"(d[37]), "+f"(d[38]), "+f"(d[39]), "+f"(d[40]), "+f"(d[41]), "+f"(d[42]), "+f"(d[43]), "+f"(d[44]), "+f"(d[45]), "+f"(d[46]), "+f"(d[47]), "+f"(d[48]), "+f"(d[49]), "+f"(d[50]), "+f"(d[51]), "+f"(d[52]), "+f"(d[53]), "+f"(d[54]), "+f"(d[55]), "+f"(d[56]), "+f"(d[57]), "+f"(d[58]), "+f"(d[59]), "+f"(d[60]), "+f"(d[61]), "+f"(d[62]), "+f"(d[63])
    : "r"(a0), "r"(a1), "r"(a2), "r"(a3), "r"(db), "r"(sd), "n"(TB), "n"(OB));
}
template<int TB, int OA, int OB> __device__ __forceinline__ void wgmma_ss_n64(float (&d)[32], uint32_t da, uint32_t db, int sd) {
  asm volatile("{\n.reg .pred p;\n.reg .b32 ta, tb;\n.reg .b64 da, db;\nsetp.ne.b32 p, %34, 0;\nadd.u32 ta, %32, %36;\nadd.u32 tb, %33, %37;\nmov.b64 da, {ta, 0x40000040};\nmov.b64 db, {tb, 0x40000040};\n"
    "wgmma.mma_async.sync.aligned.m64n64k16.f32.bf16.bf16 "
    "{%0, %1, %2, %3, %4, %5, %6, %7, %8, %9, %10, %11, %12, %13, %14, %15, %16, %17, %18, %19, %20, %21, %22, %23, %24, %25, %26, %27, %28, %29, %30, %31}, da, db, p, 1, 1, 0, %35;\n}\n"
    : "+f"(d[0]), "+f"(d[1]), "+f"(d[2]), "+f"(d[3]), "+f"(d[4]), "+f"(d[5]), "+f"(d[6]), "+f"(d[7]), "+f"(d[8]), "+f"(d[9]), "+f"(d[10]), "+f"(d[11]), "+f"(d[12]), "+f"(d[13]), "+f"(d[14]), "+f"(d[15]), "+f"(d[16]), "+f"(d[17]), "+f"(d[18]), "+f"(d[19]), "+f"(d[20]), "+f"(d[21]), "+f"(d[22]), "+f"(d[23]), "+f"(d[24]), "+f"(d[25]), "+f"(d[26]), "+f"(d[27]), "+f"(d[28]), "+f"(d[29]), "+f"(d[30]), "+f"(d[31])
    : "r"(da), "r"(db), "r"(sd), "n"(TB), "n"(OA), "n"(OB));
}
template<int TB, int OA, int OB> __device__ __forceinline__ void wgmma_ss_n128_new(float (&d)[64], uint32_t da, uint32_t db) {
  asm volatile("{\n.reg .pred p;\n.reg .b32 ta, tb;\n.reg .b64 da, db;\nsetp.ne.b32 p, %66, 0;\nadd.u32 ta, %64, %68;\nadd.u32 tb, %65, %69;\nmov.b64 da, {ta, 0x40000040};\nmov.b64 db, {tb, 0x40000040};\n"
    "wgmma.mma_async.sync.aligned.m64n128k16.f32.bf16.bf16 "
    "{%0, %1, %2, %3, %4, %5, %6, %7, %8, %9, %10, %11, %12, %13, %14, %15, %16, %17, %18, %19, %20, %21, %22, %23, %24, %25, %26, %27, %28, %29, %30, %31, %32, %33, %34, %35, %36, %37, %38, %39, %40, %41, %42, %43, %44, %45, %46, %47, %48, %49, %50, %51, %52, %53, %54, %55, %56, %57, %58, %59, %60, %61, %62, %63}, da, db, p, 1, 1, 0, %67;\n}\n"
    : "=f"(d[0]), "=f"(d[1]), "=f"(d[2]), "=f"(d[3]), "=f"(d[4]), "=f"(d[5]), "=f"(d[6]), "=f"(d[7]), "=f"(d[8]), "=f"(d[9]), "=f"(d[10]), "=f"(d[11]), "=f"(d[12]), "=f"(d[13]), "=f"(d[14]), "=f"(d[15]), "=f"(d[16]), "=f"(d[17]), "=f"(d[18]), "=f"(d[19]), "=f"(d[20]), "=f"(d[21]), "=f"(d[22]), "=f"(d[23]), "=f"(d[24]), "=f"(d[25]), "=f"(d[26]), "=f"(d[27]), "=f"(d[28]), "=f"(d[29]), "=f"(d[30]), "=f"(d[31]), "=f"(d[32]), "=f"(d[33]), "=f"(d[34]), "=f"(d[35]), "=f"(d[36]), "=f"(d[37]), "=f"(d[38]), "=f"(d[39]), "=f"(d[40]), "=f"(d[41]), "=f"(d[42]), "=f"(d[43]), "=f"(d[44]), "=f"(d[45]), "=f"(d[46]), "=f"(d[47]), "=f"(d[48]), "=f"(d[49]), "=f"(d[50]), "=f"(d[51]), "=f"(d[52]), "=f"(d[53]), "=f"(d[54]), "=f"(d[55]), "=f"(d[56]), "=f"(d[57]), "=f"(d[58]), "=f"(d[59]), "=f"(d[60]), "=f"(d[61]), "=f"(d[62]), "=f"(d[63])
    : "r"(da), "r"(db), "n"(0), "n"(TB), "n"(OA), "n"(OB));
}
template<int TB, int OA, int OB> __device__ __forceinline__ void wgmma_ss_n64_new(float (&d)[32], uint32_t da, uint32_t db) {
  asm volatile("{\n.reg .pred p;\n.reg .b32 ta, tb;\n.reg .b64 da, db;\nsetp.ne.b32 p, %34, 0;\nadd.u32 ta, %32, %36;\nadd.u32 tb, %33, %37;\nmov.b64 da, {ta, 0x40000040};\nmov.b64 db, {tb, 0x40000040};\n"
    "wgmma.mma_async.sync.aligned.m64n64k16.f32.bf16.bf16 "
    "{%0, %1, %2, %3, %4, %5, %6, %7, %8, %9, %10, %11, %12, %13, %14, %15, %16, %17, %18, %19, %20, %21, %22, %23, %24, %25, %26, %27, %28, %29, %30, %31}, da, db, p, 1, 1, 0, %35;\n}\n"
    : "=f"(d[0]), "=f"(d[1]), "=f"(d[2]), "=f"(d[3]), "=f"(d[4]), "=f"(d[5]), "=f"(d[6]), "=f"(d[7]), "=f"(d[8]), "=f"(d[9]), "=f"(d[10]), "=f"(d[11]), "=f"(d[12]), "=f"(d[13]), "=f"(d[14]), "=f"(d[15]), "=f"(d[16]), "=f"(d[17]), "=f"(d[18]), "=f"(d[19]), "=f"(d[20]), "=f"(d[21]), "=f"(d[22]), "=f"(d[23]), "=f"(d[24]), "=f"(d[25]), "=f"(d[26]), "=f"(d[27]), "=f"(d[28]), "=f"(d[29]), "=f"(d[30]), "=f"(d[31])
    : "r"(da), "r"(db), "n"(0), "n"(TB), "n"(OA), "n"(OB));
}
template<int OA, int OB = 0> __device__ __forceinline__ void kblock_n128(float (&d)[64], uint32_t da, uint32_t db, int sd) {
  wgmma_ss_n128<1, OA, OB>(d, da, db, sd); wgmma_ss_n128<1, OA + 2, OB + 128>(d, da, db, 1);
  wgmma_ss_n128<1, OA + 4, OB + 256>(d, da, db, 1); wgmma_ss_n128<1, OA + 6, OB + 384>(d, da, db, 1);
}

__device__ __forceinline__ float quad_sum(float v) {
  v += __shfl_xor_sync(0xffffffff, v, 1);
  v += __shfl_xor_sync(0xffffffff, v, 2);
  return v;
}
struct Row { uint32_t v[8]; };
template<class F> __device__ __forceinline__ Row load_row(const __nv_bfloat16* p, int lane, F ld) {
  const uint4 a = ld(reinterpret_cast<const uint4*>(p) + lane), b = ld(reinterpret_cast<const uint4*>(p) + 32 + lane);
  return Row{{a.x, a.y, a.z, a.w, b.x, b.y, b.z, b.w}};
}
__device__ __forceinline__ Row ldg_row(const __nv_bfloat16* p, int lane) { return load_row(p, lane, [](const uint4* q) { return __ldg(q); }); }
__device__ __forceinline__ Row ldca_row(const __nv_bfloat16* p, int lane) { return load_row(p, lane, [](const uint4* q) { return __ldca(q); }); }
__device__ __forceinline__ Row lds_row(uint32_t addr, int lane) {
  const uint4 a = lds_v4(addr + lane * 16), b = lds_v4(addr + 512 + lane * 16);
  return Row{{a.x, a.y, a.z, a.w, b.x, b.y, b.z, b.w}};
}
__device__ __forceinline__ void store_row(__nv_bfloat16* p, int lane, const Row& r) {
  stg_v4(p + lane * 8, r.v[0], r.v[1], r.v[2], r.v[3]); stg_v4(p + 256 + lane * 8, r.v[4], r.v[5], r.v[6], r.v[7]);
}
__device__ __forceinline__ Row fma_row(const Row& a, const Row& b, const Row& c) {
  Row r;
  #pragma unroll
  for (int i = 0; i < 8; i++) r.v[i] = fma2(a.v[i], b.v[i], c.v[i]);
  return r;
}
__device__ __forceinline__ Row one_plus(const Row& a) {
  Row r;
  #pragma unroll
  for (int i = 0; i < 8; i++) r.v[i] = add2(a.v[i], 0x3f803f80u);
  return r;
}
__device__ __forceinline__ void layer_norm2(const Row (&x)[2], Row (&n)[2]) {
  float d[2][16], s[4];
  #pragma unroll
  for (int r = 0; r < 2; r++) {
    const float c = bf_lo(__shfl_sync(0xffffffff, x[r].v[0], 0));
    float s1 = 0.f, s2 = 0.f;
    #pragma unroll
    for (int i = 0; i < 16; i++) { d[r][i] = ((i & 1) ? bf_hi(x[r].v[i >> 1]) : bf_lo(x[r].v[i >> 1])) - c; s1 += d[r][i]; s2 = fmaf(d[r][i], d[r][i], s2); }
    s[2*r] = s1; s[2*r+1] = s2;
  }
  #pragma unroll
  for (int o = 16; o > 0; o >>= 1) {
    #pragma unroll
    for (int k = 0; k < 4; k++) s[k] += __shfl_xor_sync(0xffffffff, s[k], o);
  }
  #pragma unroll
  for (int r = 0; r < 2; r++) {
    const float m = s[2*r] * (1.f / DM), rstd = rsqrtf(fmaxf(fmaf(-m, m, s[2*r+1] * (1.f / DM)), 0.f) + 1e-5f), o = -m * rstd;
    #pragma unroll
    for (int i = 0; i < 8; i++) n[r].v[i] = pack_bf16(fmaf(d[r][2*i], rstd, o), fmaf(d[r][2*i+1], rstd, o));
  }
}

constexpr int SM_Q = 6 * 32768, SM_BAR = 7 * 32768, SM_MAIL = SM_BAR + 640, SM_RED = SM_MAIL + 128, SM_H2 = SM_RED + 1024, SM_KEY = SM_H2 + 1024, SMEM = SM_KEY + 128;
constexpr int B_AF = 0, B_WF = 64, B_RF = 112, B_WE = 168, B_RE = 216, B_PUB = 272, B_RDY = 496;
constexpr int R_MOD = B_RDY, R_ITEM = B_RDY + 8, R_NEAR = B_RDY + 48, R_PART = B_RDY + 56, R_CTX = B_RDY + 64, R_KEY = B_AF + 8;
constexpr int NPUB = 14;
__device__ __forceinline__ uint32_t k_addrA(int kb) { return ((0x6310u >> ((kb >> 1) * 4)) & 15u) * 32768u + (kb & 1) * 16384u; }
__device__ __forceinline__ uint32_t k_addrW(int s) { return ((0x254u >> ((s >> 1) * 4)) & 15u) * 32768u + (s & 1) * 16384u; }

#define KORDER 0x2301
constexpr int KHEAD0 = ((KORDER >> 12) & 3) * 8;
constexpr int MAX_ITEMS = 5;
constexpr int MAX_STEPS = 10;
struct Sched {
  __nv_bfloat16 *kvc, *h1;
  struct Pair {
    uint32_t otab;
    uint8_t khead[4];
    uint8_t nitems, item[MAX_ITEMS];
    uint8_t otask, nsteps;
    uint8_t ochunk[MAX_STEPS][2];
  } pair[NGRID / 2];
};

__device__ __forceinline__ int ring_add(int e, int n) { e += n; return e >= 12 ? e - 12 : e; }
__device__ __forceinline__ int ring_slot(int e) { return e >= 6 ? e - 6 : e; }
__device__ __forceinline__ void ring_wait_full(uint32_t bars, int e) { mbar_wait(bars + B_RF + 8 * ring_slot(e), e >= 6); }

__device__ __forceinline__ uint32_t o_entry(uint32_t tab, int k) { const int pass = (k * 37) >> 8; return ((tab >> (4 * (k - 7 * pass))) & 15u) ^ ((pass & 1) << 3); }
__device__ __forceinline__ void o_wait_full(uint32_t bars, uint32_t v) { mbar_wait(bars + B_RF + 8 * (v & 7), v >> 3); }

struct Ctx {
  uint32_t base, bars;
  uint32_t rel;
  bool rel1;
  int w, nev;
  const Sched* sched;
};
__device__ __forceinline__ void slot_release(const Ctx& x, int s, bool twice) {
  mbar_arrive_remote_if(x.rel + B_RE + 8 * s, twice ? (wg_tid() & 31) == 0 : x.rel1);
}
__device__ __forceinline__ void ring_release(const Ctx& x, int e, bool twice) { slot_release(x, ring_slot(e), twice); }
__device__ __forceinline__ void publish(Ctx& x, int idx) {
  const uint32_t n = x.w * NPUB + x.nev;
  const int t = wg_tid();
  if (t == 0) asm volatile("st.shared.u32 [%0], %1;" :: "r"(x.base + SM_MAIL + 4 * n), "r"(idx) : "memory");
  __syncwarp();
  if ((t & 31) == 0) mbar_arrive(x.bars + B_PUB + 8 * n);
  x.nev++;
}

template<int KK = 0> __device__ __forceinline__ void issue_qk(float (&S)[64], uint32_t dq, uint32_t dk) {
  constexpr int off = (KK >> 2) * 1024 + (KK & 3) * 2;
  if constexpr (KK == 0) wgmma_ss_n128_new<0, 0, 0>(S, dq, dk); else wgmma_ss_n128<0, off, off>(S, dq, dk, 1);
  if constexpr (KK < 7) issue_qk<KK + 1>(S, dq, dk);
}
template<int KK = 0> __device__ __forceinline__ void issue_qk_half(float (&S)[32], uint32_t dq, uint32_t dk) {
  constexpr int off = (KK >> 2) * 1024 + (KK & 3) * 2;
  if constexpr (KK == 0) wgmma_ss_n64_new<0, 0, 512>(S, dq, dk); else wgmma_ss_n64<0, off, off + 512>(S, dq, dk, 1);
  if constexpr (KK < 7) issue_qk_half<KK + 1>(S, dq, dk);
}
template<int NK, int KK = 0>
__device__ __forceinline__ void issue_pv(float (&O)[64], uint32_t (&P)[32], uint32_t dv, int accumulate) {
  wgmma_rs_n128<1, (KK + 8 - NK) * 128>(O, P[4*KK], P[4*KK+1], P[4*KK+2], P[4*KK+3], dv, accumulate);
  if constexpr (KK + 1 < NK) issue_pv<NK, KK + 1>(O, P, dv, 1);
}
template<int K0, int K1>
__device__ __forceinline__ void exp_pack(const float (&S)[64], uint32_t (&D)[32], float& s0, float& s1) {
  #pragma unroll
  for (int k = K0; k < K1; k++) {
    const float e0 = ex2(S[2*k]), e1 = ex2(S[2*k+1]);
    D[k] = pack_bf16(e0, e1);
    if (k & 1) s1 += e0 + e1; else s0 += e0 + e1;
  }
}
__device__ __forceinline__ int q_row(int t) { return 16 * (t >> 5) + ((t >> 1) & 6) + ((t >> 4) & 1); }
__device__ __forceinline__ int diag_limit() { const int t = wg_tid(); return q_row(t) - 2 * (t & 3); }
__device__ __forceinline__ void exp_pack_diag(const float (&S)[64], uint32_t (&D)[32], int t, float& s0, float& s1) {
  #pragma unroll
  for (int k = 0; k < 16; k++) {
    const int c = 8 * (k >> 1) - 8 * (k & 1);
    const float e0 = ex2((c <= t) ? S[2*k] : -INFINITY), e1 = ex2((c + 1 <= t) ? S[2*k+1] : -INFINITY);
    D[k] = pack_bf16(e0, e1);
    if (k & 1) s1 += e0 + e1; else s0 += e0 + e1;
  }
}
constexpr float SUM_HI = 1.8446744073709552e19f;
constexpr float SUM_LO = 5.421010862427522e-20f;

__device__ __forceinline__ void classic_tile(const float (&S)[64], uint32_t (&P)[32], bool fresh, bool half, bool was_classic, volatile float* mc,
                                             float& l0, float& l1, float& s0, float& s1, float& sc0, float& sc1) {
  const int tmask = diag_limit();
  float4 t[16];
  #pragma unroll
  for (int j = 0; j < 16; j++) t[j] = make_float4(S[4*j], S[4*j+1], S[4*j+2], S[4*j+3]);
  float mx0 = -INFINITY, mx1 = -INFINITY;
  #pragma unroll 1
  for (int j = 0; j < 16; j++) {
    float4 v = t[j];
    const int lim = !fresh ? 1000 : j < 8 ? tmask - 8 * j : half ? -1000 : 1000;
    v.x = 0 <= lim ? v.x : -INFINITY; v.y = 1 <= lim ? v.y : -INFINITY; v.z = -8 <= lim ? v.z : -INFINITY; v.w = -7 <= lim ? v.w : -INFINITY;
    t[j] = v;
    mx0 = fmaxf(mx0, fmaxf(v.x, v.y)); mx1 = fmaxf(mx1, fmaxf(v.z, v.w));
  }
  mx0 = fmaxf(mx0, __shfl_xor_sync(0xffffffff, mx0, 1));
  mx1 = fmaxf(mx1, __shfl_xor_sync(0xffffffff, mx1, 1));
  mx0 = fmaxf(mx0, __shfl_xor_sync(0xffffffff, mx0, 2));
  mx1 = fmaxf(mx1, __shfl_xor_sync(0xffffffff, mx1, 2));
  const float mc0 = was_classic ? mc[0] : 0.f, mc1 = was_classic ? mc[1] : 0.f;
  const float n0 = fresh ? -mx0 : fminf(mc0, -mx0), n1 = fresh ? -mx1 : fminf(mc1, -mx1);
  sc0 = ex2(n0 - mc0); sc1 = ex2(n1 - mc1);
  mc[0] = n0; mc[1] = n1;
  s0 = 0.f; s1 = 0.f;
  #pragma unroll 1
  for (int j = 0; j < 16; j++) {
    const float4 v = t[j];
    const float e0 = ex2(v.x + n0), e1 = ex2(v.y + n0), e2 = ex2(v.z + n1), e3 = ex2(v.w + n1);
    s0 += e0 + e1; s1 += e2 + e3;
    reinterpret_cast<uint2*>(t)[j] = make_uint2(pack_bf16(e0, e1), pack_bf16(e2, e3));
  }
  #pragma unroll
  for (int j = 0; j < 8; j++) { P[4*j] = __float_as_uint(t[j].x); P[4*j+1] = __float_as_uint(t[j].y); P[4*j+2] = __float_as_uint(t[j].z); P[4*j+3] = __float_as_uint(t[j].w); }
  if (!fresh) { l0 *= sc0; l1 *= sc1; }
}
__device__ __forceinline__ void pack_tile(const float (&A)[64], uint32_t (&D)[32], float f0, float f1) {
  #pragma unroll
  for (int j = 0; j < 16; j++) {
    D[8 * (j >> 2) + (j & 3)] = pack_bf16(A[4*j] * f0, A[4*j+1] * f0);
    D[8 * (j >> 2) + 4 + (j & 3)] = pack_bf16(A[4*j+2] * f1, A[4*j+3] * f1);
  }
}
__device__ __forceinline__ void store_tile(__nv_bfloat16* p, const uint32_t (&D)[32]) {
  #pragma unroll
  for (int i = 0; i < 8; i++) stg_v4(p + (i >> 2) * (SEQ * 64) + ((i >> 1) & 1) * 32 + (i & 1) * 8 * 64, D[4*i], D[4*i+1], D[4*i+2], D[4*i+3]);
}

enum : int { PV_ACC = 0, PV_ZERO = 1, PV_HALF = 2, PV_NONE = 3 };
struct Att {
  float l0, l1, i0, i1;
  bool classic;
  volatile float* mc;
};
__device__ __forceinline__ void store_ctx(Ctx& x, int code, const uint32_t (&D)[32]) {
  const int item = code >> 2, t = wg_tid(), lane = t & 31;
  const int row = (item & 7) * 256 + (code & 3) * 64 + q_row(t);
  store_tile(x.sched->kvc + ((size_t)(128 + (item >> 3) * 2) * SEQ + row) * 64 + (lane & 3) * 8, D);
  publish(x, C_CTX + item);
}

#define G_DEEP 0
#define MERGE1 1
#define NO_CLASSIC 0
__device__ __forceinline__ void q_proj(Ctx& x, int& e, bool isY, bool dbg = false) {
  float S[64];
  bar_sync(1 + x.w, 256);
  if (dbg) DBG(80);
  if (isY) bar_arrive(1 + (x.w ^ 1), 256);
  #pragma unroll 1
  for (int kb = 0; kb < 8; kb++) {
    ring_wait_full(x.bars, e);
    if (dbg) DBG(81 + kb);
    const uint32_t ent = x.base + ring_slot(e) * 32768;
    const uint32_t da = desc_lo(ent + x.w * 8192, 16), dw = desc_lo(ent + 16384, 8192);
    wgmma_fence();
    kblock_n128<0>(S, da, dw, kb != 0);
    wgmma_commit();
    if (kb == 7 && !isY) bar_arrive(1 + (x.w ^ 1), 256);
    if (kb > 0) { wgmma_wait<1>(); ring_release(x, ring_add(e, 11), false); }
    e = ring_add(e, 1);
  }
  wgmma_wait<0>();
  fence_regs(S);
  if (dbg) DBG(89);
  ring_release(x, ring_add(e, 11), false);
  const int t = wg_tid(), lane = t & 31, g = (lane >> 3) + (lane & 4);
  const uint32_t qa = x.base + SM_Q + x.w * 8192 + ((t >> 5) * 16 + g) * 128;
  #pragma unroll
  for (int i = 0; i < 8; i++) {
    const int j = 4 * (i >> 1), o = 2 * (i & 1);
    sts_v4(qa + (i >> 2) * 16384 + (i & 1) * 1024 + (((((i >> 1) & 1) * 4 + (lane & 3)) ^ g) << 4),
           pack_bf16(S[4*j+o], S[4*j+o+1]), pack_bf16(S[4*j+4+o], S[4*j+5+o]), pack_bf16(S[4*j+8+o], S[4*j+9+o]), pack_bf16(S[4*j+12+o], S[4*j+13+o]));
  }
  fence_async_smem();
  if (dbg) DBG(90);
  ring_wait_full(x.bars, ring_add(e, isY ? 0 : 2));
  ring_wait_full(x.bars, ring_add(e, 1));
}

template<int KIND>
__device__ __forceinline__ void slot(Ctx& x, Att& a, int& e, float (&O)[64], uint32_t (&Pn)[32], uint32_t (&Po)[32],
                                     bool more, bool isY, bool half, int pv, int pend) {
  float S[64];
  const int w = x.w;
  const bool skip = KIND == 0 && !isY;
  const int en = ring_add(e, skip ? 4 : 2), sn = ring_slot(en), sv = ring_slot(e) + 1, sk = skip ? ring_slot(ring_add(e, 2)) : sv - 1;
  const uint32_t dq = desc_lo(x.base + SM_Q + w * 8192, 16), dk = desc_lo(x.base, 16) + sk * 2048, dv = desc_lo(x.base, 16384) + sv * 2048;
  bar_sync(1 + w, 256);
  if (KIND == 2) {
    wgmma_fence();
    issue_qk(S, dq, dk); wgmma_commit();
    issue_pv<8>(O, Po, dv, 1); wgmma_commit();
    bar_arrive(1 + (w ^ 1), 256);
    wgmma_wait<1>();
  } else if (KIND == 0 && half) {
    float T[32];
    wgmma_fence(); issue_qk_half(T, dq, dk); wgmma_commit();
    a.i0 = rcp_fast(quad_sum(a.l0)); a.i1 = rcp_fast(quad_sum(a.l1));
    if (pv == PV_NONE) { wgmma_fence(); wgmma_commit(); }
    else               { wgmma_fence(); issue_pv<8>(O, Po, dv, pv == PV_ACC); wgmma_commit(); }
    bar_arrive(1 + (w ^ 1), 256);
    wgmma_wait<1>();
    fence_regs(T);
    #pragma unroll
    for (int i = 0; i < 32; i++) { S[i] = T[i]; asm volatile("" : "=f"(S[32 + i])); }
  } else {
    wgmma_fence(); issue_qk(S, dq, dk); wgmma_commit();
    if (KIND == 1 && pend >= 0) { bar_arrive(1 + (w ^ 1), 256); pack_tile(O, Pn, a.i0, a.i1); store_ctx(x, pend, Pn); }
    if (KIND == 0) { a.i0 = rcp_fast(quad_sum(a.l0)); a.i1 = rcp_fast(quad_sum(a.l1)); }
    if (KIND == 0 && pv == PV_NONE) { wgmma_fence(); wgmma_commit(); }
    else if (pv == PV_HALF)         { wgmma_fence(); issue_pv<4>(O, Po, dv, 0); wgmma_commit(); }
    else                            { wgmma_fence(); issue_pv<8>(O, Po, dv, pv == PV_ACC); wgmma_commit(); }
    if (KIND == 0 || pend < 0) bar_arrive(1 + (w ^ 1), 256);
    wgmma_wait<1>();
  }
  fence_regs(S);
  fence_regs_u(Pn);
  slot_release(x, sk, KIND == 0 && isY);
  float s0 = 0.f, s1 = 0.f;
  const bool was_classic = KIND != 0 && a.classic;
  if (KIND == 0) {
    a.l0 = 0.f; a.l1 = 0.f;
    if (!half) exp_pack<16, 32>(S, Pn, s0, s1);
    else {
      #pragma unroll
      for (int i = 16; i < 32; i++) asm volatile("" : "=r"(Pn[i]));
    }
    exp_pack_diag(S, Pn, diag_limit(), s0, s1);
    uint32_t b0 = __ballot_sync(0xffffffff, s0 >= SUM_LO), b1 = __ballot_sync(0xffffffff, s1 >= SUM_LO);
    b0 |= b0 >> 1; b0 |= b0 >> 2; b1 |= b1 >> 1; b1 |= b1 >> 2;
    a.classic = __any_sync(0xffffffff, !(s0 <= SUM_HI && s1 <= SUM_HI)) || (b0 & b1 & 0x11111111u) != 0x11111111u;
  } else {
    exp_pack<0, 32>(S, Pn, s0, s1);
    a.classic = __any_sync(0xffffffff, a.classic || !(s0 <= SUM_HI && s1 <= SUM_HI));
  }
  fence_regs_u(Pn);
  mbar_wait(x.bars + B_RF + 8 * sn, en >= 6);
  if (more) mbar_wait(x.bars + B_RF + 8 * sn + 8, en >= 6);
  wgmma_wait<0>();
  fence_regs(O);
  fence_regs_u(Po);
  slot_release(x, sv, KIND == 1 && isY && pv != PV_ACC);
  if (!NO_CLASSIC && __builtin_expect(a.classic, 0)) {
    float sc0, sc1;
    classic_tile(S, Pn, KIND == 0, half, was_classic, a.mc, a.l0, a.l1, s0, s1, sc0, sc1);
    if (KIND != 0) {
      #pragma unroll
      for (int j = 0; j < 16; j++) { O[4*j] *= sc0; O[4*j+1] *= sc0; O[4*j+2] *= sc1; O[4*j+3] *= sc1; }
    }
  }
  a.l0 += s0; a.l1 += s1;
  e = en;
}

__device__ __forceinline__ void attention(Ctx& x, const uint8_t* items, int nitems, int rank) {
  int e = 0;
  float O[64]; uint32_t PA[32], PB[32];
  Att a;
  volatile float mc[2];
  a.l0 = 1.f; a.l1 = 1.f; a.i0 = 0.f; a.i1 = 0.f; a.classic = false; a.mc = mc;
  int pv = PV_NONE, cur = -1;
#define DBGS()
  #pragma unroll 1
  for (int it = 0; ; it++) {
    const bool isY = (it & 1) == x.w;
    int pend = cur;
    if (it < nitems) {
      const int item = items[it];
      const bool half = isY == (rank != 0);
      cur = item * 4 + (isY ? 3 - rank : rank);
      int rem = 2 * (item & 7) + (isY ? 1 : 0);
      DBG(16 + it);
      q_proj(x, e, isY);
      DBGS();
      slot<0>(x, a, e, O, PA, PB, rem > 0, isY, half, pv, -1);
      pv = half ? PV_HALF : PV_ZERO;
      #pragma unroll 1
      while (rem > 0) {
        DBGS();
        slot<1>(x, a, e, O, PB, PA, rem > 1, isY, false, pv, pend);
        pv = PV_ACC; pend = -1;
        if (rem == 1) break;
        rem -= 2;
        DBGS();
        slot<2>(x, a, e, O, PA, PB, rem > 0, false, false, 0, -1);
      }
    } else {
      DBGS();
      slot_release(x, 6, false);
      const uint32_t dv = desc_lo(x.base + ring_slot(e) * 32768, 16384);
      bar_sync(1 + x.w, 256);
      if (pv == PV_HALF) { wgmma_fence(); issue_pv<4>(O, PB, dv, 0); wgmma_commit(); }
      else { wgmma_fence(); issue_pv<8>(O, PB, dv, pv == PV_ACC); wgmma_commit(); }
      if (isY) bar_arrive(1 + (x.w ^ 1), 256);
      a.i0 = rcp_fast(quad_sum(a.l0)); a.i1 = rcp_fast(quad_sum(a.l1));
      ring_wait_full(x.bars, e);
      wgmma_wait<0>();
      fence_regs(O);
      fence_regs_u(PB);
      ring_release(x, e, false);
    }
    if (pend >= 0) { pack_tile(O, PB, a.i0, a.i1); store_ctx(x, pend, PB); }
    if (it == nitems) break;
    if (!isY) {
      #pragma unroll
      for (int i = 0; i < 32; i++) asm volatile("mov.b32 %0, %1;" : "=r"(PB[i]) : "r"(PA[i]));
    }
  }
}

#define LN_AT 2
#define X_AT 6
#define PF_AT 5
#define PF_N 4
#define PF_MOE 3
__device__ __forceinline__ void mod_cta(Ctx& x, const __nv_bfloat16* cvec) {
  const int t = wg_tid(), ct = x.w * 128 + t;
  #pragma unroll 1
  for (int k = 0; k < 6; k++) slot_release(x, k, false);
  const uint32_t cv = __ldg(reinterpret_cast<const uint32_t*>(cvec) + ct);
  asm volatile("st.shared.u32 [%0], %1;" :: "r"(x.base + SM_H2 + ct * 4),
               "r"(pack_bf16(__fdividef(bf_lo(cv), 1.f + __expf(-bf_lo(cv))), __fdividef(bf_hi(cv), 1.f + __expf(-bf_hi(cv))))) : "memory");
  bar_sync(5, 256);
  float acc[64];
  int e = 0;
  #pragma unroll 1
  for (int g = 0; g < 24; g++) {
    uint32_t a[8];
    #pragma unroll
    for (int i = 0; i < 8; i++) a[i] = lds_u32(x.base + SM_H2 + (g & 7) * 128 + i * 16 + (t & 3) * 4);
    ring_wait_full(x.bars, e);
    const uint32_t db = desc_lo(x.base + x.w * 16384, 8192) + ring_slot(e) * 2048;
    wgmma_fence();
    wgmma_rs_n128<1, 0>(acc, a[0], a[0], a[1], a[1], db, g & 7);
    wgmma_rs_n128<1, 128>(acc, a[2], a[2], a[3], a[3], db, 1);
    wgmma_rs_n128<1, 256>(acc, a[4], a[4], a[5], a[5], db, 1);
    wgmma_rs_n128<1, 384>(acc, a[6], a[6], a[7], a[7], db, 1);
    wgmma_commit();
    wgmma_wait<0>();
    fence_regs(acc);
    ring_release(x, e, false);
    e = ring_add(e, 1);
    if ((g & 7) == 7) {
      if (t < 4) {
        uint32_t* dst = reinterpret_cast<uint32_t*>(g_mod + (g >> 3) * 1024 + (blockIdx.x - NCTA) * 256 + x.w * 128) + t;
        #pragma unroll
        for (int j = 0; j < 16; j++) dst[4 * j] = pack_bf16(acc[4*j], acc[4*j+1]);
      }
      publish(x, g == 7 ? C_MOD : C_MOD2);
      DBG(1 + (g >> 3));
    }
  }
}

__global__ void __cluster_dims__(2, 1, 1) __launch_bounds__(384, 1)
k_fused(const __grid_constant__ CUtensorMap tmC, const __grid_constant__ CUtensorMap tmH, const __grid_constant__ CUtensorMap tmWq,
        const __grid_constant__ CUtensorMap tmWk, const __grid_constant__ CUtensorMap tmWv, const __grid_constant__ CUtensorMap tmKV,
        const __grid_constant__ CUtensorMap tmWo, const __grid_constant__ CUtensorMap tmPart, const __grid_constant__ CUtensorMap tmWg,
        const __grid_constant__ CUtensorMap tmWu, const __grid_constant__ CUtensorMap tmPl, const __grid_constant__ CUtensorMap tmWm,
        const __grid_constant__ Sched sched,
        const __nv_bfloat16* __restrict__ xin,
        const __nv_bfloat16* __restrict__ cvec, const __nv_bfloat16* __restrict__ w_o,
        const __nv_bfloat16* __restrict__ w_r, const __nv_bfloat16* __restrict__ w_gate, const __nv_bfloat16* __restrict__ w_up,
        const __nv_bfloat16* __restrict__ w_down, __nv_bfloat16* __restrict__ out) {
  extern __shared__ __align__(1024) uint8_t smem_raw[];
  const uint32_t base = smem_u32(smem_raw), bars = base + SM_BAR;
  const int warp = __shfl_sync(0xffffffff, threadIdx.x >> 5, 0), wg = warp >> 2;
  const int rank = cluster_ctarank(), p = blockIdx.x >> 1;
  const int mt = (p & 7) * 2 + rank;
  const bool spare = blockIdx.x >= NCTA;
  {
    const int h0 = KHEAD0 + (p >> 3);
    if (warp == 9) prefetch_tmap(&tmWk);
    if (warp <= 8) {
      #pragma unroll 1
      for (int t = 8 - warp; t < 80; t += (warp < 8 ? 8 : 80))
        w_mbar_init(bars + 8 * t, t < B_WE / 8 ? 1 : t < B_RE / 8 ? 2 : t < B_RDY / 8 ? 4 : 1);
      fence_mbar_init();
    }
    cluster_arrive();
    if (wg == 2) bar_arrive(1, 256);
    if (warp == 8 && !spare) {
      #pragma unroll 1
      for (int kb = 0; kb < 8; kb++) {
        w_expect_tx(bars + B_AF + 8 * kb, 16384);
        tma_load_2d(base + k_addrA(kb), &tmC, bars + B_AF + 8 * kb, kb * 64, mt * 128);
        if (kb == 0) cluster_wait();
        if (kb < 6) {
          w_expect_tx(bars + B_WF + 8 * kb, 16384);
          tma_load_2d_mc(base + k_addrW(kb) + rank * 8192, &tmWk, bars + B_WF + 8 * kb, h0 * 128 + rank * 64, kb * 64);
        }
      }
    }
  }
  const Sched::Pair& sp = sched.pair[p];
  const int nitems = sp.nitems, nsteps = sp.nsteps, odd = sp.ochunk[0][0] >= 64;
  const int ot = sp.otask, m = (ot & 7) * 2 + rank, grp = m * 8 + (ot >> 3);

  if (wg == 0) {
    asm volatile("setmaxnreg.dec.sync.aligned.u32 24;");
    const int lane = threadIdx.x & 31;
    cluster_wait();
    const unsigned int tag = ld_relaxed(&g_epoch) + 1;
    if (warp == 0) {
      if (!spare) {
        int s = 0, ph = 0;
        tma_prefetch_2d(&tmWv, sp.khead[0] * 128 + rank * 64, (p & 7) * 64);
        #pragma unroll 1
        for (int g = 6; g < 64; g++) {
          const int u = g >> 3, kb = g & 7;
          if (kb == 0 && u < 7) tma_prefetch_2d((u & 1) ? &tmWk : &tmWv, sp.khead[(u + 1) >> 1] * 128 + rank * 64, (p & 7) * 64);
          mbar_wait(bars + B_WE + 8 * s, ph);
          w_expect_tx(bars + B_WF + 8 * s, 16384);
          tma_load_2d_mc(base + k_addrW(s) + rank * 8192, (u & 1) ? &tmWv : &tmWk, bars + B_WF + 8 * s, sp.khead[u >> 1] * 128 + rank * 64, kb * 64);
          if (++s == 6) { s = 0; ph ^= 1; }
        }
      }
      int s = 0, ph = 0;
      auto next_entry = [&](bool load) {
        mbar_wait(bars + B_RE + 8 * s, ph);
        if (load) w_expect_tx(bars + B_RF + 8 * s, 32768); else w_arrive(bars + B_RF + 8 * s);
      };
      auto advance = [&]() { if (++s == 6) { s = 0; ph ^= 1; } };
      if (spare) {
        #pragma unroll 1
        for (int g = 0; g < 24; g++) {
          next_entry(true);
          for (int k = 0; k < 2; k++) tma_load_3d(base + s * 32768 + k * 16384, &tmWm, bars + B_RF + 8 * s, 0, (g & 7) * 64, (g >> 3) * 16 + (blockIdx.x - NCTA) * 4 + k * 2);
          advance();
        }
      }
      int vrow = -1;
      #pragma unroll 1
      for (int i = 0; i < nitems; i++) {
        const int item = sp.item[i], h = item >> 3, j = item & 7;
        const int row0 = j * 256 + ((i & 1) ? rank : 3 - rank) * 64, row1 = j * 256 + ((i & 1) ? 3 - rank : rank) * 64;
        mbar_wait(bars + R_ITEM + 8 * i, 0);
        fence_async_global();
        #pragma unroll 1
        for (int kb = 0; kb < 8; kb++) {
          next_entry(true);
          tma_load_2d_mc(base + s * 32768 + 16384 + rank * 8192, &tmWq, bars + B_RF + 8 * s, h * 128 + rank * 64, kb * 64);
          tma_load_2d(base + s * 32768, &tmH, bars + B_RF + 8 * s, kb * 64, row0);
          tma_load_2d(base + s * 32768 + 8192, &tmH, bars + B_RF + 8 * s, kb * 64, row1);
          advance();
        }
        #pragma unroll 1
        for (int n = 2 * j + 1; n >= 0; n--) {
          const int krow = (h * 2 + rank) * SEQ + n * 128;
          if (i + 1 == nitems && n == min(2 * j + 1, PF_AT)) w_arrive(bars + R_NEAR);
          next_entry(true);
          tma_load_2d_mc(base + s * 32768 + rank * 16384, &tmKV, bars + B_RF + 8 * s, 0, krow);
          advance();
          next_entry(vrow >= 0);
          if (vrow >= 0) tma_load_2d_mc(base + s * 32768 + rank * 16384, &tmKV, bars + B_RF + 8 * s, 0, vrow);
          advance();
          vrow = krow + 64 * SEQ;
        }
      }
      next_entry(true);
      tma_load_2d_mc(base + s * 32768 + rank * 16384, &tmKV, bars + B_RF + 8 * s, 0, vrow);
      advance();
      if (!spare) {
      const int oc = ((ot >> 3) & 1) * 4 + rank * 2;
      const uint32_t tab = sp.otab;
      auto o_next = [&](int k, int bytes) {
        const uint32_t v = o_entry(tab, k - odd); s = v & 7;
        mbar_wait(bars + B_RE + 8 * s, v >> 3);
        w_expect_tx(bars + B_RF + 8 * s, bytes);
      };
      #pragma unroll 1
      for (int i = 0; i < nsteps; i++) {
        const int c0 = sp.ochunk[i][0], c1 = sp.ochunk[i][1];
        if (i >= PF_MOE && i < PF_MOE + 3)
          bulk_prefetch((i == PF_MOE ? w_gate : i == PF_MOE + 1 ? w_up : w_down) + (size_t)blockIdx.x * (DM * FF / NCTA), DM * FF / NCTA * 2);
        if (c0 < 64) { o_next(3 * i, 32768); tma_load_3d_mc(base + s * 32768 + rank * 16384, &tmWo, bars + B_RF + 8 * s, 0, c0 * 64, oc); }
        mbar_wait(bars + R_CTX + 8 * i, 0);
        fence_async_global();
        o_next(3 * i + 1, c0 < 64 ? 32768 : 16384);
        if (c0 < 64) tma_load_2d(base + s * 32768, &tmKV, bars + B_RF + 8 * s, 0, (128 + c0) * SEQ + m * 128);
        tma_load_2d(base + s * 32768 + 16384, &tmKV, bars + B_RF + 8 * s, 0, (128 + c1) * SEQ + m * 128);
        o_next(3 * i + 2, 32768);
        tma_load_3d_mc(base + s * 32768 + rank * 16384, &tmWo, bars + B_RF + 8 * s, 0, c1 * 64, oc);
      }
      const int f0 = (blockIdx.x < FF / 16 ? blockIdx.x : 0) * 16;
      o_next(3 * nsteps, 32768);
      bulk_load(base + s * 32768, w_down + (size_t)f0 * DM, 16384, bars + B_RF + 8 * s);
      bulk_load(base + s * 32768 + 16384, xin + (size_t)grp * 16 * DM, 16384, bars + B_RF + 8 * s);
      o_next(3 * nsteps + 1, 32768);
      #pragma unroll 1
      for (int k = 0; k < 4; k++) tma_load_2d(base + s * 32768 + k * 8192, (k & 2) ? &tmWu : &tmWg, bars + B_RF + 8 * s, f0, (k & 1) * 256);
      w_expect_tx(bars + R_PART, 65536);
      mbar_wait(bars + B_PUB + 8 * (5 + nitems + 1), 0);
      mbar_wait(bars + B_PUB + 8 * (NPUB + 5 + nitems + 1), 0);
      uint32_t todo = 0xff;
      #pragma unroll 1
      for (int n = 0; n < WAIT_LIM && todo; n++) {
        uint32_t now = __ballot_sync(0xffffffff, ld_acquire(&g_pflag[m * 2 + (ot >> 5)][lane & 7]) == tag) & todo;
        todo &= ~now;
        fence_async_global();
        #pragma unroll 1
        for (; now; now &= now - 1) {
          const int q = __ffs(now) - 1;
          tma_load_3d(base + (o_entry(tab, 3 * nsteps - 3 - odd + (q >> 2)) & 7) * 32768 + (q & 3) * 8192, &tmPl, bars + R_PART, 0, grp * 16, q * 4);
        }
      }
      DBGP(11);
      }
    } else if (warp < 3) {
      const int w = warp - 1, n1 = w * NPUB + (spare ? 3 : 5) + nitems;
      #pragma unroll 1
      for (int n = w * NPUB; n < n1 + (spare ? 0 : 2); n++) {
        #pragma unroll 1
        for (int k = 0; k < 8 * WAIT_LIM; k++) { if (mbar_try(bars + B_PUB + 8 * n, 0)) break; }
        const uint32_t msg = lds_u32(base + SM_MAIL + 4 * n);
        if (n < n1) {
          fence_async_global();
          if (lane == 0 && msg < (unsigned)C_END) red_release(msg);
        } else {
          if (lane == 0) { tma_store_3d(&tmPart, base + (msg & 0x3c000), 0, m * 128 + 64 * w, (ot >> 3) * 4 + 2 * (n - n1)); bulk_commit(); }
        }
        __syncwarp();
      }
      bulk_wait<0>();
      fence_async_global();
      if (lane == 0 && !spare) st_release(&g_pflag[m * 2 + w][ot >> 3], tag);
      __syncwarp();
    } else {
      if (!spare) { mbar_wait(bars + B_AF + 8 * X_AT, 0); bulk_prefetch(xin + (size_t)blockIdx.x * 16 * DM, 16 * DM * 2); }
      wait_count_lazy(C_MOD, 8 * tag);
      DBGP(12);
      w_arrive(bars + R_MOD);
      #pragma unroll 1
      for (int i = 0; i < nitems; i++) {
        const int item = sp.item[i];
        tma_prefetch_2d(&tmWq, (item >> 3) * 128 + rank * 64, (item & 7) * 64);
        wait_count_lazy(C_H1 + (item & 7), 32 * tag);
        wait_count_lazy(C_KV + (item >> 3), 32 * tag);
        w_arrive(bars + R_ITEM + 8 * i);
      }
      wait_count_lazy(C_MOD2, 16 * tag);
      #pragma unroll 1
      for (int i = 0; i < nsteps; i++) {
        const int c = sp.ochunk[i][lane & 1];
        if (c < 64) wait_count_lazy(C_CTX + (c >> 1) * 8 + (ot & 7), 4 * tag);
        __syncwarp();
        w_arrive(bars + R_CTX + 8 * i);
        if (i == PF_N - 1) {
          #pragma unroll 1
          for (int k = 0; k < 8 * WAIT_LIM; k++) { if (mbar_try(bars + R_NEAR, 0)) break; }
          bulk_prefetch(w_o + (size_t)blockIdx.x * (NH * DH * DM / NCTA), NH * DH * DM / NCTA * 2);
          #pragma unroll 1
          for (int k = 0; k < PF_N; k++) {
            const int cc = sp.ochunk[k][(ot >> 3) & 1];
            if (cc < 64) bulk_prefetch(sched.kvc + ((size_t)(128 + cc) * SEQ + m * 128) * 64, 16384);
          }
        }
      }
    }
    bar_sync(6, 128);
    asm volatile("setmaxnreg.inc.sync.aligned.u32 88;");
    if (!spare) {
      const int pos = blockIdx.x * 4 + (lane & 1) * 2, col = (blockIdx.x >> 2) * 16 + (blockIdx.x & 3) * 2 + (lane & 1) * 8, src = threadIdx.x >> 1;
      uint32_t gbest = 0, hh = 0, gbf = 0;
      uint2 xx = make_uint2(0, 0);
      if (warp == 3) {
        gbf = __ldcg(reinterpret_cast<const uint32_t*>(g_mod + 5 * DM + col));
        uint32_t have = 0;
        #pragma unroll 1
        for (int n = 0; n < WAIT_LIM; n++) {
          uint2 k[4];
          #pragma unroll
          for (int i = 0; i < 4; i++) k[i] = ld_tagged(&g_keys[i * 32 + lane][0]);
          if (gbest != have) {
            const int g = ((0xffffu - gbest) >> 4) & 127;
            uint4 hv[4];
            #pragma unroll
            for (int i = 0; i < 4; i++) hv[i] = ld_tagged2(&g_row[g][0][i * 64 + lane * 2]);
            xx = ld_tagged(&g_row[g][1][col >> 1]);
            bool ok = xx.y == tag;
            #pragma unroll
            for (int i = 0; i < 4; i++) { ok = ok && hv[i].y == tag && hv[i].w == tag; reinterpret_cast<uint2*>(smem_raw + SM_H2)[i * 32 + lane] = make_uint2(hv[i].x, hv[i].z); }
            if (lane == 0) *reinterpret_cast<uint32_t*>(smem_raw + SM_KEY + 32) = gbest;
            have = __all_sync(0xffffffff, ok) ? gbest : 0;
          }
          bool all = true;
          #pragma unroll
          for (int i = 0; i < 4; i++) { all = all && k[i].y == tag; gbest = max(gbest, k[i].y == tag ? k[i].x : 0u); }
          gbest = __reduce_max_sync(0xffffffff, gbest);
          if (__all_sync(0xffffffff, all) && gbest == have) break;
        }
        w_arrive(bars + R_KEY);
        if (blockIdx.x == 0 && lane == 0) g_epoch = tag;
        hh = lds_u32(base + SM_H2 + col * 2);
        DBGP(13);
      }
      const uint32_t sb16 = gbest & 0xffff0000u;
      const float rsel = __uint_as_float((sb16 & 0x80000000u) ? (sb16 & 0x7fffffffu) : (~sb16 & 0xffff0000u));
      const float rs = rbf(__fdividef(1.f, 1.f + __expf(-rsel)));
      uint4 ya, yb = make_uint4(0, tag, 0, tag);
      #pragma unroll 1
      for (int n = 0; n < WAIT_LIM; n++) {
        ya = ld_tagged2(&g_yll[src][pos]);
        if (src + 64 < FF / 16) yb = ld_tagged2(&g_yll[src + 64][pos]);
        if (n == 0) mbar_wait(bars + R_KEY, 1);
        if (__all_sync(0xffffffff, ya.y == tag && ya.w == tag && yb.y == tag && yb.w == tag)) break;
      }
      float y0 = __uint_as_float(ya.x) + __uint_as_float(yb.x), y1 = __uint_as_float(ya.z) + __uint_as_float(yb.z);
      #pragma unroll
      for (int o = 2; o < 32; o <<= 1) { y0 += __shfl_xor_sync(0xffffffff, y0, o); y1 += __shfl_xor_sync(0xffffffff, y1, o); }
      float2* s_y = reinterpret_cast<float2*>(smem_raw + SM_KEY + 64);
      if (lane < 2) s_y[warp * 2 + lane] = make_float2(y0, y1);
      bar_sync(6, 128);
      if (warp == 3 && lane < 2) {
        y0 = 0.f; y1 = 0.f;
        #pragma unroll
        for (int i = 0; i < 4; i++) { y0 += reinterpret_cast<const float*>(s_y)[i * 4 + lane]; y1 += reinterpret_cast<const float*>(s_y)[i * 4 + 2 + lane]; }
        const float o0 = bf_lo(xx.x) + rbf(bf_lo(gbf) * rbf(bf_lo(hh) + rbf(rbf(y0) * rs)));
        const float o1 = bf_hi(xx.x) + rbf(bf_hi(gbf) * rbf(bf_hi(hh) + rbf(rbf(y1) * rs)));
        *reinterpret_cast<uint32_t*>(out + (size_t)((0xffffu - gbest) & (SEQ - 1)) * DM + col) = pack_bf16(o0, o1);
      }
      DBGP(14);
    }
    __syncwarp();
    cluster_arrive();
    cluster_wait();
  } else {
    asm volatile("setmaxnreg.inc.sync.aligned.u32 240;");
    Ctx x;
    x.w = wg - 1; x.base = base; x.bars = bars; x.nev = 0; x.sched = &sched;
    const int w = x.w, warp4 = warp & 3;
    x.rel = mapa(bars, (warp4 & 1) ^ 1);
    x.rel1 = (threadIdx.x & 127) == 32 || (threadIdx.x & 127) == 64;
    if (warp != 8 || spare) cluster_wait();
    DBG(1);
    if (spare) {
      mod_cta(x, cvec);
    } else {
      const int lane = wg_tid() & 31;
      Row xn[2];
      float acc0[64], acc1[64];
      const float sc = w == 0 ? 0.08838834764831845f * 1.4426950408889634f : 1.f;
      int s = 2 * w, ph = w;
      #pragma unroll 1
      for (int u = w; u < 8; u += 2) {
        bar_sync(1 + w, 256);
        DBG(4 + (u >> 1) * 3);
        int ps = 0;
        #pragma unroll 1
        for (int kb = 0; kb < 8; kb++) {
          if (u < 2) mbar_wait(bars + B_AF + 8 * kb, 0);
          mbar_wait(bars + B_WF + 8 * s, ph);
          const uint32_t da = desc_lo(base + k_addrA(kb), 16), dw = desc_lo(base + k_addrW(s), 8192);
          wgmma_fence();
          kblock_n128<0>(acc0, da, dw, kb != 0);
          kblock_n128<512>(acc1, da, dw, kb != 0);
          wgmma_commit();
          if (kb == 7) bar_arrive(1 + (w ^ 1), 256);
          if (kb > 0) {
            wgmma_wait<1>();
            mbar_arrive_remote_if(x.rel + B_WE + 8 * ps, x.rel1);
            if (u == 7 && !(kb & 1)) {
              ring_release(x, kb == 2 ? 0 : kb - 3, false);
              if (kb > 2) ring_release(x, kb - 2, false);
            }
          }
          ps = s;
          if (++s == 6) { s = 0; ph ^= 1; }
        }
        Row t[2];
        const int lrow = blockIdx.x * 16 + w * 8 + warp4 * 2;
        if (u == w) { t[0] = ldg_row(xin + (size_t)lrow * DM, lane); t[1] = ldg_row(xin + (size_t)(lrow + 1) * DM, lane); }
        if (u == LN_AT || u == LN_AT + 1) {
          mbar_wait(bars + R_MOD, 0);
          t[0] = ldca_row(g_mod, lane); t[1] = ldca_row(g_mod + DM, lane);
        }
        wgmma_wait<0>();
        fence_regs(acc0); fence_regs(acc1);
        DBG(5 + (u >> 1) * 3);
        mbar_arrive_remote_if(x.rel + B_WE + 8 * ps, x.rel1);
        if (u == 6) { for (int k = 0; k < 5; k++) ring_release(x, k, false); }
        if (u >= 6) ring_release(x, 5, false);
        s += 2; ph ^= 1; if (s >= 6) { s -= 6; ph ^= 1; }
        if (u == w) layer_norm2(t, xn);
        if ((u == LN_AT || u == LN_AT + 1)) {
          #pragma unroll
          for (int r = 0; r < 2; r++) store_row(sched.h1 + (size_t)(lrow + r) * DM, lane, fma_row(xn[r], one_plus(t[1]), t[0]));
        }
        const int h = sp.khead[u >> 1];
        __nv_bfloat16* dst = sched.kvc + ((size_t)(w * 64 + h * 2) * SEQ + mt * 128 + warp4 * 16 + (lane >> 2)) * 64 + (lane & 3) * 8;
        uint32_t D[32];
        pack_tile(acc0, D, sc, sc); store_tile(dst + 64 * 64, D);
        pack_tile(acc1, D, sc, sc); store_tile(dst, D);
        if ((u == LN_AT || u == LN_AT + 1)) publish(x, C_H1 + (blockIdx.x >> 4));
        publish(x, C_KV + h);
        DBG(6 + (u >> 1) * 3);
      }
    }
    attention(x, sp.item, nitems, rank);
    DBG(100);
    const int lane = wg_tid() & 31, cw = w * 4 + warp4, ct = cw * 32 + lane;
    const int row0 = grp * 16 + cw * 2;
    const bool moe_cta = blockIdx.x < FF / 16;
    const unsigned int tag = ld_relaxed(&g_epoch) + 1;
    asm volatile("setmaxnreg.dec.sync.aligned.u32 208;");
    if (spare) { __syncwarp(); cluster_arrive(); cluster_wait(); return; }
    const uint32_t tab = sp.otab;
    const int kl = 3 * nsteps - 3 - odd;
    {
      float accA[64], accB[64];
      uint32_t pa = 0, pb = 0;
      #pragma unroll 1
      for (int k = -odd; k < kl; k += 3) {
        const uint32_t e0 = o_entry(tab, max(k, 0)), ea = o_entry(tab, k + 1), eb = o_entry(tab, k + 2);
        const uint32_t da = desc_lo(base + w * 8192, 16) + (ea & 7) * 2048;
        o_wait_full(bars, e0);
        o_wait_full(bars, ea);
        uint32_t db = desc_lo(base, 8192) + (e0 & 7) * 2048;
        if (k >= 0) {
          wgmma_fence();
          kblock_n128<0>(accA, da, db, k != 0); kblock_n128<0, 1024>(accB, da, db, k != 0);
          wgmma_commit();
        }
        if (k > 0) { wgmma_wait<1>(); slot_release(x, pa, false); slot_release(x, pb, false); }
        o_wait_full(bars, eb);
        db = desc_lo(base, 8192) + (eb & 7) * 2048;
        wgmma_fence();
        kblock_n128<1024>(accA, da, db, k >= 0); kblock_n128<1024, 1024>(accB, da, db, k >= 0);
        wgmma_commit();
        if (k >= 0) { wgmma_wait<1>(); slot_release(x, e0 & 7, false); }
        pa = ea & 7; pb = eb & 7;
      }
      const uint32_t e0 = o_entry(tab, kl), ea = o_entry(tab, kl + 1), eb = o_entry(tab, kl + 2);
      const uint32_t da = desc_lo(base + w * 8192, 16) + (ea & 7) * 2048;
      const uint32_t db0 = desc_lo(base, 8192) + (e0 & 7) * 2048, db1 = desc_lo(base, 8192) + (eb & 7) * 2048;
      o_wait_full(bars, e0);
      o_wait_full(bars, ea);
      o_wait_full(bars, eb);
      wgmma_fence();
      kblock_n128<0>(accA, da, db0, 1); kblock_n128<1024>(accA, da, db1, 1);
      wgmma_commit();
      kblock_n128<0, 1024>(accB, da, db0, 1); kblock_n128<1024, 1024>(accB, da, db1, 1);
      wgmma_commit();
      wgmma_wait<2>();
      slot_release(x, pa, false); slot_release(x, pb, false);
      __syncwarp();
      cluster_arrive();
      const int srow = 16 * warp4 + (lane & 7) + 8 * ((lane >> 3) & 1);
      const uint32_t swz = (((lane >> 4) ^ (srow & 7)) << 4);
      auto stage = [&](const float (&acc)[64], uint32_t off) {
        #pragma unroll
        for (int j = 0; j < 16; j += 2)
          stsm_x4(base + off + srow * 128 + (j >> 3) * 8192 + (((j & 7) << 4) ^ swz),
                  pack_bf16(acc[4*j+0], acc[4*j+1]), pack_bf16(acc[4*j+2], acc[4*j+3]), pack_bf16(acc[4*j+4], acc[4*j+5]), pack_bf16(acc[4*j+6], acc[4*j+7]));
        fence_async_smem();
        publish(x, off);
      };
      mbar_wait(bars + B_RE + 8 * pa, o_entry(tab, kl + 5) >> 3);
      wgmma_wait<1>();
      fence_regs(accA);
      stage(accA, pa * 32768 + w * 16384);
      mbar_wait(bars + B_RE + 8 * pb, o_entry(tab, kl + 6) >> 3);
      wgmma_wait<0>();
      fence_regs(accB);
      DBG(101);
      stage(accB, pb * 32768 + w * 16384);
      DBG(102);
    }
    const Row ga = ldca_row(g_mod + 2 * DM, lane), sb = ldca_row(g_mod + 3 * DM, lane), cb = ldca_row(g_mod + 4 * DM, lane), gb = ldca_row(g_mod + 5 * DM, lane);
    const Row wr = ldca_row(w_r, lane);
    const uint32_t sD = base + (o_entry(tab, kl + 3) & 7) * 32768, sW = base + (o_entry(tab, kl + 4) & 7) * 32768;
    o_wait_full(bars, o_entry(tab, kl + 3)); o_wait_full(bars, o_entry(tab, kl + 4));
    Row x1[2];
    #pragma unroll
    for (int r = 0; r < 2; r++) x1[r] = lds_row(sD + 16384 + (cw * 2 + r) * 1024, lane);
    uint4 wgv[4], wuv[4], wdv[4];
    #pragma unroll
    for (int r = 0; r < 4; r++) {
      const uint32_t k = (lane & 7) + ((lane >> 4) << 3), h = (lane & 8) * 2;
      wgv[r] = ldsm_x4_t(sW + (cw * 64 + r * 16 + k) * 32 + h);
      wuv[r] = ldsm_x4_t(sW + 16384 + (cw * 64 + r * 16 + k) * 32 + h);
      wdv[r] = ldsm_x4_t(sD + k * 1024 + (cw * 64 + r * 16) * 2 + h);
    }
    const Row cb1 = one_plus(cb);
    DBG(103);
    mbar_wait(bars + R_PART, 0);
    DBG(104);
    Row h2[2];
    uint32_t key[2];
    {
      uint4 pv[2][4][2];
      const uint32_t po = base + (lane >> 3) * 2048 + cw * 256 + (lane & 7) * 16;
      const uint32_t pa[2] = {po + (o_entry(tab, kl) & 7) * 32768, po + (o_entry(tab, kl + 1) & 7) * 32768};
      #pragma unroll
      for (int r = 0; r < 2; r++)
        #pragma unroll
        for (int q = 0; q < 8; q++) pv[r][q >> 1][q & 1] = lds_v4(pa[q >> 2] + (q & 3) * 8192 + r * 128);
      #pragma unroll
      for (int r = 0; r < 2; r++) {
        Row av;
        #pragma unroll
        for (int i = 0; i < 2; i++) {
          av.v[4*i]   = add2(add2(pv[r][0][i].x, pv[r][1][i].x), add2(pv[r][2][i].x, pv[r][3][i].x));
          av.v[4*i+1] = add2(add2(pv[r][0][i].y, pv[r][1][i].y), add2(pv[r][2][i].y, pv[r][3][i].y));
          av.v[4*i+2] = add2(add2(pv[r][0][i].z, pv[r][1][i].z), add2(pv[r][2][i].z, pv[r][3][i].z));
          av.v[4*i+3] = add2(add2(pv[r][0][i].w, pv[r][1][i].w), add2(pv[r][2][i].w, pv[r][3][i].w));
        }
        x1[r] = fma_row(ga, av, x1[r]);
      }
      layer_norm2(x1, h2);
      float sc[2] = {0.f, 0.f};
      #pragma unroll
      for (int r = 0; r < 2; r++) {
        h2[r] = fma_row(h2[r], cb1, sb);
        #pragma unroll
        for (int i = 0; i < 8; i++) sc[r] = fmaf(bf_hi(h2[r].v[i]), bf_hi(wr.v[i]), fmaf(bf_lo(h2[r].v[i]), bf_lo(wr.v[i]), sc[r]));
      }
      #pragma unroll
      for (int o = 16; o > 0; o >>= 1) { sc[0] += __shfl_xor_sync(0xffffffff, sc[0], o); sc[1] += __shfl_xor_sync(0xffffffff, sc[1], o); }
      #pragma unroll
      for (int r = 0; r < 2; r++) {
        const uint32_t rb = pack_bf16(0.f, sc[r]);
        key[r] = (((rb & 0x80000000u) ? ~rb : (rb | 0x80000000u)) & 0xffff0000u) | (0xffffu - (uint32_t)(row0 + r));
      }
    }
    DBG(105);
    float* s_red = reinterpret_cast<float*>(smem_raw + SM_RED);
    uint32_t* s_key = reinterpret_cast<uint32_t*>(smem_raw + SM_KEY);
    const int rb = key[1] > key[0];
    const uint32_t wbest = rb ? key[1] : key[0];
    if (lane == 0) s_key[cw] = wbest;
    bar_sync(5, 256);
    const uint32_t cbest = __reduce_max_sync(0xffffffff, s_key[lane & 7]);
    Row ob, hb, xb;
    #pragma unroll
    for (int i = 0; i < 8; i++) { hb.v[i] = rb ? h2[1].v[i] : h2[0].v[i]; xb.v[i] = rb ? x1[1].v[i] : x1[0].v[i]; }
    if (wbest == cbest) {
      if (lane == 0) st_tagged(&g_keys[grp][0], cbest, tag);
      #pragma unroll
      for (int i = 0; i < 4; i++) st_tagged2(&g_row[grp][0][(i >> 1) * 128 + lane * 4 + (i & 1) * 2], hb.v[2*i], hb.v[2*i+1], tag);
      #pragma unroll
      for (int i = 0; i < 4; i++) st_tagged2(&g_row[grp][1][(i >> 1) * 128 + lane * 4 + (i & 1) * 2], xb.v[2*i], xb.v[2*i+1], tag);
    }
    DBG(106);
    #pragma unroll
    for (int i = 0; i < 8; i++) { ob.v[i] = fma2(gb.v[i], rb ? h2[0].v[i] : h2[1].v[i], rb ? x1[0].v[i] : x1[1].v[i]); }
    store_row(out + (size_t)(row0 + 1 - rb) * DM, lane, ob);
    ob = fma_row(gb, hb, xb);
    if (wbest != cbest) store_row(out + (size_t)(row0 + rb) * DM, lane, ob);
    mbar_wait(bars + R_KEY, 1);
    DBG(107);
    if (moe_cta) {
      float cg[4] = {0, 0, 0, 0}, cu[4] = {0, 0, 0, 0};
      #pragma unroll
      for (int r = 0; r < 4; r++) {
        const uint32_t b0 = lds_u32(base + SM_H2 + (cw * 64 + r * 16) * 2 + (lane & 3) * 4), b1 = lds_u32(base + SM_H2 + (cw * 64 + r * 16) * 2 + 16 + (lane & 3) * 4);
        mma16816(cg, wgv[r], b0, b1); mma16816(cu, wuv[r], b0, b1);
      }
      s_red[cw * 32 + (lane & 3) * 8 + (lane >> 2)] = (lane & 2) ? ((lane & 1) ? cu[2] : cu[0]) : ((lane & 1) ? cg[2] : cg[0]);
      bar_sync(5, 256);
      float g = 0.f;
      #pragma unroll
      for (int i = 0; i < 8; i++) g += s_red[i * 32 + lane];
      g = rbf(g);
      const float u = __shfl_down_sync(0xffffffff, g, 16);
      const float act = rbf(__fdividef(g, 1.f + __expf(-g))) * u;
      const uint32_t a2 = pack_bf16(act, __shfl_down_sync(0xffffffff, act, 1));
      const uint32_t b0 = __shfl_sync(0xffffffff, a2, (lane & 3) * 2), b1 = __shfl_sync(0xffffffff, a2, (lane & 3) * 2 + 8);
      float y0 = 0.f, y1 = 0.f;
      #pragma unroll
      for (int r = 0; r < 4; r++) {
        float c[4] = {0, 0, 0, 0};
        mma16816(c, wdv[r], b0, b1);
        if ((lane & 3) == r) { y0 = c[0]; y1 = c[2]; }
      }
      st_tagged2(&g_yll[blockIdx.x][cw * 64 + (lane & 3) * 16 + (lane >> 2) * 2], __float_as_uint(y0), __float_as_uint(y1), tag);
    }
    DBG(108);
    if (wbest == cbest && wbest != s_key[8]) store_row(out + (size_t)(row0 + rb) * DM, lane, ob);
    DBG(109);
    __syncwarp();
    cluster_wait();
  }
}

typedef CUresult (*EncodeFn)(CUtensorMap*, CUtensorMapDataType, cuuint32_t, void*, const cuuint64_t*, const cuuint64_t*, const cuuint32_t*,
                             const cuuint32_t*, CUtensorMapInterleave, CUtensorMapSwizzle, CUtensorMapL2promotion, CUtensorMapFloatOOBfill);

struct HostState {
  bool ready = false;
  EncodeFn encode = nullptr;
  CUtensorMap tmC, tmH, tmWq, tmWk, tmWv, tmKV, tmWo, tmPart, tmWg, tmWu, tmPl, tmWm;
  Sched sched;
};

void make_map(EncodeFn enc, CUtensorMap* m, const void* ptr, int rank, const cuuint64_t* dims, const cuuint64_t* strides, const cuuint32_t* box, bool swizzle = true) {
  const cuuint32_t es[3] = {1, 1, 1};
  enc(m, CU_TENSOR_MAP_DATA_TYPE_BFLOAT16, rank, const_cast<void*>(ptr), dims, strides, box, es, CU_TENSOR_MAP_INTERLEAVE_NONE,
      swizzle ? CU_TENSOR_MAP_SWIZZLE_128B : CU_TENSOR_MAP_SWIZZLE_NONE, swizzle ? CU_TENSOR_MAP_L2_PROMOTION_L2_128B : CU_TENSOR_MAP_L2_PROMOTION_NONE, CU_TENSOR_MAP_FLOAT_OOB_FILL_NONE);
}
void make_2d(EncodeFn enc, CUtensorMap* m, const void* ptr, int rows, int cols, int box_rows) {
  const cuuint64_t dims[2] = {(cuuint64_t)cols, (cuuint64_t)rows}, strides[1] = {(cuuint64_t)cols * 2};
  const cuuint32_t box[2] = {64, (cuuint32_t)box_rows};
  make_map(enc, m, ptr, 2, dims, strides, box);
}
void make_3d(EncodeFn enc, CUtensorMap* m, const void* ptr, int rows, int chunks, size_t row_stride, size_t chunk_stride) {
  const cuuint64_t dims[3] = {64, (cuuint64_t)rows, (cuuint64_t)chunks}, strides[2] = {row_stride, chunk_stride};
  const cuuint32_t box[3] = {64, 64, 2};
  make_map(enc, m, ptr, 3, dims, strides, box);
}

void make_ffn(EncodeFn enc, CUtensorMap* m, const void* ptr) {
  const cuuint64_t dims[2] = {(cuuint64_t)FF, (cuuint64_t)DM}, strides[1] = {(cuuint64_t)FF * 2};
  const cuuint32_t box[2] = {16, 256};
  make_map(enc, m, ptr, 2, dims, strides, box, false);
}

#define J0_FIRST 0
#define SR 0x213312
#define SEED 12345
#define SPARE_N 3
void build_sched(Sched& s) {
  memset(&s, 0, sizeof(s));
  const int NP = NCTA / 2, korder[4] = {(KORDER >> 12) & 3, (KORDER >> 8) & 3, (KORDER >> 4) & 3, KORDER & 3};
  const int sround[4][2][3] = {{}, {{1}, {2}}, {{1, 2}, {1, 2}}, {{(SR >> 20) & 3, (SR >> 16) & 3, (SR >> 12) & 3}, {(SR >> 8) & 3, (SR >> 4) & 3, SR & 3}}};
  int jv[4][NP], used[4][8] = {};
  for (int r = 0; r < 4; r++) for (int p = 0; p < NP; p++) jv[r][p] = (r & 2) ? 7 - ((p + 4 * (r & 1)) & 7) : (p + 4 * (r & 1)) & 7;
  for (int q = 0; q < 2; q++) {
    s.pair[NP + q].nitems = SPARE_N;
    for (int i = 0; i < SPARE_N; i++) {
      const int r = sround[SPARE_N][q][i];
      s.pair[NP + q].item[i] = (uint8_t)((r * 8 + used[r][6]++) * 8 + 6);
      for (int p = 0; p < NP; p++) if (jv[r][p] == 6) { jv[r][p] = -2; break; }
    }
  }
  auto cost = [&](int p) {
    int u = 8 - ((p >> 4) < SPARE_N ? 21 : 22), z = 0, none = 0;
    for (int r = 0; r < 4; r++) { u += jv[r][p]; z += jv[r][p] == 0; none += jv[r][p] < 0; }
    return 4 * u * u + (z > 1) + 4 * (none > 1);
  };
  uint32_t rng = SEED;
  for (int it = 0; it < 2000000; it++) {
    if ((it & 255) == 0) { int t = 0; for (int p = 0; p < NP; p++) t += cost(p); if (t == 0) break; }
    rng = rng * 1664525u + 1013904223u;
    const int r = (rng >> 8) & 3, a = (rng >> 12) & 63, b = (rng >> 20) & 63, before = cost(a) + cost(b);
    int t = jv[r][a]; jv[r][a] = jv[r][b]; jv[r][b] = t;
    if (cost(a) + cost(b) > before) { jv[r][b] = jv[r][a]; jv[r][a] = t; }
  }
  int done[256];
  for (int p = 0; p < NP + 2; p++) {
    Sched::Pair& q = s.pair[p];
    if (p < NP) {
      for (int k = 0; k < 4; k++) q.khead[k] = (uint8_t)(korder[k] * 8 + (p >> 3));
      for (int r = 0; r < 4; r++) {
        if (jv[r][p] < 0) continue;
        int at = q.nitems++;
        if (J0_FIRST && jv[r][p] == 0 && r != korder[3]) for (; at > 0; at--) q.item[at] = q.item[at - 1];
        q.item[at] = (uint8_t)((r * 8 + used[r][jv[r][p]]++) * 8 + jv[r][p]);
      }
    }
    int t = p < NP ? 0 : -3, e = 1;
    for (int i = 0; i < q.nitems; i++) { t += (q.item[i] & 7) + 2; done[q.item[i]] = t + (i + 1 < q.nitems ? 2 : 0); e += 8 + 4 * ((q.item[i] & 7) + 1); }
    q.otab = 6u << 16;
    for (int k = 0; k < 6; k++) { const int f = (e + k) % 12; q.otab |= (uint32_t)(f >= 6 ? f + 2 : f) << (4 * (k < 4 ? k : k + 1)); }
  }
  for (int j = 0; j < 8; j++) {
    int order[NH], left[4];
    for (int h = 0; h < NH; h++) { int k = h; for (; k > 0 && done[order[k - 1] * 8 + j] < done[h * 8 + j]; k--) order[k] = order[k - 1]; order[k] = h; }
    for (int kq = 0; kq < 4; kq++) {
      left[kq] = SPARE_N == 0 ? 16 : kq < SPARE_N ? 20 - SPARE_N : 16 - SPARE_N;
      for (int nh = 0; nh < 2; nh++) { Sched::Pair& q = s.pair[kq * 16 + nh * 8 + j]; q.otask = (uint8_t)(kq * 16 + nh * 8 + j); q.nsteps = (uint8_t)((left[kq] + 1) / 2); q.ochunk[0][0] = 255; }
    }
    for (int n = 0, kq = 0, run = 0; n < 64; ) {
      if (left[kq] > 0 && run < 2) {
        const int pos = --left[kq] + (SPARE_N & 1);
        for (int nh = 0; nh < 2; nh++) s.pair[kq * 16 + nh * 8 + j].ochunk[pos >> 1][pos & 1] = (uint8_t)(order[n >> 1] * 2 + 1 - (n & 1));
        n++; run++;
      } else { kq = (kq + 1) & 3; run = 0; }
    }
  }
}

}

extern "C" void kernel_launch(void* const* d_in, const int* in_sizes, int n_in, void* d_out, int out_size) {
  (void)in_sizes; (void)n_in; (void)out_size;
  const __nv_bfloat16* x     = (const __nv_bfloat16*)d_in[0];
  const __nv_bfloat16* ckv   = (const __nv_bfloat16*)d_in[1];
  const __nv_bfloat16* w_q   = (const __nv_bfloat16*)d_in[2];
  const __nv_bfloat16* w_uk  = (const __nv_bfloat16*)d_in[3];
  const __nv_bfloat16* w_uv  = (const __nv_bfloat16*)d_in[4];
  const __nv_bfloat16* w_o   = (const __nv_bfloat16*)d_in[5];
  const __nv_bfloat16* w_r   = (const __nv_bfloat16*)d_in[7];
  const __nv_bfloat16* w_g   = (const __nv_bfloat16*)d_in[8];
  const __nv_bfloat16* w_u   = (const __nv_bfloat16*)d_in[9];
  const __nv_bfloat16* w_d   = (const __nv_bfloat16*)d_in[10];
  const __nv_bfloat16* cvec  = (const __nv_bfloat16*)d_in[11];
  const __nv_bfloat16* w_mod = (const __nv_bfloat16*)d_in[12];
  __nv_bfloat16* out = (__nv_bfloat16*)d_out;

  static HostState st;
  if (!st.ready) {
    void* fn = nullptr; cudaDriverEntryPointQueryResult qr;
    cudaGetDriverEntryPoint("cuTensorMapEncodeTiled", &fn, cudaEnableDefault, &qr);
    st.encode = (EncodeFn)fn;
    cudaFuncSetAttribute(k_fused, cudaFuncAttributeMaxDynamicSharedMemorySize, SMEM);
    build_sched(st.sched);
    void *p_kvc, *p_h1, *p_part;
    cudaGetSymbolAddress(&p_kvc, g_kvc); cudaGetSymbolAddress(&p_h1, g_h1); cudaGetSymbolAddress(&p_part, g_part);
    st.sched.kvc = (__nv_bfloat16*)p_kvc; st.sched.h1 = (__nv_bfloat16*)p_h1;
    make_2d(st.encode, &st.tmH, p_h1, SEQ, DM, 64);
    make_2d(st.encode, &st.tmKV, p_kvc, 192 * SEQ, 64, 128);
    make_3d(st.encode, &st.tmPart, p_part, SEQ, 32, 128, (size_t)SEQ * 128);
    { const cuuint64_t dims[3] = {64, (cuuint64_t)SEQ, 32}, strides[2] = {128, (cuuint64_t)SEQ * 128}; const cuuint32_t box[3] = {64, 16, 4};
      make_map(st.encode, &st.tmPl, p_part, 3, dims, strides, box, false); }
    st.ready = true;
  }
  make_2d(st.encode, &st.tmC, ckv, SEQ, DM, 128);
  make_2d(st.encode, &st.tmWq, w_q, DM, NH * DH, 64);
  make_2d(st.encode, &st.tmWk, w_uk, DM, NH * DH, 64);
  make_2d(st.encode, &st.tmWv, w_uv, DM, NH * DH, 64);
  make_3d(st.encode, &st.tmWo, w_o, NH * DH, DM / 64, (size_t)DM * 2, 128);
  make_3d(st.encode, &st.tmWm, w_mod, DM, 6 * DM / 64, (size_t)6 * DM * 2, 128);
  make_ffn(st.encode, &st.tmWg, w_g);
  make_ffn(st.encode, &st.tmWu, w_u);

  k_fused<<<NGRID, 384, SMEM, cudaStreamPerThread>>>(st.tmC, st.tmH, st.tmWq, st.tmWk, st.tmWv, st.tmKV, st.tmWo, st.tmPart, st.tmWg, st.tmWu, st.tmPl, st.tmWm, st.sched,
                                                     x, cvec, w_o, w_r, w_g, w_u, w_d, out);
}
```

```cpp
#include <cuda_runtime.h>
#include <cuda_bf16.h>
#include <cuda.h>
#include <stdint.h>
#include <string.h>
#include <math.h>

namespace {

constexpr int SEQ = 2048, DM = 512, NH = 32, DH = 128, FF = 1792;
constexpr int NCTA = 128, NGRID = 132;

__device__ __nv_bfloat16 g_kvc[192 * SEQ * 64];
__device__ __nv_bfloat16 g_h1[SEQ * DM];
__device__ __nv_bfloat16 g_part[32 * SEQ * 64];
__device__ __align__(16) __nv_bfloat16 g_mod[6 * DM];
constexpr int C_MOD = 0, C_MOD2 = 16, C_H1 = 32, C_KV = 64, C_CTX = 128, C_END = 384;
__device__ unsigned int g_cnt[C_END];
__device__ unsigned int g_epoch;
__device__ __align__(128) unsigned int g_pflag[32][32];
__device__ __align__(128) uint2 g_keys[128][4];
__device__ __align__(16) uint2 g_row[128][2][DM / 2];
__device__ __align__(16) uint2 g_yll[FF / 16][DM];

#define DBG(i)
#define DBGP(i)

__device__ __forceinline__ uint32_t smem_u32(const void* p) { return (uint32_t)__cvta_generic_to_shared(p); }
__device__ __forceinline__ int wg_tid() { int t; asm volatile("mov.u32 %0, %%tid.x;" : "=r"(t)); return t & 127; }
__device__ __forceinline__ uint32_t clk32() { uint32_t c; asm volatile("mov.u32 %0, %%clock;" : "=r"(c)); return c; }
__device__ __forceinline__ void mbar_arrive(uint32_t bar) { asm volatile("mbarrier.arrive.shared::cta.b64 _, [%0];" :: "r"(bar) : "memory"); }
__device__ __forceinline__ uint32_t mapa(uint32_t addr, uint32_t cta) { uint32_t r; asm("mapa.shared::cluster.u32 %0, %1, %2;" : "=r"(r) : "r"(addr), "r"(cta)); return r; }
__device__ __forceinline__ void mbar_arrive_remote_if(uint32_t cluster_addr, bool pred) {
  asm volatile("{\n.reg .pred p;\nsetp.ne.u32 p, %1, 0;\n@p mbarrier.arrive.shared::cluster.b64 _, [%0];\n}" :: "r"(cluster_addr), "r"((uint32_t)pred) : "memory");
}
__device__ __forceinline__ bool mbar_try(uint32_t bar, uint32_t parity) {
  uint32_t done;
  asm volatile("{\n.reg .pred p;\nmbarrier.try_wait.parity.shared::cta.b64 p, [%1], %2;\nselp.u32 %0, 1, 0, p;\n}" : "=r"(done) : "r"(bar), "r"(parity) : "memory");
  return done;
}
#define WAIT_LIM (1 << 14)
__device__ __forceinline__ void mbar_wait(uint32_t bar, uint32_t parity) {
  #pragma unroll 1
  for (int n = 0; n < WAIT_LIM; n++) { if (mbar_try(bar, parity)) break; }
}
__device__ __forceinline__ unsigned int ld_acquire(const unsigned int* p) {
  unsigned int v; asm volatile("ld.acquire.gpu.global.u32 %0, [%1];" : "=r"(v) : "l"(p) : "memory"); return v;
}
__device__ __forceinline__ unsigned int ld_relaxed(const unsigned int* p) {
  unsigned int v; asm volatile("ld.relaxed.gpu.global.u32 %0, [%1];" : "=r"(v) : "l"(p) : "memory"); return v;
}
__device__ __forceinline__ void wait_count_lazy(int idx, unsigned int target) {
  #pragma unroll 1
  for (int n = 0; n < WAIT_LIM; n++) { if ((int)(ld_relaxed(&g_cnt[idx]) - target) >= 0) break; __nanosleep(100); }
  ld_acquire(&g_cnt[idx]);
}
__device__ __forceinline__ uint4 ld_tagged2(const void* p) {
  uint4 v;
  asm volatile("{\n.reg .b64 a, b;\nld.relaxed.gpu.global.v2.u64 {a, b}, [%4];\nmov.b64 {%0, %1}, a;\nmov.b64 {%2, %3}, b;\n}"
    : "=r"(v.x), "=r"(v.y), "=r"(v.z), "=r"(v.w) : "l"(p) : "memory");
  return v;
}
__device__ __forceinline__ uint2 ld_tagged(const void* p) {
  uint2 v; asm volatile("{\n.reg .b64 a;\nld.relaxed.gpu.global.u64 a, [%2];\nmov.b64 {%0, %1}, a;\n}" : "=r"(v.x), "=r"(v.y) : "l"(p) : "memory"); return v;
}
__device__ __forceinline__ void st_tagged2(void* p, uint32_t a, uint32_t b, uint32_t tag) {
  asm volatile("{\n.reg .b64 a, b;\nmov.b64 a, {%1, %3};\nmov.b64 b, {%2, %3};\nst.relaxed.gpu.global.v2.u64 [%0], {a, b};\n}" :: "l"(p), "r"(a), "r"(b), "r"(tag) : "memory");
}
__device__ __forceinline__ void st_tagged(void* p, uint32_t a, uint32_t tag) {
  asm volatile("{\n.reg .b64 a;\nmov.b64 a, {%1, %2};\nst.relaxed.gpu.global.u64 [%0], a;\n}" :: "l"(p), "r"(a), "r"(tag) : "memory");
}
__device__ __forceinline__ void stg_v4(void* p, uint32_t a, uint32_t b, uint32_t c, uint32_t d) {
  asm volatile("st.global.v4.u32 [%0], {%1, %2, %3, %4};" :: "l"(p), "r"(a), "r"(b), "r"(c), "r"(d) : "memory");
}
__device__ __forceinline__ uint4 lds_v4(uint32_t addr) {
  uint4 v; asm volatile("ld.shared.v4.u32 {%0, %1, %2, %3}, [%4];" : "=r"(v.x), "=r"(v.y), "=r"(v.z), "=r"(v.w) : "r"(addr) : "memory"); return v;
}
__device__ __forceinline__ uint32_t lds_u32(uint32_t addr) { uint32_t v; asm volatile("ld.shared.u32 %0, [%1];" : "=r"(v) : "r"(addr) : "memory"); return v; }
__device__ __forceinline__ void sts_v4(uint32_t addr, uint32_t a, uint32_t b, uint32_t c, uint32_t d) {
  asm volatile("st.shared.v4.u32 [%0], {%1, %2, %3, %4};" :: "r"(addr), "r"(a), "r"(b), "r"(c), "r"(d) : "memory");
}
#define ELECT "{\n.reg .pred p;\nelect.sync _|p, 0xffffffff;\n@p "
__device__ __forceinline__ void w_mbar_init(uint32_t bar, uint32_t cnt) { asm volatile(ELECT "mbarrier.init.shared::cta.b64 [%0], %1;\n}" :: "r"(bar), "r"(cnt) : "memory"); }
__device__ __forceinline__ void w_expect_tx(uint32_t bar, uint32_t bytes) { asm volatile(ELECT "mbarrier.arrive.expect_tx.shared::cta.b64 _, [%0], %1;\n}" :: "r"(bar), "r"(bytes) : "memory"); }
__device__ __forceinline__ void w_arrive(uint32_t bar) { asm volatile(ELECT "mbarrier.arrive.shared::cta.b64 _, [%0];\n}" :: "r"(bar) : "memory"); }
__device__ __forceinline__ void tma_load_2d(uint32_t dst, const CUtensorMap* tm, uint32_t bar, int c0, int c1) {
  asm volatile(ELECT "cp.async.bulk.tensor.2d.shared::cluster.global.mbarrier::complete_tx::bytes [%0], [%1, {%3, %4}], [%2];\n}"
    :: "r"(dst), "l"(tm), "r"(bar), "r"(c0), "r"(c1) : "memory");
}
__device__ __forceinline__ void tma_load_2d_mc(uint32_t dst, const CUtensorMap* tm, uint32_t bar, int c0, int c1) {
  asm volatile(ELECT "cp.async.bulk.tensor.2d.shared::cluster.global.mbarrier::complete_tx::bytes.multicast::cluster [%0], [%1, {%3, %4}], [%2], %5;\n}"
    :: "r"(dst), "l"(tm), "r"(bar), "r"(c0), "r"(c1), "h"((uint16_t)3) : "memory");
}
__device__ __forceinline__ void tma_load_3d(uint32_t dst, const CUtensorMap* tm, uint32_t bar, int c0, int c1, int c2) {
  asm volatile(ELECT "cp.async.bulk.tensor.3d.shared::cluster.global.mbarrier::complete_tx::bytes [%0], [%1, {%3, %4, %5}], [%2];\n}"
    :: "r"(dst), "l"(tm), "r"(bar), "r"(c0), "r"(c1), "r"(c2) : "memory");
}
__device__ __forceinline__ void tma_load_3d_mc(uint32_t dst, const CUtensorMap* tm, uint32_t bar, int c0, int c1, int c2) {
  asm volatile(ELECT "cp.async.bulk.tensor.3d.shared::cluster.global.mbarrier::complete_tx::bytes.multicast::cluster [%0], [%1, {%3, %4, %5}], [%2], %6;\n}"
    :: "r"(dst), "l"(tm), "r"(bar), "r"(c0), "r"(c1), "r"(c2), "h"((uint16_t)3) : "memory");
}
__device__ __forceinline__ uint64_t evict_first() { uint64_t a; asm("createpolicy.fractional.L2::evict_first.b64 %0, 1.0;" : "=l"(a)); return a; }
__device__ __forceinline__ void tma_load_2d_mc(uint32_t dst, const CUtensorMap* tm, uint32_t bar, int c0, int c1, bool ef) {
  if (!ef) tma_load_2d_mc(dst, tm, bar, c0, c1); else
  asm volatile(ELECT "cp.async.bulk.tensor.2d.shared::cluster.global.mbarrier::complete_tx::bytes.multicast::cluster.L2::cache_hint [%0], [%1, {%3, %4}], [%2], %5, %6;\n}"
    :: "r"(dst), "l"(tm), "r"(bar), "r"(c0), "r"(c1), "h"((uint16_t)3), "l"(evict_first()) : "memory");
}
__device__ __forceinline__ void bulk_load(uint32_t dst, const void* src, uint32_t bytes, uint32_t bar) {
  asm volatile(ELECT "cp.async.bulk.shared::cluster.global.mbarrier::complete_tx::bytes [%0], [%1], %2, [%3];\n}" :: "r"(dst), "l"(src), "r"(bytes), "r"(bar) : "memory");
}
__device__ __forceinline__ void tma_prefetch_2d(const CUtensorMap* tm, int c0, int c1) {
  asm volatile(ELECT "cp.async.bulk.prefetch.tensor.2d.L2.global [%0, {%1, %2}];\n}" :: "l"(tm), "r"(c0), "r"(c1) : "memory");
}
__device__ __forceinline__ void bulk_prefetch(const void* p, uint32_t bytes) {
  asm volatile(ELECT "cp.async.bulk.prefetch.L2.global [%0], %1;\n}" :: "l"(p), "r"(bytes) : "memory");
}
__device__ __forceinline__ void tma_store_3d(const CUtensorMap* tm, uint32_t src, int c0, int c1, int c2) {
  asm volatile("cp.async.bulk.tensor.3d.global.shared::cta.bulk_group [%0, {%2, %3, %4}], [%1];"
    :: "l"(tm), "r"(src), "r"(c0), "r"(c1), "r"(c2) : "memory");
}
__device__ __forceinline__ void st_release(unsigned int* p, unsigned int v) { asm volatile("st.release.gpu.global.u32 [%0], %1;" :: "l"(p), "r"(v) : "memory"); }
__device__ __forceinline__ void red_release(int idx) { asm volatile("red.release.gpu.global.add.u32 [%0], 1;" :: "l"(&g_cnt[idx]) : "memory"); }
__device__ __forceinline__ void prefetch_tmap(const CUtensorMap* tm) { asm volatile("prefetch.tensormap [%0];" :: "l"(tm) : "memory"); }
__device__ __forceinline__ void bulk_commit() { asm volatile("cp.async.bulk.commit_group;" ::: "memory"); }
template<int N> __device__ __forceinline__ void bulk_wait() { asm volatile("cp.async.bulk.wait_group %0;" :: "n"(N) : "memory"); }
__device__ __forceinline__ void bar_sync(int id, int n) { asm volatile("bar.sync %0, %1;" :: "r"(id), "r"(n) : "memory"); }
__device__ __forceinline__ void bar_arrive(int id, int n) { asm volatile("bar.arrive %0, %1;" :: "r"(id), "r"(n) : "memory"); }
__device__ __forceinline__ void fence_async_smem() { asm volatile("fence.proxy.async.shared::cta;" ::: "memory"); }
__device__ __forceinline__ void fence_async_global() { asm volatile("fence.proxy.async.global;" ::: "memory"); }
__device__ __forceinline__ void fence_mbar_init() { asm volatile("fence.mbarrier_init.release.cluster;" ::: "memory"); }
__device__ __forceinline__ void cluster_arrive() { asm volatile("barrier.cluster.arrive.relaxed.aligned;" ::: "memory"); }
__device__ __forceinline__ void cluster_wait() { asm volatile("barrier.cluster.wait.aligned;" ::: "memory"); }
__device__ __forceinline__ uint32_t cluster_ctarank() { uint32_t r; asm volatile("mov.u32 %0, %%cluster_ctarank;" : "=r"(r)); return r; }
__device__ __forceinline__ void wgmma_fence() { asm volatile("wgmma.fence.sync.aligned;" ::: "memory"); }
__device__ __forceinline__ void wgmma_commit() { asm volatile("wgmma.commit_group.sync.aligned;" ::: "memory"); }
template<int N> __device__ __forceinline__ void wgmma_wait() { asm volatile("wgmma.wait_group.sync.aligned %0;" :: "n"(N) : "memory"); }
__device__ __forceinline__ float ex2(float x) { float y; asm("ex2.approx.ftz.f32 %0, %1;" : "=f"(y) : "f"(x)); return y; }
__device__ __forceinline__ float rcp_fast(float x) { float y; asm("rcp.approx.ftz.f32 %0, %1;" : "=f"(y) : "f"(x)); return y; }
__device__ __forceinline__ uint32_t pack_bf16(float lo, float hi) { uint32_t r; asm("cvt.rn.bf16x2.f32 %0, %1, %2;" : "=r"(r) : "f"(hi), "f"(lo)); return r; }
__device__ __forceinline__ float rbf(float x) { return __uint_as_float(pack_bf16(0.f, x)); }
__device__ __forceinline__ float bf_lo(uint32_t v) { return __uint_as_float(v << 16); }
__device__ __forceinline__ float bf_hi(uint32_t v) { return __uint_as_float(v & 0xffff0000u); }
__device__ __forceinline__ uint32_t add2(uint32_t a, uint32_t b) { uint32_t r; asm("add.rn.bf16x2 %0, %1, %2;" : "=r"(r) : "r"(a), "r"(b)); return r; }
__device__ __forceinline__ uint32_t fma2(uint32_t a, uint32_t b, uint32_t c) { uint32_t r; asm("fma.rn.bf16x2 %0, %1, %2, %3;" : "=r"(r) : "r"(a), "r"(b), "r"(c)); return r; }
__device__ __forceinline__ uint4 ldsm_x4_t(uint32_t addr) {
  uint4 v; asm volatile("ldmatrix.sync.aligned.m8n8.x4.trans.shared.b16 {%0, %1, %2, %3}, [%4];" : "=r"(v.x), "=r"(v.y), "=r"(v.z), "=r"(v.w) : "r"(addr) : "memory"); return v;
}
__device__ __forceinline__ void mma16816(float (&c)[4], const uint4& a, uint32_t b0, uint32_t b1) {
  asm("mma.sync.aligned.m16n8k16.row.col.f32.bf16.bf16.f32 {%0, %1, %2, %3}, {%4, %5, %6, %7}, {%8, %9}, {%0, %1, %2, %3};"
    : "+f"(c[0]), "+f"(c[1]), "+f"(c[2]), "+f"(c[3]) : "r"(a.x), "r"(a.y), "r"(a.z), "r"(a.w), "r"(b0), "r"(b1));
}
__device__ __forceinline__ void stsm_x4(uint32_t addr, uint32_t r0, uint32_t r1, uint32_t r2, uint32_t r3) {
  asm volatile("stmatrix.sync.aligned.m8n8.x4.shared.b16 [%0], {%1, %2, %3, %4};" :: "r"(addr), "r"(r0), "r"(r1), "r"(r2), "r"(r3) : "memory");
}
template<int N> __device__ __forceinline__ void fence_regs(float (&a)[N]) {
  #pragma unroll
  for (int i = 0; i < N; i++) asm volatile("" : "+f"(a[i]) :: "memory");
}
template<int N> __device__ __forceinline__ void fence_regs_u(uint32_t (&a)[N]) {
  #pragma unroll
  for (int i = 0; i < N; i++) asm volatile("" : "+r"(a[i]) :: "memory");
}
__device__ __forceinline__ uint32_t desc_lo(uint32_t addr, uint32_t lbo) { return ((addr & 0x3FFFF) >> 4) | ((lbo >> 4) << 16); }

template<int TB, int OA, int OB> __device__ __forceinline__ void wgmma_ss_n128(float (&d)[64], uint32_t da, uint32_t db, int sd) {
  asm volatile("{\n.reg .pred p;\n.reg .b32 ta, tb;\n.reg .b64 da, db;\nsetp.ne.b32 p, %66, 0;\nadd.u32 ta, %64, %68;\nadd.u32 tb, %65, %69;\nmov.b64 da, {ta, 0x40000040};\nmov.b64 db, {tb, 0x40000040};\n"
    "wgmma.mma_async.sync.aligned.m64n128k16.f32.bf16.bf16 "
    "{%0, %1, %2, %3, %4, %5, %6, %7, %8, %9, %10, %11, %12, %13, %14, %15, %16, %17, %18, %19, %20, %21, %22, %23, %24, %25, %26, %27, %28, %29, %30, %31, %32, %33, %34, %35, %36, %37, %38, %39, %40, %41, %42, %43, %44, %45, %46, %47, %48, %49, %50, %51, %52, %53, %54, %55, %56, %57, %58, %59, %60, %61, %62, %63}, da, db, p, 1, 1, 0, %67;\n}\n"
    : "+f"(d[0]), "+f"(d[1]), "+f"(d[2]), "+f"(d[3]), "+f"(d[4]), "+f"(d[5]), "+f"(d[6]), "+f"(d[7]), "+f"(d[8]), "+f"(d[9]), "+f"(d[10]), "+f"(d[11]), "+f"(d[12]), "+f"(d[13]), "+f"(d[14]), "+f"(d[15]), "+f"(d[16]), "+f"(d[17]), "+f"(d[18]), "+f"(d[19]), "+f"(d[20]), "+f"(d[21]), "+f"(d[22]), "+f"(d[23]), "+f"(d[24]), "+f"(d[25]), "+f"(d[26]), "+f"(d[27]), "+f"(d[28]), "+f"(d[29]), "+f"(d[30]), "+f"(d[31]), "+f"(d[32]), "+f"(d[33]), "+f"(d[34]), "+f"(d[35]), "+f"(d[36]), "+f"(d[37]), "+f"(d[38]), "+f"(d[39]), "+f"(d[40]), "+f"(d[41]), "+f"(d[42]), "+f"(d[43]), "+f"(d[44]), "+f"(d[45]), "+f"(d[46]), "+f"(d[47]), "+f"(d[48]), "+f"(d[49]), "+f"(d[50]), "+f"(d[51]), "+f"(d[52]), "+f"(d[53]), "+f"(d[54]), "+f"(d[55]), "+f"(d[56]), "+f"(d[57]), "+f"(d[58]), "+f"(d[59]), "+f"(d[60]), "+f"(d[61]), "+f"(d[62]), "+f"(d[63])
    : "r"(da), "r"(db), "r"(sd), "n"(TB), "n"(OA), "n"(OB));
}
template<int TB, int OB> __device__ __forceinline__ void wgmma_rs_n128(float (&d)[64], uint32_t a0, uint32_t a1, uint32_t a2, uint32_t a3, uint32_t db, int sd) {
  asm volatile("{\n.reg .pred p;\n.reg .b32 tb;\n.reg .b64 db;\nsetp.ne.b32 p, %69, 0;\nadd.u32 tb, %68, %71;\nmov.b64 db, {tb, 0x40000040};\n"
    "wgmma.mma_async.sync.aligned.m64n128k16.f32.bf16.bf16 "
    "{%0, %1, %2, %3, %4, %5, %6, %7, %8, %9, %10, %11, %12, %13, %14, %15, %16, %17, %18, %19, %20, %21, %22, %23, %24, %25, %26, %27, %28, %29, %30, %31, %32, %33, %34, %35, %36, %37, %38, %39, %40, %41, %42, %43, %44, %45, %46, %47, %48, %49, %50, %51, %52, %53, %54, %55, %56, %57, %58, %59, %60, %61, %62, %63}, {%64,%65,%66,%67}, db, p, 1, 1, %70;\n}\n"
    : "+f"(d[0]), "+f"(d[1]), "+f"(d[2]), "+f"(d[3]), "+f"(d[4]), "+f"(d[5]), "+f"(d[6]), "+f"(d[7]), "+f"(d[8]), "+f"(d[9]), "+f"(d[10]), "+f"(d[11]), "+f"(d[12]), "+f"(d[13]), "+f"(d[14]), "+f"(d[15]), "+f"(d[16]), "+f"(d[17]), "+f"(d[18]), "+f"(d[19]), "+f"(d[20]), "+f"(d[21]), "+f"(d[22]), "+f"(d[23]), "+f"(d[24]), "+f"(d[25]), "+f"(d[26]), "+f"(d[27]), "+f"(d[28]), "+f"(d[29]), "+f"(d[30]), "+f"(d[31]), "+f"(d[32]), "+f"(d[33]), "+f"(d[34]), "+f"(d[35]), "+f"(d[36]), "+f"(d[37]), "+f"(d[38]), "+f"(d[39]), "+f"(d[40]), "+f"(d[41]), "+f"(d[42]), "+f"(d[43]), "+f"(d[44]), "+f"(d[45]), "+f"(d[46]), "+f"(d[47]), "+f"(d[48]), "+f"(d[49]), "+f"(d[50]), "+f"(d[51]), "+f"(d[52]), "+f"(d[53]), "+f"(d[54]), "+f"(d[55]), "+f"(d[56]), "+f"(d[57]), "+f"(d[58]), "+f"(d[59]), "+f"(d[60]), "+f"(d[61]), "+f"(d[62]), "+f"(d[63])
    : "r"(a0), "r"(a1), "r"(a2), "r"(a3), "r"(db), "r"(sd), "n"(TB), "n"(OB));
}
template<int TB, int OA, int OB> __device__ __forceinline__ void wgmma_ss_n64(float (&d)[32], uint32_t da, uint32_t db, int sd) {
  asm volatile("{\n.reg .pred p;\n.reg .b32 ta, tb;\n.reg .b64 da, db;\nsetp.ne.b32 p, %34, 0;\nadd.u32 ta, %32, %36;\nadd.u32 tb, %33, %37;\nmov.b64 da, {ta, 0x40000040};\nmov.b64 db, {tb, 0x40000040};\n"
    "wgmma.mma_async.sync.aligned.m64n64k16.f32.bf16.bf16 "
    "{%0, %1, %2, %3, %4, %5, %6, %7, %8, %9, %10, %11, %12, %13, %14, %15, %16, %17, %18, %19, %20, %21, %22, %23, %24, %25, %26, %27, %28, %29, %30, %31}, da, db, p, 1, 1, 0, %35;\n}\n"
    : "+f"(d[0]), "+f"(d[1]), "+f"(d[2]), "+f"(d[3]), "+f"(d[4]), "+f"(d[5]), "+f"(d[6]), "+f"(d[7]), "+f"(d[8]), "+f"(d[9]), "+f"(d[10]), "+f"(d[11]), "+f"(d[12]), "+f"(d[13]), "+f"(d[14]), "+f"(d[15]), "+f"(d[16]), "+f"(d[17]), "+f"(d[18]), "+f"(d[19]), "+f"(d[20]), "+f"(d[21]), "+f"(d[22]), "+f"(d[23]), "+f"(d[24]), "+f"(d[25]), "+f"(d[26]), "+f"(d[27]), "+f"(d[28]), "+f"(d[29]), "+f"(d[30]), "+f"(d[31])
    : "r"(da), "r"(db), "r"(sd), "n"(TB), "n"(OA), "n"(OB));
}
template<int TB, int OA, int OB> __device__ __forceinline__ void wgmma_ss_n128_new(float (&d)[64], uint32_t da, uint32_t db) {
  asm volatile("{\n.reg .pred p;\n.reg .b32 ta, tb;\n.reg .b64 da, db;\nsetp.ne.b32 p, %66, 0;\nadd.u32 ta, %64, %68;\nadd.u32 tb, %65, %69;\nmov.b64 da, {ta, 0x40000040};\nmov.b64 db, {tb, 0x40000040};\n"
    "wgmma.mma_async.sync.aligned.m64n128k16.f32.bf16.bf16 "
    "{%0, %1, %2, %3, %4, %5, %6, %7, %8, %9, %10, %11, %12, %13, %14, %15, %16, %17, %18, %19, %20, %21, %22, %23, %24, %25, %26, %27, %28, %29, %30, %31, %32, %33, %34, %35, %36, %37, %38, %39, %40, %41, %42, %43, %44, %45, %46, %47, %48, %49, %50, %51, %52, %53, %54, %55, %56, %57, %58, %59, %60, %61, %62, %63}, da, db, p, 1, 1, 0, %67;\n}\n"
    : "=f"(d[0]), "=f"(d[1]), "=f"(d[2]), "=f"(d[3]), "=f"(d[4]), "=f"(d[5]), "=f"(d[6]), "=f"(d[7]), "=f"(d[8]), "=f"(d[9]), "=f"(d[10]), "=f"(d[11]), "=f"(d[12]), "=f"(d[13]), "=f"(d[14]), "=f"(d[15]), "=f"(d[16]), "=f"(d[17]), "=f"(d[18]), "=f"(d[19]), "=f"(d[20]), "=f"(d[21]), "=f"(d[22]), "=f"(d[23]), "=f"(d[24]), "=f"(d[25]), "=f"(d[26]), "=f"(d[27]), "=f"(d[28]), "=f"(d[29]), "=f"(d[30]), "=f"(d[31]), "=f"(d[32]), "=f"(d[33]), "=f"(d[34]), "=f"(d[35]), "=f"(d[36]), "=f"(d[37]), "=f"(d[38]), "=f"(d[39]), "=f"(d[40]), "=f"(d[41]), "=f"(d[42]), "=f"(d[43]), "=f"(d[44]), "=f"(d[45]), "=f"(d[46]), "=f"(d[47]), "=f"(d[48]), "=f"(d[49]), "=f"(d[50]), "=f"(d[51]), "=f"(d[52]), "=f"(d[53]), "=f"(d[54]), "=f"(d[55]), "=f"(d[56]), "=f"(d[57]), "=f"(d[58]), "=f"(d[59]), "=f"(d[60]), "=f"(d[61]), "=f"(d[62]), "=f"(d[63])
    : "r"(da), "r"(db), "n"(0), "n"(TB), "n"(OA), "n"(OB));
}
template<int TB, int OA, int OB> __device__ __forceinline__ void wgmma_ss_n64_new(float (&d)[32], uint32_t da, uint32_t db) {
  asm volatile("{\n.reg .pred p;\n.reg .b32 ta, tb;\n.reg .b64 da, db;\nsetp.ne.b32 p, %34, 0;\nadd.u32 ta, %32, %36;\nadd.u32 tb, %33, %37;\nmov.b64 da, {ta, 0x40000040};\nmov.b64 db, {tb, 0x40000040};\n"
    "wgmma.mma_async.sync.aligned.m64n64k16.f32.bf16.bf16 "
    "{%0, %1, %2, %3, %4, %5, %6, %7, %8, %9, %10, %11, %12, %13, %14, %15, %16, %17, %18, %19, %20, %21, %22, %23, %24, %25, %26, %27, %28, %29, %30, %31}, da, db, p, 1, 1, 0, %35;\n}\n"
    : "=f"(d[0]), "=f"(d[1]), "=f"(d[2]), "=f"(d[3]), "=f"(d[4]), "=f"(d[5]), "=f"(d[6]), "=f"(d[7]), "=f"(d[8]), "=f"(d[9]), "=f"(d[10]), "=f"(d[11]), "=f"(d[12]), "=f"(d[13]), "=f"(d[14]), "=f"(d[15]), "=f"(d[16]), "=f"(d[17]), "=f"(d[18]), "=f"(d[19]), "=f"(d[20]), "=f"(d[21]), "=f"(d[22]), "=f"(d[23]), "=f"(d[24]), "=f"(d[25]), "=f"(d[26]), "=f"(d[27]), "=f"(d[28]), "=f"(d[29]), "=f"(d[30]), "=f"(d[31])
    : "r"(da), "r"(db), "n"(0), "n"(TB), "n"(OA), "n"(OB));
}
template<int OA, int OB = 0> __device__ __forceinline__ void kblock_n128(float (&d)[64], uint32_t da, uint32_t db, int sd) {
  wgmma_ss_n128<1, OA, OB>(d, da, db, sd); wgmma_ss_n128<1, OA + 2, OB + 128>(d, da, db, 1);
  wgmma_ss_n128<1, OA + 4, OB + 256>(d, da, db, 1); wgmma_ss_n128<1, OA + 6, OB + 384>(d, da, db, 1);
}

__device__ __forceinline__ float quad_sum(float v) {
  v += __shfl_xor_sync(0xffffffff, v, 1);
  v += __shfl_xor_sync(0xffffffff, v, 2);
  return v;
}
struct Row { uint32_t v[8]; };
template<class F> __device__ __forceinline__ Row load_row(const __nv_bfloat16* p, int lane, F ld) {
  const uint4 a = ld(reinterpret_cast<const uint4*>(p) + lane), b = ld(reinterpret_cast<const uint4*>(p) + 32 + lane);
  return Row{{a.x, a.y, a.z, a.w, b.x, b.y, b.z, b.w}};
}
__device__ __forceinline__ Row ldg_row(const __nv_bfloat16* p, int lane) { return load_row(p, lane, [](const uint4* q) { return __ldg(q); }); }
__device__ __forceinline__ Row ldca_row(const __nv_bfloat16* p, int lane) { return load_row(p, lane, [](const uint4* q) { return __ldca(q); }); }
__device__ __forceinline__ Row lds_row(uint32_t addr, int lane) {
  const uint4 a = lds_v4(addr + lane * 16), b = lds_v4(addr + 512 + lane * 16);
  return Row{{a.x, a.y, a.z, a.w, b.x, b.y, b.z, b.w}};
}
__device__ __forceinline__ void store_row(__nv_bfloat16* p, int lane, const Row& r) {
  stg_v4(p + lane * 8, r.v[0], r.v[1], r.v[2], r.v[3]); stg_v4(p + 256 + lane * 8, r.v[4], r.v[5], r.v[6], r.v[7]);
}
__device__ __forceinline__ Row fma_row(const Row& a, const Row& b, const Row& c) {
  Row r;
  #pragma unroll
  for (int i = 0; i < 8; i++) r.v[i] = fma2(a.v[i], b.v[i], c.v[i]);
  return r;
}
__device__ __forceinline__ Row one_plus(const Row& a) {
  Row r;
  #pragma unroll
  for (int i = 0; i < 8; i++) r.v[i] = add2(a.v[i], 0x3f803f80u);
  return r;
}
__device__ __forceinline__ void layer_norm2(const Row (&x)[2], Row (&n)[2], float scale = 1.f) {
  float d[2][16], s[4];
  #pragma unroll
  for (int r = 0; r < 2; r++) {
    const float c = bf_lo(__shfl_sync(0xffffffff, x[r].v[0], 0));
    float s1 = 0.f, s2 = 0.f;
    #pragma unroll
    for (int i = 0; i < 16; i++) { d[r][i] = ((i & 1) ? bf_hi(x[r].v[i >> 1]) : bf_lo(x[r].v[i >> 1])) - c; s1 += d[r][i]; s2 = fmaf(d[r][i], d[r][i], s2); }
    s[2*r] = s1; s[2*r+1] = s2;
  }
  #pragma unroll
  for (int o = 16; o > 0; o >>= 1) {
    #pragma unroll
    for (int k = 0; k < 4; k++) s[k] += __shfl_xor_sync(0xffffffff, s[k], o);
  }
  #pragma unroll
  for (int r = 0; r < 2; r++) {
    const float m = s[2*r] * (1.f / DM), rstd = scale * rsqrtf(fmaxf(fmaf(-m, m, s[2*r+1] * (1.f / DM)), 0.f) + 1e-5f), o = -m * rstd;
    #pragma unroll
    for (int i = 0; i < 8; i++) n[r].v[i] = pack_bf16(fmaf(d[r][2*i], rstd, o), fmaf(d[r][2*i+1], rstd, o));
  }
}

constexpr int SM_Q = 6 * 32768, SM_BAR = 7 * 32768, SM_MAIL = SM_BAR + 640, SM_RED = SM_MAIL + 128, SM_H2 = SM_RED + 1024, SM_KEY = SM_H2 + 1024, SMEM = SM_KEY + 128;
constexpr int B_AF = 0, B_WF = 64, B_RF = 112, B_WE = 168, B_RE = 216, B_PUB = 272, B_RDY = 496;
constexpr int R_MOD = B_RDY, R_ITEM = B_RDY + 8, R_NEAR = B_RDY + 48, R_PART = B_RDY + 56, R_CTX = B_RDY + 64, R_KEY = B_AF + 8, R_H1 = B_RDY + 40;
constexpr int NPUB = 14;
__device__ __forceinline__ uint32_t k_addrA(int kb) { return ((0x6310u >> ((kb >> 1) * 4)) & 15u) * 32768u + (kb & 1) * 16384u; }
__device__ __forceinline__ uint32_t k_addrW(int s) { return ((0x254u >> ((s >> 1) * 4)) & 15u) * 32768u + (s & 1) * 16384u; }

#define KORDER 0x2301
constexpr int KHEAD0 = ((KORDER >> 12) & 3) * 8;
constexpr int MAX_ITEMS = 4;
constexpr int MAX_STEPS = 10;
struct Sched {
  __nv_bfloat16 *kvc, *h1;
  struct Pair {
    uint8_t oent[3 * MAX_STEPS + 6];
    uint16_t lastuse[MAX_ITEMS];
    uint8_t khead[4];
    uint8_t nitems, item[MAX_ITEMS];
    uint8_t otask, nsteps;
    uint8_t ochunk[MAX_STEPS][2];
  } pair[NGRID / 2];
};

__device__ __forceinline__ int ring_add(int e, int n) { e += n; return e >= 12 ? e - 12 : e; }
__device__ __forceinline__ int ring_slot(int e) { return e >= 6 ? e - 6 : e; }
__device__ __forceinline__ void ring_wait_full(uint32_t bars, int e) { mbar_wait(bars + B_RF + 8 * ring_slot(e), e >= 6); }

__device__ __forceinline__ void o_wait_full(uint32_t bars, uint32_t v) { mbar_wait(bars + B_RF + 8 * (v & 7), v >> 3); }

struct Ctx {
  uint32_t base, bars;
  uint32_t rel;
  bool rel1;
  int w, nev;
  const Sched* sched;
};
__device__ __forceinline__ void slot_release(const Ctx& x, int s, bool twice) {
  mbar_arrive_remote_if(x.rel + B_RE + 8 * s, twice ? (wg_tid() & 31) == 0 : x.rel1);
}
__device__ __forceinline__ void ring_release(const Ctx& x, int e, bool twice) { slot_release(x, ring_slot(e), twice); }
__device__ __forceinline__ void publish(Ctx& x, int idx) {
  const uint32_t n = x.w * NPUB + x.nev;
  const int t = wg_tid();
  if (t == 0) asm volatile("st.shared.u32 [%0], %1;" :: "r"(x.base + SM_MAIL + 4 * n), "r"(idx) : "memory");
  __syncwarp();
  if ((t & 31) == 0) mbar_arrive(x.bars + B_PUB + 8 * n);
  x.nev++;
}

template<int KK = 0> __device__ __forceinline__ void issue_qk(float (&S)[64], uint32_t dq, uint32_t dk) {
  constexpr int off = (KK >> 2) * 1024 + (KK & 3) * 2;
  if constexpr (KK == 0) wgmma_ss_n128_new<0, 0, 0>(S, dq, dk); else wgmma_ss_n128<0, off, off>(S, dq, dk, 1);
  if constexpr (KK < 7) issue_qk<KK + 1>(S, dq, dk);
}
template<int KK = 0> __device__ __forceinline__ void issue_qk_half(float (&S)[32], uint32_t dq, uint32_t dk) {
  constexpr int off = (KK >> 2) * 1024 + (KK & 3) * 2;
  if constexpr (KK == 0) wgmma_ss_n64_new<0, 0, 512>(S, dq, dk); else wgmma_ss_n64<0, off, off + 512>(S, dq, dk, 1);
  if constexpr (KK < 7) issue_qk_half<KK + 1>(S, dq, dk);
}
template<int NK, int KK = 0>
__device__ __forceinline__ void issue_pv(float (&O)[64], uint32_t (&P)[32], uint32_t dv, int accumulate) {
  wgmma_rs_n128<1, (KK + 8 - NK) * 128>(O, P[4*KK], P[4*KK+1], P[4*KK+2], P[4*KK+3], dv, accumulate);
  if constexpr (KK + 1 < NK) issue_pv<NK, KK + 1>(O, P, dv, 1);
}
template<int K0, int K1>
__device__ __forceinline__ void exp_pack(const float (&S)[64], uint32_t (&D)[32], float& s0, float& s1) {
  #pragma unroll
  for (int k = K0; k < K1; k++) {
    const float e0 = ex2(S[2*k]), e1 = ex2(S[2*k+1]);
    D[k] = pack_bf16(e0, e1);
    if (k & 1) s1 += e0 + e1; else s0 += e0 + e1;
  }
}
__device__ __forceinline__ int q_row(int t) { return 16 * (t >> 5) + ((t >> 1) & 6) + ((t >> 4) & 1); }
__device__ __forceinline__ int diag_limit() { const int t = wg_tid(); return q_row(t) - 2 * (t & 3); }
__device__ __forceinline__ void exp_pack_diag(const float (&S)[64], uint32_t (&D)[32], int t, float& s0, float& s1) {
  #pragma unroll
  for (int k = 0; k < 16; k++) {
    const int c = 8 * (k >> 1) - 8 * (k & 1);
    const float e0 = ex2((c <= t) ? S[2*k] : -INFINITY), e1 = ex2((c + 1 <= t) ? S[2*k+1] : -INFINITY);
    D[k] = pack_bf16(e0, e1);
    if (k & 1) s1 += e0 + e1; else s0 += e0 + e1;
  }
}
constexpr float SUM_HI = 1.8446744073709552e19f;
constexpr float SUM_LO = 5.421010862427522e-20f;

__device__ __forceinline__ void classic_tile(const float (&S)[64], uint32_t (&P)[32], bool fresh, bool half, bool was_classic, volatile float* mc,
                                             float& l0, float& l1, float& s0, float& s1, float& sc0, float& sc1) {
  const int tmask = diag_limit();
  float4 t[16];
  #pragma unroll
  for (int j = 0; j < 16; j++) t[j] = make_float4(S[4*j], S[4*j+1], S[4*j+2], S[4*j+3]);
  float mx0 = -INFINITY, mx1 = -INFINITY;
  #pragma unroll 1
  for (int j = 0; j < 16; j++) {
    float4 v = t[j];
    const int lim = !fresh ? 1000 : j < 8 ? tmask - 8 * j : half ? -1000 : 1000;
    v.x = 0 <= lim ? v.x : -INFINITY; v.y = 1 <= lim ? v.y : -INFINITY; v.z = -8 <= lim ? v.z : -INFINITY; v.w = -7 <= lim ? v.w : -INFINITY;
    t[j] = v;
    mx0 = fmaxf(mx0, fmaxf(v.x, v.y)); mx1 = fmaxf(mx1, fmaxf(v.z, v.w));
  }
  mx0 = fmaxf(mx0, __shfl_xor_sync(0xffffffff, mx0, 1));
  mx1 = fmaxf(mx1, __shfl_xor_sync(0xffffffff, mx1, 1));
  mx0 = fmaxf(mx0, __shfl_xor_sync(0xffffffff, mx0, 2));
  mx1 = fmaxf(mx1, __shfl_xor_sync(0xffffffff, mx1, 2));
  const float mc0 = was_classic ? mc[0] : 0.f, mc1 = was_classic ? mc[1] : 0.f;
  const float n0 = fresh ? -mx0 : fminf(mc0, -mx0), n1 = fresh ? -mx1 : fminf(mc1, -mx1);
  sc0 = ex2(n0 - mc0); sc1 = ex2(n1 - mc1);
  mc[0] = n0; mc[1] = n1;
  s0 = 0.f; s1 = 0.f;
  #pragma unroll 1
  for (int j = 0; j < 16; j++) {
    const float4 v = t[j];
    const float e0 = ex2(v.x + n0), e1 = ex2(v.y + n0), e2 = ex2(v.z + n1), e3 = ex2(v.w + n1);
    s0 += e0 + e1; s1 += e2 + e3;
    reinterpret_cast<uint2*>(t)[j] = make_uint2(pack_bf16(e0, e1), pack_bf16(e2, e3));
  }
  #pragma unroll
  for (int j = 0; j < 8; j++) { P[4*j] = __float_as_uint(t[j].x); P[4*j+1] = __float_as_uint(t[j].y); P[4*j+2] = __float_as_uint(t[j].z); P[4*j+3] = __float_as_uint(t[j].w); }
  if (!fresh) { l0 *= sc0; l1 *= sc1; }
}
__device__ __forceinline__ void pack_tile(const float (&A)[64], uint32_t (&D)[32], float f0, float f1) {
  #pragma unroll
  for (int j = 0; j < 16; j++) {
    D[8 * (j >> 2) + (j & 3)] = pack_bf16(A[4*j] * f0, A[4*j+1] * f0);
    D[8 * (j >> 2) + 4 + (j & 3)] = pack_bf16(A[4*j+2] * f1, A[4*j+3] * f1);
  }
}
__device__ __forceinline__ void store_tile(__nv_bfloat16* p, const uint32_t (&D)[32]) {
  #pragma unroll
  for (int i = 0; i < 8; i++) stg_v4(p + (i >> 2) * (SEQ * 64) + ((i >> 1) & 1) * 32 + (i & 1) * 8 * 64, D[4*i], D[4*i+1], D[4*i+2], D[4*i+3]);
}

enum : int { PV_ACC = 0, PV_ZERO = 1, PV_HALF = 2, PV_NONE = 3 };
struct Att {
  float l0, l1, i0, i1;
  bool classic;
  volatile float* mc;
};
__device__ __forceinline__ void store_ctx(Ctx& x, int code, const uint32_t (&D)[32]) {
  const int item = code >> 2, t = wg_tid(), lane = t & 31;
  const int row = (item & 7) * 256 + (code & 3) * 64 + q_row(t);
  store_tile(x.sched->kvc + ((size_t)(128 + (item >> 3) * 2) * SEQ + row) * 64 + (lane & 3) * 8, D);
  publish(x, C_CTX + item);
}

__device__ __forceinline__ __nv_bfloat16* kv_tile(const Ctx& x, int code) {
  const int t = wg_tid();
  return x.sched->kvc + ((size_t)(x.w * 64 + (code >> 4) * 2) * SEQ + (code & 15) * 128 + (t >> 5) * 16 + ((t & 31) >> 2)) * 64 + (t & 3) * 8;
}
#define V_AT 3
#define V_AT2 7
#define MERGE1 1
#define NO_CLASSIC 0
__device__ __forceinline__ void q_proj(Ctx& x, int& e, bool isY, const uint32_t (&PA)[32], const uint32_t (&PB)[32], int vtile, bool dbg = false) {
  float S[64];
  bar_sync(1 + x.w, 256);
  if (isY) bar_arrive(1 + (x.w ^ 1), 256);
  if (dbg) DBG(80);
  #pragma unroll 1
  for (int kb = 0; kb < 8; kb++) {
    ring_wait_full(x.bars, e);
    if (dbg) DBG(81 + kb);
    const uint32_t da = desc_lo(x.base + x.w * 8192, 16) + ring_slot(e) * 2048, dw = desc_lo(x.base + 16384, 8192) + ring_slot(e) * 2048;
    wgmma_fence();
    kblock_n128<0>(S, da, dw, kb != 0);
    wgmma_commit();
    if (kb == 7 && !isY) bar_arrive(1 + (x.w ^ 1), 256);
    if (kb > 0) { wgmma_wait<1>(); ring_release(x, ring_add(e, 11), false); }
    if (kb == V_AT && vtile >= 0) store_tile(kv_tile(x, vtile) + 64 * 64, PA);
    if (kb == V_AT2 && vtile >= 0) { store_tile(kv_tile(x, vtile), PB); publish(x, C_KV + (vtile >> 4)); }
    e = ring_add(e, 1);
  }
  wgmma_wait<0>();
  fence_regs(S);
  if (dbg) DBG(89);
  ring_release(x, ring_add(e, 11), false);
  const int t = wg_tid(), lane = t & 31, g = (lane >> 3) + (lane & 4);
  const uint32_t qa = x.base + SM_Q + x.w * 8192 + ((t >> 5) * 16 + g) * 128;
  #pragma unroll
  for (int i = 0; i < 8; i++) {
    const int j = 4 * (i >> 1), o = 2 * (i & 1);
    sts_v4(qa + (i >> 2) * 16384 + (i & 1) * 1024 + (((((i >> 1) & 1) * 4 + (lane & 3)) ^ g) << 4),
           pack_bf16(S[4*j+o], S[4*j+o+1]), pack_bf16(S[4*j+4+o], S[4*j+5+o]), pack_bf16(S[4*j+8+o], S[4*j+9+o]), pack_bf16(S[4*j+12+o], S[4*j+13+o]));
  }
  fence_async_smem();
  if (dbg) DBG(90);
  ring_wait_full(x.bars, ring_add(e, isY ? 0 : 2));
  ring_wait_full(x.bars, ring_add(e, 1));
}

template<int KIND>
__device__ __forceinline__ void slot(Ctx& x, Att& a, int& e, float (&O)[64], uint32_t (&Pn)[32], uint32_t (&Po)[32],
                                     bool more, bool isY, bool half, int pv, int pend) {
  float S[64];
  const int w = x.w;
  const bool skip = KIND == 0 && !isY;
  const int en = ring_add(e, skip ? 4 : 2), sn = ring_slot(en), sv = ring_slot(e) + 1, sk = skip ? ring_slot(ring_add(e, 2)) : sv - 1;
  const uint32_t dq = desc_lo(x.base + SM_Q + w * 8192, 16), dk = desc_lo(x.base, 16) + sk * 2048, dv = desc_lo(x.base, 16384) + sv * 2048;
  bar_sync(1 + w, 256);
  if (KIND == 2) {
    wgmma_fence();
    issue_qk(S, dq, dk); wgmma_commit();
    issue_pv<8>(O, Po, dv, 1); wgmma_commit();
    bar_arrive(1 + (w ^ 1), 256);
    wgmma_wait<1>();
  } else if (KIND == 0 && half) {
    float T[32];
    wgmma_fence(); issue_qk_half(T, dq, dk); wgmma_commit();
    a.i0 = rcp_fast(quad_sum(a.l0)); a.i1 = rcp_fast(quad_sum(a.l1));
    if (pv == PV_NONE) { wgmma_fence(); wgmma_commit(); }
    else               { wgmma_fence(); issue_pv<8>(O, Po, dv, pv == PV_ACC); wgmma_commit(); }
    bar_arrive(1 + (w ^ 1), 256);
    wgmma_wait<1>();
    fence_regs(T);
    #pragma unroll
    for (int i = 0; i < 32; i++) { S[i] = T[i]; asm volatile("" : "=f"(S[32 + i])); }
  } else {
    wgmma_fence(); issue_qk(S, dq, dk); wgmma_commit();
    if (KIND == 1 && pend >= 0) { bar_arrive(1 + (w ^ 1), 256); pack_tile(O, Pn, a.i0, a.i1); store_ctx(x, pend, Pn); }
    if (KIND == 0) { a.i0 = rcp_fast(quad_sum(a.l0)); a.i1 = rcp_fast(quad_sum(a.l1)); }
    if (KIND == 0 && pv == PV_NONE) { wgmma_fence(); wgmma_commit(); }
    else if (pv == PV_HALF)         { wgmma_fence(); issue_pv<4>(O, Po, dv, 0); wgmma_commit(); }
    else                            { wgmma_fence(); issue_pv<8>(O, Po, dv, pv == PV_ACC); wgmma_commit(); }
    if (KIND == 0 || pend < 0) bar_arrive(1 + (w ^ 1), 256);
    wgmma_wait<1>();
  }
  fence_regs(S);
  fence_regs_u(Pn);
  slot_release(x, sk, KIND == 0 && isY);
  float s0 = 0.f, s1 = 0.f;
  const bool was_classic = KIND != 0 && a.classic;
  if (KIND == 0) {
    a.l0 = 0.f; a.l1 = 0.f;
    if (!half) exp_pack<16, 32>(S, Pn, s0, s1);
    else {
      #pragma unroll
      for (int i = 16; i < 32; i++) asm volatile("" : "=r"(Pn[i]));
    }
    exp_pack_diag(S, Pn, diag_limit(), s0, s1);
    uint32_t b0 = __ballot_sync(0xffffffff, s0 >= SUM_LO), b1 = __ballot_sync(0xffffffff, s1 >= SUM_LO);
    b0 |= b0 >> 1; b0 |= b0 >> 2; b1 |= b1 >> 1; b1 |= b1 >> 2;
    a.classic = __any_sync(0xffffffff, !(s0 <= SUM_HI && s1 <= SUM_HI)) || (b0 & b1 & 0x11111111u) != 0x11111111u;
  } else {
    exp_pack<0, 32>(S, Pn, s0, s1);
    a.classic = __any_sync(0xffffffff, a.classic || !(s0 <= SUM_HI && s1 <= SUM_HI));
  }
  fence_regs_u(Pn);
  mbar_wait(x.bars + B_RF + 8 * sn, en >= 6);
  if (more) mbar_wait(x.bars + B_RF + 8 * sn + 8, en >= 6);
  wgmma_wait<0>();
  fence_regs(O);
  fence_regs_u(Po);
  slot_release(x, sv, KIND == 1 && isY && pv != PV_ACC);
  if (!NO_CLASSIC && __builtin_expect(a.classic, 0)) {
    float sc0, sc1;
    classic_tile(S, Pn, KIND == 0, half, was_classic, a.mc, a.l0, a.l1, s0, s1, sc0, sc1);
    if (KIND != 0) {
      #pragma unroll
      for (int j = 0; j < 16; j++) { O[4*j] *= sc0; O[4*j+1] *= sc0; O[4*j+2] *= sc1; O[4*j+3] *= sc1; }
    }
  }
  a.l0 += s0; a.l1 += s1;
  e = en;
}

__device__ __forceinline__ int attention(Ctx& x, const uint8_t* items, int nitems, int rank, uint32_t (&PA)[32], uint32_t (&PB)[32], int vtile) {
  int e = 0;
  float O[64];
  Att a;
  volatile float mc[2];
  a.l0 = 1.f; a.l1 = 1.f; a.i0 = 0.f; a.i1 = 0.f; a.classic = false; a.mc = mc;
  int pv = PV_NONE, cur = -1;
#define DBGS()
  #pragma unroll 1
  for (int it = 0; ; it++) {
    const bool isY = (it & 1) == x.w;
    int pend = cur;
    if (it < nitems) {
      const int item = items[it];
      const bool half = isY == (rank != 0);
      cur = item * 4 + (isY ? 3 - rank : rank);
      int rem = 2 * (item & 7) + (isY ? 1 : 0);
      DBG(16 + it);
      q_proj(x, e, isY, PA, PB, vtile);
      vtile = -1;
      DBGS();
      slot<0>(x, a, e, O, PA, PB, rem > 0, isY, half, pv, -1);
      pv = half ? PV_HALF : PV_ZERO;
      #pragma unroll 1
      while (rem > 0) {
        DBGS();
        slot<1>(x, a, e, O, PB, PA, rem > 1, isY, false, pv, pend);
        pv = PV_ACC; pend = -1;
        if (rem == 1) break;
        rem -= 2;
        DBGS();
        slot<2>(x, a, e, O, PA, PB, rem > 0, false, false, 0, -1);
      }
    } else {
      DBGS();
      slot_release(x, 6, false);
      const uint32_t dv = desc_lo(x.base + ring_slot(e) * 32768, 16384);
      bar_sync(1 + x.w, 256);
      if (pv == PV_HALF) { wgmma_fence(); issue_pv<4>(O, PB, dv, 0); wgmma_commit(); }
      else { wgmma_fence(); issue_pv<8>(O, PB, dv, pv == PV_ACC); wgmma_commit(); }
      if (isY) bar_arrive(1 + (x.w ^ 1), 256);
      a.i0 = rcp_fast(quad_sum(a.l0)); a.i1 = rcp_fast(quad_sum(a.l1));
      ring_wait_full(x.bars, e);
      wgmma_wait<0>();
      fence_regs(O);
      fence_regs_u(PB);
      ring_release(x, e, false);
    }
    if (pend >= 0) pack_tile(O, PB, a.i0, a.i1);
    if (it == nitems) return pend;
    if (pend >= 0) store_ctx(x, pend, PB);
    if (!isY) {
      #pragma unroll
      for (int i = 0; i < 32; i++) asm volatile("mov.b32 %0, %1;" : "=r"(PB[i]) : "r"(PA[i]));
    }
  }
}

#define LN_AT 2
#define X_AT 6
#define EFM 16
#define PF_AT 5
#define PF_N 4
#define PF_MOE 3
constexpr float QSCALE = 0.08838834764831845f * 1.4426950408889634f;
__device__ __forceinline__ void mod_cta(Ctx& x, const __nv_bfloat16* cvec) {
  const int t = wg_tid(), ct = x.w * 128 + t;
  #pragma unroll 1
  for (int k = 0; k < 6; k++) slot_release(x, k, false);
  const uint32_t cv = __ldg(reinterpret_cast<const uint32_t*>(cvec) + ct);
  asm volatile("st.shared.u32 [%0], %1;" :: "r"(x.base + SM_H2 + ct * 4),
               "r"(pack_bf16(__fdividef(bf_lo(cv), 1.f + __expf(-bf_lo(cv))), __fdividef(bf_hi(cv), 1.f + __expf(-bf_hi(cv))))) : "memory");
  bar_sync(5, 256);
  float acc[64];
  int e = 0;
  #pragma unroll 1
  for (int g = 0; g < 24; g++) {
    uint32_t a[8];
    #pragma unroll
    for (int i = 0; i < 8; i++) a[i] = lds_u32(x.base + SM_H2 + (g & 7) * 128 + i * 16 + (t & 3) * 4);
    ring_wait_full(x.bars, e);
    const uint32_t db = desc_lo(x.base + x.w * 16384, 8192) + ring_slot(e) * 2048;
    wgmma_fence();
    wgmma_rs_n128<1, 0>(acc, a[0], a[0], a[1], a[1], db, g & 7);
    wgmma_rs_n128<1, 128>(acc, a[2], a[2], a[3], a[3], db, 1);
    wgmma_rs_n128<1, 256>(acc, a[4], a[4], a[5], a[5], db, 1);
    wgmma_rs_n128<1, 384>(acc, a[6], a[6], a[7], a[7], db, 1);
    wgmma_commit();
    wgmma_wait<0>();
    fence_regs(acc);
    ring_release(x, e, false);
    e = ring_add(e, 1);
    if ((g & 7) == 7) {
      if (t < 4) {
        const float sc = (g == 7 && blockIdx.x < NCTA + 2) ? QSCALE : 1.f;
        uint32_t* dst = reinterpret_cast<uint32_t*>(g_mod + (g >> 3) * 1024 + (blockIdx.x - NCTA) * 256 + x.w * 128) + t;
        #pragma unroll
        for (int j = 0; j < 16; j++) dst[4 * j] = pack_bf16(rbf(acc[4*j]) * sc, rbf(acc[4*j+1]) * sc);
      }
      publish(x, g == 7 ? C_MOD : C_MOD2);
      DBG(1 + (g >> 3));
    }
  }
}

__global__ void __cluster_dims__(2, 1, 1) __launch_bounds__(384, 1)
k_fused(const __grid_constant__ CUtensorMap tmC, const __grid_constant__ CUtensorMap tmH, const __grid_constant__ CUtensorMap tmWq,
        const __grid_constant__ CUtensorMap tmWk, const __grid_constant__ CUtensorMap tmWv, const __grid_constant__ CUtensorMap tmKV,
        const __grid_constant__ CUtensorMap tmWo, const __grid_constant__ CUtensorMap tmPart, const __grid_constant__ CUtensorMap tmWg,
        const __grid_constant__ CUtensorMap tmWu, const __grid_constant__ CUtensorMap tmPl, const __grid_constant__ CUtensorMap tmWm,
        const __grid_constant__ Sched sched,
        const __nv_bfloat16* __restrict__ xin,
        const __nv_bfloat16* __restrict__ cvec, const __nv_bfloat16* __restrict__ w_o,
        const __nv_bfloat16* __restrict__ w_r, const __nv_bfloat16* __restrict__ w_gate, const __nv_bfloat16* __restrict__ w_up,
        const __nv_bfloat16* __restrict__ w_down, __nv_bfloat16* __restrict__ out) {
  extern __shared__ __align__(1024) uint8_t smem_raw[];
  const uint32_t base = smem_u32(smem_raw), bars = base + SM_BAR;
  const int warp = __shfl_sync(0xffffffff, threadIdx.x >> 5, 0), wg = warp >> 2;
  const int rank = cluster_ctarank(), p = blockIdx.x >> 1;
  const int mt = (p & 7) * 2 + rank;
  const bool spare = blockIdx.x >= NCTA;
  {
    const int h0 = KHEAD0 + (p >> 3);
    if (warp == 9) prefetch_tmap(&tmWk);
    if (warp <= 8) {
      #pragma unroll 1
      for (int t = 8 - warp; t < 80; t += (warp < 8 ? 8 : 80))
        w_mbar_init(bars + 8 * t, t < B_WE / 8 ? 1 : t < B_RE / 8 ? 2 : t < B_RDY / 8 ? 4 : 1);
      fence_mbar_init();
    }
    cluster_arrive();
    if (wg == 2) bar_arrive(1, 256);
    if (warp == 8 && !spare) {
      #pragma unroll 1
      for (int kb = 0; kb < 8; kb++) {
        w_expect_tx(bars + B_AF + 8 * kb, 16384);
        tma_load_2d(base + k_addrA(kb), &tmC, bars + B_AF + 8 * kb, kb * 64, mt * 128);
        if (kb == 0) cluster_wait();
        if (kb < 6) {
          w_expect_tx(bars + B_WF + 8 * kb, 16384);
          tma_load_2d_mc(base + k_addrW(kb) + rank * 8192, &tmWk, bars + B_WF + 8 * kb, h0 * 128 + rank * 64, kb * 64);
        }
      }
    }
  }
  const Sched::Pair& sp = sched.pair[p];
  const int nitems = sp.nitems, nsteps = sp.nsteps;
  auto oent = [&](int k) -> uint32_t { return sp.oent[k]; };
  const int ot = sp.otask, m = (ot & 7) * 2 + rank, grp = m * 8 + (ot >> 3);

  if (wg == 0) {
    asm volatile("setmaxnreg.dec.sync.aligned.u32 24;");
    const int lane = threadIdx.x & 31;
    cluster_wait();
    const unsigned int tag = ld_relaxed(&g_epoch) + 1;
    if (warp == 0) {
      if (!spare) {
        int s = 0, ph = 0;
        tma_prefetch_2d(&tmWv, sp.khead[0] * 128 + rank * 64, (p & 7) * 64);
        #pragma unroll 1
        for (int g = 6; g < 64; g++) {
          const int u = g >> 3, kb = g & 7;
          if (kb == 0 && u < 7) tma_prefetch_2d((u & 1) ? &tmWk : &tmWv, sp.khead[(u + 1) >> 1] * 128 + rank * 64, (p & 7) * 64);
          mbar_wait(bars + B_WE + 8 * s, ph);
          w_expect_tx(bars + B_WF + 8 * s, 16384);
          tma_load_2d_mc(base + k_addrW(s) + rank * 8192, (u & 1) ? &tmWv : &tmWk, bars + B_WF + 8 * s, sp.khead[u >> 1] * 128 + rank * 64, kb * 64);
          if (++s == 6) { s = 0; ph ^= 1; }
        }
      }
      int s = 0, ph = 0;
      auto next_entry = [&](bool load) {
        mbar_wait(bars + B_RE + 8 * s, ph);
        if (load) w_expect_tx(bars + B_RF + 8 * s, 32768); else w_arrive(bars + B_RF + 8 * s);
      };
      auto advance = [&]() { if (++s == 6) { s = 0; ph ^= 1; } };
      if (spare) {
        #pragma unroll 1
        for (int g = 0; g < 24; g++) {
          if (g == 8) mbar_wait(bars + R_MOD, 0);
          next_entry(true);
          for (int k = 0; k < 2; k++) tma_load_3d(base + s * 32768 + k * 16384, &tmWm, bars + B_RF + 8 * s, 0, (g & 7) * 64, (g >> 3) * 16 + (blockIdx.x - NCTA) * 4 + k * 2);
          advance();
        }
      }
      mbar_wait(bars + R_H1, 0);
      fence_async_global();
      bool lastv = false;
      int vrow = -1;
      #pragma unroll 1
      for (int i = 0; i < nitems; i++) {
        const int item = sp.item[i], h = item >> 3, j = item & 7;
        const int row0 = j * 256 + ((i & 1) ? rank : 3 - rank) * 64, row1 = j * 256 + ((i & 1) ? 3 - rank : rank) * 64;
        #pragma unroll 1
        for (int kb = 0; kb < 8; kb++) {
          next_entry(true);
          tma_load_2d_mc(base + s * 32768 + 16384 + rank * 8192, &tmWq, bars + B_RF + 8 * s, h * 128 + rank * 64, kb * 64);
          tma_load_2d(base + s * 32768, &tmH, bars + B_RF + 8 * s, kb * 64, row0);
          tma_load_2d(base + s * 32768 + 8192, &tmH, bars + B_RF + 8 * s, kb * 64, row1);
          advance();
        }
        mbar_wait(bars + R_ITEM + 8 * i, 0);
        fence_async_global();
        #pragma unroll 1
        for (int n = 2 * j + 1; n >= 0; n--) {
          const int krow = (h * 2 + rank) * SEQ + n * 128;
          const bool lastk = (EFM & 16) && ((sp.lastuse[i] >> n) & 1);
          if (i + 1 == nitems && n == min(2 * j + 1, PF_AT)) w_arrive(bars + R_NEAR);
          next_entry(true);
          tma_load_2d_mc(base + s * 32768 + rank * 16384, &tmKV, bars + B_RF + 8 * s, 0, krow, lastk);
          advance();
          next_entry(vrow >= 0);
          if (vrow >= 0) tma_load_2d_mc(base + s * 32768 + rank * 16384, &tmKV, bars + B_RF + 8 * s, 0, vrow, lastv);
          advance();
          vrow = krow + 64 * SEQ; lastv = lastk;
        }
      }
      next_entry(true);
      tma_load_2d_mc(base + s * 32768 + rank * 16384, &tmKV, bars + B_RF + 8 * s, 0, vrow, lastv);
      advance();
      if (!spare) {
      const int oc = ((ot >> 3) & 1) * 4 + rank * 2;
      auto o_next = [&](int k, int bytes) {
        const uint32_t v = oent(k); s = v & 7;
        mbar_wait(bars + B_RE + 8 * s, v >> 3);
        w_expect_tx(bars + B_RF + 8 * s, bytes);
      };
      #pragma unroll 1
      for (int i = 0; i < nsteps; i++) {
        const int c0 = sp.ochunk[i][0], c1 = sp.ochunk[i][1];
        if (i >= PF_MOE && i < PF_MOE + 3)
          bulk_prefetch((i == PF_MOE ? w_gate : i == PF_MOE + 1 ? w_up : w_down) + (size_t)blockIdx.x * (DM * FF / NCTA), DM * FF / NCTA * 2);
        if (c0 < 64) { o_next(3 * i, 32768); tma_load_3d_mc(base + s * 32768 + rank * 16384, &tmWo, bars + B_RF + 8 * s, 0, c0 * 64, oc); }
        mbar_wait(bars + R_CTX + 8 * i, 0);
        fence_async_global();
        o_next(3 * i + 1, c0 < 64 ? 32768 : 16384);
        if (c0 < 64) tma_load_2d(base + s * 32768, &tmKV, bars + B_RF + 8 * s, 0, (128 + c0) * SEQ + m * 128);
        tma_load_2d(base + s * 32768 + 16384, &tmKV, bars + B_RF + 8 * s, 0, (128 + c1) * SEQ + m * 128);
        o_next(3 * i + 2, 32768);
        tma_load_3d_mc(base + s * 32768 + rank * 16384, &tmWo, bars + B_RF + 8 * s, 0, c1 * 64, oc);
      }
      const int f0 = (blockIdx.x < FF / 16 ? blockIdx.x : 0) * 16;
      o_next(3 * nsteps, 32768);
      bulk_load(base + s * 32768, w_down + (size_t)f0 * DM, 16384, bars + B_RF + 8 * s);
      bulk_load(base + s * 32768 + 16384, xin + (size_t)grp * 16 * DM, 16384, bars + B_RF + 8 * s);
      o_next(3 * nsteps + 1, 32768);
      #pragma unroll 1
      for (int k = 0; k < 4; k++) tma_load_2d(base + s * 32768 + k * 8192, (k & 2) ? &tmWu : &tmWg, bars + B_RF + 8 * s, f0, (k & 1) * 256);
      w_expect_tx(bars + R_PART, 65536);
      mbar_wait(bars + B_PUB + 8 * (5 + nitems + 1), 0);
      mbar_wait(bars + B_PUB + 8 * (NPUB + 5 + nitems + 1), 0);
      uint32_t todo = 0xff;
      #pragma unroll 1
      for (int n = 0; n < WAIT_LIM && todo; n++) {
        uint32_t now = __ballot_sync(0xffffffff, ld_acquire(&g_pflag[m * 2 + (ot >> 5)][lane & 7]) == tag) & todo;
        todo &= ~now;
        fence_async_global();
        #pragma unroll 1
        for (; now; now &= now - 1) {
          const int q = __ffs(now) - 1;
          tma_load_3d(base + (oent(3 * nsteps - 3 + (q >> 2)) & 7) * 32768 + (q & 3) * 8192, &tmPl, bars + R_PART, 0, grp * 16, q * 4);
        }
      }
      DBGP(11);
      }
    } else if (warp < 3) {
      const int w = warp - 1, n1 = w * NPUB + (spare ? 3 : 5) + nitems;
      #pragma unroll 1
      for (int n = w * NPUB; n < n1 + (spare ? 0 : 2); n++) {
        #pragma unroll 1
        for (int k = 0; k < 8 * WAIT_LIM; k++) { if (mbar_try(bars + B_PUB + 8 * n, 0)) break; }
        const uint32_t msg = lds_u32(base + SM_MAIL + 4 * n);
        if (n < n1) {
          fence_async_global();
          if (lane == 0 && msg < (unsigned)C_END) red_release(msg);
        } else {
          if (lane == 0) { tma_store_3d(&tmPart, base + (msg & 0x3c000), 0, m * 128 + 64 * w, (ot >> 3) * 4 + 2 * (n - n1)); bulk_commit(); }
        }
        __syncwarp();
      }
      bulk_wait<0>();
      fence_async_global();
      if (lane == 0 && !spare) st_release(&g_pflag[m * 2 + w][ot >> 3], tag);
      __syncwarp();
    } else {
      if (!spare) { mbar_wait(bars + B_AF + 8 * X_AT, 0); bulk_prefetch(xin + (size_t)blockIdx.x * 16 * DM, 16 * DM * 2); }
      wait_count_lazy(C_MOD, 8 * tag);
      DBGP(12);
      w_arrive(bars + R_MOD);
      #pragma unroll 1
      for (int i = 0; i < nitems; i++) {
        const int item = sp.item[i];
        tma_prefetch_2d(&tmWq, (item >> 3) * 128 + rank * 64, (item & 7) * 64);
        if (i == 0) { wait_count_lazy(C_H1, 256 * tag); w_arrive(bars + R_H1); }
        wait_count_lazy(C_KV + (item >> 3), 32 * tag);
        w_arrive(bars + R_ITEM + 8 * i);
      }
      wait_count_lazy(C_MOD2, 16 * tag);
      #pragma unroll 1
      for (int i = 0; i < nsteps; i++) {
        const int c = sp.ochunk[i][lane & 1];
        if (c < 64) wait_count_lazy(C_CTX + (c >> 1) * 8 + (ot & 7), 4 * tag);
        __syncwarp();
        w_arrive(bars + R_CTX + 8 * i);
        if (i == PF_N - 1) {
          #pragma unroll 1
          for (int k = 0; k < 8 * WAIT_LIM; k++) { if (mbar_try(bars + R_NEAR, 0)) break; }
          bulk_prefetch(w_o + (size_t)blockIdx.x * (NH * DH * DM / NCTA), NH * DH * DM / NCTA * 2);
          #pragma unroll 1
          for (int k = 0; k < PF_N; k++) {
            const int cc = sp.ochunk[k][(ot >> 3) & 1];
            if (cc < 64) bulk_prefetch(sched.kvc + ((size_t)(128 + cc) * SEQ + m * 128) * 64, 16384);
          }
        }
      }
    }
    if (!spare) {
      bar_sync(6, 128);
      asm volatile("setmaxnreg.inc.sync.aligned.u32 88;");
      const int pos = blockIdx.x * 4 + (lane & 1) * 2, col = (blockIdx.x >> 2) * 16 + (blockIdx.x & 3) * 2 + (lane & 1) * 8, src = threadIdx.x >> 1;
      uint32_t gbest = 0, hh = 0, gbf = 0;
      uint2 xx = make_uint2(0, 0);
      if (warp == 3) {
        gbf = __ldcg(reinterpret_cast<const uint32_t*>(g_mod + 5 * DM + col));
        uint32_t have = 0;
        #pragma unroll 1
        for (int n = 0; n < WAIT_LIM; n++) {
          uint2 k[4];
          #pragma unroll
          for (int i = 0; i < 4; i++) k[i] = ld_tagged(&g_keys[i * 32 + lane][0]);
          if (gbest != have) {
            const int g = ((0xffffu - gbest) >> 4) & 127;
            uint4 hv[4];
            #pragma unroll
            for (int i = 0; i < 4; i++) hv[i] = ld_tagged2(&g_row[g][0][i * 64 + lane * 2]);
            xx = ld_tagged(&g_row[g][1][col >> 1]);
            bool ok = xx.y == tag;
            #pragma unroll
            for (int i = 0; i < 4; i++) { ok = ok && hv[i].y == tag && hv[i].w == tag; reinterpret_cast<uint2*>(smem_raw + SM_H2)[i * 32 + lane] = make_uint2(hv[i].x, hv[i].z); }
            if (lane == 0) *reinterpret_cast<uint32_t*>(smem_raw + SM_KEY + 32) = gbest;
            have = __all_sync(0xffffffff, ok) ? gbest : 0;
          }
          bool all = true;
          #pragma unroll
          for (int i = 0; i < 4; i++) { all = all && k[i].y == tag; gbest = max(gbest, k[i].y == tag ? k[i].x : 0u); }
          gbest = __reduce_max_sync(0xffffffff, gbest);
          if (__all_sync(0xffffffff, all) && gbest == have) break;
        }
        w_arrive(bars + R_KEY);
        if (blockIdx.x == 0 && lane == 0) g_epoch = tag;
        hh = lds_u32(base + SM_H2 + col * 2);
        DBGP(13);
      }
      const uint32_t sb16 = gbest & 0xffff0000u;
      const float rsel = __uint_as_float((sb16 & 0x80000000u) ? (sb16 & 0x7fffffffu) : (~sb16 & 0xffff0000u));
      const float rs = rbf(__fdividef(1.f, 1.f + __expf(-rsel)));
      uint4 ya, yb = make_uint4(0, tag, 0, tag);
      #pragma unroll 1
      for (int n = 0; n < WAIT_LIM; n++) {
        ya = ld_tagged2(&g_yll[src][pos]);
        if (src + 64 < FF / 16) yb = ld_tagged2(&g_yll[src + 64][pos]);
        if (n == 0) mbar_wait(bars + R_KEY, 1);
        if (__all_sync(0xffffffff, ya.y == tag && ya.w == tag && yb.y == tag && yb.w == tag)) break;
      }
      float y0 = __uint_as_float(ya.x) + __uint_as_float(yb.x), y1 = __uint_as_float(ya.z) + __uint_as_float(yb.z);
      #pragma unroll
      for (int o = 2; o < 32; o <<= 1) { y0 += __shfl_xor_sync(0xffffffff, y0, o); y1 += __shfl_xor_sync(0xffffffff, y1, o); }
      float2* s_y = reinterpret_cast<float2*>(smem_raw + SM_KEY + 64);
      if (lane < 2) s_y[warp * 2 + lane] = make_float2(y0, y1);
      bar_sync(6, 128);
      if (warp == 3 && lane < 2) {
        y0 = 0.f; y1 = 0.f;
        #pragma unroll
        for (int i = 0; i < 4; i++) { y0 += reinterpret_cast<const float*>(s_y)[i * 4 + lane]; y1 += reinterpret_cast<const float*>(s_y)[i * 4 + 2 + lane]; }
        const float o0 = bf_lo(xx.x) + rbf(bf_lo(gbf) * rbf(bf_lo(hh) + rbf(rbf(y0) * rs)));
        const float o1 = bf_hi(xx.x) + rbf(bf_hi(gbf) * rbf(bf_hi(hh) + rbf(rbf(y1) * rs)));
        *reinterpret_cast<uint32_t*>(out + (size_t)((0xffffu - gbest) & (SEQ - 1)) * DM + col) = pack_bf16(o0, o1);
      }
      DBGP(14);
    }
    __syncwarp();
    cluster_arrive();
    cluster_wait();
  } else {
    asm volatile("setmaxnreg.inc.sync.aligned.u32 240;");
    Ctx x;
    x.w = wg - 1; x.base = base; x.bars = bars; x.nev = 0; x.sched = &sched;
    const int w = x.w, warp4 = warp & 3;
    x.rel = mapa(bars, (warp4 & 1) ^ 1);
    x.rel1 = (threadIdx.x & 127) == 32 || (threadIdx.x & 127) == 64;
    if (warp != 8 || spare) cluster_wait();
    DBG(1);
    uint32_t PA[32], PB[32];
    int vtile = -1;
    if (spare) {
      mod_cta(x, cvec);
    } else {
      const int lane = wg_tid() & 31;
      Row xn[2];
      float acc0[64], acc1[64];
      int s = 2 * w, ph = w;
      #pragma unroll 1
      for (int u = w; u < 8; u += 2) {
        bar_sync(1 + w, 256);
        DBG(4 + (u >> 1) * 3);
        int ps = 0;
        #pragma unroll 1
        for (int kb = 0; kb < 8; kb++) {
          if (u < 2) mbar_wait(bars + B_AF + 8 * kb, 0);
          mbar_wait(bars + B_WF + 8 * s, ph);
          const uint32_t da = desc_lo(base + k_addrA(kb), 16), dw = desc_lo(base + k_addrW(s), 8192);
          wgmma_fence();
          kblock_n128<0>(acc0, da, dw, kb != 0);
          kblock_n128<512>(acc1, da, dw, kb != 0);
          wgmma_commit();
          if (kb == 7) bar_arrive(1 + (w ^ 1), 256);
          if (kb > 0) {
            wgmma_wait<1>();
            mbar_arrive_remote_if(x.rel + B_WE + 8 * ps, x.rel1);
            if (u == 7 && !(kb & 1)) {
              ring_release(x, kb == 2 ? 0 : kb - 3, false);
              if (kb > 2) ring_release(x, kb - 2, false);
            }
          }
          ps = s;
          if (++s == 6) { s = 0; ph ^= 1; }
        }
        Row t[2];
        const int lrow = blockIdx.x * 16 + w * 8 + warp4 * 2;
        if (u == w) { t[0] = ldg_row(xin + (size_t)lrow * DM, lane); t[1] = ldg_row(xin + (size_t)(lrow + 1) * DM, lane); }
        if (u == LN_AT || u == LN_AT + 1) {
          mbar_wait(bars + R_MOD, 0);
          t[0] = ldca_row(g_mod, lane); t[1] = ldca_row(g_mod + DM, lane);
        }
        wgmma_wait<0>();
        fence_regs(acc0); fence_regs(acc1);
        DBG(5 + (u >> 1) * 3);
        mbar_arrive_remote_if(x.rel + B_WE + 8 * ps, x.rel1);
        if (u == 6) { for (int k = 0; k < 5; k++) ring_release(x, k, false); }
        if (u >= 6) ring_release(x, 5, false);
        if (V_AT >= 0 && u == 7) {
          pack_tile(acc0, PA, 1.f, 1.f); pack_tile(acc1, PB, 1.f, 1.f);
          vtile = sp.khead[3] * 16 + mt;
          break;
        }
        s += 2; ph ^= 1; if (s >= 6) { s -= 6; ph ^= 1; }
        if (u == w) layer_norm2(t, xn, QSCALE);
        if ((u == LN_AT || u == LN_AT + 1)) {
          #pragma unroll
          for (int r = 0; r < 2; r++) store_row(sched.h1 + (size_t)(lrow + r) * DM, lane, fma_row(xn[r], one_plus(t[1]), t[0]));
        }
        const int tile = sp.khead[u >> 1] * 16 + mt;
        __nv_bfloat16* dst = kv_tile(x, tile);
        uint32_t D[32];
        pack_tile(acc0, D, 1.f, 1.f); store_tile(dst + 64 * 64, D);
        pack_tile(acc1, D, 1.f, 1.f); store_tile(dst, D);
        if (u == LN_AT || u == LN_AT + 1) publish(x, C_H1);
        publish(x, C_KV + (tile >> 4));
        DBG(6 + (u >> 1) * 3);
      }
    }
    const int last = attention(x, sp.item, nitems, rank, PA, PB, vtile);
    DBG(100);
    const int lane = wg_tid() & 31, cw = w * 4 + warp4, ct = cw * 32 + lane;
    const int row0 = grp * 16 + cw * 2;
    const bool moe_cta = blockIdx.x < FF / 16;
    const unsigned int tag = ld_relaxed(&g_epoch) + 1;
    if (spare) { store_ctx(x, last, PB); __syncwarp(); cluster_arrive(); cluster_wait(); return; }
    const int kl = 3 * nsteps - 3;
    {
      float accA[64], accB[64];
      uint32_t pa = 0, pb = 0;
      #pragma unroll 1
      for (int k = 0; k < kl; k += 3) {
        const uint32_t e0 = oent(k), ea = oent(k + 1), eb = oent(k + 2);
        const uint32_t da = desc_lo(base + w * 8192, 16) + (ea & 7) * 2048;
        o_wait_full(bars, e0);
        o_wait_full(bars, ea);
        uint32_t db = desc_lo(base, 8192) + (e0 & 7) * 2048;
        const bool both = e0 != ea;
        if (both) {
          wgmma_fence();
          kblock_n128<0>(accA, da, db, k != 0); kblock_n128<0, 1024>(accB, da, db, k != 0);
          wgmma_commit();
        }
        if (k > 0) { wgmma_wait<1>(); slot_release(x, pa, false); slot_release(x, pb, false); }
        o_wait_full(bars, eb);
        db = desc_lo(base, 8192) + (eb & 7) * 2048;
        wgmma_fence();
        kblock_n128<1024>(accA, da, db, both); kblock_n128<1024, 1024>(accB, da, db, both);
        wgmma_commit();
        if (k == 0) store_ctx(x, last, PB);
        if (both) { wgmma_wait<1>(); slot_release(x, e0 & 7, false); }
        pa = ea & 7; pb = eb & 7;
      }
      const uint32_t e0 = oent(kl), ea = oent(kl + 1), eb = oent(kl + 2);
      const uint32_t da = desc_lo(base + w * 8192, 16) + (ea & 7) * 2048;
      const uint32_t db0 = desc_lo(base, 8192) + (e0 & 7) * 2048, db1 = desc_lo(base, 8192) + (eb & 7) * 2048;
      o_wait_full(bars, e0);
      o_wait_full(bars, ea);
      o_wait_full(bars, eb);
      wgmma_fence();
      kblock_n128<0>(accA, da, db0, 1); kblock_n128<1024>(accA, da, db1, 1);
      wgmma_commit();
      kblock_n128<0, 1024>(accB, da, db0, 1); kblock_n128<1024, 1024>(accB, da, db1, 1);
      wgmma_commit();
      wgmma_wait<2>();
      slot_release(x, pa, false); slot_release(x, pb, false);
      __syncwarp();
      cluster_arrive();
      const int srow = 16 * warp4 + (lane & 7) + 8 * ((lane >> 3) & 1);
      const uint32_t swz = (((lane >> 4) ^ (srow & 7)) << 4);
      auto stage = [&](const float (&acc)[64], uint32_t off) {
        #pragma unroll
        for (int j = 0; j < 16; j += 2)
          stsm_x4(base + off + srow * 128 + (j >> 3) * 8192 + (((j & 7) << 4) ^ swz),
                  pack_bf16(acc[4*j+0], acc[4*j+1]), pack_bf16(acc[4*j+2], acc[4*j+3]), pack_bf16(acc[4*j+4], acc[4*j+5]), pack_bf16(acc[4*j+6], acc[4*j+7]));
        fence_async_smem();
        publish(x, off);
      };
      mbar_wait(bars + B_RE + 8 * pa, oent(kl + 5) >> 3);
      wgmma_wait<1>();
      fence_regs(accA);
      stage(accA, pa * 32768 + w * 16384);
      mbar_wait(bars + B_RE + 8 * pb, oent(kl + 6) >> 3);
      wgmma_wait<0>();
      fence_regs(accB);
      DBG(101);
      stage(accB, pb * 32768 + w * 16384);
      DBG(102);
    }
    asm volatile("setmaxnreg.dec.sync.aligned.u32 208;");
    const Row ga = ldca_row(g_mod + 2 * DM, lane), sb = ldca_row(g_mod + 3 * DM, lane), cb = ldca_row(g_mod + 4 * DM, lane), gb = ldca_row(g_mod + 5 * DM, lane);
    const Row wr = ldca_row(w_r, lane);
    const uint32_t sD = base + (oent(kl + 3) & 7) * 32768, sW = base + (oent(kl + 4) & 7) * 32768;
    o_wait_full(bars, oent(kl + 3)); o_wait_full(bars, oent(kl + 4));
    Row x1[2];
    #pragma unroll
    for (int r = 0; r < 2; r++) x1[r] = lds_row(sD + 16384 + (cw * 2 + r) * 1024, lane);
    uint4 wgv[4], wuv[4], wdv[4];
    #pragma unroll
    for (int r = 0; r < 4; r++) {
      const uint32_t k = (lane & 7) + ((lane >> 4) << 3), h = (lane & 8) * 2;
      wgv[r] = ldsm_x4_t(sW + (cw * 64 + r * 16 + k) * 32 + h);
      wuv[r] = ldsm_x4_t(sW + 16384 + (cw * 64 + r * 16 + k) * 32 + h);
      wdv[r] = ldsm_x4_t(sD + k * 1024 + (cw * 64 + r * 16) * 2 + h);
    }
    const Row cb1 = one_plus(cb);
    DBG(103);
    mbar_wait(bars + R_PART, 0);
    DBG(104);
    Row h2[2];
    uint32_t key[2];
    {
      uint4 pv[2][4][2];
      const uint32_t po = base + (lane >> 3) * 2048 + cw * 256 + (lane & 7) * 16;
      const uint32_t pa[2] = {po + (oent(kl) & 7) * 32768, po + (oent(kl + 1) & 7) * 32768};
      #pragma unroll
      for (int r = 0; r < 2; r++)
        #pragma unroll
        for (int q = 0; q < 8; q++) pv[r][q >> 1][q & 1] = lds_v4(pa[q >> 2] + (q & 3) * 8192 + r * 128);
      #pragma unroll
      for (int r = 0; r < 2; r++) {
        Row av;
        #pragma unroll
        for (int i = 0; i < 2; i++) {
          av.v[4*i]   = add2(add2(pv[r][0][i].x, pv[r][1][i].x), add2(pv[r][2][i].x, pv[r][3][i].x));
          av.v[4*i+1] = add2(add2(pv[r][0][i].y, pv[r][1][i].y), add2(pv[r][2][i].y, pv[r][3][i].y));
          av.v[4*i+2] = add2(add2(pv[r][0][i].z, pv[r][1][i].z), add2(pv[r][2][i].z, pv[r][3][i].z));
          av.v[4*i+3] = add2(add2(pv[r][0][i].w, pv[r][1][i].w), add2(pv[r][2][i].w, pv[r][3][i].w));
        }
        x1[r] = fma_row(ga, av, x1[r]);
      }
      layer_norm2(x1, h2);
      float sc[2] = {0.f, 0.f};
      #pragma unroll
      for (int r = 0; r < 2; r++) {
        h2[r] = fma_row(h2[r], cb1, sb);
        #pragma unroll
        for (int i = 0; i < 8; i++) sc[r] = fmaf(bf_hi(h2[r].v[i]), bf_hi(wr.v[i]), fmaf(bf_lo(h2[r].v[i]), bf_lo(wr.v[i]), sc[r]));
      }
      #pragma unroll
      for (int o = 16; o > 0; o >>= 1) { sc[0] += __shfl_xor_sync(0xffffffff, sc[0], o); sc[1] += __shfl_xor_sync(0xffffffff, sc[1], o); }
      #pragma unroll
      for (int r = 0; r < 2; r++) {
        const uint32_t rb = pack_bf16(0.f, sc[r]);
        key[r] = (((rb & 0x80000000u) ? ~rb : (rb | 0x80000000u)) & 0xffff0000u) | (0xffffu - (uint32_t)(row0 + r));
      }
    }
    DBG(105);
    float* s_red = reinterpret_cast<float*>(smem_raw + SM_RED);
    uint32_t* s_key = reinterpret_cast<uint32_t*>(smem_raw + SM_KEY);
    const int rb = key[1] > key[0];
    const uint32_t wbest = rb ? key[1] : key[0];
    if (lane == 0) s_key[cw] = wbest;
    bar_sync(5, 256);
    const uint32_t cbest = __reduce_max_sync(0xffffffff, s_key[lane & 7]);
    Row ob, hb, xb;
    #pragma unroll
    for (int i = 0; i < 8; i++) { hb.v[i] = rb ? h2[1].v[i] : h2[0].v[i]; xb.v[i] = rb ? x1[1].v[i] : x1[0].v[i]; }
    if (wbest == cbest) {
      if (lane == 0) st_tagged(&g_keys[grp][0], cbest, tag);
      #pragma unroll
      for (int i = 0; i < 4; i++) st_tagged2(&g_row[grp][0][(i >> 1) * 128 + lane * 4 + (i & 1) * 2], hb.v[2*i], hb.v[2*i+1], tag);
      #pragma unroll
      for (int i = 0; i < 4; i++) st_tagged2(&g_row[grp][1][(i >> 1) * 128 + lane * 4 + (i & 1) * 2], xb.v[2*i], xb.v[2*i+1], tag);
    }
    DBG(106);
    #pragma unroll
    for (int i = 0; i < 8; i++) { ob.v[i] = fma2(gb.v[i], rb ? h2[0].v[i] : h2[1].v[i], rb ? x1[0].v[i] : x1[1].v[i]); }
    store_row(out + (size_t)(row0 + 1 - rb) * DM, lane, ob);
    ob = fma_row(gb, hb, xb);
    if (wbest != cbest) store_row(out + (size_t)(row0 + rb) * DM, lane, ob);
    mbar_wait(bars + R_KEY, 1);
    DBG(107);
    if (moe_cta) {
      float cg[4] = {0, 0, 0, 0}, cu[4] = {0, 0, 0, 0};
      #pragma unroll
      for (int r = 0; r < 4; r++) {
        const uint32_t b0 = lds_u32(base + SM_H2 + (cw * 64 + r * 16) * 2 + (lane & 3) * 4), b1 = lds_u32(base + SM_H2 + (cw * 64 + r * 16) * 2 + 16 + (lane & 3) * 4);
        mma16816(cg, wgv[r], b0, b1); mma16816(cu, wuv[r], b0, b1);
      }
      s_red[cw * 32 + (lane & 3) * 8 + (lane >> 2)] = (lane & 2) ? ((lane & 1) ? cu[2] : cu[0]) : ((lane & 1) ? cg[2] : cg[0]);
      bar_sync(5, 256);
      float g = 0.f;
      #pragma unroll
      for (int i = 0; i < 8; i++) g += s_red[i * 32 + lane];
      g = rbf(g);
      const float u = __shfl_down_sync(0xffffffff, g, 16);
      const float act = rbf(__fdividef(g, 1.f + __expf(-g))) * u;
      const uint32_t a2 = pack_bf16(act, __shfl_down_sync(0xffffffff, act, 1));
      const uint32_t b0 = __shfl_sync(0xffffffff, a2, (lane & 3) * 2), b1 = __shfl_sync(0xffffffff, a2, (lane & 3) * 2 + 8);
      float y0 = 0.f, y1 = 0.f;
      #pragma unroll
      for (int r = 0; r < 4; r++) {
        float c[4] = {0, 0, 0, 0};
        mma16816(c, wdv[r], b0, b1);
        if ((lane & 3) == r) { y0 = c[0]; y1 = c[2]; }
      }
      st_tagged2(&g_yll[blockIdx.x][cw * 64 + (lane & 3) * 16 + (lane >> 2) * 2], __float_as_uint(y0), __float_as_uint(y1), tag);
    }
    DBG(108);
    if (wbest == cbest && wbest != s_key[8]) store_row(out + (size_t)(row0 + rb) * DM, lane, ob);
    DBG(109);
    __syncwarp();
    cluster_wait();
  }
}

typedef CUresult (*EncodeFn)(CUtensorMap*, CUtensorMapDataType, cuuint32_t, void*, const cuuint64_t*, const cuuint64_t*, const cuuint32_t*,
                             const cuuint32_t*, CUtensorMapInterleave, CUtensorMapSwizzle, CUtensorMapL2promotion, CUtensorMapFloatOOBfill);

struct HostState {
  bool ready = false;
  EncodeFn encode = nullptr;
  CUtensorMap tmC, tmH, tmWq, tmWk, tmWv, tmKV, tmWo, tmPart, tmWg, tmWu, tmPl, tmWm;
  Sched sched;
};

void make_map(EncodeFn enc, CUtensorMap* m, const void* ptr, int rank, const cuuint64_t* dims, const cuuint64_t* strides, const cuuint32_t* box, bool swizzle = true) {
  const cuuint32_t es[3] = {1, 1, 1};
  enc(m, CU_TENSOR_MAP_DATA_TYPE_BFLOAT16, rank, const_cast<void*>(ptr), dims, strides, box, es, CU_TENSOR_MAP_INTERLEAVE_NONE,
      swizzle ? CU_TENSOR_MAP_SWIZZLE_128B : CU_TENSOR_MAP_SWIZZLE_NONE, swizzle ? CU_TENSOR_MAP_L2_PROMOTION_L2_128B : CU_TENSOR_MAP_L2_PROMOTION_NONE, CU_TENSOR_MAP_FLOAT_OOB_FILL_NONE);
}
void make_2d(EncodeFn enc, CUtensorMap* m, const void* ptr, int rows, int cols, int box_rows) {
  const cuuint64_t dims[2] = {(cuuint64_t)cols, (cuuint64_t)rows}, strides[1] = {(cuuint64_t)cols * 2};
  const cuuint32_t box[2] = {64, (cuuint32_t)box_rows};
  make_map(enc, m, ptr, 2, dims, strides, box);
}
void make_3d(EncodeFn enc, CUtensorMap* m, const void* ptr, int rows, int chunks, size_t row_stride, size_t chunk_stride) {
  const cuuint64_t dims[3] = {64, (cuuint64_t)rows, (cuuint64_t)chunks}, strides[2] = {row_stride, chunk_stride};
  const cuuint32_t box[3] = {64, 64, 2};
  make_map(enc, m, ptr, 3, dims, strides, box);
}

void make_ffn(EncodeFn enc, CUtensorMap* m, const void* ptr) {
  const cuuint64_t dims[2] = {(cuuint64_t)FF, (cuuint64_t)DM}, strides[1] = {(cuuint64_t)FF * 2};
  const cuuint32_t box[2] = {16, 256};
  make_map(enc, m, ptr, 2, dims, strides, box, false);
}

#define J0_FIRST 0
#define SR 0x213312
#define SEED 12345
#define LU_MARGIN 0
#define SPARE_N 3
void build_sched(Sched& s) {
  memset(&s, 0, sizeof(s));
  const int NP = NCTA / 2, korder[4] = {(KORDER >> 12) & 3, (KORDER >> 8) & 3, (KORDER >> 4) & 3, KORDER & 3};
  const int sround[4][2][3] = {{}, {{1}, {2}}, {{1, 2}, {1, 2}}, {{(SR >> 20) & 3, (SR >> 16) & 3, (SR >> 12) & 3}, {(SR >> 8) & 3, (SR >> 4) & 3, SR & 3}}};
  int jv[4][NP], used[4][8] = {};
  for (int r = 0; r < 4; r++) for (int p = 0; p < NP; p++) jv[r][p] = (r & 2) ? 7 - ((p + 4 * (r & 1)) & 7) : (p + 4 * (r & 1)) & 7;
  for (int q = 0; q < 2; q++) {
    s.pair[NP + q].nitems = SPARE_N;
    for (int i = 0; i < SPARE_N; i++) {
      const int r = sround[SPARE_N][q][i];
      s.pair[NP + q].item[i] = (uint8_t)((r * 8 + used[r][6]++) * 8 + 6);
      for (int p = 0; p < NP; p++) if (jv[r][p] == 6) { jv[r][p] = -2; break; }
    }
  }
  auto cost = [&](int p) {
    int u = 8 - ((p >> 4) < SPARE_N ? 21 : 22), z = 0, none = 0;
    for (int r = 0; r < 4; r++) { u += jv[r][p]; z += jv[r][p] == 0; none += jv[r][p] < 0; }
    return 4 * u * u + (z > 1) + 4 * (none > 1);
  };
  uint32_t rng = SEED;
  for (int it = 0; it < 2000000; it++) {
    if ((it & 255) == 0) { int t = 0; for (int p = 0; p < NP; p++) t += cost(p); if (t == 0) break; }
    rng = rng * 1664525u + 1013904223u;
    const int r = (rng >> 8) & 3, a = (rng >> 12) & 63, b = (rng >> 20) & 63, before = cost(a) + cost(b);
    int t = jv[r][a]; jv[r][a] = jv[r][b]; jv[r][b] = t;
    if (cost(a) + cost(b) > before) { jv[r][b] = jv[r][a]; jv[r][a] = t; }
  }
  int fin[256], done[256];
  for (int p = 0; p < NP + 2; p++) {
    Sched::Pair& q = s.pair[p];
    if (p < NP) {
      for (int k = 0; k < 4; k++) q.khead[k] = (uint8_t)(korder[k] * 8 + (p >> 3));
      for (int r = 0; r < 4; r++) {
        if (jv[r][p] < 0) continue;
        int at = q.nitems++;
        if (J0_FIRST && jv[r][p] == 0 && r != korder[3]) for (; at > 0; at--) q.item[at] = q.item[at - 1];
        q.item[at] = (uint8_t)((r * 8 + used[r][jv[r][p]]++) * 8 + jv[r][p]);
      }
    }
    int t = p < NP ? 0 : -3, e = 1;
    for (int i = 0; i < q.nitems; i++) { t += (q.item[i] & 7) + 2; fin[q.item[i]] = t; done[q.item[i]] = t + (i + 1 < q.nitems ? 2 : 0); e += 8 + 4 * ((q.item[i] & 7) + 1); }
    for (int k = 0; k < 3 * MAX_STEPS + 6; k++) {
      const int n = k > 0 ? k - (SPARE_N & 1) : 0, r = n % 7, f = (e + (r < 4 ? r : r - 1)) % 12;
      q.oent[k] = (uint8_t)((r == 4 ? 6 : f >= 6 ? f + 2 : f) ^ (((n / 7) & 1) << 3));
    }
  }
  for (int p = 0; p < NP + 2; p++)
    for (int i = 0; i < s.pair[p].nitems; i++) {
      const int it = s.pair[p].item[i];
      for (int n = 0; n < 2 * (it & 7) + 2; n++) {
        bool last = true;
        for (int j = n >> 1; j < 8; j++) { const int o = (it & ~7) + j; if (o != it && fin[o] + LU_MARGIN > fin[it]) last = false; }
        if (last) s.pair[p].lastuse[i] |= (uint16_t)(1 << n);
      }
    }
  for (int j = 0; j < 8; j++) {
    int order[NH], left[4];
    for (int h = 0; h < NH; h++) { int k = h; for (; k > 0 && done[order[k - 1] * 8 + j] < done[h * 8 + j]; k--) order[k] = order[k - 1]; order[k] = h; }
    for (int kq = 0; kq < 4; kq++) {
      left[kq] = SPARE_N == 0 ? 16 : kq < SPARE_N ? 20 - SPARE_N : 16 - SPARE_N;
      for (int nh = 0; nh < 2; nh++) { Sched::Pair& q = s.pair[kq * 16 + nh * 8 + j]; q.otask = (uint8_t)(kq * 16 + nh * 8 + j); q.nsteps = (uint8_t)((left[kq] + 1) / 2); q.ochunk[0][0] = 255; }
    }
    for (int n = 0, kq = 0, run = 0; n < 64; ) {
      if (left[kq] > 0 && run < 2) {
        const int pos = --left[kq] + (SPARE_N & 1);
        for (int nh = 0; nh < 2; nh++) s.pair[kq * 16 + nh * 8 + j].ochunk[pos >> 1][pos & 1] = (uint8_t)(order[n >> 1] * 2 + 1 - (n & 1));
        n++; run++;
      } else { kq = (kq + 1) & 3; run = 0; }
    }
  }
}

}

extern "C" void kernel_launch(void* const* d_in, const int* in_sizes, int n_in, void* d_out, int out_size) {
  (void)in_sizes; (void)n_in; (void)out_size;
  const __nv_bfloat16* x     = (const __nv_bfloat16*)d_in[0];
  const __nv_bfloat16* ckv   = (const __nv_bfloat16*)d_in[1];
  const __nv_bfloat16* w_q   = (const __nv_bfloat16*)d_in[2];
  const __nv_bfloat16* w_uk  = (const __nv_bfloat16*)d_in[3];
  const __nv_bfloat16* w_uv  = (const __nv_bfloat16*)d_in[4];
  const __nv_bfloat16* w_o   = (const __nv_bfloat16*)d_in[5];
  const __nv_bfloat16* w_r   = (const __nv_bfloat16*)d_in[7];
  const __nv_bfloat16* w_g   = (const __nv_bfloat16*)d_in[8];
  const __nv_bfloat16* w_u   = (const __nv_bfloat16*)d_in[9];
  const __nv_bfloat16* w_d   = (const __nv_bfloat16*)d_in[10];
  const __nv_bfloat16* cvec  = (const __nv_bfloat16*)d_in[11];
  const __nv_bfloat16* w_mod = (const __nv_bfloat16*)d_in[12];
  __nv_bfloat16* out = (__nv_bfloat16*)d_out;

  static HostState st;
  if (!st.ready) {
    void* fn = nullptr; cudaDriverEntryPointQueryResult qr;
    cudaGetDriverEntryPoint("cuTensorMapEncodeTiled", &fn, cudaEnableDefault, &qr);
    st.encode = (EncodeFn)fn;
    cudaFuncSetAttribute(k_fused, cudaFuncAttributeMaxDynamicSharedMemorySize, SMEM);
    build_sched(st.sched);
    void *p_kvc, *p_h1, *p_part;
    cudaGetSymbolAddress(&p_kvc, g_kvc); cudaGetSymbolAddress(&p_h1, g_h1); cudaGetSymbolAddress(&p_part, g_part);
    st.sched.kvc = (__nv_bfloat16*)p_kvc; st.sched.h1 = (__nv_bfloat16*)p_h1;
    make_2d(st.encode, &st.tmH, p_h1, SEQ, DM, 64);
    make_2d(st.encode, &st.tmKV, p_kvc, 192 * SEQ, 64, 128);
    make_3d(st.encode, &st.tmPart, p_part, SEQ, 32, 128, (size_t)SEQ * 128);
    { const cuuint64_t dims[3] = {64, (cuuint64_t)SEQ, 32}, strides[2] = {128, (cuuint64_t)SEQ * 128}; const cuuint32_t box[3] = {64, 16, 4};
      make_map(st.encode, &st.tmPl, p_part, 3, dims, strides, box, false); }
    st.ready = true;
  }
  make_2d(st.encode, &st.tmC, ckv, SEQ, DM, 128);
  make_2d(st.encode, &st.tmWq, w_q, DM, NH * DH, 64);
  make_2d(st.encode, &st.tmWk, w_uk, DM, NH * DH, 64);
  make_2d(st.encode, &st.tmWv, w_uv, DM, NH * DH, 64);
  make_3d(st.encode, &st.tmWo, w_o, NH * DH, DM / 64, (size_t)DM * 2, 128);
  make_3d(st.encode, &st.tmWm, w_mod, DM, 6 * DM / 64, (size_t)6 * DM * 2, 128);
  make_ffn(st.encode, &st.tmWg, w_g);
  make_ffn(st.encode, &st.tmWu, w_u);

  k_fused<<<NGRID, 384, SMEM, cudaStreamPerThread>>>(st.tmC, st.tmH, st.tmWq, st.tmWk, st.tmWv, st.tmKV, st.tmWo, st.tmPart, st.tmWg, st.tmWu, st.tmPl, st.tmWm, st.sched,
                                                     x, cvec, w_o, w_r, w_g, w_u, w_d, out);
}
```

```cpp
#include <cuda_runtime.h>
#include <cuda_bf16.h>
#include <cuda.h>
#include <stdint.h>
#include <string.h>
#include <math.h>

namespace {

constexpr int SEQ = 2048, DM = 512, NH = 32, DH = 128, FF = 1792;
constexpr int NCTA = 128, NGRID = 132;

__device__ __nv_bfloat16 g_kvc[192 * SEQ * 64];
__device__ __nv_bfloat16 g_h1[SEQ * DM];
__device__ __nv_bfloat16 g_part[32 * SEQ * 64];
__device__ __align__(16) __nv_bfloat16 g_mod[6 * DM];
constexpr int C_MOD = 0, C_MOD2 = 16, C_H1 = 32, C_KV = 64, C_CTX = 128, C_END = 384;
__device__ unsigned int g_cnt[C_END];
__device__ unsigned int g_epoch;
__device__ __align__(128) unsigned int g_pflag[32][32];
__device__ __align__(128) uint2 g_keys[128][4];
__device__ __align__(16) uint2 g_row[128][2][DM / 2];
__device__ __align__(16) uint2 g_yll[FF / 16][DM];

#define DBG(i)
#define DBGP(i)

__device__ __forceinline__ uint32_t smem_u32(const void* p) { return (uint32_t)__cvta_generic_to_shared(p); }
__device__ __forceinline__ int wg_tid() { int t; asm volatile("mov.u32 %0, %%tid.x;" : "=r"(t)); return t & 127; }
__device__ __forceinline__ uint32_t clk32() { uint32_t c; asm volatile("mov.u32 %0, %%clock;" : "=r"(c)); return c; }
__device__ __forceinline__ void mbar_arrive(uint32_t bar) { asm volatile("mbarrier.arrive.shared::cta.b64 _, [%0];" :: "r"(bar) : "memory"); }
__device__ __forceinline__ uint32_t mapa(uint32_t addr, uint32_t cta) { uint32_t r; asm("mapa.shared::cluster.u32 %0, %1, %2;" : "=r"(r) : "r"(addr), "r"(cta)); return r; }
__device__ __forceinline__ void mbar_arrive_remote_if(uint32_t cluster_addr, bool pred) {
  asm volatile("{\n.reg .pred p;\nsetp.ne.u32 p, %1, 0;\n@p mbarrier.arrive.shared::cluster.b64 _, [%0];\n}" :: "r"(cluster_addr), "r"((uint32_t)pred) : "memory");
}
__device__ __forceinline__ bool mbar_try(uint32_t bar, uint32_t parity) {
  uint32_t done;
  asm volatile("{\n.reg .pred p;\nmbarrier.try_wait.parity.shared::cta.b64 p, [%1], %2;\nselp.u32 %0, 1, 0, p;\n}" : "=r"(done) : "r"(bar), "r"(parity) : "memory");
  return done;
}
#define WAIT_LIM (1 << 14)
__device__ __forceinline__ void mbar_wait(uint32_t bar, uint32_t parity) {
  #pragma unroll 1
  for (int n = 0; n < WAIT_LIM; n++) { if (mbar_try(bar, parity)) break; }
}
__device__ __forceinline__ unsigned int ld_acquire(const unsigned int* p) {
  unsigned int v; asm volatile("ld.acquire.gpu.global.u32 %0, [%1];" : "=r"(v) : "l"(p) : "memory"); return v;
}
__device__ __forceinline__ unsigned int ld_relaxed(const unsigned int* p) {
  unsigned int v; asm volatile("ld.relaxed.gpu.global.u32 %0, [%1];" : "=r"(v) : "l"(p) : "memory"); return v;
}
__device__ __forceinline__ void wait_count_lazy(int idx, unsigned int target) {
  #pragma unroll 1
  for (int n = 0; n < WAIT_LIM; n++) { if ((int)(ld_relaxed(&g_cnt[idx]) - target) >= 0) break; __nanosleep(100); }
  ld_acquire(&g_cnt[idx]);
}
__device__ __forceinline__ uint4 ld_tagged2(const void* p) {
  uint4 v;
  asm volatile("{\n.reg .b64 a, b;\nld.relaxed.gpu.global.v2.u64 {a, b}, [%4];\nmov.b64 {%0, %1}, a;\nmov.b64 {%2, %3}, b;\n}"
    : "=r"(v.x), "=r"(v.y), "=r"(v.z), "=r"(v.w) : "l"(p) : "memory");
  return v;
}
__device__ __forceinline__ uint2 ld_tagged(const void* p) {
  uint2 v; asm volatile("{\n.reg .b64 a;\nld.relaxed.gpu.global.u64 a, [%2];\nmov.b64 {%0, %1}, a;\n}" : "=r"(v.x), "=r"(v.y) : "l"(p) : "memory"); return v;
}
__device__ __forceinline__ void st_tagged2(void* p, uint32_t a, uint32_t b, uint32_t tag) {
  asm volatile("{\n.reg .b64 a, b;\nmov.b64 a, {%1, %3};\nmov.b64 b, {%2, %3};\nst.relaxed.gpu.global.v2.u64 [%0], {a, b};\n}" :: "l"(p), "r"(a), "r"(b), "r"(tag) : "memory");
}
__device__ __forceinline__ void st_tagged(void* p, uint32_t a, uint32_t tag) {
  asm volatile("{\n.reg .b64 a;\nmov.b64 a, {%1, %2};\nst.relaxed.gpu.global.u64 [%0], a;\n}" :: "l"(p), "r"(a), "r"(tag) : "memory");
}
__device__ __forceinline__ void stg_v4(void* p, uint32_t a, uint32_t b, uint32_t c, uint32_t d) {
  asm volatile("st.global.v4.u32 [%0], {%1, %2, %3, %4};" :: "l"(p), "r"(a), "r"(b), "r"(c), "r"(d) : "memory");
}
__device__ __forceinline__ uint4 lds_v4(uint32_t addr) {
  uint4 v; asm volatile("ld.shared.v4.u32 {%0, %1, %2, %3}, [%4];" : "=r"(v.x), "=r"(v.y), "=r"(v.z), "=r"(v.w) : "r"(addr) : "memory"); return v;
}
__device__ __forceinline__ uint32_t lds_u32(uint32_t addr) { uint32_t v; asm volatile("ld.shared.u32 %0, [%1];" : "=r"(v) : "r"(addr) : "memory"); return v; }
__device__ __forceinline__ void sts_v4(uint32_t addr, uint32_t a, uint32_t b, uint32_t c, uint32_t d) {
  asm volatile("st.shared.v4.u32 [%0], {%1, %2, %3, %4};" :: "r"(addr), "r"(a), "r"(b), "r"(c), "r"(d) : "memory");
}
#define ELECT "{\n.reg .pred p;\nelect.sync _|p, 0xffffffff;\n@p "
__device__ __forceinline__ void w_mbar_init(uint32_t bar, uint32_t cnt) { asm volatile(ELECT "mbarrier.init.shared::cta.b64 [%0], %1;\n}" :: "r"(bar), "r"(cnt) : "memory"); }
__device__ __forceinline__ void w_expect_tx(uint32_t bar, uint32_t bytes) { asm volatile(ELECT "mbarrier.arrive.expect_tx.shared::cta.b64 _, [%0], %1;\n}" :: "r"(bar), "r"(bytes) : "memory"); }
__device__ __forceinline__ void w_arrive(uint32_t bar) { asm volatile(ELECT "mbarrier.arrive.shared::cta.b64 _, [%0];\n}" :: "r"(bar) : "memory"); }
__device__ __forceinline__ void tma_load_2d(uint32_t dst, const CUtensorMap* tm, uint32_t bar, int c0, int c1) {
  asm volatile(ELECT "cp.async.bulk.tensor.2d.shared::cluster.global.mbarrier::complete_tx::bytes [%0], [%1, {%3, %4}], [%2];\n}"
    :: "r"(dst), "l"(tm), "r"(bar), "r"(c0), "r"(c1) : "memory");
}
__device__ __forceinline__ void tma_load_2d_mc(uint32_t dst, const CUtensorMap* tm, uint32_t bar, int c0, int c1) {
  asm volatile(ELECT "cp.async.bulk.tensor.2d.shared::cluster.global.mbarrier::complete_tx::bytes.multicast::cluster [%0], [%1, {%3, %4}], [%2], %5;\n}"
    :: "r"(dst), "l"(tm), "r"(bar), "r"(c0), "r"(c1), "h"((uint16_t)3) : "memory");
}
__device__ __forceinline__ void tma_load_3d(uint32_t dst, const CUtensorMap* tm, uint32_t bar, int c0, int c1, int c2) {
  asm volatile(ELECT "cp.async.bulk.tensor.3d.shared::cluster.global.mbarrier::complete_tx::bytes [%0], [%1, {%3, %4, %5}], [%2];\n}"
    :: "r"(dst), "l"(tm), "r"(bar), "r"(c0), "r"(c1), "r"(c2) : "memory");
}
__device__ __forceinline__ void tma_load_3d_mc(uint32_t dst, const CUtensorMap* tm, uint32_t bar, int c0, int c1, int c2) {
  asm volatile(ELECT "cp.async.bulk.tensor.3d.shared::cluster.global.mbarrier::complete_tx::bytes.multicast::cluster [%0], [%1, {%3, %4, %5}], [%2], %6;\n}"
    :: "r"(dst), "l"(tm), "r"(bar), "r"(c0), "r"(c1), "r"(c2), "h"((uint16_t)3) : "memory");
}
__device__ __forceinline__ uint64_t evict_first() { uint64_t a; asm("createpolicy.fractional.L2::evict_first.b64 %0, 1.0;" : "=l"(a)); return a; }
__device__ __forceinline__ void tma_load_2d_mc(uint32_t dst, const CUtensorMap* tm, uint32_t bar, int c0, int c1, bool ef) {
  if (!ef) tma_load_2d_mc(dst, tm, bar, c0, c1); else
  asm volatile(ELECT "cp.async.bulk.tensor.2d.shared::cluster.global.mbarrier::complete_tx::bytes.multicast::cluster.L2::cache_hint [%0], [%1, {%3, %4}], [%2], %5, %6;\n}"
    :: "r"(dst), "l"(tm), "r"(bar), "r"(c0), "r"(c1), "h"((uint16_t)3), "l"(evict_first()) : "memory");
}
__device__ __forceinline__ void bulk_load(uint32_t dst, const void* src, uint32_t bytes, uint32_t bar) {
  asm volatile(ELECT "cp.async.bulk.shared::cluster.global.mbarrier::complete_tx::bytes [%0], [%1], %2, [%3];\n}" :: "r"(dst), "l"(src), "r"(bytes), "r"(bar) : "memory");
}
__device__ __forceinline__ void tma_prefetch_2d(const CUtensorMap* tm, int c0, int c1) {
  asm volatile(ELECT "cp.async.bulk.prefetch.tensor.2d.L2.global [%0, {%1, %2}];\n}" :: "l"(tm), "r"(c0), "r"(c1) : "memory");
}
__device__ __forceinline__ void bulk_prefetch(const void* p, uint32_t bytes) {
  asm volatile(ELECT "cp.async.bulk.prefetch.L2.global [%0], %1;\n}" :: "l"(p), "r"(bytes) : "memory");
}
__device__ __forceinline__ void tma_store_3d(const CUtensorMap* tm, uint32_t src, int c0, int c1, int c2) {
  asm volatile("cp.async.bulk.tensor.3d.global.shared::cta.bulk_group [%0, {%2, %3, %4}], [%1];"
    :: "l"(tm), "r"(src), "r"(c0), "r"(c1), "r"(c2) : "memory");
}
__device__ __forceinline__ void st_release(unsigned int* p, unsigned int v) { asm volatile("st.release.gpu.global.u32 [%0], %1;" :: "l"(p), "r"(v) : "memory"); }
__device__ __forceinline__ void red_release(int idx) { asm volatile("red.release.gpu.global.add.u32 [%0], 1;" :: "l"(&g_cnt[idx]) : "memory"); }
__device__ __forceinline__ void prefetch_tmap(const CUtensorMap* tm) { asm volatile("prefetch.tensormap [%0];" :: "l"(tm) : "memory"); }
__device__ __forceinline__ void bulk_commit() { asm volatile("cp.async.bulk.commit_group;" ::: "memory"); }
template<int N> __device__ __forceinline__ void bulk_wait() { asm volatile("cp.async.bulk.wait_group %0;" :: "n"(N) : "memory"); }
__device__ __forceinline__ void bar_sync(int id, int n) { asm volatile("bar.sync %0, %1;" :: "r"(id), "r"(n) : "memory"); }
__device__ __forceinline__ void bar_arrive(int id, int n) { asm volatile("bar.arrive %0, %1;" :: "r"(id), "r"(n) : "memory"); }
__device__ __forceinline__ void fence_async_smem() { asm volatile("fence.proxy.async.shared::cta;" ::: "memory"); }
__device__ __forceinline__ void fence_async_global() { asm volatile("fence.proxy.async.global;" ::: "memory"); }
__device__ __forceinline__ void fence_mbar_init() { asm volatile("fence.mbarrier_init.release.cluster;" ::: "memory"); }
__device__ __forceinline__ void cluster_arrive() { asm volatile("barrier.cluster.arrive.relaxed.aligned;" ::: "memory"); }
__device__ __forceinline__ void cluster_wait() { asm volatile("barrier.cluster.wait.aligned;" ::: "memory"); }
__device__ __forceinline__ uint32_t cluster_ctarank() { uint32_t r; asm volatile("mov.u32 %0, %%cluster_ctarank;" : "=r"(r)); return r; }
__device__ __forceinline__ void wgmma_fence() { asm volatile("wgmma.fence.sync.aligned;" ::: "memory"); }
__device__ __forceinline__ void wgmma_commit() { asm volatile("wgmma.commit_group.sync.aligned;" ::: "memory"); }
template<int N> __device__ __forceinline__ void wgmma_wait() { asm volatile("wgmma.wait_group.sync.aligned %0;" :: "n"(N) : "memory"); }
__device__ __forceinline__ float ex2(float x) { float y; asm("ex2.approx.ftz.f32 %0, %1;" : "=f"(y) : "f"(x)); return y; }
__device__ __forceinline__ float rcp_fast(float x) { float y; asm("rcp.approx.ftz.f32 %0, %1;" : "=f"(y) : "f"(x)); return y; }
__device__ __forceinline__ uint32_t pack_bf16(float lo, float hi) { uint32_t r; asm("cvt.rn.bf16x2.f32 %0, %1, %2;" : "=r"(r) : "f"(hi), "f"(lo)); return r; }
__device__ __forceinline__ float rbf(float x) { return __uint_as_float(pack_bf16(0.f, x)); }
__device__ __forceinline__ float bf_lo(uint32_t v) { return __uint_as_float(v << 16); }
__device__ __forceinline__ float bf_hi(uint32_t v) { return __uint_as_float(v & 0xffff0000u); }
__device__ __forceinline__ uint32_t add2(uint32_t a, uint32_t b) { uint32_t r; asm("add.rn.bf16x2 %0, %1, %2;" : "=r"(r) : "r"(a), "r"(b)); return r; }
__device__ __forceinline__ uint32_t fma2(uint32_t a, uint32_t b, uint32_t c) { uint32_t r; asm("fma.rn.bf16x2 %0, %1, %2, %3;" : "=r"(r) : "r"(a), "r"(b), "r"(c)); return r; }
__device__ __forceinline__ uint4 ldsm_x4_t(uint32_t addr) {
  uint4 v; asm volatile("ldmatrix.sync.aligned.m8n8.x4.trans.shared.b16 {%0, %1, %2, %3}, [%4];" : "=r"(v.x), "=r"(v.y), "=r"(v.z), "=r"(v.w) : "r"(addr) : "memory"); return v;
}
__device__ __forceinline__ void mma16816(float (&c)[4], const uint4& a, uint32_t b0, uint32_t b1) {
  asm("mma.sync.aligned.m16n8k16.row.col.f32.bf16.bf16.f32 {%0, %1, %2, %3}, {%4, %5, %6, %7}, {%8, %9}, {%0, %1, %2, %3};"
    : "+f"(c[0]), "+f"(c[1]), "+f"(c[2]), "+f"(c[3]) : "r"(a.x), "r"(a.y), "r"(a.z), "r"(a.w), "r"(b0), "r"(b1));
}
__device__ __forceinline__ void stsm_x4(uint32_t addr, uint32_t r0, uint32_t r1, uint32_t r2, uint32_t r3) {
  asm volatile("stmatrix.sync.aligned.m8n8.x4.shared.b16 [%0], {%1, %2, %3, %4};" :: "r"(addr), "r"(r0), "r"(r1), "r"(r2), "r"(r3) : "memory");
}
template<int N> __device__ __forceinline__ void fence_regs(float (&a)[N]) {
  #pragma unroll
  for (int i = 0; i < N; i++) asm volatile("" : "+f"(a[i]) :: "memory");
}
template<int N> __device__ __forceinline__ void fence_regs_u(uint32_t (&a)[N]) {
  #pragma unroll
  for (int i = 0; i < N; i++) asm volatile("" : "+r"(a[i]) :: "memory");
}
__device__ __forceinline__ uint32_t desc_lo(uint32_t addr, uint32_t lbo) { return ((addr & 0x3FFFF) >> 4) | ((lbo >> 4) << 16); }

template<int TB, int OA, int OB> __device__ __forceinline__ void wgmma_ss_n128(float (&d)[64], uint32_t da, uint32_t db, int sd) {
  asm volatile("{\n.reg .pred p;\n.reg .b32 ta, tb;\n.reg .b64 da, db;\nsetp.ne.b32 p, %66, 0;\nadd.u32 ta, %64, %68;\nadd.u32 tb, %65, %69;\nmov.b64 da, {ta, 0x40000040};\nmov.b64 db, {tb, 0x40000040};\n"
    "wgmma.mma_async.sync.aligned.m64n128k16.f32.bf16.bf16 "
    "{%0, %1, %2, %3, %4, %5, %6, %7, %8, %9, %10, %11, %12, %13, %14, %15, %16, %17, %18, %19, %20, %21, %22, %23, %24, %25, %26, %27, %28, %29, %30, %31, %32, %33, %34, %35, %36, %37, %38, %39, %40, %41, %42, %43, %44, %45, %46, %47, %48, %49, %50, %51, %52, %53, %54, %55, %56, %57, %58, %59, %60, %61, %62, %63}, da, db, p, 1, 1, 0, %67;\n}\n"
    : "+f"(d[0]), "+f"(d[1]), "+f"(d[2]), "+f"(d[3]), "+f"(d[4]), "+f"(d[5]), "+f"(d[6]), "+f"(d[7]), "+f"(d[8]), "+f"(d[9]), "+f"(d[10]), "+f"(d[11]), "+f"(d[12]), "+f"(d[13]), "+f"(d[14]), "+f"(d[15]), "+f"(d[16]), "+f"(d[17]), "+f"(d[18]), "+f"(d[19]), "+f"(d[20]), "+f"(d[21]), "+f"(d[22]), "+f"(d[23]), "+f"(d[24]), "+f"(d[25]), "+f"(d[26]), "+f"(d[27]), "+f"(d[28]), "+f"(d[29]), "+f"(d[30]), "+f"(d[31]), "+f"(d[32]), "+f"(d[33]), "+f"(d[34]), "+f"(d[35]), "+f"(d[36]), "+f"(d[37]), "+f"(d[38]), "+f"(d[39]), "+f"(d[40]), "+f"(d[41]), "+f"(d[42]), "+f"(d[43]), "+f"(d[44]), "+f"(d[45]), "+f"(d[46]), "+f"(d[47]), "+f"(d[48]), "+f"(d[49]), "+f"(d[50]), "+f"(d[51]), "+f"(d[52]), "+f"(d[53]), "+f"(d[54]), "+f"(d[55]), "+f"(d[56]), "+f"(d[57]), "+f"(d[58]), "+f"(d[59]), "+f"(d[60]), "+f"(d[61]), "+f"(d[62]), "+f"(d[63])
    : "r"(da), "r"(db), "r"(sd), "n"(TB), "n"(OA), "n"(OB));
}
template<int TB, int OB> __device__ __forceinline__ void wgmma_rs_n128(float (&d)[64], uint32_t a0, uint32_t a1, uint32_t a2, uint32_t a3, uint32_t db, int sd) {
  asm volatile("{\n.reg .pred p;\n.reg .b32 tb;\n.reg .b64 db;\nsetp.ne.b32 p, %69, 0;\nadd.u32 tb, %68, %71;\nmov.b64 db, {tb, 0x40000040};\n"
    "wgmma.mma_async.sync.aligned.m64n128k16.f32.bf16.bf16 "
    "{%0, %1, %2, %3, %4, %5, %6, %7, %8, %9, %10, %11, %12, %13, %14, %15, %16, %17, %18, %19, %20, %21, %22, %23, %24, %25, %26, %27, %28, %29, %30, %31, %32, %33, %34, %35, %36, %37, %38, %39, %40, %41, %42, %43, %44, %45, %46, %47, %48, %49, %50, %51, %52, %53, %54, %55, %56, %57, %58, %59, %60, %61, %62, %63}, {%64,%65,%66,%67}, db, p, 1, 1, %70;\n}\n"
    : "+f"(d[0]), "+f"(d[1]), "+f"(d[2]), "+f"(d[3]), "+f"(d[4]), "+f"(d[5]), "+f"(d[6]), "+f"(d[7]), "+f"(d[8]), "+f"(d[9]), "+f"(d[10]), "+f"(d[11]), "+f"(d[12]), "+f"(d[13]), "+f"(d[14]), "+f"(d[15]), "+f"(d[16]), "+f"(d[17]), "+f"(d[18]), "+f"(d[19]), "+f"(d[20]), "+f"(d[21]), "+f"(d[22]), "+f"(d[23]), "+f"(d[24]), "+f"(d[25]), "+f"(d[26]), "+f"(d[27]), "+f"(d[28]), "+f"(d[29]), "+f"(d[30]), "+f"(d[31]), "+f"(d[32]), "+f"(d[33]), "+f"(d[34]), "+f"(d[35]), "+f"(d[36]), "+f"(d[37]), "+f"(d[38]), "+f"(d[39]), "+f"(d[40]), "+f"(d[41]), "+f"(d[42]), "+f"(d[43]), "+f"(d[44]), "+f"(d[45]), "+f"(d[46]), "+f"(d[47]), "+f"(d[48]), "+f"(d[49]), "+f"(d[50]), "+f"(d[51]), "+f"(d[52]), "+f"(d[53]), "+f"(d[54]), "+f"(d[55]), "+f"(d[56]), "+f"(d[57]), "+f"(d[58]), "+f"(d[59]), "+f"(d[60]), "+f"(d[61]), "+f"(d[62]), "+f"(d[63])
    : "r"(a0), "r"(a1), "r"(a2), "r"(a3), "r"(db), "r"(sd), "n"(TB), "n"(OB));
}
template<int TB, int OA, int OB> __device__ __forceinline__ void wgmma_ss_n64(float (&d)[32], uint32_t da, uint32_t db, int sd) {
  asm volatile("{\n.reg .pred p;\n.reg .b32 ta, tb;\n.reg .b64 da, db;\nsetp.ne.b32 p, %34, 0;\nadd.u32 ta, %32, %36;\nadd.u32 tb, %33, %37;\nmov.b64 da, {ta, 0x40000040};\nmov.b64 db, {tb, 0x40000040};\n"
    "wgmma.mma_async.sync.aligned.m64n64k16.f32.bf16.bf16 "
    "{%0, %1, %2, %3, %4, %5, %6, %7, %8, %9, %10, %11, %12, %13, %14, %15, %16, %17, %18, %19, %20, %21, %22, %23, %24, %25, %26, %27, %28, %29, %30, %31}, da, db, p, 1, 1, 0, %35;\n}\n"
    : "+f"(d[0]), "+f"(d[1]), "+f"(d[2]), "+f"(d[3]), "+f"(d[4]), "+f"(d[5]), "+f"(d[6]), "+f"(d[7]), "+f"(d[8]), "+f"(d[9]), "+f"(d[10]), "+f"(d[11]), "+f"(d[12]), "+f"(d[13]), "+f"(d[14]), "+f"(d[15]), "+f"(d[16]), "+f"(d[17]), "+f"(d[18]), "+f"(d[19]), "+f"(d[20]), "+f"(d[21]), "+f"(d[22]), "+f"(d[23]), "+f"(d[24]), "+f"(d[25]), "+f"(d[26]), "+f"(d[27]), "+f"(d[28]), "+f"(d[29]), "+f"(d[30]), "+f"(d[31])
    : "r"(da), "r"(db), "r"(sd), "n"(TB), "n"(OA), "n"(OB));
}
template<int TB, int OA, int OB> __device__ __forceinline__ void wgmma_ss_n128_new(float (&d)[64], uint32_t da, uint32_t db) {
  asm volatile("{\n.reg .pred p;\n.reg .b32 ta, tb;\n.reg .b64 da, db;\nsetp.ne.b32 p, %66, 0;\nadd.u32 ta, %64, %68;\nadd.u32 tb, %65, %69;\nmov.b64 da, {ta, 0x40000040};\nmov.b64 db, {tb, 0x40000040};\n"
    "wgmma.mma_async.sync.aligned.m64n128k16.f32.bf16.bf16 "
    "{%0, %1, %2, %3, %4, %5, %6, %7, %8, %9, %10, %11, %12, %13, %14, %15, %16, %17, %18, %19, %20, %21, %22, %23, %24, %25, %26, %27, %28, %29, %30, %31, %32, %33, %34, %35, %36, %37, %38, %39, %40, %41, %42, %43, %44, %45, %46, %47, %48, %49, %50, %51, %52, %53, %54, %55, %56, %57, %58, %59, %60, %61, %62, %63}, da, db, p, 1, 1, 0, %67;\n}\n"
    : "=f"(d[0]), "=f"(d[1]), "=f"(d[2]), "=f"(d[3]), "=f"(d[4]), "=f"(d[5]), "=f"(d[6]), "=f"(d[7]), "=f"(d[8]), "=f"(d[9]), "=f"(d[10]), "=f"(d[11]), "=f"(d[12]), "=f"(d[13]), "=f"(d[14]), "=f"(d[15]), "=f"(d[16]), "=f"(d[17]), "=f"(d[18]), "=f"(d[19]), "=f"(d[20]), "=f"(d[21]), "=f"(d[22]), "=f"(d[23]), "=f"(d[24]), "=f"(d[25]), "=f"(d[26]), "=f"(d[27]), "=f"(d[28]), "=f"(d[29]), "=f"(d[30]), "=f"(d[31]), "=f"(d[32]), "=f"(d[33]), "=f"(d[34]), "=f"(d[35]), "=f"(d[36]), "=f"(d[37]), "=f"(d[38]), "=f"(d[39]), "=f"(d[40]), "=f"(d[41]), "=f"(d[42]), "=f"(d[43]), "=f"(d[44]), "=f"(d[45]), "=f"(d[46]), "=f"(d[47]), "=f"(d[48]), "=f"(d[49]), "=f"(d[50]), "=f"(d[51]), "=f"(d[52]), "=f"(d[53]), "=f"(d[54]), "=f"(d[55]), "=f"(d[56]), "=f"(d[57]), "=f"(d[58]), "=f"(d[59]), "=f"(d[60]), "=f"(d[61]), "=f"(d[62]), "=f"(d[63])
    : "r"(da), "r"(db), "n"(0), "n"(TB), "n"(OA), "n"(OB));
}
template<int TB, int OA, int OB> __device__ __forceinline__ void wgmma_ss_n64_new(float (&d)[32], uint32_t da, uint32_t db) {
  asm volatile("{\n.reg .pred p;\n.reg .b32 ta, tb;\n.reg .b64 da, db;\nsetp.ne.b32 p, %34, 0;\nadd.u32 ta, %32, %36;\nadd.u32 tb, %33, %37;\nmov.b64 da, {ta, 0x40000040};\nmov.b64 db, {tb, 0x40000040};\n"
    "wgmma.mma_async.sync.aligned.m64n64k16.f32.bf16.bf16 "
    "{%0, %1, %2, %3, %4, %5, %6, %7, %8, %9, %10, %11, %12, %13, %14, %15, %16, %17, %18, %19, %20, %21, %22, %23, %24, %25, %26, %27, %28, %29, %30, %31}, da, db, p, 1, 1, 0, %35;\n}\n"
    : "=f"(d[0]), "=f"(d[1]), "=f"(d[2]), "=f"(d[3]), "=f"(d[4]), "=f"(d[5]), "=f"(d[6]), "=f"(d[7]), "=f"(d[8]), "=f"(d[9]), "=f"(d[10]), "=f"(d[11]), "=f"(d[12]), "=f"(d[13]), "=f"(d[14]), "=f"(d[15]), "=f"(d[16]), "=f"(d[17]), "=f"(d[18]), "=f"(d[19]), "=f"(d[20]), "=f"(d[21]), "=f"(d[22]), "=f"(d[23]), "=f"(d[24]), "=f"(d[25]), "=f"(d[26]), "=f"(d[27]), "=f"(d[28]), "=f"(d[29]), "=f"(d[30]), "=f"(d[31])
    : "r"(da), "r"(db), "n"(0), "n"(TB), "n"(OA), "n"(OB));
}
template<int OA, int OB = 0> __device__ __forceinline__ void kblock_n128(float (&d)[64], uint32_t da, uint32_t db, int sd) {
  wgmma_ss_n128<1, OA, OB>(d, da, db, sd); wgmma_ss_n128<1, OA + 2, OB + 128>(d, da, db, 1);
  wgmma_ss_n128<1, OA + 4, OB + 256>(d, da, db, 1); wgmma_ss_n128<1, OA + 6, OB + 384>(d, da, db, 1);
}

__device__ __forceinline__ float quad_sum(float v) {
  v += __shfl_xor_sync(0xffffffff, v, 1);
  v += __shfl_xor_sync(0xffffffff, v, 2);
  return v;
}
struct Row { uint32_t v[8]; };
template<class F> __device__ __forceinline__ Row load_row(const __nv_bfloat16* p, int lane, F ld) {
  const uint4 a = ld(reinterpret_cast<const uint4*>(p) + lane), b = ld(reinterpret_cast<const uint4*>(p) + 32 + lane);
  return Row{{a.x, a.y, a.z, a.w, b.x, b.y, b.z, b.w}};
}
__device__ __forceinline__ Row ldg_row(const __nv_bfloat16* p, int lane) { return load_row(p, lane, [](const uint4* q) { return __ldg(q); }); }
__device__ __forceinline__ Row ldca_row(const __nv_bfloat16* p, int lane) { return load_row(p, lane, [](const uint4* q) { return __ldca(q); }); }
__device__ __forceinline__ Row lds_row(uint32_t addr, int lane) {
  const uint4 a = lds_v4(addr + lane * 16), b = lds_v4(addr + 512 + lane * 16);
  return Row{{a.x, a.y, a.z, a.w, b.x, b.y, b.z, b.w}};
}
__device__ __forceinline__ void store_row(__nv_bfloat16* p, int lane, const Row& r) {
  stg_v4(p + lane * 8, r.v[0], r.v[1], r.v[2], r.v[3]); stg_v4(p + 256 + lane * 8, r.v[4], r.v[5], r.v[6], r.v[7]);
}
__device__ __forceinline__ Row fma_row(const Row& a, const Row& b, const Row& c) {
  Row r;
  #pragma unroll
  for (int i = 0; i < 8; i++) r.v[i] = fma2(a.v[i], b.v[i], c.v[i]);
  return r;
}
__device__ __forceinline__ Row add_row(const Row& a, const Row& b) {
  Row r;
  #pragma unroll
  for (int i = 0; i < 8; i++) r.v[i] = add2(a.v[i], b.v[i]);
  return r;
}
__device__ __forceinline__ Row one_plus(const Row& a) {
  Row r;
  #pragma unroll
  for (int i = 0; i < 8; i++) r.v[i] = add2(a.v[i], 0x3f803f80u);
  return r;
}
__device__ __forceinline__ float row_at(const Row& x, int i) { return (i & 1) ? bf_hi(x.v[i >> 1]) : bf_lo(x.v[i >> 1]); }
template<int N> __device__ __forceinline__ void warp_sums(float (&s)[N]) {
  #pragma unroll
  for (int o = 16; o > 0; o >>= 1) {
    #pragma unroll
    for (int k = 0; k < N; k++) s[k] += __shfl_xor_sync(0xffffffff, s[k], o);
  }
}
__device__ __forceinline__ void ln_stats(float& s1, float& s2) {
  s1 *= 1.f / DM;
  asm("rsqrt.approx.ftz.f32 %0, %1;" : "=f"(s2) : "f"(fmaxf(fmaf(-s1, s1, s2 * (1.f / DM)), 0.f) + 1e-5f));
}
__device__ __forceinline__ Row ln_apply(const Row& x, float mean, float f) {
  Row n;
  const float o = -mean * f;
  #pragma unroll
  for (int i = 0; i < 8; i++) n.v[i] = pack_bf16(fmaf(bf_lo(x.v[i]), f, o), fmaf(bf_hi(x.v[i]), f, o));
  return n;
}

constexpr int SM_Q = 6 * 32768, SM_BAR = 7 * 32768, SM_MAIL = SM_BAR + 640, SM_RED = SM_MAIL + 128, SM_H2 = SM_RED + 1024, SM_KEY = SM_H2 + 1024, SMEM = SM_KEY + 128;
constexpr int B_AF = 0, B_WF = 64, B_RF = 112, B_WE = 168, B_RE = 216, B_PUB = 272, B_RDY = 496;
constexpr int R_MOD = B_RDY, R_ITEM = B_RDY + 8, R_NEAR = B_RDY + 48, R_CTX = B_RDY + 64, R_H1 = B_RDY + 40;
constexpr int R_KEY = B_AF + 8, R_PART = B_AF + 32;
constexpr int NPUB = 14;
__device__ __forceinline__ uint32_t k_addrA(int kb) { return ((0x6310u >> ((kb >> 1) * 4)) & 15u) * 32768u + (kb & 1) * 16384u; }
__device__ __forceinline__ uint32_t k_addrW(int s) { return ((0x254u >> ((s >> 1) * 4)) & 15u) * 32768u + (s & 1) * 16384u; }

#define KORDER 0x2301
constexpr int KHEAD0 = ((KORDER >> 12) & 3) * 8;
constexpr int MAX_ITEMS = 4;
constexpr int MAX_STEPS = 10;
struct Sched {
  __nv_bfloat16 *kvc, *h1;
  struct Pair {
    uint8_t oent[3 * MAX_STEPS + 6];
    uint16_t lastuse[MAX_ITEMS];
    uint8_t khead[4];
    uint8_t nitems, item[MAX_ITEMS];
    uint8_t otask, nsteps;
    uint8_t ochunk[MAX_STEPS][2];
  } pair[NGRID / 2];
};

__device__ __forceinline__ int ring_add(int e, int n) { e += n; return e >= 12 ? e - 12 : e; }
__device__ __forceinline__ int ring_slot(int e) { return e >= 6 ? e - 6 : e; }
__device__ __forceinline__ void ring_wait_full(uint32_t bars, int e) { mbar_wait(bars + B_RF + 8 * ring_slot(e), e >= 6); }

__device__ __forceinline__ void o_wait_full(uint32_t bars, uint32_t v) { mbar_wait(bars + B_RF + 8 * (v & 7), v >> 3); }

struct Ctx {
  uint32_t base, bars;
  uint32_t rel;
  bool rel1;
  int w, nev;
  const Sched* sched;
};
__device__ __forceinline__ void slot_release(const Ctx& x, int s, bool twice) {
  mbar_arrive_remote_if(x.rel + B_RE + 8 * s, twice ? (wg_tid() & 31) == 0 : x.rel1);
}
__device__ __forceinline__ void ring_release(const Ctx& x, int e, bool twice) { slot_release(x, ring_slot(e), twice); }
__device__ __forceinline__ void publish(Ctx& x, int idx) {
  const uint32_t n = x.w * NPUB + x.nev;
  const int t = wg_tid();
  if (t == 0) asm volatile("st.shared.u32 [%0], %1;" :: "r"(x.base + SM_MAIL + 4 * n), "r"(idx) : "memory");
  __syncwarp();
  if ((t & 31) == 0) mbar_arrive(x.bars + B_PUB + 8 * n);
  x.nev++;
}

template<int KK = 0> __device__ __forceinline__ void issue_qk(float (&S)[64], uint32_t dq, uint32_t dk) {
  constexpr int off = (KK >> 2) * 1024 + (KK & 3) * 2;
  if constexpr (KK == 0) wgmma_ss_n128_new<0, 0, 0>(S, dq, dk); else wgmma_ss_n128<0, off, off>(S, dq, dk, 1);
  if constexpr (KK < 7) issue_qk<KK + 1>(S, dq, dk);
}
template<int KK = 0> __device__ __forceinline__ void issue_qk_half(float (&S)[32], uint32_t dq, uint32_t dk) {
  constexpr int off = (KK >> 2) * 1024 + (KK & 3) * 2;
  if constexpr (KK == 0) wgmma_ss_n64_new<0, 0, 512>(S, dq, dk); else wgmma_ss_n64<0, off, off + 512>(S, dq, dk, 1);
  if constexpr (KK < 7) issue_qk_half<KK + 1>(S, dq, dk);
}
template<int NK, int KK = 0>
__device__ __forceinline__ void issue_pv(float (&O)[64], uint32_t (&P)[32], uint32_t dv, int accumulate) {
  wgmma_rs_n128<1, (KK + 8 - NK) * 128>(O, P[4*KK], P[4*KK+1], P[4*KK+2], P[4*KK+3], dv, accumulate);
  if constexpr (KK + 1 < NK) issue_pv<NK, KK + 1>(O, P, dv, 1);
}
template<int K0, int K1>
__device__ __forceinline__ void exp_pack(const float (&S)[64], uint32_t (&D)[32], float& s0, float& s1) {
  #pragma unroll
  for (int k = K0; k < K1; k++) {
    const float e0 = ex2(S[2*k]), e1 = ex2(S[2*k+1]);
    D[k] = pack_bf16(e0, e1);
    if (k & 1) s1 += e0 + e1; else s0 += e0 + e1;
  }
}
__device__ __forceinline__ int q_row(int t) { return 16 * (t >> 5) + ((t >> 1) & 6) + ((t >> 4) & 1); }
__device__ __forceinline__ int diag_limit() { const int t = wg_tid(); return q_row(t) - 2 * (t & 3); }
__device__ __forceinline__ void exp_pack_diag(const float (&S)[64], uint32_t (&D)[32], int t, float& s0, float& s1) {
  #pragma unroll
  for (int k = 0; k < 16; k++) {
    const int c = 8 * (k >> 1) - 8 * (k & 1);
    const float e0 = ex2((c <= t) ? S[2*k] : -INFINITY), e1 = ex2((c + 1 <= t) ? S[2*k+1] : -INFINITY);
    D[k] = pack_bf16(e0, e1);
    if (k & 1) s1 += e0 + e1; else s0 += e0 + e1;
  }
}
constexpr float SUM_HI = 1.8446744073709552e19f;
constexpr float SUM_LO = 5.421010862427522e-20f;

__device__ __forceinline__ void classic_tile(const float (&S)[64], uint32_t (&P)[32], bool fresh, bool half, bool was_classic, volatile float* mc,
                                             float& l0, float& l1, float& s0, float& s1, float& sc0, float& sc1) {
  const int tmask = diag_limit();
  float4 t[16];
  #pragma unroll
  for (int j = 0; j < 16; j++) t[j] = make_float4(S[4*j], S[4*j+1], S[4*j+2], S[4*j+3]);
  float mx0 = -INFINITY, mx1 = -INFINITY;
  #pragma unroll 1
  for (int j = 0; j < 16; j++) {
    float4 v = t[j];
    const int lim = !fresh ? 1000 : j < 8 ? tmask - 8 * j : half ? -1000 : 1000;
    v.x = 0 <= lim ? v.x : -INFINITY; v.y = 1 <= lim ? v.y : -INFINITY; v.z = -8 <= lim ? v.z : -INFINITY; v.w = -7 <= lim ? v.w : -INFINITY;
    t[j] = v;
    mx0 = fmaxf(mx0, fmaxf(v.x, v.y)); mx1 = fmaxf(mx1, fmaxf(v.z, v.w));
  }
  mx0 = fmaxf(mx0, __shfl_xor_sync(0xffffffff, mx0, 1));
  mx1 = fmaxf(mx1, __shfl_xor_sync(0xffffffff, mx1, 1));
  mx0 = fmaxf(mx0, __shfl_xor_sync(0xffffffff, mx0, 2));
  mx1 = fmaxf(mx1, __shfl_xor_sync(0xffffffff, mx1, 2));
  const float mc0 = was_classic ? mc[0] : 0.f, mc1 = was_classic ? mc[1] : 0.f;
  const float n0 = fresh ? -mx0 : fminf(mc0, -mx0), n1 = fresh ? -mx1 : fminf(mc1, -mx1);
  sc0 = ex2(n0 - mc0); sc1 = ex2(n1 - mc1);
  mc[0] = n0; mc[1] = n1;
  s0 = 0.f; s1 = 0.f;
  #pragma unroll 1
  for (int j = 0; j < 16; j++) {
    const float4 v = t[j];
    const float e0 = ex2(v.x + n0), e1 = ex2(v.y + n0), e2 = ex2(v.z + n1), e3 = ex2(v.w + n1);
    s0 += e0 + e1; s1 += e2 + e3;
    reinterpret_cast<uint2*>(t)[j] = make_uint2(pack_bf16(e0, e1), pack_bf16(e2, e3));
  }
  #pragma unroll
  for (int j = 0; j < 8; j++) { P[4*j] = __float_as_uint(t[j].x); P[4*j+1] = __float_as_uint(t[j].y); P[4*j+2] = __float_as_uint(t[j].z); P[4*j+3] = __float_as_uint(t[j].w); }
  if (!fresh) { l0 *= sc0; l1 *= sc1; }
}
__device__ __forceinline__ void pack_tile(const float (&A)[64], uint32_t (&D)[32], float f0, float f1) {
  #pragma unroll
  for (int j = 0; j < 16; j++) {
    D[8 * (j >> 2) + (j & 3)] = pack_bf16(A[4*j] * f0, A[4*j+1] * f0);
    D[8 * (j >> 2) + 4 + (j & 3)] = pack_bf16(A[4*j+2] * f1, A[4*j+3] * f1);
  }
}
__device__ __forceinline__ void store_tile(__nv_bfloat16* p, const uint32_t (&D)[32]) {
  #pragma unroll
  for (int i = 0; i < 8; i++) stg_v4(p + (i >> 2) * (SEQ * 64) + ((i >> 1) & 1) * 32 + (i & 1) * 8 * 64, D[4*i], D[4*i+1], D[4*i+2], D[4*i+3]);
}

enum : int { PV_ACC = 0, PV_ZERO = 1, PV_HALF = 2, PV_NONE = 3 };
struct Att {
  float l0, l1, i0, i1;
  bool classic;
  volatile float* mc;
};
__device__ __forceinline__ void store_ctx(Ctx& x, int code, const uint32_t (&D)[32]) {
  const int item = code >> 2, t = wg_tid(), lane = t & 31;
  const int row = (item & 7) * 256 + (code & 3) * 64 + q_row(t);
  store_tile(x.sched->kvc + ((size_t)(128 + (item >> 3) * 2) * SEQ + row) * 64 + (lane & 3) * 8, D);
  publish(x, C_CTX + item);
}

__device__ __forceinline__ __nv_bfloat16* kv_tile(const Ctx& x, int code) {
  const int t = wg_tid();
  return x.sched->kvc + ((size_t)(x.w * 64 + (code >> 4) * 2) * SEQ + (code & 15) * 128 + (t >> 5) * 16 + ((t & 31) >> 2)) * 64 + (t & 3) * 8;
}
#define V_AT 3
#define V_AT2 7
#define MERGE1 1
#define NO_CLASSIC 0
__device__ __forceinline__ void q_proj(Ctx& x, int& e, bool isY, const uint32_t (&PA)[32], const uint32_t (&PB)[32], int vtile, bool dbg = false) {
  float S[64];
  bar_sync(1 + x.w, 256);
  if (isY) bar_arrive(1 + (x.w ^ 1), 256);
  if (dbg) DBG(80);
  #pragma unroll 1
  for (int kb = 0; kb < 8; kb++) {
    ring_wait_full(x.bars, e);
    if (dbg) DBG(81 + kb);
    const uint32_t da = desc_lo(x.base + x.w * 8192, 16) + ring_slot(e) * 2048, dw = desc_lo(x.base + 16384, 8192) + ring_slot(e) * 2048;
    wgmma_fence();
    kblock_n128<0>(S, da, dw, kb != 0);
    wgmma_commit();
    if (kb == 7 && !isY) bar_arrive(1 + (x.w ^ 1), 256);
    if (kb > 0) { wgmma_wait<1>(); ring_release(x, ring_add(e, 11), false); }
    if (kb == V_AT && vtile >= 0) store_tile(kv_tile(x, vtile) + 64 * 64, PA);
    if (kb == V_AT2 && vtile >= 0) { store_tile(kv_tile(x, vtile), PB); publish(x, C_KV + (vtile >> 4)); }
    e = ring_add(e, 1);
  }
  wgmma_wait<0>();
  fence_regs(S);
  if (dbg) DBG(89);
  ring_release(x, ring_add(e, 11), false);
  const int t = wg_tid(), lane = t & 31, g = (lane >> 3) + (lane & 4);
  const uint32_t qa = x.base + SM_Q + x.w * 8192 + ((t >> 5) * 16 + g) * 128;
  #pragma unroll
  for (int i = 0; i < 8; i++) {
    const int j = 4 * (i >> 1), o = 2 * (i & 1);
    sts_v4(qa + (i >> 2) * 16384 + (i & 1) * 1024 + (((((i >> 1) & 1) * 4 + (lane & 3)) ^ g) << 4),
           pack_bf16(S[4*j+o], S[4*j+o+1]), pack_bf16(S[4*j+4+o], S[4*j+5+o]), pack_bf16(S[4*j+8+o], S[4*j+9+o]), pack_bf16(S[4*j+12+o], S[4*j+13+o]));
  }
  fence_async_smem();
  if (dbg) DBG(90);
  ring_wait_full(x.bars, ring_add(e, isY ? 0 : 2));
  ring_wait_full(x.bars, ring_add(e, 1));
}

template<int KIND>
__device__ __forceinline__ void slot(Ctx& x, Att& a, int& e, float (&O)[64], uint32_t (&Pn)[32], uint32_t (&Po)[32],
                                     bool more, bool isY, bool half, int pv, int pend) {
  float S[64];
  const int w = x.w;
  const bool skip = KIND == 0 && !isY;
  const int en = ring_add(e, skip ? 4 : 2), sn = ring_slot(en), sv = ring_slot(e) + 1, sk = skip ? ring_slot(ring_add(e, 2)) : sv - 1;
  const uint32_t dq = desc_lo(x.base + SM_Q + w * 8192, 16), dk = desc_lo(x.base, 16) + sk * 2048, dv = desc_lo(x.base, 16384) + sv * 2048;
  bar_sync(1 + w, 256);
  if (KIND == 2) {
    wgmma_fence();
    issue_qk(S, dq, dk); wgmma_commit();
    issue_pv<8>(O, Po, dv, 1); wgmma_commit();
    bar_arrive(1 + (w ^ 1), 256);
    wgmma_wait<1>();
  } else if (KIND == 0 && half) {
    float T[32];
    wgmma_fence(); issue_qk_half(T, dq, dk); wgmma_commit();
    a.i0 = rcp_fast(quad_sum(a.l0)); a.i1 = rcp_fast(quad_sum(a.l1));
    if (pv == PV_NONE) { wgmma_fence(); wgmma_commit(); }
    else               { wgmma_fence(); issue_pv<8>(O, Po, dv, pv == PV_ACC); wgmma_commit(); }
    bar_arrive(1 + (w ^ 1), 256);
    wgmma_wait<1>();
    fence_regs(T);
    #pragma unroll
    for (int i = 0; i < 32; i++) { S[i] = T[i]; asm volatile("" : "=f"(S[32 + i])); }
  } else {
    wgmma_fence(); issue_qk(S, dq, dk); wgmma_commit();
    if (KIND == 1 && pend >= 0) { bar_arrive(1 + (w ^ 1), 256); pack_tile(O, Pn, a.i0, a.i1); store_ctx(x, pend, Pn); }
    if (KIND == 0) { a.i0 = rcp_fast(quad_sum(a.l0)); a.i1 = rcp_fast(quad_sum(a.l1)); }
    if (KIND == 0 && pv == PV_NONE) { wgmma_fence(); wgmma_commit(); }
    else if (pv == PV_HALF)         { wgmma_fence(); issue_pv<4>(O, Po, dv, 0); wgmma_commit(); }
    else                            { wgmma_fence(); issue_pv<8>(O, Po, dv, pv == PV_ACC); wgmma_commit(); }
    if (KIND == 0 || pend < 0) bar_arrive(1 + (w ^ 1), 256);
    wgmma_wait<1>();
  }
  fence_regs(S);
  fence_regs_u(Pn);
  slot_release(x, sk, KIND == 0 && isY);
  float s0 = 0.f, s1 = 0.f;
  const bool was_classic = KIND != 0 && a.classic;
  if (KIND == 0) {
    a.l0 = 0.f; a.l1 = 0.f;
    if (!half) exp_pack<16, 32>(S, Pn, s0, s1);
    else {
      #pragma unroll
      for (int i = 16; i < 32; i++) asm volatile("" : "=r"(Pn[i]));
    }
    exp_pack_diag(S, Pn, diag_limit(), s0, s1);
    uint32_t b0 = __ballot_sync(0xffffffff, s0 >= SUM_LO), b1 = __ballot_sync(0xffffffff, s1 >= SUM_LO);
    b0 |= b0 >> 1; b0 |= b0 >> 2; b1 |= b1 >> 1; b1 |= b1 >> 2;
    a.classic = __any_sync(0xffffffff, !(s0 <= SUM_HI && s1 <= SUM_HI)) || (b0 & b1 & 0x11111111u) != 0x11111111u;
  } else {
    exp_pack<0, 32>(S, Pn, s0, s1);
    a.classic = __any_sync(0xffffffff, a.classic || !(s0 <= SUM_HI && s1 <= SUM_HI));
  }
  fence_regs_u(Pn);
  mbar_wait(x.bars + B_RF + 8 * sn, en >= 6);
  if (more) mbar_wait(x.bars + B_RF + 8 * sn + 8, en >= 6);
  wgmma_wait<0>();
  fence_regs(O);
  fence_regs_u(Po);
  slot_release(x, sv, KIND == 1 && isY && pv != PV_ACC);
  if (!NO_CLASSIC && __builtin_expect(a.classic, 0)) {
    float sc0, sc1;
    classic_tile(S, Pn, KIND == 0, half, was_classic, a.mc, a.l0, a.l1, s0, s1, sc0, sc1);
    if (KIND != 0) {
      #pragma unroll
      for (int j = 0; j < 16; j++) { O[4*j] *= sc0; O[4*j+1] *= sc0; O[4*j+2] *= sc1; O[4*j+3] *= sc1; }
    }
  }
  a.l0 += s0; a.l1 += s1;
  e = en;
}

__device__ __forceinline__ int attention(Ctx& x, const uint8_t* items, int nitems, int rank, uint32_t (&PA)[32], uint32_t (&PB)[32], int vtile) {
  int e = 0;
  float O[64];
  Att a;
  volatile float mc[2];
  a.l0 = 1.f; a.l1 = 1.f; a.i0 = 0.f; a.i1 = 0.f; a.classic = false; a.mc = mc;
  int pv = PV_NONE, cur = -1;
#define DBGS()
  #pragma unroll 1
  for (int it = 0; ; it++) {
    const bool isY = (it & 1) == x.w;
    int pend = cur;
    if (it < nitems) {
      const int item = items[it];
      const bool half = isY == (rank != 0);
      cur = item * 4 + (isY ? 3 - rank : rank);
      int rem = 2 * (item & 7) + (isY ? 1 : 0);
      DBG(16 + it);
      q_proj(x, e, isY, PA, PB, vtile);
      vtile = -1;
      DBGS();
      slot<0>(x, a, e, O, PA, PB, rem > 0, isY, half, pv, -1);
      pv = half ? PV_HALF : PV_ZERO;
      #pragma unroll 1
      while (rem > 0) {
        DBGS();
        slot<1>(x, a, e, O, PB, PA, rem > 1, isY, false, pv, pend);
        pv = PV_ACC; pend = -1;
        if (rem == 1) break;
        rem -= 2;
        DBGS();
        slot<2>(x, a, e, O, PA, PB, rem > 0, false, false, 0, -1);
      }
    } else {
      DBGS();
      slot_release(x, 6, false);
      const uint32_t dv = desc_lo(x.base + ring_slot(e) * 32768, 16384);
      bar_sync(1 + x.w, 256);
      if (pv == PV_HALF) { wgmma_fence(); issue_pv<4>(O, PB, dv, 0); wgmma_commit(); }
      else { wgmma_fence(); issue_pv<8>(O, PB, dv, pv == PV_ACC); wgmma_commit(); }
      if (isY) bar_arrive(1 + (x.w ^ 1), 256);
      a.i0 = rcp_fast(quad_sum(a.l0)); a.i1 = rcp_fast(quad_sum(a.l1));
      ring_wait_full(x.bars, e);
      wgmma_wait<0>();
      fence_regs(O);
      fence_regs_u(PB);
      ring_release(x, e, false);
    }
    if (pend >= 0) pack_tile(O, PB, a.i0, a.i1);
    if (it == nitems) return pend;
    if (pend >= 0) store_ctx(x, pend, PB);
    if (!isY) {
      #pragma unroll
      for (int i = 0; i < 32; i++) asm volatile("mov.b32 %0, %1;" : "=r"(PB[i]) : "r"(PA[i]));
    }
  }
}

#define LN_AT 2
#define X_AT 6
#define EFM 16
#define PERT 1
#define PF_AT 5
#define PF_N 4
#define PF_MOE 3
constexpr float QSCALE = 0.08838834764831845f * 1.4426950408889634f;
__device__ __forceinline__ void mod_cta(Ctx& x, const __nv_bfloat16* cvec) {
  const int t = wg_tid(), ct = x.w * 128 + t;
  #pragma unroll 1
  for (int k = 0; k < 6; k++) slot_release(x, k, false);
  const uint32_t cv = __ldg(reinterpret_cast<const uint32_t*>(cvec) + ct);
  asm volatile("st.shared.u32 [%0], %1;" :: "r"(x.base + SM_H2 + ct * 4),
               "r"(pack_bf16(__fdividef(bf_lo(cv), 1.f + __expf(-bf_lo(cv))), __fdividef(bf_hi(cv), 1.f + __expf(-bf_hi(cv))))) : "memory");
  bar_sync(5, 256);
  float acc[64];
  int e = 0;
  #pragma unroll 1
  for (int g = 0; g < 24; g++) {
    uint32_t a[8];
    #pragma unroll
    for (int i = 0; i < 8; i++) a[i] = lds_u32(x.base + SM_H2 + (g & 7) * 128 + i * 16 + (t & 3) * 4);
    ring_wait_full(x.bars, e);
    const uint32_t db = desc_lo(x.base + x.w * 16384, 8192) + ring_slot(e) * 2048;
    wgmma_fence();
    wgmma_rs_n128<1, 0>(acc, a[0], a[0], a[1], a[1], db, g & 7);
    wgmma_rs_n128<1, 128>(acc, a[2], a[2], a[3], a[3], db, 1);
    wgmma_rs_n128<1, 256>(acc, a[4], a[4], a[5], a[5], db, 1);
    wgmma_rs_n128<1, 384>(acc, a[6], a[6], a[7], a[7], db, 1);
    wgmma_commit();
    wgmma_wait<0>();
    fence_regs(acc);
    ring_release(x, e, false);
    e = ring_add(e, 1);
    if ((g & 7) == 7) {
      if (t < 4) {
        const float sc = (g == 7 && blockIdx.x < NCTA + 2) ? QSCALE : 1.f;
        uint32_t* dst = reinterpret_cast<uint32_t*>(g_mod + (g >> 3) * 1024 + (blockIdx.x - NCTA) * 256 + x.w * 128) + t;
        #pragma unroll
        for (int j = 0; j < 16; j++) dst[4 * j] = pack_bf16(rbf(acc[4*j]) * sc, rbf(acc[4*j+1]) * sc);
      }
      publish(x, g == 7 ? C_MOD : C_MOD2);
      DBG(1 + (g >> 3));
    }
  }
}

__global__ void __cluster_dims__(2, 1, 1) __launch_bounds__(384, 1)
k_fused(const __grid_constant__ CUtensorMap tmC, const __grid_constant__ CUtensorMap tmH, const __grid_constant__ CUtensorMap tmWq,
        const __grid_constant__ CUtensorMap tmWk, const __grid_constant__ CUtensorMap tmWv, const __grid_constant__ CUtensorMap tmKV,
        const __grid_constant__ CUtensorMap tmWo, const __grid_constant__ CUtensorMap tmPart, const __grid_constant__ CUtensorMap tmWg,
        const __grid_constant__ CUtensorMap tmWu, const __grid_constant__ CUtensorMap tmPl, const __grid_constant__ CUtensorMap tmWm,
        const __grid_constant__ Sched sched,
        const __nv_bfloat16* __restrict__ xin,
        const __nv_bfloat16* __restrict__ cvec, const __nv_bfloat16* __restrict__ w_o,
        const __nv_bfloat16* __restrict__ w_r, const __nv_bfloat16* __restrict__ w_gate, const __nv_bfloat16* __restrict__ w_up,
        const __nv_bfloat16* __restrict__ w_down, __nv_bfloat16* __restrict__ out) {
  extern __shared__ __align__(1024) uint8_t smem_raw[];
  const uint32_t base = smem_u32(smem_raw), bars = base + SM_BAR;
  const int warp = __shfl_sync(0xffffffff, threadIdx.x >> 5, 0), wg = warp >> 2;
  const int rank = cluster_ctarank(), p = blockIdx.x >> 1;
  const int mt = (p & 7) * 2 + rank;
  const bool spare = blockIdx.x >= NCTA;
  #pragma unroll
  for (int i = 0; i < PERT; i++) { uint32_t d; asm volatile("mov.u32 %0, %%laneid;" : "=r"(d)); }
  {
    const int h0 = KHEAD0 + (p >> 3);
    if (warp == 9) prefetch_tmap(&tmWk);
    if (warp <= 8) {
      #pragma unroll 1
      for (int t = 8 - warp; t < 80; t += (warp < 8 ? 8 : 80))
        w_mbar_init(bars + 8 * t, t < B_WE / 8 ? 1 : t < B_RE / 8 ? 2 : t < B_RDY / 8 ? 4 : 1);
      fence_mbar_init();
    }
    cluster_arrive();
    if (wg == 2) bar_arrive(1, 256);
    if (warp == 8 && !spare) {
      #pragma unroll 1
      for (int kb = 0; kb < 8; kb++) {
        w_expect_tx(bars + B_AF + 8 * kb, 16384);
        tma_load_2d(base + k_addrA(kb), &tmC, bars + B_AF + 8 * kb, kb * 64, mt * 128);
        if (kb == 0) cluster_wait();
        if (kb < 6) {
          w_expect_tx(bars + B_WF + 8 * kb, 16384);
          tma_load_2d_mc(base + k_addrW(kb) + rank * 8192, &tmWk, bars + B_WF + 8 * kb, h0 * 128 + rank * 64, kb * 64);
        }
      }
    }
  }
  const Sched::Pair& sp = sched.pair[p];
  const int nitems = sp.nitems, nsteps = sp.nsteps;
  auto oent = [&](int k) -> uint32_t { return sp.oent[k]; };
  const int ot = sp.otask, m = (ot & 7) * 2 + rank, grp = m * 8 + (ot >> 3);

  if (wg == 0) {
    asm volatile("setmaxnreg.dec.sync.aligned.u32 24;");
    const int lane = threadIdx.x & 31;
    cluster_wait();
    const unsigned int tag = ld_relaxed(&g_epoch) + 1;
    if (warp == 0) {
      if (!spare) {
        int s = 0, ph = 0;
        tma_prefetch_2d(&tmWv, sp.khead[0] * 128 + rank * 64, (p & 7) * 64);
        #pragma unroll 1
        for (int g = 6; g < 64; g++) {
          const int u = g >> 3, kb = g & 7;
          if (kb == 0 && u < 7) tma_prefetch_2d((u & 1) ? &tmWk : &tmWv, sp.khead[(u + 1) >> 1] * 128 + rank * 64, (p & 7) * 64);
          mbar_wait(bars + B_WE + 8 * s, ph);
          w_expect_tx(bars + B_WF + 8 * s, 16384);
          tma_load_2d_mc(base + k_addrW(s) + rank * 8192, (u & 1) ? &tmWv : &tmWk, bars + B_WF + 8 * s, sp.khead[u >> 1] * 128 + rank * 64, kb * 64);
          if (++s == 6) { s = 0; ph ^= 1; }
        }
      }
      int s = 0, ph = 0;
      auto next_entry = [&](bool load) {
        mbar_wait(bars + B_RE + 8 * s, ph);
        if (load) w_expect_tx(bars + B_RF + 8 * s, 32768); else w_arrive(bars + B_RF + 8 * s);
      };
      auto advance = [&]() { if (++s == 6) { s = 0; ph ^= 1; } };
      if (spare) {
        #pragma unroll 1
        for (int g = 0; g < 24; g++) {
          if (g == 8) mbar_wait(bars + R_MOD, 0);
          next_entry(true);
          for (int k = 0; k < 2; k++) tma_load_3d(base + s * 32768 + k * 16384, &tmWm, bars + B_RF + 8 * s, 0, (g & 7) * 64, (g >> 3) * 16 + (blockIdx.x - NCTA) * 4 + k * 2);
          advance();
        }
      }
      mbar_wait(bars + R_H1, 0);
      fence_async_global();
      bool lastv = false;
      int vrow = -1;
      #pragma unroll 1
      for (int i = 0; i < nitems; i++) {
        const int item = sp.item[i], h = item >> 3, j = item & 7;
        const int row0 = j * 256 + ((i & 1) ? rank : 3 - rank) * 64, row1 = j * 256 + ((i & 1) ? 3 - rank : rank) * 64;
        #pragma unroll 1
        for (int kb = 0; kb < 8; kb++) {
          next_entry(true);
          tma_load_2d_mc(base + s * 32768 + 16384 + rank * 8192, &tmWq, bars + B_RF + 8 * s, h * 128 + rank * 64, kb * 64);
          tma_load_2d(base + s * 32768, &tmH, bars + B_RF + 8 * s, kb * 64, row0);
          tma_load_2d(base + s * 32768 + 8192, &tmH, bars + B_RF + 8 * s, kb * 64, row1);
          advance();
        }
        mbar_wait(bars + R_ITEM + 8 * i, 0);
        fence_async_global();
        #pragma unroll 1
        for (int n = 2 * j + 1; n >= 0; n--) {
          const int krow = (h * 2 + rank) * SEQ + n * 128;
          const bool lastk = (EFM & 16) && ((sp.lastuse[i] >> n) & 1);
          if (i + 1 == nitems && n == min(2 * j + 1, PF_AT)) w_arrive(bars + R_NEAR);
          next_entry(true);
          tma_load_2d_mc(base + s * 32768 + rank * 16384, &tmKV, bars + B_RF + 8 * s, 0, krow, lastk);
          advance();
          next_entry(vrow >= 0);
          if (vrow >= 0) tma_load_2d_mc(base + s * 32768 + rank * 16384, &tmKV, bars + B_RF + 8 * s, 0, vrow, lastv);
          advance();
          vrow = krow + 64 * SEQ; lastv = lastk;
        }
      }
      next_entry(true);
      tma_load_2d_mc(base + s * 32768 + rank * 16384, &tmKV, bars + B_RF + 8 * s, 0, vrow, lastv);
      advance();
      if (!spare) {
      const int oc = ((ot >> 3) & 1) * 4 + rank * 2;
      auto o_next = [&](int k, int bytes) {
        const uint32_t v = oent(k); s = v & 7;
        mbar_wait(bars + B_RE + 8 * s, v >> 3);
        w_expect_tx(bars + B_RF + 8 * s, bytes);
      };
      #pragma unroll 1
      for (int i = 0; i < nsteps; i++) {
        const int c0 = sp.ochunk[i][0], c1 = sp.ochunk[i][1];
        if (i >= PF_MOE && i < PF_MOE + 3)
          bulk_prefetch((i == PF_MOE ? w_gate : i == PF_MOE + 1 ? w_up : w_down) + (size_t)blockIdx.x * (DM * FF / NCTA), DM * FF / NCTA * 2);
        if (c0 < 64) { o_next(3 * i, 32768); tma_load_3d_mc(base + s * 32768 + rank * 16384, &tmWo, bars + B_RF + 8 * s, 0, c0 * 64, oc); }
        mbar_wait(bars + R_CTX + 8 * i, 0);
        fence_async_global();
        o_next(3 * i + 1, c0 < 64 ? 32768 : 16384);
        if (c0 < 64) tma_load_2d(base + s * 32768, &tmKV, bars + B_RF + 8 * s, 0, (128 + c0) * SEQ + m * 128);
        tma_load_2d(base + s * 32768 + 16384, &tmKV, bars + B_RF + 8 * s, 0, (128 + c1) * SEQ + m * 128);
        o_next(3 * i + 2, 32768);
        tma_load_3d_mc(base + s * 32768 + rank * 16384, &tmWo, bars + B_RF + 8 * s, 0, c1 * 64, oc);
      }
      const int f0 = (blockIdx.x < FF / 16 ? blockIdx.x : 0) * 16;
      o_next(3 * nsteps, 32768);
      bulk_load(base + s * 32768, w_down + (size_t)f0 * DM, 16384, bars + B_RF + 8 * s);
      bulk_load(base + s * 32768 + 16384, xin + (size_t)grp * 16 * DM, 16384, bars + B_RF + 8 * s);
      o_next(3 * nsteps + 1, 32768);
      #pragma unroll 1
      for (int k = 0; k < 4; k++) tma_load_2d(base + s * 32768 + k * 8192, (k & 2) ? &tmWu : &tmWg, bars + B_RF + 8 * s, f0, (k & 1) * 256);
      #pragma unroll 1
      for (int k = 0; k < 4; k++) w_expect_tx(bars + R_PART + 8 * k, 16384);
      mbar_wait(bars + B_PUB + 8 * (5 + nitems + 1), 0);
      mbar_wait(bars + B_PUB + 8 * (NPUB + 5 + nitems + 1), 0);
      uint32_t todo = 0xff;
      #pragma unroll 1
      for (int n = 0; n < WAIT_LIM && todo; n++) {
        uint32_t now = __ballot_sync(0xffffffff, ld_acquire(&g_pflag[m * 2 + (ot >> 5)][lane & 7]) == tag) & todo;
        todo &= ~now;
        fence_async_global();
        #pragma unroll 1
        for (; now; now &= now - 1) {
          const int q = __ffs(now) - 1;
          tma_load_3d(base + (oent(3 * nsteps - 3 + (q >> 2)) & 7) * 32768 + (q & 3) * 8192, &tmPl, bars + R_PART + 8 * (q >> 1), 0, grp * 16, q * 4);
        }
      }
      DBGP(11);
      }
    } else if (warp < 3) {
      const int w = warp - 1, n1 = w * NPUB + (spare ? 3 : 5) + nitems;
      #pragma unroll 1
      for (int n = w * NPUB; n < n1 + (spare ? 0 : 2); n++) {
        #pragma unroll 1
        for (int k = 0; k < 8 * WAIT_LIM; k++) { if (mbar_try(bars + B_PUB + 8 * n, 0)) break; }
        const uint32_t msg = lds_u32(base + SM_MAIL + 4 * n);
        if (n < n1) {
          fence_async_global();
          if (lane == 0 && msg < (unsigned)C_END) red_release(msg);
        } else {
          if (lane == 0) { tma_store_3d(&tmPart, base + (msg & 0x3c000), 0, m * 128 + 64 * w, (ot >> 3) * 4 + 2 * (n - n1)); bulk_commit(); }
        }
        __syncwarp();
      }
      bulk_wait<0>();
      fence_async_global();
      if (lane == 0 && !spare) st_release(&g_pflag[m * 2 + w][ot >> 3], tag);
      __syncwarp();
    } else {
      if (!spare) { mbar_wait(bars + B_AF + 8 * X_AT, 0); bulk_prefetch(xin + (size_t)blockIdx.x * 16 * DM, 16 * DM * 2); }
      wait_count_lazy(C_MOD, 8 * tag);
      DBGP(12);
      w_arrive(bars + R_MOD);
      #pragma unroll 1
      for (int i = 0; i < nitems; i++) {
        const int item = sp.item[i];
        tma_prefetch_2d(&tmWq, (item >> 3) * 128 + rank * 64, (item & 7) * 64);
        if (i == 0) { wait_count_lazy(C_H1, 256 * tag); w_arrive(bars + R_H1); }
        wait_count_lazy(C_KV + (item >> 3), 32 * tag);
        w_arrive(bars + R_ITEM + 8 * i);
      }
      wait_count_lazy(C_MOD2, 16 * tag);
      #pragma unroll 1
      for (int i = 0; i < nsteps; i++) {
        const int c = sp.ochunk[i][lane & 1];
        if (c < 64) wait_count_lazy(C_CTX + (c >> 1) * 8 + (ot & 7), 4 * tag);
        __syncwarp();
        w_arrive(bars + R_CTX + 8 * i);
        if (i == PF_N - 1) {
          #pragma unroll 1
          for (int k = 0; k < 8 * WAIT_LIM; k++) { if (mbar_try(bars + R_NEAR, 0)) break; }
          bulk_prefetch(w_o + (size_t)blockIdx.x * (NH * DH * DM / NCTA), NH * DH * DM / NCTA * 2);
          #pragma unroll 1
          for (int k = 0; k < PF_N; k++) {
            const int cc = sp.ochunk[k][(ot >> 3) & 1];
            if (cc < 64) bulk_prefetch(sched.kvc + ((size_t)(128 + cc) * SEQ + m * 128) * 64, 16384);
          }
        }
      }
    }
    __syncwarp();
    cluster_arrive();
    if (!spare) {
      bar_sync(6, 128);
      asm volatile("setmaxnreg.inc.sync.aligned.u32 88;");
      const int pos = blockIdx.x * 4 + (lane & 1) * 2, col = (blockIdx.x >> 2) * 16 + (blockIdx.x & 3) * 2 + (lane & 1) * 8, src = threadIdx.x >> 1;
      uint32_t gbest = 0, hh = 0, gbf = 0;
      uint2 xx = make_uint2(0, 0);
      uint4 ya = make_uint4(0, 0, 0, 0), yb = make_uint4(0, tag, 0, tag);
      auto poll_y = [&]() {
        if (ya.y != tag || ya.w != tag) ya = ld_tagged2(&g_yll[src][pos]);
        if (yb.y != tag || yb.w != tag) yb = ld_tagged2(&g_yll[src + 64][pos]);
        return __all_sync(0xffffffff, ya.y == tag && ya.w == tag && yb.y == tag && yb.w == tag);
      };
      ya.y = tag - 1; if (src + 64 < FF / 16) yb.y = tag - 1;
      poll_y();
      if (warp == 3) {
        gbf = __ldcg(reinterpret_cast<const uint32_t*>(g_mod + 5 * DM + col));
        uint32_t have = 0;
        uint2 k[4];
        #pragma unroll
        for (int i = 0; i < 4; i++) k[i] = make_uint2(0, tag - 1);
        #pragma unroll 1
        for (int n = 0; n < WAIT_LIM; n++) {
          #pragma unroll
          for (int i = 0; i < 4; i++) if (k[i].y != tag) k[i] = ld_tagged(&g_keys[i * 32 + lane][0]);
          if (gbest != have) {
            const int g = ((0xffffu - gbest) >> 4) & 127;
            uint4 hv[4];
            #pragma unroll
            for (int i = 0; i < 4; i++) hv[i] = ld_tagged2(&g_row[g][0][i * 64 + lane * 2]);
            xx = ld_tagged(&g_row[g][1][col >> 1]);
            bool ok = xx.y == tag;
            #pragma unroll
            for (int i = 0; i < 4; i++) { ok = ok && hv[i].y == tag && hv[i].w == tag; reinterpret_cast<uint2*>(smem_raw + SM_H2)[i * 32 + lane] = make_uint2(hv[i].x, hv[i].z); }
            if (lane == 0) *reinterpret_cast<uint32_t*>(smem_raw + SM_KEY + 32) = gbest;
            have = __all_sync(0xffffffff, ok) ? gbest : 0;
          }
          bool all = true;
          #pragma unroll
          for (int i = 0; i < 4; i++) { all = all && k[i].y == tag; gbest = max(gbest, k[i].y == tag ? k[i].x : 0u); }
          gbest = __reduce_max_sync(0xffffffff, gbest);
          if (__all_sync(0xffffffff, all) && gbest == have) break;
        }
        w_arrive(bars + R_KEY);
        if (blockIdx.x == 0 && lane == 0) g_epoch = tag;
        hh = lds_u32(base + SM_H2 + col * 2);
        DBGP(13);
      }
      const uint32_t sb16 = gbest & 0xffff0000u;
      const float rsel = __uint_as_float((sb16 & 0x80000000u) ? (sb16 & 0x7fffffffu) : (~sb16 & 0xffff0000u));
      const float rs = rbf(__fdividef(1.f, 1.f + __expf(-rsel)));
      mbar_wait(bars + R_KEY, 1);
      #pragma unroll 1
      for (int n = 0; n < WAIT_LIM; n++) { if (poll_y()) break; }
      float y0 = __uint_as_float(ya.x) + __uint_as_float(yb.x), y1 = __uint_as_float(ya.z) + __uint_as_float(yb.z);
      #pragma unroll
      for (int o = 2; o < 32; o <<= 1) { y0 += __shfl_xor_sync(0xffffffff, y0, o); y1 += __shfl_xor_sync(0xffffffff, y1, o); }
      float2* s_y = reinterpret_cast<float2*>(smem_raw + SM_KEY + 64);
      if (lane < 2) s_y[warp * 2 + lane] = make_float2(y0, y1);
      bar_sync(6, 128);
      if (warp == 3 && lane < 2) {
        y0 = 0.f; y1 = 0.f;
        #pragma unroll
        for (int i = 0; i < 4; i++) { y0 += reinterpret_cast<const float*>(s_y)[i * 4 + lane]; y1 += reinterpret_cast<const float*>(s_y)[i * 4 + 2 + lane]; }
        const float o0 = bf_lo(xx.x) + rbf(bf_lo(gbf) * rbf(bf_lo(hh) + rbf(rbf(y0) * rs)));
        const float o1 = bf_hi(xx.x) + rbf(bf_hi(gbf) * rbf(bf_hi(hh) + rbf(rbf(y1) * rs)));
        *reinterpret_cast<uint32_t*>(out + (size_t)((0xffffu - gbest) & (SEQ - 1)) * DM + col) = pack_bf16(o0, o1);
      }
      DBGP(14);
    }
    __syncwarp();
    cluster_wait();
  } else {
    asm volatile("setmaxnreg.inc.sync.aligned.u32 240;");
    Ctx x;
    x.w = wg - 1; x.base = base; x.bars = bars; x.nev = 0; x.sched = &sched;
    const int w = x.w, warp4 = warp & 3;
    x.rel = mapa(bars, (warp4 & 1) ^ 1);
    x.rel1 = (threadIdx.x & 127) == 32 || (threadIdx.x & 127) == 64;
    if (warp != 8 || spare) cluster_wait();
    DBG(1);
    uint32_t PA[32], PB[32];
    int vtile = -1;
    if (spare) {
      mod_cta(x, cvec);
    } else {
      const int lane = wg_tid() & 31;
      Row xn[2];
      float acc0[64], acc1[64];
      int s = 2 * w, ph = w;
      #pragma unroll 1
      for (int u = w; u < 8; u += 2) {
        bar_sync(1 + w, 256);
        DBG(4 + (u >> 1) * 3);
        int ps = 0;
        #pragma unroll 1
        for (int kb = 0; kb < 8; kb++) {
          if (u < 2) mbar_wait(bars + B_AF + 8 * kb, 0);
          mbar_wait(bars + B_WF + 8 * s, ph);
          const uint32_t da = desc_lo(base + k_addrA(kb), 16), dw = desc_lo(base + k_addrW(s), 8192);
          wgmma_fence();
          kblock_n128<0>(acc0, da, dw, kb != 0);
          kblock_n128<512>(acc1, da, dw, kb != 0);
          wgmma_commit();
          if (kb == 7) bar_arrive(1 + (w ^ 1), 256);
          if (kb > 0) {
            wgmma_wait<1>();
            mbar_arrive_remote_if(x.rel + B_WE + 8 * ps, x.rel1);
            if (u == 7 && !(kb & 1)) {
              ring_release(x, kb == 2 ? 0 : kb - 3, false);
              if (kb > 2) ring_release(x, kb - 2, false);
            }
          }
          ps = s;
          if (++s == 6) { s = 0; ph ^= 1; }
        }
        Row t[2];
        const int lrow = blockIdx.x * 16 + w * 8 + warp4 * 2;
        if (u == w) { t[0] = ldg_row(xin + (size_t)lrow * DM, lane); t[1] = ldg_row(xin + (size_t)(lrow + 1) * DM, lane); }
        if (u == LN_AT || u == LN_AT + 1) {
          mbar_wait(bars + R_MOD, 0);
          t[0] = ldca_row(g_mod, lane); t[1] = ldca_row(g_mod + DM, lane);
        }
        wgmma_wait<0>();
        fence_regs(acc0); fence_regs(acc1);
        DBG(5 + (u >> 1) * 3);
        mbar_arrive_remote_if(x.rel + B_WE + 8 * ps, x.rel1);
        if (u == 6) { for (int k = 0; k < 5; k++) ring_release(x, k, false); }
        if (u >= 6) ring_release(x, 5, false);
        if (V_AT >= 0 && u == 7) {
          pack_tile(acc0, PA, 1.f, 1.f); pack_tile(acc1, PB, 1.f, 1.f);
          vtile = sp.khead[3] * 16 + mt;
          break;
        }
        s += 2; ph ^= 1; if (s >= 6) { s -= 6; ph ^= 1; }
        if (u == w) {
          float st[4] = {0.f, 0.f, 0.f, 0.f};
          #pragma unroll
          for (int i = 0; i < 32; i++) { const float v = row_at(t[i >> 4], i & 15); st[(i >> 4) * 2] += v; st[(i >> 4) * 2 + 1] = fmaf(v, v, st[(i >> 4) * 2 + 1]); }
          warp_sums(st);
          #pragma unroll
          for (int r = 0; r < 2; r++) { ln_stats(st[2*r], st[2*r+1]); xn[r] = ln_apply(t[r], st[2*r], st[2*r+1] * QSCALE); }
        }
        if ((u == LN_AT || u == LN_AT + 1)) {
          #pragma unroll
          for (int r = 0; r < 2; r++) store_row(sched.h1 + (size_t)(lrow + r) * DM, lane, fma_row(xn[r], one_plus(t[1]), t[0]));
        }
        const int tile = sp.khead[u >> 1] * 16 + mt;
        __nv_bfloat16* dst = kv_tile(x, tile);
        uint32_t D[32];
        pack_tile(acc0, D, 1.f, 1.f); store_tile(dst + 64 * 64, D);
        pack_tile(acc1, D, 1.f, 1.f); store_tile(dst, D);
        if (u == LN_AT || u == LN_AT + 1) publish(x, C_H1);
        publish(x, C_KV + (tile >> 4));
        DBG(6 + (u >> 1) * 3);
      }
    }
    const int last = attention(x, sp.item, nitems, rank, PA, PB, vtile);
    DBG(100);
    const int lane = wg_tid() & 31, cw = w * 4 + warp4, ct = cw * 32 + lane;
    const int row0 = grp * 16 + cw * 2;
    const bool moe_cta = blockIdx.x < FF / 16;
    const unsigned int tag = ld_relaxed(&g_epoch) + 1;
    if (spare) { store_ctx(x, last, PB); __syncwarp(); cluster_arrive(); cluster_wait(); return; }
    const int kl = 3 * nsteps - 3;
    {
      float accA[64], accB[64];
      uint32_t pa = 0, pb = 0;
      #pragma unroll 1
      for (int k = 0; k < kl; k += 3) {
        const uint32_t e0 = oent(k), ea = oent(k + 1), eb = oent(k + 2);
        const uint32_t da = desc_lo(base + w * 8192, 16) + (ea & 7) * 2048;
        o_wait_full(bars, e0);
        o_wait_full(bars, ea);
        uint32_t db = desc_lo(base, 8192) + (e0 & 7) * 2048;
        const bool both = e0 != ea;
        if (both) {
          wgmma_fence();
          kblock_n128<0>(accA, da, db, k != 0); kblock_n128<0, 1024>(accB, da, db, k != 0);
          wgmma_commit();
        }
        if (k > 0) { wgmma_wait<1>(); slot_release(x, pa, false); slot_release(x, pb, false); }
        o_wait_full(bars, eb);
        db = desc_lo(base, 8192) + (eb & 7) * 2048;
        wgmma_fence();
        kblock_n128<1024>(accA, da, db, both); kblock_n128<1024, 1024>(accB, da, db, both);
        wgmma_commit();
        if (k == 0) store_ctx(x, last, PB);
        if (both) { wgmma_wait<1>(); slot_release(x, e0 & 7, false); }
        pa = ea & 7; pb = eb & 7;
      }
      const uint32_t e0 = oent(kl), ea = oent(kl + 1), eb = oent(kl + 2);
      const uint32_t da = desc_lo(base + w * 8192, 16) + (ea & 7) * 2048;
      const uint32_t db0 = desc_lo(base, 8192) + (e0 & 7) * 2048, db1 = desc_lo(base, 8192) + (eb & 7) * 2048;
      o_wait_full(bars, e0);
      o_wait_full(bars, ea);
      o_wait_full(bars, eb);
      wgmma_fence();
      kblock_n128<0>(accA, da, db0, 1); kblock_n128<1024>(accA, da, db1, 1);
      wgmma_commit();
      kblock_n128<0, 1024>(accB, da, db0, 1); kblock_n128<1024, 1024>(accB, da, db1, 1);
      wgmma_commit();
      wgmma_wait<2>();
      slot_release(x, pa, false); slot_release(x, pb, false);
      __syncwarp();
      cluster_arrive();
      const int srow = 16 * warp4 + (lane & 7) + 8 * ((lane >> 3) & 1);
      const uint32_t swz = (((lane >> 4) ^ (srow & 7)) << 4);
      auto stage = [&](const float (&acc)[64], uint32_t off) {
        #pragma unroll
        for (int j = 0; j < 16; j += 2)
          stsm_x4(base + off + srow * 128 + (j >> 3) * 8192 + (((j & 7) << 4) ^ swz),
                  pack_bf16(acc[4*j+0], acc[4*j+1]), pack_bf16(acc[4*j+2], acc[4*j+3]), pack_bf16(acc[4*j+4], acc[4*j+5]), pack_bf16(acc[4*j+6], acc[4*j+7]));
        fence_async_smem();
        publish(x, off);
      };
      mbar_wait(bars + B_RE + 8 * pa, oent(kl + 5) >> 3);
      wgmma_wait<1>();
      fence_regs(accA);
      stage(accA, pa * 32768 + w * 16384);
      mbar_wait(bars + B_RE + 8 * pb, oent(kl + 6) >> 3);
      wgmma_wait<0>();
      fence_regs(accB);
      DBG(101);
      stage(accB, pb * 32768 + w * 16384);
      DBG(102);
    }
    asm volatile("setmaxnreg.dec.sync.aligned.u32 208;");
    const Row ga = ldca_row(g_mod + 2 * DM, lane), sb = ldca_row(g_mod + 3 * DM, lane), cb = ldca_row(g_mod + 4 * DM, lane), gb = ldca_row(g_mod + 5 * DM, lane);
    const Row wr = ldca_row(w_r, lane);
    const uint32_t sD = base + (oent(kl + 3) & 7) * 32768, sW = base + (oent(kl + 4) & 7) * 32768;
    o_wait_full(bars, oent(kl + 3)); o_wait_full(bars, oent(kl + 4));
    Row x1[2];
    #pragma unroll
    for (int r = 0; r < 2; r++) x1[r] = lds_row(sD + 16384 + (cw * 2 + r) * 1024, lane);
    uint4 wgv[4], wuv[4], wdv[4];
    #pragma unroll
    for (int r = 0; r < 4; r++) {
      const uint32_t k = (lane & 7) + ((lane >> 4) << 3), h = (lane & 8) * 2;
      wgv[r] = ldsm_x4_t(sW + (cw * 64 + r * 16 + k) * 32 + h);
      wuv[r] = ldsm_x4_t(sW + 16384 + (cw * 64 + r * 16 + k) * 32 + h);
      wdv[r] = ldsm_x4_t(sD + k * 1024 + (cw * 64 + r * 16) * 2 + h);
    }
    const Row cb1 = one_plus(cb);
    DBG(103);
    float u[16], ub[2] = {0.f, 0.f};
    #pragma unroll
    for (int i = 0; i < 16; i++) { u[i] = row_at(cb1, i) * row_at(wr, i); ub[0] += u[i]; ub[1] = fmaf(row_at(sb, i), row_at(wr, i), ub[1]); }
    warp_sums(ub);
    float st[6] = {0.f, 0.f, 0.f, 0.f, 0.f, 0.f};
    uint32_t key[2];
    {
      const uint32_t po = base + (lane >> 3) * 2048 + cw * 256 + (lane & 7) * 16;
      Row av[2][2];
      #pragma unroll
      for (int k = 0; k < 4; k++) {
        mbar_wait(bars + R_PART + 8 * k, 1);
        const uint32_t pa = po + (oent(kl + (k >> 1)) & 7) * 32768 + (k & 1) * 16384;
        #pragma unroll
        for (int r = 0; r < 2; r++) {
          const uint4 lo = lds_v4(pa + r * 128), hi = lds_v4(pa + 8192 + r * 128);
          const Row v{{lo.x, lo.y, lo.z, lo.w, hi.x, hi.y, hi.z, hi.w}};
          av[r][k >> 1] = (k & 1) ? add_row(av[r][k >> 1], v) : v;
        }
      }
      DBG(104);
      #pragma unroll
      for (int r = 0; r < 2; r++) {
        x1[r] = fma_row(ga, add_row(av[r][0], av[r][1]), x1[r]);
        #pragma unroll
        for (int i = 0; i < 16; i++) { const float v = row_at(x1[r], i); st[3*r] += v; st[3*r+1] = fmaf(v, v, st[3*r+1]); st[3*r+2] = fmaf(v, u[i], st[3*r+2]); }
      }
      warp_sums(st);
      #pragma unroll
      for (int r = 0; r < 2; r++) {
        ln_stats(st[3*r], st[3*r+1]);
        const uint32_t rb = pack_bf16(0.f, fmaf(st[3*r+1], fmaf(-st[3*r], ub[0], st[3*r+2]), ub[1]));
        key[r] = (((rb & 0x80000000u) ? ~rb : (rb | 0x80000000u)) & 0xffff0000u) | (0xffffu - (uint32_t)(row0 + r));
      }
    }
    DBG(105);
    float* s_red = reinterpret_cast<float*>(smem_raw + SM_RED);
    uint32_t* s_key = reinterpret_cast<uint32_t*>(smem_raw + SM_KEY);
    const int rb = key[1] > key[0];
    const uint32_t wbest = rb ? key[1] : key[0];
    if (lane == 0) s_key[cw] = wbest;
    bar_sync(5, 256);
    const uint32_t cbest = __reduce_max_sync(0xffffffff, s_key[lane & 7]);
    if (wbest == cbest && lane == 0) st_tagged(&g_keys[grp][0], cbest, tag);
    Row xb, xo;
    #pragma unroll
    for (int i = 0; i < 8; i++) { xb.v[i] = rb ? x1[1].v[i] : x1[0].v[i]; xo.v[i] = rb ? x1[0].v[i] : x1[1].v[i]; }
    const Row hb = fma_row(ln_apply(xb, rb ? st[3] : st[0], rb ? st[4] : st[1]), cb1, sb);
    if (wbest == cbest) {
      #pragma unroll
      for (int i = 0; i < 4; i++) st_tagged2(&g_row[grp][0][(i >> 1) * 128 + lane * 4 + (i & 1) * 2], hb.v[2*i], hb.v[2*i+1], tag);
      #pragma unroll
      for (int i = 0; i < 4; i++) st_tagged2(&g_row[grp][1][(i >> 1) * 128 + lane * 4 + (i & 1) * 2], xb.v[2*i], xb.v[2*i+1], tag);
    }
    DBG(106);
    const Row ob = fma_row(gb, hb, xb);
    if (wbest != cbest) store_row(out + (size_t)(row0 + rb) * DM, lane, ob);
    store_row(out + (size_t)(row0 + 1 - rb) * DM, lane, fma_row(gb, fma_row(ln_apply(xo, rb ? st[0] : st[3], rb ? st[1] : st[4]), cb1, sb), xo));
    mbar_wait(bars + R_KEY, 1);
    DBG(107);
    if (moe_cta) {
      float cg[4] = {0, 0, 0, 0}, cu[4] = {0, 0, 0, 0};
      #pragma unroll
      for (int r = 0; r < 4; r++) {
        const uint32_t b0 = lds_u32(base + SM_H2 + (cw * 64 + r * 16) * 2 + (lane & 3) * 4), b1 = lds_u32(base + SM_H2 + (cw * 64 + r * 16) * 2 + 16 + (lane & 3) * 4);
        mma16816(cg, wgv[r], b0, b1); mma16816(cu, wuv[r], b0, b1);
      }
      s_red[cw * 32 + (lane & 3) * 8 + (lane >> 2)] = (lane & 2) ? ((lane & 1) ? cu[2] : cu[0]) : ((lane & 1) ? cg[2] : cg[0]);
      bar_sync(5, 256);
      float g = 0.f;
      #pragma unroll
      for (int i = 0; i < 8; i++) g += s_red[i * 32 + lane];
      g = rbf(g);
      const float act = rbf(__fdividef(g, 1.f + __expf(-g))) * __shfl_down_sync(0xffffffff, g, 16);
      const uint32_t a2 = pack_bf16(act, __shfl_down_sync(0xffffffff, act, 1));
      const uint32_t b0 = __shfl_sync(0xffffffff, a2, (lane & 3) * 2), b1 = __shfl_sync(0xffffffff, a2, (lane & 3) * 2 + 8);
      float y0 = 0.f, y1 = 0.f;
      #pragma unroll
      for (int r = 0; r < 4; r++) {
        float c[4] = {0, 0, 0, 0};
        mma16816(c, wdv[r], b0, b1);
        if ((lane & 3) == r) { y0 = c[0]; y1 = c[2]; }
      }
      st_tagged2(&g_yll[blockIdx.x][cw * 64 + (lane & 3) * 16 + (lane >> 2) * 2], __float_as_uint(y0), __float_as_uint(y1), tag);
    }
    DBG(108);
    if (wbest == cbest && wbest != s_key[8]) store_row(out + (size_t)(row0 + rb) * DM, lane, ob);
    DBG(109);
    __syncwarp();
    cluster_wait();
  }
}

typedef CUresult (*EncodeFn)(CUtensorMap*, CUtensorMapDataType, cuuint32_t, void*, const cuuint64_t*, const cuuint64_t*, const cuuint32_t*,
                             const cuuint32_t*, CUtensorMapInterleave, CUtensorMapSwizzle, CUtensorMapL2promotion, CUtensorMapFloatOOBfill);

struct HostState {
  bool ready = false;
  EncodeFn encode = nullptr;
  CUtensorMap tmC, tmH, tmWq, tmWk, tmWv, tmKV, tmWo, tmPart, tmWg, tmWu, tmPl, tmWm;
  Sched sched;
};

void make_map(EncodeFn enc, CUtensorMap* m, const void* ptr, int rank, const cuuint64_t* dims, const cuuint64_t* strides, const cuuint32_t* box, bool swizzle = true) {
  const cuuint32_t es[3] = {1, 1, 1};
  enc(m, CU_TENSOR_MAP_DATA_TYPE_BFLOAT16, rank, const_cast<void*>(ptr), dims, strides, box, es, CU_TENSOR_MAP_INTERLEAVE_NONE,
      swizzle ? CU_TENSOR_MAP_SWIZZLE_128B : CU_TENSOR_MAP_SWIZZLE_NONE, swizzle ? CU_TENSOR_MAP_L2_PROMOTION_L2_128B : CU_TENSOR_MAP_L2_PROMOTION_NONE, CU_TENSOR_MAP_FLOAT_OOB_FILL_NONE);
}
void make_2d(EncodeFn enc, CUtensorMap* m, const void* ptr, int rows, int cols, int box_rows) {
  const cuuint64_t dims[2] = {(cuuint64_t)cols, (cuuint64_t)rows}, strides[1] = {(cuuint64_t)cols * 2};
  const cuuint32_t box[2] = {64, (cuuint32_t)box_rows};
  make_map(enc, m, ptr, 2, dims, strides, box);
}
void make_3d(EncodeFn enc, CUtensorMap* m, const void* ptr, int rows, int chunks, size_t row_stride, size_t chunk_stride) {
  const cuuint64_t dims[3] = {64, (cuuint64_t)rows, (cuuint64_t)chunks}, strides[2] = {row_stride, chunk_stride};
  const cuuint32_t box[3] = {64, 64, 2};
  make_map(enc, m, ptr, 3, dims, strides, box);
}

void make_ffn(EncodeFn enc, CUtensorMap* m, const void* ptr) {
  const cuuint64_t dims[2] = {(cuuint64_t)FF, (cuuint64_t)DM}, strides[1] = {(cuuint64_t)FF * 2};
  const cuuint32_t box[2] = {16, 256};
  make_map(enc, m, ptr, 2, dims, strides, box, false);
}

#define J0_FIRST 0
#define SR 0x213312
#define SEED 12345
#define LU_MARGIN 0
#define SPARE_N 3
void build_sched(Sched& s) {
  memset(&s, 0, sizeof(s));
  const int NP = NCTA / 2, korder[4] = {(KORDER >> 12) & 3, (KORDER >> 8) & 3, (KORDER >> 4) & 3, KORDER & 3};
  const int sround[4][2][3] = {{}, {{1}, {2}}, {{1, 2}, {1, 2}}, {{(SR >> 20) & 3, (SR >> 16) & 3, (SR >> 12) & 3}, {(SR >> 8) & 3, (SR >> 4) & 3, SR & 3}}};
  int jv[4][NP], used[4][8] = {};
  for (int r = 0; r < 4; r++) for (int p = 0; p < NP; p++) jv[r][p] = (r & 2) ? 7 - ((p + 4 * (r & 1)) & 7) : (p + 4 * (r & 1)) & 7;
  for (int q = 0; q < 2; q++) {
    s.pair[NP + q].nitems = SPARE_N;
    for (int i = 0; i < SPARE_N; i++) {
      const int r = sround[SPARE_N][q][i];
      s.pair[NP + q].item[i] = (uint8_t)((r * 8 + used[r][6]++) * 8 + 6);
      for (int p = 0; p < NP; p++) if (jv[r][p] == 6) { jv[r][p] = -2; break; }
    }
  }
  auto cost = [&](int p) {
    int u = 8 - ((p >> 4) < SPARE_N ? 21 : 22), z = 0, none = 0;
    for (int r = 0; r < 4; r++) { u += jv[r][p]; z += jv[r][p] == 0; none += jv[r][p] < 0; }
    return 4 * u * u + (z > 1) + 4 * (none > 1);
  };
  uint32_t rng = SEED;
  for (int it = 0; it < 2000000; it++) {
    if ((it & 255) == 0) { int t = 0; for (int p = 0; p < NP; p++) t += cost(p); if (t == 0) break; }
    rng = rng * 1664525u + 1013904223u;
    const int r = (rng >> 8) & 3, a = (rng >> 12) & 63, b = (rng >> 20) & 63, before = cost(a) + cost(b);
    int t = jv[r][a]; jv[r][a] = jv[r][b]; jv[r][b] = t;
    if (cost(a) + cost(b) > before) { jv[r][b] = jv[r][a]; jv[r][a] = t; }
  }
  int fin[256], done[256];
  for (int p = 0; p < NP + 2; p++) {
    Sched::Pair& q = s.pair[p];
    if (p < NP) {
      for (int k = 0; k < 4; k++) q.khead[k] = (uint8_t)(korder[k] * 8 + (p >> 3));
      for (int r = 0; r < 4; r++) {
        if (jv[r][p] < 0) continue;
        int at = q.nitems++;
        if (J0_FIRST && jv[r][p] == 0 && r != korder[3]) for (; at > 0; at--) q.item[at] = q.item[at - 1];
        q.item[at] = (uint8_t)((r * 8 + used[r][jv[r][p]]++) * 8 + jv[r][p]);
      }
    }
    int t = p < NP ? 0 : -3, e = 1;
    for (int i = 0; i < q.nitems; i++) { t += (q.item[i] & 7) + 2; fin[q.item[i]] = t; done[q.item[i]] = t + (i + 1 < q.nitems ? 2 : 0); e += 8 + 4 * ((q.item[i] & 7) + 1); }
    for (int k = 0; k < 3 * MAX_STEPS + 6; k++) {
      const int n = k > 0 ? k - (SPARE_N & 1) : 0, r = n % 7, f = (e + (r < 4 ? r : r - 1)) % 12;
      q.oent[k] = (uint8_t)((r == 4 ? 6 : f >= 6 ? f + 2 : f) ^ (((n / 7) & 1) << 3));
    }
  }
  for (int p = 0; p < NP + 2; p++)
    for (int i = 0; i < s.pair[p].nitems; i++) {
      const int it = s.pair[p].item[i];
      for (int n = 0; n < 2 * (it & 7) + 2; n++) {
        bool last = true;
        for (int j = n >> 1; j < 8; j++) { const int o = (it & ~7) + j; if (o != it && fin[o] + LU_MARGIN > fin[it]) last = false; }
        if (last) s.pair[p].lastuse[i] |= (uint16_t)(1 << n);
      }
    }
  for (int j = 0; j < 8; j++) {
    int order[NH], left[4];
    for (int h = 0; h < NH; h++) { int k = h; for (; k > 0 && done[order[k - 1] * 8 + j] < done[h * 8 + j]; k--) order[k] = order[k - 1]; order[k] = h; }
    for (int kq = 0; kq < 4; kq++) {
      left[kq] = SPARE_N == 0 ? 16 : kq < SPARE_N ? 20 - SPARE_N : 16 - SPARE_N;
      for (int nh = 0; nh < 2; nh++) { Sched::Pair& q = s.pair[kq * 16 + nh * 8 + j]; q.otask = (uint8_t)(kq * 16 + nh * 8 + j); q.nsteps = (uint8_t)((left[kq] + 1) / 2); q.ochunk[0][0] = 255; }
    }
    for (int n = 0, kq = 0, run = 0; n < 64; ) {
      if (left[kq] > 0 && run < 2) {
        const int pos = --left[kq] + (SPARE_N & 1);
        for (int nh = 0; nh < 2; nh++) s.pair[kq * 16 + nh * 8 + j].ochunk[pos >> 1][pos & 1] = (uint8_t)(order[n >> 1] * 2 + 1 - (n & 1));
        n++; run++;
      } else { kq = (kq + 1) & 3; run = 0; }
    }
  }
}

}

extern "C" void kernel_launch(void* const* d_in, const int* in_sizes, int n_in, void* d_out, int out_size) {
  (void)in_sizes; (void)n_in; (void)out_size;
  const __nv_bfloat16* x     = (const __nv_bfloat16*)d_in[0];
  const __nv_bfloat16* ckv   = (const __nv_bfloat16*)d_in[1];
  const __nv_bfloat16* w_q   = (const __nv_bfloat16*)d_in[2];
  const __nv_bfloat16* w_uk  = (const __nv_bfloat16*)d_in[3];
  const __nv_bfloat16* w_uv  = (const __nv_bfloat16*)d_in[4];
  const __nv_bfloat16* w_o   = (const __nv_bfloat16*)d_in[5];
  const __nv_bfloat16* w_r   = (const __nv_bfloat16*)d_in[7];
  const __nv_bfloat16* w_g   = (const __nv_bfloat16*)d_in[8];
  const __nv_bfloat16* w_u   = (const __nv_bfloat16*)d_in[9];
  const __nv_bfloat16* w_d   = (const __nv_bfloat16*)d_in[10];
  const __nv_bfloat16* cvec  = (const __nv_bfloat16*)d_in[11];
  const __nv_bfloat16* w_mod = (const __nv_bfloat16*)d_in[12];
  __nv_bfloat16* out = (__nv_bfloat16*)d_out;

  static HostState st;
  if (!st.ready) {
    void* fn = nullptr; cudaDriverEntryPointQueryResult qr;
    cudaGetDriverEntryPoint("cuTensorMapEncodeTiled", &fn, cudaEnableDefault, &qr);
    st.encode = (EncodeFn)fn;
    cudaFuncSetAttribute(k_fused, cudaFuncAttributeMaxDynamicSharedMemorySize, SMEM);
    build_sched(st.sched);
    void *p_kvc, *p_h1, *p_part;
    cudaGetSymbolAddress(&p_kvc, g_kvc); cudaGetSymbolAddress(&p_h1, g_h1); cudaGetSymbolAddress(&p_part, g_part);
    st.sched.kvc = (__nv_bfloat16*)p_kvc; st.sched.h1 = (__nv_bfloat16*)p_h1;
    make_2d(st.encode, &st.tmH, p_h1, SEQ, DM, 64);
    make_2d(st.encode, &st.tmKV, p_kvc, 192 * SEQ, 64, 128);
    make_3d(st.encode, &st.tmPart, p_part, SEQ, 32, 128, (size_t)SEQ * 128);
    { const cuuint64_t dims[3] = {64, (cuuint64_t)SEQ, 32}, strides[2] = {128, (cuuint64_t)SEQ * 128}; const cuuint32_t box[3] = {64, 16, 4};
      make_map(st.encode, &st.tmPl, p_part, 3, dims, strides, box, false); }
    st.ready = true;
  }
  make_2d(st.encode, &st.tmC, ckv, SEQ, DM, 128);
  make_2d(st.encode, &st.tmWq, w_q, DM, NH * DH, 64);
  make_2d(st.encode, &st.tmWk, w_uk, DM, NH * DH, 64);
  make_2d(st.encode, &st.tmWv, w_uv, DM, NH * DH, 64);
  make_3d(st.encode, &st.tmWo, w_o, NH * DH, DM / 64, (size_t)DM * 2, 128);
  make_3d(st.encode, &st.tmWm, w_mod, DM, 6 * DM / 64, (size_t)6 * DM * 2, 128);
  make_ffn(st.encode, &st.tmWg, w_g);
  make_ffn(st.encode, &st.tmWu, w_u);

  k_fused<<<NGRID, 384, SMEM, cudaStreamPerThread>>>(st.tmC, st.tmH, st.tmWq, st.tmWk, st.tmWv, st.tmKV, st.tmWo, st.tmPart, st.tmWg, st.tmWu, st.tmPl, st.tmWm, st.sched,
                                                     x, cvec, w_o, w_r, w_g, w_u, w_d, out);
}
```

```cpp
#include <cuda_runtime.h>
#include <cuda_bf16.h>
#include <cuda.h>
#include <stdint.h>
#include <string.h>
#include <math.h>

namespace {

constexpr int SEQ = 2048, DM = 512, NH = 32, DH = 128, FF = 1792;
constexpr int NCTA = 128, NGRID = 132;

__device__ __nv_bfloat16 g_kvc[192 * SEQ * 64];
__device__ __nv_bfloat16 g_h1[SEQ * DM];
__device__ __nv_bfloat16 g_part[32 * SEQ * 64];
__device__ __align__(16) __nv_bfloat16 g_mod[6 * DM];
constexpr int C_MOD = 0, C_MOD2 = 16, C_H1 = 32, C_KV = 64, C_CTX = 128, C_END = 384;
__device__ unsigned int g_cnt[C_END];
__device__ unsigned int g_epoch;
__device__ __align__(128) unsigned int g_pflag[32][32];
__device__ __align__(128) uint2 g_keys[128][4];
__device__ __align__(16) uint2 g_row[128][2][DM / 2];
__device__ __align__(16) uint2 g_yll[FF / 16][DM];

#define DBG(i)
#define DBGP(i)

__device__ __forceinline__ uint32_t smem_u32(const void* p) { return (uint32_t)__cvta_generic_to_shared(p); }
__device__ __forceinline__ int wg_tid() { int t; asm volatile("mov.u32 %0, %%tid.x;" : "=r"(t)); return t & 127; }
__device__ __forceinline__ uint32_t clk32() { uint32_t c; asm volatile("mov.u32 %0, %%clock;" : "=r"(c)); return c; }
__device__ __forceinline__ void mbar_arrive(uint32_t bar) { asm volatile("mbarrier.arrive.shared::cta.b64 _, [%0];" :: "r"(bar) : "memory"); }
__device__ __forceinline__ uint32_t mapa(uint32_t addr, uint32_t cta) { uint32_t r; asm("mapa.shared::cluster.u32 %0, %1, %2;" : "=r"(r) : "r"(addr), "r"(cta)); return r; }
__device__ __forceinline__ void mbar_arrive_remote_if(uint32_t cluster_addr, bool pred) {
  asm volatile("{\n.reg .pred p;\nsetp.ne.u32 p, %1, 0;\n@p mbarrier.arrive.shared::cluster.b64 _, [%0];\n}" :: "r"(cluster_addr), "r"((uint32_t)pred) : "memory");
}
__device__ __forceinline__ bool mbar_try(uint32_t bar, uint32_t parity) {
  uint32_t done;
  asm volatile("{\n.reg .pred p;\nmbarrier.try_wait.parity.shared::cta.b64 p, [%1], %2;\nselp.u32 %0, 1, 0, p;\n}" : "=r"(done) : "r"(bar), "r"(parity) : "memory");
  return done;
}
#define WAIT_LIM (1 << 14)
__device__ __forceinline__ void mbar_wait(uint32_t bar, uint32_t parity) {
  #pragma unroll 1
  for (int n = 0; n < WAIT_LIM; n++) { if (mbar_try(bar, parity)) break; }
}
__device__ __forceinline__ unsigned int ld_acquire(const unsigned int* p) {
  unsigned int v; asm volatile("ld.acquire.gpu.global.u32 %0, [%1];" : "=r"(v) : "l"(p) : "memory"); return v;
}
__device__ __forceinline__ unsigned int ld_relaxed(const unsigned int* p) {
  unsigned int v; asm volatile("ld.relaxed.gpu.global.u32 %0, [%1];" : "=r"(v) : "l"(p) : "memory"); return v;
}
__device__ __forceinline__ void wait_count_lazy(int idx, unsigned int target) {
  #pragma unroll 1
  for (int n = 0; n < WAIT_LIM; n++) { if (__all_sync(0xffffffff, (int)(ld_relaxed(&g_cnt[idx]) - target) >= 0)) break; __nanosleep(100); }
  ld_acquire(&g_cnt[idx]);
}
__device__ __forceinline__ uint4 ld_tagged2(const void* p) {
  uint4 v;
  asm volatile("{\n.reg .b64 a, b;\nld.relaxed.gpu.global.v2.u64 {a, b}, [%4];\nmov.b64 {%0, %1}, a;\nmov.b64 {%2, %3}, b;\n}"
    : "=r"(v.x), "=r"(v.y), "=r"(v.z), "=r"(v.w) : "l"(p) : "memory");
  return v;
}
__device__ __forceinline__ uint2 ld_tagged(const void* p) {
  uint2 v; asm volatile("{\n.reg .b64 a;\nld.relaxed.gpu.global.u64 a, [%2];\nmov.b64 {%0, %1}, a;\n}" : "=r"(v.x), "=r"(v.y) : "l"(p) : "memory"); return v;
}
__device__ __forceinline__ void st_tagged2(void* p, uint32_t a, uint32_t b, uint32_t tag) {
  asm volatile("{\n.reg .b64 a, b;\nmov.b64 a, {%1, %3};\nmov.b64 b, {%2, %3};\nst.relaxed.gpu.global.v2.u64 [%0], {a, b};\n}" :: "l"(p), "r"(a), "r"(b), "r"(tag) : "memory");
}
__device__ __forceinline__ void st_tagged(void* p, uint32_t a, uint32_t tag) {
  asm volatile("{\n.reg .b64 a;\nmov.b64 a, {%1, %2};\nst.relaxed.gpu.global.u64 [%0], a;\n}" :: "l"(p), "r"(a), "r"(tag) : "memory");
}
__device__ __forceinline__ void stg_v4(void* p, uint32_t a, uint32_t b, uint32_t c, uint32_t d) {
  asm volatile("st.global.v4.u32 [%0], {%1, %2, %3, %4};" :: "l"(p), "r"(a), "r"(b), "r"(c), "r"(d) : "memory");
}
__device__ __forceinline__ uint4 lds_v4(uint32_t addr) {
  uint4 v; asm volatile("ld.shared.v4.u32 {%0, %1, %2, %3}, [%4];" : "=r"(v.x), "=r"(v.y), "=r"(v.z), "=r"(v.w) : "r"(addr) : "memory"); return v;
}
__device__ __forceinline__ uint32_t lds_u32(uint32_t addr) { uint32_t v; asm volatile("ld.shared.u32 %0, [%1];" : "=r"(v) : "r"(addr) : "memory"); return v; }
__device__ __forceinline__ void sts_v4(uint32_t addr, uint32_t a, uint32_t b, uint32_t c, uint32_t d) {
  asm volatile("st.shared.v4.u32 [%0], {%1, %2, %3, %4};" :: "r"(addr), "r"(a), "r"(b), "r"(c), "r"(d) : "memory");
}
#define ELECT "{\n.reg .pred p;\nelect.sync _|p, 0xffffffff;\n@p "
__device__ __forceinline__ void w_mbar_init(uint32_t bar, uint32_t cnt) { asm volatile(ELECT "mbarrier.init.shared::cta.b64 [%0], %1;\n}" :: "r"(bar), "r"(cnt) : "memory"); }
__device__ __forceinline__ void w_expect_tx(uint32_t bar, uint32_t bytes) { asm volatile(ELECT "mbarrier.arrive.expect_tx.shared::cta.b64 _, [%0], %1;\n}" :: "r"(bar), "r"(bytes) : "memory"); }
__device__ __forceinline__ void w_arrive(uint32_t bar) { asm volatile(ELECT "mbarrier.arrive.shared::cta.b64 _, [%0];\n}" :: "r"(bar) : "memory"); }
__device__ __forceinline__ void tma_load_2d(uint32_t dst, const CUtensorMap* tm, uint32_t bar, int c0, int c1) {
  asm volatile(ELECT "cp.async.bulk.tensor.2d.shared::cluster.global.mbarrier::complete_tx::bytes [%0], [%1, {%3, %4}], [%2];\n}"
    :: "r"(dst), "l"(tm), "r"(bar), "r"(c0), "r"(c1) : "memory");
}
__device__ __forceinline__ void tma_load_2d_mc(uint32_t dst, const CUtensorMap* tm, uint32_t bar, int c0, int c1) {
  asm volatile(ELECT "cp.async.bulk.tensor.2d.shared::cluster.global.mbarrier::complete_tx::bytes.multicast::cluster [%0], [%1, {%3, %4}], [%2], %5;\n}"
    :: "r"(dst), "l"(tm), "r"(bar), "r"(c0), "r"(c1), "h"((uint16_t)3) : "memory");
}
__device__ __forceinline__ void tma_load_3d(uint32_t dst, const CUtensorMap* tm, uint32_t bar, int c0, int c1, int c2) {
  asm volatile(ELECT "cp.async.bulk.tensor.3d.shared::cluster.global.mbarrier::complete_tx::bytes [%0], [%1, {%3, %4, %5}], [%2];\n}"
    :: "r"(dst), "l"(tm), "r"(bar), "r"(c0), "r"(c1), "r"(c2) : "memory");
}
__device__ __forceinline__ void tma_load_3d_mc(uint32_t dst, const CUtensorMap* tm, uint32_t bar, int c0, int c1, int c2) {
  asm volatile(ELECT "cp.async.bulk.tensor.3d.shared::cluster.global.mbarrier::complete_tx::bytes.multicast::cluster [%0], [%1, {%3, %4, %5}], [%2], %6;\n}"
    :: "r"(dst), "l"(tm), "r"(bar), "r"(c0), "r"(c1), "r"(c2), "h"((uint16_t)3) : "memory");
}
__device__ __forceinline__ uint64_t evict_first() { uint64_t a; asm("createpolicy.fractional.L2::evict_first.b64 %0, 1.0;" : "=l"(a)); return a; }
__device__ __forceinline__ void tma_load_2d_mc(uint32_t dst, const CUtensorMap* tm, uint32_t bar, int c0, int c1, bool ef) {
  if (!ef) tma_load_2d_mc(dst, tm, bar, c0, c1); else
  asm volatile(ELECT "cp.async.bulk.tensor.2d.shared::cluster.global.mbarrier::complete_tx::bytes.multicast::cluster.L2::cache_hint [%0], [%1, {%3, %4}], [%2], %5, %6;\n}"
    :: "r"(dst), "l"(tm), "r"(bar), "r"(c0), "r"(c1), "h"((uint16_t)3), "l"(evict_first()) : "memory");
}
__device__ __forceinline__ void bulk_load(uint32_t dst, const void* src, uint32_t bytes, uint32_t bar) {
  asm volatile(ELECT "cp.async.bulk.shared::cluster.global.mbarrier::complete_tx::bytes [%0], [%1], %2, [%3];\n}" :: "r"(dst), "l"(src), "r"(bytes), "r"(bar) : "memory");
}
__device__ __forceinline__ void tma_prefetch_2d(const CUtensorMap* tm, int c0, int c1) {
  asm volatile(ELECT "cp.async.bulk.prefetch.tensor.2d.L2.global [%0, {%1, %2}];\n}" :: "l"(tm), "r"(c0), "r"(c1) : "memory");
}
__device__ __forceinline__ void bulk_prefetch(const void* p, uint32_t bytes) {
  asm volatile(ELECT "cp.async.bulk.prefetch.L2.global [%0], %1;\n}" :: "l"(p), "r"(bytes) : "memory");
}
__device__ __forceinline__ void tma_store_3d(const CUtensorMap* tm, uint32_t src, int c0, int c1, int c2) {
  asm volatile("cp.async.bulk.tensor.3d.global.shared::cta.bulk_group [%0, {%2, %3, %4}], [%1];"
    :: "l"(tm), "r"(src), "r"(c0), "r"(c1), "r"(c2) : "memory");
}
__device__ __forceinline__ void st_release(unsigned int* p, unsigned int v) { asm volatile("st.release.gpu.global.u32 [%0], %1;" :: "l"(p), "r"(v) : "memory"); }
__device__ __forceinline__ void red_release(int idx) { asm volatile("red.release.gpu.global.add.u32 [%0], 1;" :: "l"(&g_cnt[idx]) : "memory"); }
__device__ __forceinline__ void prefetch_tmap(const CUtensorMap* tm) { asm volatile("prefetch.tensormap [%0];" :: "l"(tm) : "memory"); }
__device__ __forceinline__ void bulk_commit() { asm volatile("cp.async.bulk.commit_group;" ::: "memory"); }
template<int N> __device__ __forceinline__ void bulk_wait() { asm volatile("cp.async.bulk.wait_group %0;" :: "n"(N) : "memory"); }
__device__ __forceinline__ void bar_sync(int id, int n) { asm volatile("bar.sync %0, %1;" :: "r"(id), "r"(n) : "memory"); }
__device__ __forceinline__ void bar_arrive(int id, int n) { asm volatile("bar.arrive %0, %1;" :: "r"(id), "r"(n) : "memory"); }
__device__ __forceinline__ void fence_async_smem() { asm volatile("fence.proxy.async.shared::cta;" ::: "memory"); }
__device__ __forceinline__ void fence_async_global() { asm volatile("fence.proxy.async.global;" ::: "memory"); }
__device__ __forceinline__ void fence_mbar_init() { asm volatile("fence.mbarrier_init.release.cluster;" ::: "memory"); }
__device__ __forceinline__ void cluster_arrive() { asm volatile("barrier.cluster.arrive.relaxed.aligned;" ::: "memory"); }
__device__ __forceinline__ void cluster_wait() { asm volatile("barrier.cluster.wait.aligned;" ::: "memory"); }
__device__ __forceinline__ uint32_t cluster_ctarank() { uint32_t r; asm volatile("mov.u32 %0, %%cluster_ctarank;" : "=r"(r)); return r; }
__device__ __forceinline__ void wgmma_fence() { asm volatile("wgmma.fence.sync.aligned;" ::: "memory"); }
__device__ __forceinline__ void wgmma_commit() { asm volatile("wgmma.commit_group.sync.aligned;" ::: "memory"); }
template<int N> __device__ __forceinline__ void wgmma_wait() { asm volatile("wgmma.wait_group.sync.aligned %0;" :: "n"(N) : "memory"); }
__device__ __forceinline__ float ex2(float x) { float y; asm("ex2.approx.ftz.f32 %0, %1;" : "=f"(y) : "f"(x)); return y; }
__device__ __forceinline__ float rcp_fast(float x) { float y; asm("rcp.approx.ftz.f32 %0, %1;" : "=f"(y) : "f"(x)); return y; }
__device__ __forceinline__ uint32_t pack_bf16(float lo, float hi) { uint32_t r; asm("cvt.rn.bf16x2.f32 %0, %1, %2;" : "=r"(r) : "f"(hi), "f"(lo)); return r; }
__device__ __forceinline__ float rbf(float x) { return __uint_as_float(pack_bf16(0.f, x)); }
__device__ __forceinline__ float bf_lo(uint32_t v) { return __uint_as_float(v << 16); }
__device__ __forceinline__ float bf_hi(uint32_t v) { return __uint_as_float(v & 0xffff0000u); }
__device__ __forceinline__ uint32_t add2(uint32_t a, uint32_t b) { uint32_t r; asm("add.rn.bf16x2 %0, %1, %2;" : "=r"(r) : "r"(a), "r"(b)); return r; }
__device__ __forceinline__ uint32_t fma2(uint32_t a, uint32_t b, uint32_t c) { uint32_t r; asm("fma.rn.bf16x2 %0, %1, %2, %3;" : "=r"(r) : "r"(a), "r"(b), "r"(c)); return r; }
__device__ __forceinline__ uint4 ldsm_x4_t(uint32_t addr) {
  uint4 v; asm volatile("ldmatrix.sync.aligned.m8n8.x4.trans.shared.b16 {%0, %1, %2, %3}, [%4];" : "=r"(v.x), "=r"(v.y), "=r"(v.z), "=r"(v.w) : "r"(addr) : "memory"); return v;
}
__device__ __forceinline__ void mma16816(float (&c)[4], const uint4& a, uint32_t b0, uint32_t b1) {
  asm("mma.sync.aligned.m16n8k16.row.col.f32.bf16.bf16.f32 {%0, %1, %2, %3}, {%4, %5, %6, %7}, {%8, %9}, {%0, %1, %2, %3};"
    : "+f"(c[0]), "+f"(c[1]), "+f"(c[2]), "+f"(c[3]) : "r"(a.x), "r"(a.y), "r"(a.z), "r"(a.w), "r"(b0), "r"(b1));
}
__device__ __forceinline__ void stsm_x4(uint32_t addr, uint32_t r0, uint32_t r1, uint32_t r2, uint32_t r3) {
  asm volatile("stmatrix.sync.aligned.m8n8.x4.shared.b16 [%0], {%1, %2, %3, %4};" :: "r"(addr), "r"(r0), "r"(r1), "r"(r2), "r"(r3) : "memory");
}
template<int N> __device__ __forceinline__ void fence_regs(float (&a)[N]) {
  #pragma unroll
  for (int i = 0; i < N; i++) asm volatile("" : "+f"(a[i]) :: "memory");
}
template<int N> __device__ __forceinline__ void fence_regs_u(uint32_t (&a)[N]) {
  #pragma unroll
  for (int i = 0; i < N; i++) asm volatile("" : "+r"(a[i]) :: "memory");
}
__device__ __forceinline__ uint32_t desc_lo(uint32_t addr, uint32_t lbo) { return ((addr & 0x3FFFF) >> 4) | ((lbo >> 4) << 16); }

template<int TB, int OA, int OB> __device__ __forceinline__ void wgmma_ss_n128(float (&d)[64], uint32_t da, uint32_t db, int sd) {
  asm volatile("{\n.reg .pred p;\n.reg .b32 ta, tb;\n.reg .b64 da, db;\nsetp.ne.b32 p, %66, 0;\nadd.u32 ta, %64, %68;\nadd.u32 tb, %65, %69;\nmov.b64 da, {ta, 0x40000040};\nmov.b64 db, {tb, 0x40000040};\n"
    "wgmma.mma_async.sync.aligned.m64n128k16.f32.bf16.bf16 "
    "{%0, %1, %2, %3, %4, %5, %6, %7, %8, %9, %10, %11, %12, %13, %14, %15, %16, %17, %18, %19, %20, %21, %22, %23, %24, %25, %26, %27, %28, %29, %30, %31, %32, %33, %34, %35, %36, %37, %38, %39, %40, %41, %42, %43, %44, %45, %46, %47, %48, %49, %50, %51, %52, %53, %54, %55, %56, %57, %58, %59, %60, %61, %62, %63}, da, db, p, 1, 1, 0, %67;\n}\n"
    : "+f"(d[0]), "+f"(d[1]), "+f"(d[2]), "+f"(d[3]), "+f"(d[4]), "+f"(d[5]), "+f"(d[6]), "+f"(d[7]), "+f"(d[8]), "+f"(d[9]), "+f"(d[10]), "+f"(d[11]), "+f"(d[12]), "+f"(d[13]), "+f"(d[14]), "+f"(d[15]), "+f"(d[16]), "+f"(d[17]), "+f"(d[18]), "+f"(d[19]), "+f"(d[20]), "+f"(d[21]), "+f"(d[22]), "+f"(d[23]), "+f"(d[24]), "+f"(d[25]), "+f"(d[26]), "+f"(d[27]), "+f"(d[28]), "+f"(d[29]), "+f"(d[30]), "+f"(d[31]), "+f"(d[32]), "+f"(d[33]), "+f"(d[34]), "+f"(d[35]), "+f"(d[36]), "+f"(d[37]), "+f"(d[38]), "+f"(d[39]), "+f"(d[40]), "+f"(d[41]), "+f"(d[42]), "+f"(d[43]), "+f"(d[44]), "+f"(d[45]), "+f"(d[46]), "+f"(d[47]), "+f"(d[48]), "+f"(d[49]), "+f"(d[50]), "+f"(d[51]), "+f"(d[52]), "+f"(d[53]), "+f"(d[54]), "+f"(d[55]), "+f"(d[56]), "+f"(d[57]), "+f"(d[58]), "+f"(d[59]), "+f"(d[60]), "+f"(d[61]), "+f"(d[62]), "+f"(d[63])
    : "r"(da), "r"(db), "r"(sd), "n"(TB), "n"(OA), "n"(OB));
}
template<int TB, int OB> __device__ __forceinline__ void wgmma_rs_n128(float (&d)[64], uint32_t a0, uint32_t a1, uint32_t a2, uint32_t a3, uint32_t db, int sd) {
  asm volatile("{\n.reg .pred p;\n.reg .b32 tb;\n.reg .b64 db;\nsetp.ne.b32 p, %69, 0;\nadd.u32 tb, %68, %71;\nmov.b64 db, {tb, 0x40000040};\n"
    "wgmma.mma_async.sync.aligned.m64n128k16.f32.bf16.bf16 "
    "{%0, %1, %2, %3, %4, %5, %6, %7, %8, %9, %10, %11, %12, %13, %14, %15, %16, %17, %18, %19, %20, %21, %22, %23, %24, %25, %26, %27, %28, %29, %30, %31, %32, %33, %34, %35, %36, %37, %38, %39, %40, %41, %42, %43, %44, %45, %46, %47, %48, %49, %50, %51, %52, %53, %54, %55, %56, %57, %58, %59, %60, %61, %62, %63}, {%64,%65,%66,%67}, db, p, 1, 1, %70;\n}\n"
    : "+f"(d[0]), "+f"(d[1]), "+f"(d[2]), "+f"(d[3]), "+f"(d[4]), "+f"(d[5]), "+f"(d[6]), "+f"(d[7]), "+f"(d[8]), "+f"(d[9]), "+f"(d[10]), "+f"(d[11]), "+f"(d[12]), "+f"(d[13]), "+f"(d[14]), "+f"(d[15]), "+f"(d[16]), "+f"(d[17]), "+f"(d[18]), "+f"(d[19]), "+f"(d[20]), "+f"(d[21]), "+f"(d[22]), "+f"(d[23]), "+f"(d[24]), "+f"(d[25]), "+f"(d[26]), "+f"(d[27]), "+f"(d[28]), "+f"(d[29]), "+f"(d[30]), "+f"(d[31]), "+f"(d[32]), "+f"(d[33]), "+f"(d[34]), "+f"(d[35]), "+f"(d[36]), "+f"(d[37]), "+f"(d[38]), "+f"(d[39]), "+f"(d[40]), "+f"(d[41]), "+f"(d[42]), "+f"(d[43]), "+f"(d[44]), "+f"(d[45]), "+f"(d[46]), "+f"(d[47]), "+f"(d[48]), "+f"(d[49]), "+f"(d[50]), "+f"(d[51]), "+f"(d[52]), "+f"(d[53]), "+f"(d[54]), "+f"(d[55]), "+f"(d[56]), "+f"(d[57]), "+f"(d[58]), "+f"(d[59]), "+f"(d[60]), "+f"(d[61]), "+f"(d[62]), "+f"(d[63])
    : "r"(a0), "r"(a1), "r"(a2), "r"(a3), "r"(db), "r"(sd), "n"(TB), "n"(OB));
}
template<int TB, int OA, int OB> __device__ __forceinline__ void wgmma_ss_n64(float (&d)[32], uint32_t da, uint32_t db, int sd) {
  asm volatile("{\n.reg .pred p;\n.reg .b32 ta, tb;\n.reg .b64 da, db;\nsetp.ne.b32 p, %34, 0;\nadd.u32 ta, %32, %36;\nadd.u32 tb, %33, %37;\nmov.b64 da, {ta, 0x40000040};\nmov.b64 db, {tb, 0x40000040};\n"
    "wgmma.mma_async.sync.aligned.m64n64k16.f32.bf16.bf16 "
    "{%0, %1, %2, %3, %4, %5, %6, %7, %8, %9, %10, %11, %12, %13, %14, %15, %16, %17, %18, %19, %20, %21, %22, %23, %24, %25, %26, %27, %28, %29, %30, %31}, da, db, p, 1, 1, 0, %35;\n}\n"
    : "+f"(d[0]), "+f"(d[1]), "+f"(d[2]), "+f"(d[3]), "+f"(d[4]), "+f"(d[5]), "+f"(d[6]), "+f"(d[7]), "+f"(d[8]), "+f"(d[9]), "+f"(d[10]), "+f"(d[11]), "+f"(d[12]), "+f"(d[13]), "+f"(d[14]), "+f"(d[15]), "+f"(d[16]), "+f"(d[17]), "+f"(d[18]), "+f"(d[19]), "+f"(d[20]), "+f"(d[21]), "+f"(d[22]), "+f"(d[23]), "+f"(d[24]), "+f"(d[25]), "+f"(d[26]), "+f"(d[27]), "+f"(d[28]), "+f"(d[29]), "+f"(d[30]), "+f"(d[31])
    : "r"(da), "r"(db), "r"(sd), "n"(TB), "n"(OA), "n"(OB));
}
template<int TB, int OA, int OB> __device__ __forceinline__ void wgmma_ss_n128_new(float (&d)[64], uint32_t da, uint32_t db) {
  asm volatile("{\n.reg .pred p;\n.reg .b32 ta, tb;\n.reg .b64 da, db;\nsetp.ne.b32 p, %66, 0;\nadd.u32 ta, %64, %68;\nadd.u32 tb, %65, %69;\nmov.b64 da, {ta, 0x40000040};\nmov.b64 db, {tb, 0x40000040};\n"
    "wgmma.mma_async.sync.aligned.m64n128k16.f32.bf16.bf16 "
    "{%0, %1, %2, %3, %4, %5, %6, %7, %8, %9, %10, %11, %12, %13, %14, %15, %16, %17, %18, %19, %20, %21, %22, %23, %24, %25, %26, %27, %28, %29, %30, %31, %32, %33, %34, %35, %36, %37, %38, %39, %40, %41, %42, %43, %44, %45, %46, %47, %48, %49, %50, %51, %52, %53, %54, %55, %56, %57, %58, %59, %60, %61, %62, %63}, da, db, p, 1, 1, 0, %67;\n}\n"
    : "=f"(d[0]), "=f"(d[1]), "=f"(d[2]), "=f"(d[3]), "=f"(d[4]), "=f"(d[5]), "=f"(d[6]), "=f"(d[7]), "=f"(d[8]), "=f"(d[9]), "=f"(d[10]), "=f"(d[11]), "=f"(d[12]), "=f"(d[13]), "=f"(d[14]), "=f"(d[15]), "=f"(d[16]), "=f"(d[17]), "=f"(d[18]), "=f"(d[19]), "=f"(d[20]), "=f"(d[21]), "=f"(d[22]), "=f"(d[23]), "=f"(d[24]), "=f"(d[25]), "=f"(d[26]), "=f"(d[27]), "=f"(d[28]), "=f"(d[29]), "=f"(d[30]), "=f"(d[31]), "=f"(d[32]), "=f"(d[33]), "=f"(d[34]), "=f"(d[35]), "=f"(d[36]), "=f"(d[37]), "=f"(d[38]), "=f"(d[39]), "=f"(d[40]), "=f"(d[41]), "=f"(d[42]), "=f"(d[43]), "=f"(d[44]), "=f"(d[45]), "=f"(d[46]), "=f"(d[47]), "=f"(d[48]), "=f"(d[49]), "=f"(d[50]), "=f"(d[51]), "=f"(d[52]), "=f"(d[53]), "=f"(d[54]), "=f"(d[55]), "=f"(d[56]), "=f"(d[57]), "=f"(d[58]), "=f"(d[59]), "=f"(d[60]), "=f"(d[61]), "=f"(d[62]), "=f"(d[63])
    : "r"(da), "r"(db), "n"(0), "n"(TB), "n"(OA), "n"(OB));
}
template<int TB, int OA, int OB> __device__ __forceinline__ void wgmma_ss_n64_new(float (&d)[32], uint32_t da, uint32_t db) {
  asm volatile("{\n.reg .pred p;\n.reg .b32 ta, tb;\n.reg .b64 da, db;\nsetp.ne.b32 p, %34, 0;\nadd.u32 ta, %32, %36;\nadd.u32 tb, %33, %37;\nmov.b64 da, {ta, 0x40000040};\nmov.b64 db, {tb, 0x40000040};\n"
    "wgmma.mma_async.sync.aligned.m64n64k16.f32.bf16.bf16 "
    "{%0, %1, %2, %3, %4, %5, %6, %7, %8, %9, %10, %11, %12, %13, %14, %15, %16, %17, %18, %19, %20, %21, %22, %23, %24, %25, %26, %27, %28, %29, %30, %31}, da, db, p, 1, 1, 0, %35;\n}\n"
    : "=f"(d[0]), "=f"(d[1]), "=f"(d[2]), "=f"(d[3]), "=f"(d[4]), "=f"(d[5]), "=f"(d[6]), "=f"(d[7]), "=f"(d[8]), "=f"(d[9]), "=f"(d[10]), "=f"(d[11]), "=f"(d[12]), "=f"(d[13]), "=f"(d[14]), "=f"(d[15]), "=f"(d[16]), "=f"(d[17]), "=f"(d[18]), "=f"(d[19]), "=f"(d[20]), "=f"(d[21]), "=f"(d[22]), "=f"(d[23]), "=f"(d[24]), "=f"(d[25]), "=f"(d[26]), "=f"(d[27]), "=f"(d[28]), "=f"(d[29]), "=f"(d[30]), "=f"(d[31])
    : "r"(da), "r"(db), "n"(0), "n"(TB), "n"(OA), "n"(OB));
}
template<int OA, int OB = 0> __device__ __forceinline__ void kblock_n128(float (&d)[64], uint32_t da, uint32_t db, int sd) {
  wgmma_ss_n128<1, OA, OB>(d, da, db, sd); wgmma_ss_n128<1, OA + 2, OB + 128>(d, da, db, 1);
  wgmma_ss_n128<1, OA + 4, OB + 256>(d, da, db, 1); wgmma_ss_n128<1, OA + 6, OB + 384>(d, da, db, 1);
}

__device__ __forceinline__ float quad_sum(float v) {
  v += __shfl_xor_sync(0xffffffff, v, 1);
  v += __shfl_xor_sync(0xffffffff, v, 2);
  return v;
}
struct Row { uint32_t v[8]; };
template<class F> __device__ __forceinline__ Row load_row(const __nv_bfloat16* p, int lane, F ld) {
  const uint4 a = ld(reinterpret_cast<const uint4*>(p) + lane), b = ld(reinterpret_cast<const uint4*>(p) + 32 + lane);
  return Row{{a.x, a.y, a.z, a.w, b.x, b.y, b.z, b.w}};
}
__device__ __forceinline__ Row ldg_row(const __nv_bfloat16* p, int lane) { return load_row(p, lane, [](const uint4* q) { return __ldg(q); }); }
__device__ __forceinline__ Row ldca_row(const __nv_bfloat16* p, int lane) { return load_row(p, lane, [](const uint4* q) { return __ldca(q); }); }
__device__ __forceinline__ Row lds_row(uint32_t addr, int lane) {
  const uint4 a = lds_v4(addr + lane * 16), b = lds_v4(addr + 512 + lane * 16);
  return Row{{a.x, a.y, a.z, a.w, b.x, b.y, b.z, b.w}};
}
__device__ __forceinline__ void store_row(__nv_bfloat16* p, int lane, const Row& r) {
  stg_v4(p + lane * 8, r.v[0], r.v[1], r.v[2], r.v[3]); stg_v4(p + 256 + lane * 8, r.v[4], r.v[5], r.v[6], r.v[7]);
}
__device__ __forceinline__ Row fma_row(const Row& a, const Row& b, const Row& c) {
  Row r;
  #pragma unroll
  for (int i = 0; i < 8; i++) r.v[i] = fma2(a.v[i], b.v[i], c.v[i]);
  return r;
}
__device__ __forceinline__ Row add_row(const Row& a, const Row& b) {
  Row r;
  #pragma unroll
  for (int i = 0; i < 8; i++) r.v[i] = add2(a.v[i], b.v[i]);
  return r;
}
__device__ __forceinline__ Row one_plus(const Row& a) {
  Row r;
  #pragma unroll
  for (int i = 0; i < 8; i++) r.v[i] = add2(a.v[i], 0x3f803f80u);
  return r;
}
__device__ __forceinline__ float row_at(const Row& x, int i) { return (i & 1) ? bf_hi(x.v[i >> 1]) : bf_lo(x.v[i >> 1]); }
template<int N> __device__ __forceinline__ void warp_sums(float (&s)[N]) {
  #pragma unroll
  for (int o = 16; o > 0; o >>= 1) {
    #pragma unroll
    for (int k = 0; k < N; k++) s[k] += __shfl_xor_sync(0xffffffff, s[k], o);
  }
}
__device__ __forceinline__ void ln_stats(float& s1, float& s2) {
  s1 *= 1.f / DM;
  asm("rsqrt.approx.ftz.f32 %0, %1;" : "=f"(s2) : "f"(fmaxf(fmaf(-s1, s1, s2 * (1.f / DM)), 0.f) + 1e-5f));
}
__device__ __forceinline__ Row ln_apply(const Row& x, float mean, float f) {
  Row n;
  const float o = -mean * f;
  #pragma unroll
  for (int i = 0; i < 8; i++) n.v[i] = pack_bf16(fmaf(bf_lo(x.v[i]), f, o), fmaf(bf_hi(x.v[i]), f, o));
  return n;
}

constexpr int SM_Q = 6 * 32768, SM_BAR = 7 * 32768, SM_MAIL = SM_BAR + 640, SM_RED = SM_MAIL + 128, SM_H2 = SM_RED + 1024, SM_KEY = SM_H2 + 1024, SMEM = SM_KEY + 128;
constexpr int B_AF = 0, B_WF = 64, B_RF = 112, B_WE = 168, B_RE = 216, B_PUB = 272, B_RDY = 496;
constexpr int R_MOD = B_RDY, R_H1 = B_RDY + 8, R_ITEM = B_RDY + 16, R_NEAR = B_RDY + 48, R_CTX = B_RDY + 64;
constexpr int R_KEY = B_AF + 8, R_PART = B_AF + 32;
constexpr int NPUB = 14;
__device__ __forceinline__ uint32_t k_addrA(int kb) { return ((0x6310u >> ((kb >> 1) * 4)) & 15u) * 32768u + (kb & 1) * 16384u; }
__device__ __forceinline__ uint32_t k_addrW(int s) { return ((0x254u >> ((s >> 1) * 4)) & 15u) * 32768u + (s & 1) * 16384u; }

#define KORDER 0x2301
constexpr int KHEAD0 = ((KORDER >> 12) & 3) * 8;
constexpr int MAX_ITEMS = 4;
constexpr int MAX_STEPS = 10;
struct Sched {
  __nv_bfloat16 *kvc, *h1;
  struct Pair {
    uint8_t oent[3 * MAX_STEPS + 6];
    uint16_t lastuse[MAX_ITEMS];
    uint8_t khead[4];
    uint8_t nitems, item[MAX_ITEMS];
    uint8_t otask, nsteps;
    uint8_t ochunk[MAX_STEPS][2];
  } pair[NGRID / 2];
};

__device__ __forceinline__ int ring_add(int e, int n) { e += n; return e >= 12 ? e - 12 : e; }
__device__ __forceinline__ int ring_slot(int e) { return e >= 6 ? e - 6 : e; }
__device__ __forceinline__ void ring_wait_full(uint32_t bars, int e) { mbar_wait(bars + B_RF + 8 * ring_slot(e), e >= 6); }

__device__ __forceinline__ void o_wait_full(uint32_t bars, uint32_t v) { mbar_wait(bars + B_RF + 8 * (v & 7), v >> 3); }

struct Ctx {
  uint32_t base, bars;
  uint32_t rel;
  bool rel1;
  int w, nev;
  const Sched* sched;
};
__device__ __forceinline__ void slot_release(const Ctx& x, int s, bool twice) {
  mbar_arrive_remote_if(x.rel + B_RE + 8 * s, twice ? (wg_tid() & 31) == 0 : x.rel1);
}
__device__ __forceinline__ void ring_release(const Ctx& x, int e, bool twice) { slot_release(x, ring_slot(e), twice); }
__device__ __forceinline__ void publish(Ctx& x, int idx) {
  const uint32_t n = x.w * NPUB + x.nev;
  const int t = wg_tid();
  if (t == 0) asm volatile("st.shared.u32 [%0], %1;" :: "r"(x.base + SM_MAIL + 4 * n), "r"(idx) : "memory");
  __syncwarp();
  if ((t & 31) == 0) mbar_arrive(x.bars + B_PUB + 8 * n);
  x.nev++;
}

template<int KK = 0> __device__ __forceinline__ void issue_qk(float (&S)[64], uint32_t dq, uint32_t dk) {
  constexpr int off = (KK >> 2) * 1024 + (KK & 3) * 2;
  if constexpr (KK == 0) wgmma_ss_n128_new<0, 0, 0>(S, dq, dk); else wgmma_ss_n128<0, off, off>(S, dq, dk, 1);
  if constexpr (KK < 7) issue_qk<KK + 1>(S, dq, dk);
}
template<int KK = 0> __device__ __forceinline__ void issue_qk_half(float (&S)[32], uint32_t dq, uint32_t dk) {
  constexpr int off = (KK >> 2) * 1024 + (KK & 3) * 2;
  if constexpr (KK == 0) wgmma_ss_n64_new<0, 0, 512>(S, dq, dk); else wgmma_ss_n64<0, off, off + 512>(S, dq, dk, 1);
  if constexpr (KK < 7) issue_qk_half<KK + 1>(S, dq, dk);
}
template<int NK, int KK = 0>
__device__ __forceinline__ void issue_pv(float (&O)[64], uint32_t (&P)[32], uint32_t dv, int accumulate) {
  wgmma_rs_n128<1, (KK + 8 - NK) * 128>(O, P[4*KK], P[4*KK+1], P[4*KK+2], P[4*KK+3], dv, accumulate);
  if constexpr (KK + 1 < NK) issue_pv<NK, KK + 1>(O, P, dv, 1);
}
template<int K0, int K1>
__device__ __forceinline__ void exp_pack(const float (&S)[64], uint32_t (&D)[32], float& s0, float& s1) {
  #pragma unroll
  for (int k = K0; k < K1; k++) {
    const float e0 = ex2(S[2*k]), e1 = ex2(S[2*k+1]);
    D[k] = pack_bf16(e0, e1);
    if (k & 1) s1 += e0 + e1; else s0 += e0 + e1;
  }
}
__device__ __forceinline__ int q_row(int t) { return 16 * (t >> 5) + ((t >> 1) & 6) + ((t >> 4) & 1); }
__device__ __forceinline__ int diag_limit() { const int t = wg_tid(); return q_row(t) - 2 * (t & 3); }
__device__ __forceinline__ void exp_pack_diag(const float (&S)[64], uint32_t (&D)[32], int t, float& s0, float& s1) {
  #pragma unroll
  for (int k = 0; k < 16; k++) {
    const int c = 8 * (k >> 1) - 8 * (k & 1);
    const float e0 = ex2((c <= t) ? S[2*k] : -INFINITY), e1 = ex2((c + 1 <= t) ? S[2*k+1] : -INFINITY);
    D[k] = pack_bf16(e0, e1);
    if (k & 1) s1 += e0 + e1; else s0 += e0 + e1;
  }
}
constexpr float SUM_HI = 1.8446744073709552e19f;
constexpr float SUM_LO = 5.421010862427522e-20f;

__device__ __forceinline__ void classic_tile(const float (&S)[64], uint32_t (&P)[32], bool fresh, bool half, bool was_classic, volatile float* mc,
                                             float& l0, float& l1, float& s0, float& s1, float& sc0, float& sc1) {
  const int tmask = diag_limit();
  float4 t[16];
  #pragma unroll
  for (int j = 0; j < 16; j++) t[j] = make_float4(S[4*j], S[4*j+1], S[4*j+2], S[4*j+3]);
  float mx0 = -INFINITY, mx1 = -INFINITY;
  #pragma unroll 1
  for (int j = 0; j < 16; j++) {
    float4 v = t[j];
    const int lim = !fresh ? 1000 : j < 8 ? tmask - 8 * j : half ? -1000 : 1000;
    v.x = 0 <= lim ? v.x : -INFINITY; v.y = 1 <= lim ? v.y : -INFINITY; v.z = -8 <= lim ? v.z : -INFINITY; v.w = -7 <= lim ? v.w : -INFINITY;
    t[j] = v;
    mx0 = fmaxf(mx0, fmaxf(v.x, v.y)); mx1 = fmaxf(mx1, fmaxf(v.z, v.w));
  }
  mx0 = fmaxf(mx0, __shfl_xor_sync(0xffffffff, mx0, 1));
  mx1 = fmaxf(mx1, __shfl_xor_sync(0xffffffff, mx1, 1));
  mx0 = fmaxf(mx0, __shfl_xor_sync(0xffffffff, mx0, 2));
  mx1 = fmaxf(mx1, __shfl_xor_sync(0xffffffff, mx1, 2));
  const float mc0 = was_classic ? mc[0] : 0.f, mc1 = was_classic ? mc[1] : 0.f;
  const float n0 = fresh ? -mx0 : fminf(mc0, -mx0), n1 = fresh ? -mx1 : fminf(mc1, -mx1);
  sc0 = ex2(n0 - mc0); sc1 = ex2(n1 - mc1);
  mc[0] = n0; mc[1] = n1;
  s0 = 0.f; s1 = 0.f;
  #pragma unroll 1
  for (int j = 0; j < 16; j++) {
    const float4 v = t[j];
    const float e0 = ex2(v.x + n0), e1 = ex2(v.y + n0), e2 = ex2(v.z + n1), e3 = ex2(v.w + n1);
    s0 += e0 + e1; s1 += e2 + e3;
    reinterpret_cast<uint2*>(t)[j] = make_uint2(pack_bf16(e0, e1), pack_bf16(e2, e3));
  }
  #pragma unroll
  for (int j = 0; j < 8; j++) { P[4*j] = __float_as_uint(t[j].x); P[4*j+1] = __float_as_uint(t[j].y); P[4*j+2] = __float_as_uint(t[j].z); P[4*j+3] = __float_as_uint(t[j].w); }
  if (!fresh) { l0 *= sc0; l1 *= sc1; }
}
__device__ __forceinline__ void pack_tile(const float (&A)[64], uint32_t (&D)[32], float f0, float f1) {
  #pragma unroll
  for (int j = 0; j < 16; j++) {
    D[8 * (j >> 2) + (j & 3)] = pack_bf16(A[4*j] * f0, A[4*j+1] * f0);
    D[8 * (j >> 2) + 4 + (j & 3)] = pack_bf16(A[4*j+2] * f1, A[4*j+3] * f1);
  }
}
__device__ __forceinline__ void store_tile(__nv_bfloat16* p, const uint32_t (&D)[32]) {
  #pragma unroll
  for (int i = 0; i < 8; i++) stg_v4(p + (i >> 2) * (SEQ * 64) + ((i >> 1) & 1) * 32 + (i & 1) * 8 * 64, D[4*i], D[4*i+1], D[4*i+2], D[4*i+3]);
}

enum : int { PV_ACC = 0, PV_ZERO = 1, PV_HALF = 2, PV_NONE = 3 };
struct Att {
  float l0, l1, i0, i1;
  bool classic;
  volatile float* mc;
};
__device__ __forceinline__ void store_ctx(Ctx& x, int code, const uint32_t (&D)[32]) {
  const int item = code >> 2, t = wg_tid(), lane = t & 31;
  const int row = (item & 7) * 256 + (code & 3) * 64 + q_row(t);
  store_tile(x.sched->kvc + ((size_t)(128 + (item >> 3) * 2) * SEQ + row) * 64 + (lane & 3) * 8, D);
  publish(x, C_CTX + item);
}

__device__ __forceinline__ __nv_bfloat16* kv_tile(const Ctx& x, int code) {
  const int t = wg_tid();
  return x.sched->kvc + ((size_t)(x.w * 64 + (code >> 4) * 2) * SEQ + (code & 15) * 128 + (t >> 5) * 16 + ((t & 31) >> 2)) * 64 + (t & 3) * 8;
}
#define V_AT 3
#define V_AT2 7
#define MERGE1 1
#define NO_CLASSIC 0
__device__ __forceinline__ void q_proj(Ctx& x, int& e, bool isY, const uint32_t (&PA)[32], const uint32_t (&PB)[32], int vtile, bool dbg = false) {
  float S[64];
  bar_sync(1 + x.w, 256);
  if (isY) bar_arrive(1 + (x.w ^ 1), 256);
  if (dbg) DBG(80);
  #pragma unroll 1
  for (int kb = 0; kb < 8; kb++) {
    ring_wait_full(x.bars, e);
    if (dbg) DBG(81 + kb);
    const uint32_t da = desc_lo(x.base + x.w * 8192, 16) + ring_slot(e) * 2048, dw = desc_lo(x.base + 16384, 8192) + ring_slot(e) * 2048;
    wgmma_fence();
    kblock_n128<0>(S, da, dw, kb != 0);
    wgmma_commit();
    if (kb == 7 && !isY) bar_arrive(1 + (x.w ^ 1), 256);
    if (kb > 0) { wgmma_wait<1>(); ring_release(x, ring_add(e, 11), false); }
    if (kb == V_AT && vtile >= 0) store_tile(kv_tile(x, vtile) + 64 * 64, PA);
    if (kb == V_AT2 && vtile >= 0) { store_tile(kv_tile(x, vtile), PB); publish(x, C_KV + (vtile >> 4)); }
    e = ring_add(e, 1);
  }
  wgmma_wait<0>();
  fence_regs(S);
  if (dbg) DBG(89);
  ring_release(x, ring_add(e, 11), false);
  const int t = wg_tid(), lane = t & 31, g = (lane >> 3) + (lane & 4);
  const uint32_t qa = x.base + SM_Q + x.w * 8192 + ((t >> 5) * 16 + g) * 128;
  #pragma unroll
  for (int i = 0; i < 8; i++) {
    const int j = 4 * (i >> 1), o = 2 * (i & 1);
    sts_v4(qa + (i >> 2) * 16384 + (i & 1) * 1024 + (((((i >> 1) & 1) * 4 + (lane & 3)) ^ g) << 4),
           pack_bf16(S[4*j+o], S[4*j+o+1]), pack_bf16(S[4*j+4+o], S[4*j+5+o]), pack_bf16(S[4*j+8+o], S[4*j+9+o]), pack_bf16(S[4*j+12+o], S[4*j+13+o]));
  }
  fence_async_smem();
  if (dbg) DBG(90);
  ring_wait_full(x.bars, ring_add(e, isY ? 0 : 2));
  ring_wait_full(x.bars, ring_add(e, 1));
}

template<int KIND>
__device__ __forceinline__ void slot(Ctx& x, Att& a, int& e, float (&O)[64], uint32_t (&Pn)[32], uint32_t (&Po)[32],
                                     bool more, bool isY, bool half, int pv, int pend) {
  float S[64];
  const int w = x.w;
  const bool skip = KIND == 0 && !isY;
  const int en = ring_add(e, skip ? 4 : 2), sn = ring_slot(en), sv = ring_slot(e) + 1, sk = skip ? ring_slot(ring_add(e, 2)) : sv - 1;
  const uint32_t dq = desc_lo(x.base + SM_Q + w * 8192, 16), dk = desc_lo(x.base, 16) + sk * 2048, dv = desc_lo(x.base, 16384) + sv * 2048;
  bar_sync(1 + w, 256);
  if (KIND == 2) {
    wgmma_fence();
    issue_qk(S, dq, dk); wgmma_commit();
    issue_pv<8>(O, Po, dv, 1); wgmma_commit();
    bar_arrive(1 + (w ^ 1), 256);
    wgmma_wait<1>();
  } else if (KIND == 0 && half) {
    float T[32];
    wgmma_fence(); issue_qk_half(T, dq, dk); wgmma_commit();
    a.i0 = rcp_fast(quad_sum(a.l0)); a.i1 = rcp_fast(quad_sum(a.l1));
    if (pv == PV_NONE) { wgmma_fence(); wgmma_commit(); }
    else               { wgmma_fence(); issue_pv<8>(O, Po, dv, pv == PV_ACC); wgmma_commit(); }
    bar_arrive(1 + (w ^ 1), 256);
    wgmma_wait<1>();
    fence_regs(T);
    #pragma unroll
    for (int i = 0; i < 32; i++) { S[i] = T[i]; asm volatile("" : "=f"(S[32 + i])); }
  } else {
    wgmma_fence(); issue_qk(S, dq, dk); wgmma_commit();
    if (KIND == 1 && pend >= 0) { bar_arrive(1 + (w ^ 1), 256); pack_tile(O, Pn, a.i0, a.i1); store_ctx(x, pend, Pn); }
    if (KIND == 0) { a.i0 = rcp_fast(quad_sum(a.l0)); a.i1 = rcp_fast(quad_sum(a.l1)); }
    if (KIND == 0 && pv == PV_NONE) { wgmma_fence(); wgmma_commit(); }
    else if (pv == PV_HALF)         { wgmma_fence(); issue_pv<4>(O, Po, dv, 0); wgmma_commit(); }
    else                            { wgmma_fence(); issue_pv<8>(O, Po, dv, pv == PV_ACC); wgmma_commit(); }
    if (KIND == 0 || pend < 0) bar_arrive(1 + (w ^ 1), 256);
    wgmma_wait<1>();
  }
  fence_regs(S);
  fence_regs_u(Pn);
  slot_release(x, sk, KIND == 0 && isY);
  float s0 = 0.f, s1 = 0.f;
  const bool was_classic = KIND != 0 && a.classic;
  if (KIND == 0) {
    a.l0 = 0.f; a.l1 = 0.f;
    if (!half) exp_pack<16, 32>(S, Pn, s0, s1);
    else {
      #pragma unroll
      for (int i = 16; i < 32; i++) asm volatile("" : "=r"(Pn[i]));
    }
    exp_pack_diag(S, Pn, diag_limit(), s0, s1);
    uint32_t b0 = __ballot_sync(0xffffffff, s0 >= SUM_LO), b1 = __ballot_sync(0xffffffff, s1 >= SUM_LO);
    b0 |= b0 >> 1; b0 |= b0 >> 2; b1 |= b1 >> 1; b1 |= b1 >> 2;
    a.classic = __any_sync(0xffffffff, !(s0 <= SUM_HI && s1 <= SUM_HI)) || (b0 & b1 & 0x11111111u) != 0x11111111u;
  } else {
    exp_pack<0, 32>(S, Pn, s0, s1);
    a.classic = __any_sync(0xffffffff, a.classic || !(s0 <= SUM_HI && s1 <= SUM_HI));
  }
  fence_regs_u(Pn);
  mbar_wait(x.bars + B_RF + 8 * sn, en >= 6);
  if (more) mbar_wait(x.bars + B_RF + 8 * sn + 8, en >= 6);
  wgmma_wait<0>();
  fence_regs(O);
  fence_regs_u(Po);
  slot_release(x, sv, KIND == 1 && isY && pv != PV_ACC);
  if (!NO_CLASSIC && __builtin_expect(a.classic, 0)) {
    float sc0, sc1;
    classic_tile(S, Pn, KIND == 0, half, was_classic, a.mc, a.l0, a.l1, s0, s1, sc0, sc1);
    if (KIND != 0) {
      #pragma unroll
      for (int j = 0; j < 16; j++) { O[4*j] *= sc0; O[4*j+1] *= sc0; O[4*j+2] *= sc1; O[4*j+3] *= sc1; }
    }
  }
  a.l0 += s0; a.l1 += s1;
  e = en;
}

__device__ __forceinline__ int attention(Ctx& x, const uint8_t* items, int nitems, int rank, uint32_t (&PA)[32], uint32_t (&PB)[32], int vtile) {
  int e = 0;
  float O[64];
  Att a;
  volatile float mc[2];
  a.l0 = 1.f; a.l1 = 1.f; a.i0 = 0.f; a.i1 = 0.f; a.classic = false; a.mc = mc;
  int pv = PV_NONE, cur = -1;
#define DBGS()
  #pragma unroll 1
  for (int it = 0; ; it++) {
    const bool isY = (it & 1) == x.w;
    int pend = cur;
    if (it < nitems) {
      const int item = items[it];
      const bool half = isY == (rank != 0);
      cur = item * 4 + (isY ? 3 - rank : rank);
      int rem = 2 * (item & 7) + (isY ? 1 : 0);
      DBG(16 + it);
      q_proj(x, e, isY, PA, PB, vtile);
      vtile = -1;
      DBGS();
      slot<0>(x, a, e, O, PA, PB, rem > 0, isY, half, pv, -1);
      pv = half ? PV_HALF : PV_ZERO;
      #pragma unroll 1
      while (rem > 0) {
        DBGS();
        slot<1>(x, a, e, O, PB, PA, rem > 1, isY, false, pv, pend);
        pv = PV_ACC; pend = -1;
        if (rem == 1) break;
        rem -= 2;
        DBGS();
        slot<2>(x, a, e, O, PA, PB, rem > 0, false, false, 0, -1);
      }
    } else {
      DBGS();
      slot_release(x, 6, false);
      const uint32_t dv = desc_lo(x.base + ring_slot(e) * 32768, 16384);
      bar_sync(1 + x.w, 256);
      if (pv == PV_HALF) { wgmma_fence(); issue_pv<4>(O, PB, dv, 0); wgmma_commit(); }
      else { wgmma_fence(); issue_pv<8>(O, PB, dv, pv == PV_ACC); wgmma_commit(); }
      if (isY) bar_arrive(1 + (x.w ^ 1), 256);
      a.i0 = rcp_fast(quad_sum(a.l0)); a.i1 = rcp_fast(quad_sum(a.l1));
      ring_wait_full(x.bars, e);
      wgmma_wait<0>();
      fence_regs(O);
      fence_regs_u(PB);
      ring_release(x, e, false);
    }
    if (pend >= 0) pack_tile(O, PB, a.i0, a.i1);
    if (it == nitems) return pend;
    if (pend >= 0) store_ctx(x, pend, PB);
    if (!isY) {
      #pragma unroll
      for (int i = 0; i < 32; i++) asm volatile("mov.b32 %0, %1;" : "=r"(PB[i]) : "r"(PA[i]));
    }
  }
}

#define LN_AT 2
#define X_AT 6
#define PERT 0
#define CTX_T 3
#define PF_AT 5
#define PF_N 4
#define PF_MOE 3
constexpr float QSCALE = 0.08838834764831845f * 1.4426950408889634f;
__device__ __forceinline__ void mod_cta(Ctx& x, const __nv_bfloat16* cvec) {
  const int t = wg_tid(), ct = x.w * 128 + t;
  #pragma unroll 1
  for (int k = 0; k < 6; k++) slot_release(x, k, false);
  const uint32_t cv = __ldg(reinterpret_cast<const uint32_t*>(cvec) + ct);
  asm volatile("st.shared.u32 [%0], %1;" :: "r"(x.base + SM_H2 + ct * 4),
               "r"(pack_bf16(__fdividef(bf_lo(cv), 1.f + __expf(-bf_lo(cv))), __fdividef(bf_hi(cv), 1.f + __expf(-bf_hi(cv))))) : "memory");
  bar_sync(5, 256);
  float acc[64];
  int e = 0;
  #pragma unroll 1
  for (int g = 0; g < 24; g++) {
    uint32_t a[8];
    #pragma unroll
    for (int i = 0; i < 8; i++) a[i] = lds_u32(x.base + SM_H2 + (g & 7) * 128 + i * 16 + (t & 3) * 4);
    ring_wait_full(x.bars, e);
    const uint32_t db = desc_lo(x.base + x.w * 16384, 8192) + ring_slot(e) * 2048;
    wgmma_fence();
    wgmma_rs_n128<1, 0>(acc, a[0], a[0], a[1], a[1], db, g & 7);
    wgmma_rs_n128<1, 128>(acc, a[2], a[2], a[3], a[3], db, 1);
    wgmma_rs_n128<1, 256>(acc, a[4], a[4], a[5], a[5], db, 1);
    wgmma_rs_n128<1, 384>(acc, a[6], a[6], a[7], a[7], db, 1);
    wgmma_commit();
    wgmma_wait<0>();
    fence_regs(acc);
    ring_release(x, e, false);
    e = ring_add(e, 1);
    if ((g & 7) == 7) {
      if (t < 4) {
        const float sc = (g == 7 && blockIdx.x < NCTA + 2) ? QSCALE : 1.f;
        uint32_t* dst = reinterpret_cast<uint32_t*>(g_mod + (g >> 3) * 1024 + (blockIdx.x - NCTA) * 256 + x.w * 128) + t;
        #pragma unroll
        for (int j = 0; j < 16; j++) dst[4 * j] = pack_bf16(rbf(acc[4*j]) * sc, rbf(acc[4*j+1]) * sc);
      }
      publish(x, g == 7 ? C_MOD : C_MOD2);
      DBG(1 + (g >> 3));
    }
  }
}

__global__ void __cluster_dims__(2, 1, 1) __launch_bounds__(384, 1)
k_fused(const __grid_constant__ CUtensorMap tmC, const __grid_constant__ CUtensorMap tmH, const __grid_constant__ CUtensorMap tmWq,
        const __grid_constant__ CUtensorMap tmWk, const __grid_constant__ CUtensorMap tmWv, const __grid_constant__ CUtensorMap tmKV,
        const __grid_constant__ CUtensorMap tmWo, const __grid_constant__ CUtensorMap tmPart, const __grid_constant__ CUtensorMap tmWg,
        const __grid_constant__ CUtensorMap tmWu, const __grid_constant__ CUtensorMap tmPl, const __grid_constant__ CUtensorMap tmWm,
        const __grid_constant__ Sched sched,
        const __nv_bfloat16* __restrict__ xin,
        const __nv_bfloat16* __restrict__ cvec, const __nv_bfloat16* __restrict__ w_o,
        const __nv_bfloat16* __restrict__ w_r, const __nv_bfloat16* __restrict__ w_gate, const __nv_bfloat16* __restrict__ w_up,
        const __nv_bfloat16* __restrict__ w_down, __nv_bfloat16* __restrict__ out) {
  extern __shared__ __align__(1024) uint8_t smem_raw[];
  const uint32_t base = smem_u32(smem_raw), bars = base + SM_BAR;
  const int warp = __shfl_sync(0xffffffff, threadIdx.x >> 5, 0), wg = warp >> 2;
  const int rank = cluster_ctarank(), p = blockIdx.x >> 1;
  const int mt = (p & 7) * 2 + rank;
  const bool spare = blockIdx.x >= NCTA;
  #pragma unroll
  for (int i = 0; i < PERT; i++) { uint32_t d; asm volatile("mov.u32 %0, %%laneid;" : "=r"(d)); }
  {
    const int h0 = KHEAD0 + (p >> 3);
    #pragma unroll 1
    for (int t = warp == 8 ? 0 : warp < 8 ? warp + 1 : warp; t < B_PUB / 8; t += (warp == 8 ? 64 : 11))
      w_mbar_init(bars + 8 * t, t < B_WE / 8 ? 1 : t < B_RE / 8 ? 2 : 4);
    fence_mbar_init();
    cluster_arrive();
    if (warp == 9) prefetch_tmap(&tmWk);
    if (wg == 2) bar_arrive(1, 256);
    if (warp == 8 && !spare) {
      #pragma unroll 1
      for (int kb = 0; kb < 8; kb++) {
        w_expect_tx(bars + B_AF + 8 * kb, 16384);
        tma_load_2d(base + k_addrA(kb), &tmC, bars + B_AF + 8 * kb, kb * 64, mt * 128);
        if (kb == 0) cluster_wait();
        if (kb < 6) {
          w_expect_tx(bars + B_WF + 8 * kb, 16384);
          tma_load_2d_mc(base + k_addrW(kb) + rank * 8192, &tmWk, bars + B_WF + 8 * kb, h0 * 128 + rank * 64, kb * 64);
        }
      }
    }
  }
  const Sched::Pair& sp = sched.pair[p];
  const int nitems = sp.nitems, nsteps = sp.nsteps;
  auto oent = [&](int k) -> uint32_t { return sp.oent[k]; };
  const int ot = sp.otask, m = (ot & 7) * 2 + rank, grp = m * 8 + (ot >> 3);

  if (wg == 0) {
    asm volatile("setmaxnreg.dec.sync.aligned.u32 24;");
    const int lane = threadIdx.x & 31;
    #pragma unroll 1
    for (int t = B_PUB / 8 + warp; t < 80; t += 4) w_mbar_init(bars + 8 * t, t < B_RDY / 8 ? 4 : 1);
    bar_sync(6, 128);
    bar_arrive(7, 256); bar_arrive(8, 256);
    cluster_wait();
    const unsigned int tag = ld_relaxed(&g_epoch) + 1;
    if (warp == 0) {
      if (!spare) {
        int s = 0, ph = 0;
        tma_prefetch_2d(&tmWv, sp.khead[0] * 128 + rank * 64, (p & 7) * 64);
        #pragma unroll 1
        for (int g = 6; g < 64; g++) {
          const int u = g >> 3, kb = g & 7;
          if (kb == 0 && u < 7) tma_prefetch_2d((u & 1) ? &tmWk : &tmWv, sp.khead[(u + 1) >> 1] * 128 + rank * 64, (p & 7) * 64);
          mbar_wait(bars + B_WE + 8 * s, ph);
          w_expect_tx(bars + B_WF + 8 * s, 16384);
          tma_load_2d_mc(base + k_addrW(s) + rank * 8192, (u & 1) ? &tmWv : &tmWk, bars + B_WF + 8 * s, sp.khead[u >> 1] * 128 + rank * 64, kb * 64);
          if (++s == 6) { s = 0; ph ^= 1; }
        }
      }
      int s = 0, ph = 0;
      auto next_entry = [&](int bytes) {
        mbar_wait(bars + B_RE + 8 * s, ph);
        w_expect_tx(bars + B_RF + 8 * s, bytes);
      };
      auto advance = [&]() { if (++s == 6) { s = 0; ph ^= 1; } };
      if (spare) {
        #pragma unroll 1
        for (int g = 0; g < 24; g++) {
          if (g == 8) mbar_wait(bars + R_MOD, 0);
          next_entry(32768);
          for (int k = 0; k < 2; k++) tma_load_3d(base + s * 32768 + k * 16384, &tmWm, bars + B_RF + 8 * s, 0, (g & 7) * 64, (g >> 3) * 16 + (blockIdx.x - NCTA) * 4 + k * 2);
          advance();
        }
      }
      mbar_wait(bars + R_H1, 0);
      fence_async_global();
      int vrow = -1;
      #pragma unroll 1
      for (int i = 0; i <= nitems; i++) {
        const int item = sp.item[i & (MAX_ITEMS - 1)], h = item >> 3, j = item & 7;
        if (i < nitems) {
          const int row0 = j * 256 + ((i & 1) ? rank : 3 - rank) * 64, row1 = j * 256 + ((i & 1) ? 3 - rank : rank) * 64;
          #pragma unroll 1
          for (int kb = 0; kb < 8; kb++) {
            next_entry(32768);
            tma_load_2d_mc(base + s * 32768 + 16384 + rank * 8192, &tmWq, bars + B_RF + 8 * s, h * 128 + rank * 64, kb * 64);
            tma_load_2d(base + s * 32768, &tmH, bars + B_RF + 8 * s, kb * 64, row0);
            tma_load_2d(base + s * 32768 + 8192, &tmH, bars + B_RF + 8 * s, kb * 64, row1);
            advance();
          }
          mbar_wait(bars + R_ITEM + 8 * i, 0);
          fence_async_global();
        }
        #pragma unroll 1
        for (int n = i < nitems ? 4 * j + 3 : 0; n >= 0; n--) {
          const int krow = (h * 2 + rank) * SEQ + (n >> 1) * 128 + ((sp.lastuse[i & (MAX_ITEMS - 1)] >> (n >> 1)) & 1);
          const int row = (n & 1) ? krow : vrow;
          if (i + 1 == nitems && n == min(4 * j + 3, 2 * PF_AT + 1)) w_arrive(bars + R_NEAR);
          next_entry(row >= 0 ? 32768 : 0);
          if (row >= 0) tma_load_2d_mc(base + s * 32768 + rank * 16384, &tmKV, bars + B_RF + 8 * s, 0, row & ~1, row & 1);
          advance();
          if (!(n & 1)) vrow = krow + 64 * SEQ;
        }
      }
      if (!spare) {
      const int oc = ((ot >> 3) & 1) * 4 + rank * 2;
      auto o_next = [&](int k, int bytes) {
        const uint32_t v = oent(k); s = v & 7;
        mbar_wait(bars + B_RE + 8 * s, v >> 3);
        w_expect_tx(bars + B_RF + 8 * s, bytes);
      };
      #pragma unroll 1
      for (int i = 0; i < nsteps; i++) {
        const int c0 = sp.ochunk[i][0], c1 = sp.ochunk[i][1];
        if (i >= PF_MOE && i < PF_MOE + 3)
          bulk_prefetch((i == PF_MOE ? w_gate : i == PF_MOE + 1 ? w_up : w_down) + (size_t)blockIdx.x * (DM * FF / NCTA), DM * FF / NCTA * 2);
        if (c0 < 64) { o_next(3 * i, 32768); tma_load_3d_mc(base + s * 32768 + rank * 16384, &tmWo, bars + B_RF + 8 * s, 0, c0 * 64, oc); }
        mbar_wait(bars + R_CTX + 8 * i, 0);
        fence_async_global();
        o_next(3 * i + 1, c0 < 64 ? 32768 : 16384);
        if (c0 < 64) tma_load_2d(base + s * 32768, &tmKV, bars + B_RF + 8 * s, 0, (128 + c0) * SEQ + m * 128);
        tma_load_2d(base + s * 32768 + 16384, &tmKV, bars + B_RF + 8 * s, 0, (128 + c1) * SEQ + m * 128);
        o_next(3 * i + 2, 32768);
        tma_load_3d_mc(base + s * 32768 + rank * 16384, &tmWo, bars + B_RF + 8 * s, 0, c1 * 64, oc);
      }
      const int f0 = (blockIdx.x < FF / 16 ? blockIdx.x : 0) * 16;
      o_next(3 * nsteps, 32768);
      bulk_load(base + s * 32768, w_down + (size_t)f0 * DM, 16384, bars + B_RF + 8 * s);
      bulk_load(base + s * 32768 + 16384, xin + (size_t)grp * 16 * DM, 16384, bars + B_RF + 8 * s);
      o_next(3 * nsteps + 1, 32768);
      #pragma unroll 1
      for (int k = 0; k < 4; k++) tma_load_2d(base + s * 32768 + k * 8192, (k & 2) ? &tmWu : &tmWg, bars + B_RF + 8 * s, f0, (k & 1) * 256);
      #pragma unroll 1
      for (int k = 0; k < 4; k++) w_expect_tx(bars + R_PART + 8 * k, 16384);
      mbar_wait(bars + B_PUB + 8 * (5 + nitems + 1), 0);
      mbar_wait(bars + B_PUB + 8 * (NPUB + 5 + nitems + 1), 0);
      uint32_t todo = 0xff;
      #pragma unroll 1
      for (int n = 0; n < WAIT_LIM && todo; n++) {
        uint32_t now = __ballot_sync(0xffffffff, ld_acquire(&g_pflag[m * 2 + (ot >> 5)][lane & 7]) == tag) & todo;
        todo &= ~now;
        fence_async_global();
        #pragma unroll 1
        for (; now; now &= now - 1) {
          const int q = __ffs(now) - 1;
          tma_load_3d(base + (oent(3 * nsteps - 3 + (q >> 2)) & 7) * 32768 + (q & 3) * 8192, &tmPl, bars + R_PART + 8 * (q >> 1), 0, grp * 16, q * 4);
        }
      }
      DBGP(11);
      }
    } else if (warp < 3) {
      const int w = warp - 1, n1 = w * NPUB + (spare ? 3 : 5) + nitems;
      #pragma unroll 1
      for (int n = w * NPUB; n < n1 + (spare ? 0 : 2); n++) {
        #pragma unroll 1
        for (int k = 0; k < 8 * WAIT_LIM; k++) { if (mbar_try(bars + B_PUB + 8 * n, 0)) break; }
        const uint32_t msg = lds_u32(base + SM_MAIL + 4 * n);
        if (n < n1) {
          fence_async_global();
          if (lane == 0 && msg < (unsigned)C_END) red_release(msg);
        } else {
          if (lane == 0) { tma_store_3d(&tmPart, base + (msg & 0x3c000), 0, m * 128 + 64 * w, (ot >> 3) * 4 + 2 * (n - n1)); bulk_commit(); }
        }
        __syncwarp();
      }
      bulk_wait<0>();
      fence_async_global();
      if (lane == 0 && !spare) st_release(&g_pflag[m * 2 + w][ot >> 3], tag);
      __syncwarp();
    } else {
      if (!spare) { mbar_wait(bars + B_AF + 8 * X_AT, 0); bulk_prefetch(xin + (size_t)blockIdx.x * 16 * DM, 16 * DM * 2); }
      #pragma unroll 1
      for (int n = 0; n < 8 + nsteps; n++) {
        if (n == 2 + nitems) n = 7;
        int idx = n == 0 ? C_MOD : n == 1 ? C_H1 : C_MOD2, cnt = n == 0 ? 8 : n == 1 ? 256 : 16;
        if (n >= 1 && n <= nitems) { const int item = sp.item[n - 1]; tma_prefetch_2d(&tmWq, (item >> 3) * 128 + rank * 64, (item & 7) * 64); }
        if (n >= 2 && n < 7) { idx = C_KV + (sp.item[n - 2] >> 3); cnt = 32; }
        if (n >= 8) { const int c0 = sp.ochunk[n - 8][0], c1 = sp.ochunk[n - 8][1]; idx = C_CTX + (((lane & 1) && c0 < 64 ? c0 : c1) >> 1) * 8 + (ot & 7); cnt = 4; }
        wait_count_lazy(idx, cnt * tag);
        w_arrive(bars + B_RDY + 8 * n);
        if (n == 0) DBGP(12);
        if (n == 8 + PF_N - 1) {
          #pragma unroll 1
          for (int k = 0; k < 8 * WAIT_LIM; k++) { if (mbar_try(bars + R_NEAR, 0)) break; }
          bulk_prefetch(w_o + (size_t)blockIdx.x * (NH * DH * DM / NCTA), NH * DH * DM / NCTA * 2);
          #pragma unroll 1
          for (int k = 0; k < PF_N; k++) {
            const int cc = sp.ochunk[k][(ot >> 3) & 1];
            if (cc < 64) bulk_prefetch(sched.kvc + ((size_t)(128 + cc) * SEQ + m * 128) * 64, 16384);
          }
        }
      }
    }
    __syncwarp();
    cluster_arrive();
    if (!spare) {
      bar_sync(6, 128);
      asm volatile("setmaxnreg.inc.sync.aligned.u32 88;");
      const int pos = blockIdx.x * 4 + (lane & 1) * 2, col = (blockIdx.x >> 2) * 16 + (blockIdx.x & 3) * 2 + (lane & 1) * 8, src = threadIdx.x >> 1;
      uint32_t gbest = 0, hh = 0, gbf = 0;
      uint2 xx = make_uint2(0, 0);
      uint4 ya = make_uint4(0, 0, 0, 0), yb = make_uint4(0, tag, 0, tag);
      auto poll_y = [&]() {
        if (ya.y != tag || ya.w != tag) ya = ld_tagged2(&g_yll[src][pos]);
        if (yb.y != tag || yb.w != tag) yb = ld_tagged2(&g_yll[src + 64][pos]);
        return __all_sync(0xffffffff, ya.y == tag && ya.w == tag && yb.y == tag && yb.w == tag);
      };
      ya.y = tag - 1; if (src + 64 < FF / 16) yb.y = tag - 1;
      poll_y();
      if (warp == 3) {
        gbf = __ldcg(reinterpret_cast<const uint32_t*>(g_mod + 5 * DM + col));
        uint32_t have = 0;
        uint2 k[4];
        #pragma unroll
        for (int i = 0; i < 4; i++) k[i] = make_uint2(0, tag - 1);
        #pragma unroll 1
        for (int n = 0; n < WAIT_LIM; n++) {
          #pragma unroll
          for (int i = 0; i < 4; i++) if (k[i].y != tag) k[i] = ld_tagged(&g_keys[i * 32 + lane][0]);
          if (gbest != have) {
            const int g = ((0xffffu - gbest) >> 4) & 127;
            uint4 hv[4];
            #pragma unroll
            for (int i = 0; i < 4; i++) hv[i] = ld_tagged2(&g_row[g][0][i * 64 + lane * 2]);
            xx = ld_tagged(&g_row[g][1][col >> 1]);
            bool ok = xx.y == tag;
            #pragma unroll
            for (int i = 0; i < 4; i++) { ok = ok && hv[i].y == tag && hv[i].w == tag; reinterpret_cast<uint2*>(smem_raw + SM_H2)[i * 32 + lane] = make_uint2(hv[i].x, hv[i].z); }
            if (lane == 0) *reinterpret_cast<uint32_t*>(smem_raw + SM_KEY + 32) = gbest;
            have = __all_sync(0xffffffff, ok) ? gbest : 0;
          }
          bool all = true;
          #pragma unroll
          for (int i = 0; i < 4; i++) { all = all && k[i].y == tag; gbest = max(gbest, k[i].y == tag ? k[i].x : 0u); }
          gbest = __reduce_max_sync(0xffffffff, gbest);
          if (__all_sync(0xffffffff, all) && gbest == have) break;
        }
        w_arrive(bars + R_KEY);
        if (blockIdx.x == 0 && lane == 0) g_epoch = tag;
        hh = lds_u32(base + SM_H2 + col * 2);
        DBGP(13);
      }
      const uint32_t sb16 = gbest & 0xffff0000u;
      const float rsel = __uint_as_float((sb16 & 0x80000000u) ? (sb16 & 0x7fffffffu) : (~sb16 & 0xffff0000u));
      const float rs = rbf(__fdividef(1.f, 1.f + __expf(-rsel)));
      mbar_wait(bars + R_KEY, 1);
      #pragma unroll 1
      for (int n = 0; n < WAIT_LIM; n++) { if (poll_y()) break; }
      float y0 = __uint_as_float(ya.x) + __uint_as_float(yb.x), y1 = __uint_as_float(ya.z) + __uint_as_float(yb.z);
      #pragma unroll
      for (int o = 2; o < 32; o <<= 1) { y0 += __shfl_xor_sync(0xffffffff, y0, o); y1 += __shfl_xor_sync(0xffffffff, y1, o); }
      float2* s_y = reinterpret_cast<float2*>(smem_raw + SM_KEY + 64);
      if (lane < 2) s_y[warp * 2 + lane] = make_float2(y0, y1);
      bar_sync(6, 128);
      if (warp == 3 && lane < 2) {
        y0 = 0.f; y1 = 0.f;
        #pragma unroll
        for (int i = 0; i < 4; i++) { y0 += reinterpret_cast<const float*>(s_y)[i * 4 + lane]; y1 += reinterpret_cast<const float*>(s_y)[i * 4 + 2 + lane]; }
        const float o0 = bf_lo(xx.x) + rbf(bf_lo(gbf) * rbf(bf_lo(hh) + rbf(rbf(y0) * rs)));
        const float o1 = bf_hi(xx.x) + rbf(bf_hi(gbf) * rbf(bf_hi(hh) + rbf(rbf(y1) * rs)));
        *reinterpret_cast<uint32_t*>(out + (size_t)((0xffffu - gbest) & (SEQ - 1)) * DM + col) = pack_bf16(o0, o1);
      }
      DBGP(14);
    }
    __syncwarp();
    cluster_wait();
  } else {
    asm volatile("setmaxnreg.inc.sync.aligned.u32 240;");
    Ctx x;
    x.w = wg - 1; x.base = base; x.bars = bars; x.nev = 0; x.sched = &sched;
    const int w = x.w, warp4 = warp & 3;
    x.rel = mapa(bars, (warp4 & 1) ^ 1);
    x.rel1 = (threadIdx.x & 127) == 32 || (threadIdx.x & 127) == 64;
    if (warp != 8 || spare) cluster_wait();
    if (w == 1 || spare) bar_sync(7 + w, 256);
    DBG(1);
    uint32_t PA[32], PB[32];
    int vtile = -1;
    if (spare) {
      mod_cta(x, cvec);
    } else {
      const int lane = wg_tid() & 31;
      Row xn[2];
      float acc0[64], acc1[64];
      int s = 2 * w, ph = w;
      #pragma unroll 1
      for (int u = w; u < 8; u += 2) {
        bar_sync(1 + w, 256);
        DBG(4 + (u >> 1) * 3);
        int ps = 0;
        #pragma unroll 1
        for (int kb = 0; kb < 8; kb++) {
          if (u < 2) mbar_wait(bars + B_AF + 8 * kb, 0);
          mbar_wait(bars + B_WF + 8 * s, ph);
          const uint32_t da = desc_lo(base + k_addrA(kb), 16), dw = desc_lo(base + k_addrW(s), 8192);
          wgmma_fence();
          kblock_n128<0>(acc0, da, dw, kb != 0);
          kblock_n128<512>(acc1, da, dw, kb != 0);
          wgmma_commit();
          if (kb == 7) bar_arrive(1 + (w ^ 1), 256);
          if (kb > 0) {
            wgmma_wait<1>();
            mbar_arrive_remote_if(x.rel + B_WE + 8 * ps, x.rel1);
            if (u == 7 && !(kb & 1)) {
              ring_release(x, kb == 2 ? 0 : kb - 3, false);
              if (kb > 2) ring_release(x, kb - 2, false);
            }
          }
          ps = s;
          if (++s == 6) { s = 0; ph ^= 1; }
        }
        Row t[2];
        const int lrow = blockIdx.x * 16 + w * 8 + warp4 * 2;
        if (u == w) { t[0] = ldg_row(xin + (size_t)lrow * DM, lane); t[1] = ldg_row(xin + (size_t)(lrow + 1) * DM, lane); }
        if (u == LN_AT || u == LN_AT + 1) {
          mbar_wait(bars + R_MOD, 0);
          t[0] = ldca_row(g_mod, lane); t[1] = ldca_row(g_mod + DM, lane);
        }
        wgmma_wait<0>();
        fence_regs(acc0); fence_regs(acc1);
        DBG(5 + (u >> 1) * 3);
        mbar_arrive_remote_if(x.rel + B_WE + 8 * ps, x.rel1);
        if (u == 6) { for (int k = 0; k < 5; k++) ring_release(x, k, false); }
        if (u >= 6) ring_release(x, 5, false);
        if (V_AT >= 0 && u == 7) {
          pack_tile(acc0, PA, 1.f, 1.f); pack_tile(acc1, PB, 1.f, 1.f);
          vtile = sp.khead[3] * 16 + mt;
          break;
        }
        s += 2; ph ^= 1; if (s >= 6) { s -= 6; ph ^= 1; }
        if (u == 0) bar_sync(7, 256);
        if (u == w) {
          float st[4] = {0.f, 0.f, 0.f, 0.f};
          #pragma unroll
          for (int i = 0; i < 32; i++) { const float v = row_at(t[i >> 4], i & 15); st[(i >> 4) * 2] += v; st[(i >> 4) * 2 + 1] = fmaf(v, v, st[(i >> 4) * 2 + 1]); }
          warp_sums(st);
          #pragma unroll
          for (int r = 0; r < 2; r++) { ln_stats(st[2*r], st[2*r+1]); xn[r] = ln_apply(t[r], st[2*r], st[2*r+1] * QSCALE); }
        }
        if ((u == LN_AT || u == LN_AT + 1)) {
          #pragma unroll
          for (int r = 0; r < 2; r++) store_row(sched.h1 + (size_t)(lrow + r) * DM, lane, fma_row(xn[r], one_plus(t[1]), t[0]));
        }
        const int tile = sp.khead[u >> 1] * 16 + mt;
        __nv_bfloat16* dst = kv_tile(x, tile);
        uint32_t D[32];
        pack_tile(acc0, D, 1.f, 1.f); store_tile(dst + 64 * 64, D);
        pack_tile(acc1, D, 1.f, 1.f); store_tile(dst, D);
        if (u == LN_AT || u == LN_AT + 1) publish(x, C_H1);
        publish(x, C_KV + (tile >> 4));
        DBG(6 + (u >> 1) * 3);
      }
    }
    const int last = attention(x, sp.item, nitems, rank, PA, PB, vtile);
    DBG(100);
    const int lane = wg_tid() & 31, cw = w * 4 + warp4, ct = cw * 32 + lane;
    const int row0 = grp * 16 + cw * 2;
    const bool moe_cta = blockIdx.x < FF / 16;
    const unsigned int tag = ld_relaxed(&g_epoch) + 1;
    if (spare) { store_ctx(x, last, PB); __syncwarp(); cluster_arrive(); cluster_wait(); return; }
    const int kl = 3 * nsteps - 3;
    {
      float accA[64], accB[64];
      const int t0 = oent(0) == oent(1);
      uint32_t pa = 0, pb = 0;
      #pragma unroll 1
      for (int t = t0; t < 2 * nsteps - 2; t++) {
        const uint32_t eb = oent(3 * (t >> 1) + 2 * (t & 1)), ea = oent(3 * (t >> 1) + 1);
        o_wait_full(bars, eb);
        o_wait_full(bars, ea);
        const uint32_t da = desc_lo(base + w * 8192, 16) + (ea & 7) * 2048 + (t & 1) * 1024, db = desc_lo(base, 8192) + (eb & 7) * 2048;
        wgmma_fence();
        kblock_n128<0>(accA, da, db, t != t0); kblock_n128<0, 1024>(accB, da, db, t != t0);
        wgmma_commit();
        if (t == CTX_T) store_ctx(x, last, PB);
        if (t > t0) { wgmma_wait<1>(); slot_release(x, pb, false); if (!(t & 1)) slot_release(x, pa, false); }
        pa = ea & 7; pb = eb & 7;
      }
      const uint32_t e0 = oent(kl), ea = oent(kl + 1), eb = oent(kl + 2);
      const uint32_t da = desc_lo(base + w * 8192, 16) + (ea & 7) * 2048;
      const uint32_t db0 = desc_lo(base, 8192) + (e0 & 7) * 2048, db1 = desc_lo(base, 8192) + (eb & 7) * 2048;
      o_wait_full(bars, e0);
      o_wait_full(bars, ea);
      o_wait_full(bars, eb);
      wgmma_fence();
      kblock_n128<0>(accA, da, db0, 1); kblock_n128<1024>(accA, da, db1, 1);
      wgmma_commit();
      kblock_n128<0, 1024>(accB, da, db0, 1); kblock_n128<1024, 1024>(accB, da, db1, 1);
      wgmma_commit();
      wgmma_wait<2>();
      slot_release(x, pa, false); slot_release(x, pb, false);
      __syncwarp();
      cluster_arrive();
      const int srow = 16 * warp4 + (lane & 7) + 8 * ((lane >> 3) & 1);
      const uint32_t swz = (((lane >> 4) ^ (srow & 7)) << 4);
      auto stage = [&](const float (&acc)[64], uint32_t off) {
        #pragma unroll
        for (int j = 0; j < 16; j += 2)
          stsm_x4(base + off + srow * 128 + (j >> 3) * 8192 + (((j & 7) << 4) ^ swz),
                  pack_bf16(acc[4*j+0], acc[4*j+1]), pack_bf16(acc[4*j+2], acc[4*j+3]), pack_bf16(acc[4*j+4], acc[4*j+5]), pack_bf16(acc[4*j+6], acc[4*j+7]));
        fence_async_smem();
        publish(x, off);
      };
      mbar_wait(bars + B_RE + 8 * pa, oent(kl + 5) >> 3);
      wgmma_wait<1>();
      fence_regs(accA);
      stage(accA, pa * 32768 + w * 16384);
      mbar_wait(bars + B_RE + 8 * pb, oent(kl + 6) >> 3);
      wgmma_wait<0>();
      fence_regs(accB);
      DBG(101);
      stage(accB, pb * 32768 + w * 16384);
      DBG(102);
    }
    asm volatile("setmaxnreg.dec.sync.aligned.u32 208;");
    const Row ga = ldca_row(g_mod + 2 * DM, lane), sb = ldca_row(g_mod + 3 * DM, lane), cb = ldca_row(g_mod + 4 * DM, lane), gb = ldca_row(g_mod + 5 * DM, lane);
    const Row wr = ldca_row(w_r, lane);
    const uint32_t sD = base + (oent(kl + 3) & 7) * 32768, sW = base + (oent(kl + 4) & 7) * 32768;
    o_wait_full(bars, oent(kl + 3)); o_wait_full(bars, oent(kl + 4));
    Row x1[2];
    #pragma unroll
    for (int r = 0; r < 2; r++) x1[r] = lds_row(sD + 16384 + (cw * 2 + r) * 1024, lane);
    uint4 wgv[4], wuv[4], wdv[4];
    #pragma unroll
    for (int r = 0; r < 4; r++) {
      const uint32_t k = (lane & 7) + ((lane >> 4) << 3), h = (lane & 8) * 2;
      wgv[r] = ldsm_x4_t(sW + (cw * 64 + r * 16 + k) * 32 + h);
      wuv[r] = ldsm_x4_t(sW + 16384 + (cw * 64 + r * 16 + k) * 32 + h);
      wdv[r] = ldsm_x4_t(sD + k * 1024 + (cw * 64 + r * 16) * 2 + h);
    }
    const Row cb1 = one_plus(cb);
    DBG(103);
    float u[16], ub[2] = {0.f, 0.f};
    #pragma unroll
    for (int i = 0; i < 16; i++) { u[i] = row_at(cb1, i) * row_at(wr, i); ub[0] += u[i]; ub[1] = fmaf(row_at(sb, i), row_at(wr, i), ub[1]); }
    warp_sums(ub);
    float st[6] = {0.f, 0.f, 0.f, 0.f, 0.f, 0.f};
    uint32_t key[2];
    {
      const uint32_t po = base + (lane >> 3) * 2048 + cw * 256 + (lane & 7) * 16;
      Row av[2][2];
      #pragma unroll
      for (int k = 0; k < 4; k++) {
        mbar_wait(bars + R_PART + 8 * k, 1);
        const uint32_t pa = po + (oent(kl + (k >> 1)) & 7) * 32768 + (k & 1) * 16384;
        #pragma unroll
        for (int r = 0; r < 2; r++) {
          const uint4 lo = lds_v4(pa + r * 128), hi = lds_v4(pa + 8192 + r * 128);
          const Row v{{lo.x, lo.y, lo.z, lo.w, hi.x, hi.y, hi.z, hi.w}};
          av[r][k >> 1] = (k & 1) ? add_row(av[r][k >> 1], v) : v;
        }
      }
      DBG(104);
      #pragma unroll
      for (int r = 0; r < 2; r++) {
        x1[r] = fma_row(ga, add_row(av[r][0], av[r][1]), x1[r]);
        #pragma unroll
        for (int i = 0; i < 16; i++) { const float v = row_at(x1[r], i); st[3*r] += v; st[3*r+1] = fmaf(v, v, st[3*r+1]); st[3*r+2] = fmaf(v, u[i], st[3*r+2]); }
      }
      warp_sums(st);
      #pragma unroll
      for (int r = 0; r < 2; r++) {
        ln_stats(st[3*r], st[3*r+1]);
        const uint32_t rb = pack_bf16(0.f, fmaf(st[3*r+1], fmaf(-st[3*r], ub[0], st[3*r+2]), ub[1]));
        key[r] = (((rb & 0x80000000u) ? ~rb : (rb | 0x80000000u)) & 0xffff0000u) | (0xffffu - (uint32_t)(row0 + r));
      }
    }
    DBG(105);
    float* s_red = reinterpret_cast<float*>(smem_raw + SM_RED);
    uint32_t* s_key = reinterpret_cast<uint32_t*>(smem_raw + SM_KEY);
    const int rb = key[1] > key[0];
    const uint32_t wbest = rb ? key[1] : key[0];
    if (lane == 0) s_key[cw] = wbest;
    bar_sync(5, 256);
    const uint32_t cbest = __reduce_max_sync(0xffffffff, s_key[lane & 7]);
    if (wbest == cbest && lane == 0) st_tagged(&g_keys[grp][0], cbest, tag);
    Row xb, xo;
    #pragma unroll
    for (int i = 0; i < 8; i++) { xb.v[i] = rb ? x1[1].v[i] : x1[0].v[i]; xo.v[i] = rb ? x1[0].v[i] : x1[1].v[i]; }
    const Row hb = fma_row(ln_apply(xb, rb ? st[3] : st[0], rb ? st[4] : st[1]), cb1, sb);
    if (wbest == cbest) {
      #pragma unroll
      for (int i = 0; i < 4; i++) st_tagged2(&g_row[grp][0][(i >> 1) * 128 + lane * 4 + (i & 1) * 2], hb.v[2*i], hb.v[2*i+1], tag);
      #pragma unroll
      for (int i = 0; i < 4; i++) st_tagged2(&g_row[grp][1][(i >> 1) * 128 + lane * 4 + (i & 1) * 2], xb.v[2*i], xb.v[2*i+1], tag);
    }
    DBG(106);
    const Row ob = fma_row(gb, hb, xb);
    if (wbest != cbest) store_row(out + (size_t)(row0 + rb) * DM, lane, ob);
    store_row(out + (size_t)(row0 + 1 - rb) * DM, lane, fma_row(gb, fma_row(ln_apply(xo, rb ? st[0] : st[3], rb ? st[1] : st[4]), cb1, sb), xo));
    mbar_wait(bars + R_KEY, 1);
    DBG(107);
    if (moe_cta) {
      float cg[4] = {0, 0, 0, 0}, cu[4] = {0, 0, 0, 0};
      #pragma unroll
      for (int r = 0; r < 4; r++) {
        const uint32_t b0 = lds_u32(base + SM_H2 + (cw * 64 + r * 16) * 2 + (lane & 3) * 4), b1 = lds_u32(base + SM_H2 + (cw * 64 + r * 16) * 2 + 16 + (lane & 3) * 4);
        mma16816(cg, wgv[r], b0, b1); mma16816(cu, wuv[r], b0, b1);
      }
      s_red[cw * 32 + (lane & 3) * 8 + (lane >> 2)] = (lane & 2) ? ((lane & 1) ? cu[2] : cu[0]) : ((lane & 1) ? cg[2] : cg[0]);
      bar_sync(5, 256);
      float g = 0.f;
      #pragma unroll
      for (int i = 0; i < 8; i++) g += s_red[i * 32 + lane];
      g = rbf(g);
      const float act = rbf(__fdividef(g, 1.f + __expf(-g))) * __shfl_down_sync(0xffffffff, g, 16);
      const uint32_t a2 = pack_bf16(act, __shfl_down_sync(0xffffffff, act, 1));
      const uint32_t b0 = __shfl_sync(0xffffffff, a2, (lane & 3) * 2), b1 = __shfl_sync(0xffffffff, a2, (lane & 3) * 2 + 8);
      float y0 = 0.f, y1 = 0.f;
      #pragma unroll
      for (int r = 0; r < 4; r++) {
        float c[4] = {0, 0, 0, 0};
        mma16816(c, wdv[r], b0, b1);
        if ((lane & 3) == r) { y0 = c[0]; y1 = c[2]; }
      }
      st_tagged2(&g_yll[blockIdx.x][cw * 64 + (lane & 3) * 16 + (lane >> 2) * 2], __float_as_uint(y0), __float_as_uint(y1), tag);
    }
    DBG(108);
    if (wbest == cbest && wbest != s_key[8]) store_row(out + (size_t)(row0 + rb) * DM, lane, ob);
    DBG(109);
    __syncwarp();
    cluster_wait();
  }
}

typedef CUresult (*EncodeFn)(CUtensorMap*, CUtensorMapDataType, cuuint32_t, void*, const cuuint64_t*, const cuuint64_t*, const cuuint32_t*,
                             const cuuint32_t*, CUtensorMapInterleave, CUtensorMapSwizzle, CUtensorMapL2promotion, CUtensorMapFloatOOBfill);

struct HostState {
  bool ready = false;
  EncodeFn encode = nullptr;
  CUtensorMap tmC, tmH, tmWq, tmWk, tmWv, tmKV, tmWo, tmPart, tmWg, tmWu, tmPl, tmWm;
  Sched sched;
};

void make_map(EncodeFn enc, CUtensorMap* m, const void* ptr, int rank, const cuuint64_t* dims, const cuuint64_t* strides, const cuuint32_t* box, bool swizzle = true) {
  const cuuint32_t es[3] = {1, 1, 1};
  enc(m, CU_TENSOR_MAP_DATA_TYPE_BFLOAT16, rank, const_cast<void*>(ptr), dims, strides, box, es, CU_TENSOR_MAP_INTERLEAVE_NONE,
      swizzle ? CU_TENSOR_MAP_SWIZZLE_128B : CU_TENSOR_MAP_SWIZZLE_NONE, swizzle ? CU_TENSOR_MAP_L2_PROMOTION_L2_128B : CU_TENSOR_MAP_L2_PROMOTION_NONE, CU_TENSOR_MAP_FLOAT_OOB_FILL_NONE);
}
void make_2d(EncodeFn enc, CUtensorMap* m, const void* ptr, int rows, int cols, int box_rows) {
  const cuuint64_t dims[2] = {(cuuint64_t)cols, (cuuint64_t)rows}, strides[1] = {(cuuint64_t)cols * 2};
  const cuuint32_t box[2] = {64, (cuuint32_t)box_rows};
  make_map(enc, m, ptr, 2, dims, strides, box);
}
void make_3d(EncodeFn enc, CUtensorMap* m, const void* ptr, int rows, int chunks, size_t row_stride, size_t chunk_stride) {
  const cuuint64_t dims[3] = {64, (cuuint64_t)rows, (cuuint64_t)chunks}, strides[2] = {row_stride, chunk_stride};
  const cuuint32_t box[3] = {64, 64, 2};
  make_map(enc, m, ptr, 3, dims, strides, box);
}

void make_ffn(EncodeFn enc, CUtensorMap* m, const void* ptr) {
  const cuuint64_t dims[2] = {(cuuint64_t)FF, (cuuint64_t)DM}, strides[1] = {(cuuint64_t)FF * 2};
  const cuuint32_t box[2] = {16, 256};
  make_map(enc, m, ptr, 2, dims, strides, box, false);
}

#define SR 0x213312
#define SEED 12345
#define LU_MARGIN 0
#define SPARE_N 3
void build_sched(Sched& s) {
  memset(&s, 0, sizeof(s));
  const int NP = NCTA / 2, korder[4] = {(KORDER >> 12) & 3, (KORDER >> 8) & 3, (KORDER >> 4) & 3, KORDER & 3};
  const int sround[4][2][3] = {{}, {{1}, {2}}, {{1, 2}, {1, 2}}, {{(SR >> 20) & 3, (SR >> 16) & 3, (SR >> 12) & 3}, {(SR >> 8) & 3, (SR >> 4) & 3, SR & 3}}};
  int jv[4][NP], used[4][8] = {};
  for (int r = 0; r < 4; r++) for (int p = 0; p < NP; p++) jv[r][p] = (r & 2) ? 7 - ((p + 4 * (r & 1)) & 7) : (p + 4 * (r & 1)) & 7;
  for (int q = 0; q < 2; q++) {
    s.pair[NP + q].nitems = SPARE_N;
    for (int i = 0; i < SPARE_N; i++) {
      const int r = sround[SPARE_N][q][i];
      s.pair[NP + q].item[i] = (uint8_t)((r * 8 + used[r][6]++) * 8 + 6);
      for (int p = 0; p < NP; p++) if (jv[r][p] == 6) { jv[r][p] = -2; break; }
    }
  }
  auto cost = [&](int p) {
    int u = 8 - ((p >> 4) < SPARE_N ? 21 : 22), z = 0, none = 0;
    for (int r = 0; r < 4; r++) { u += jv[r][p]; z += jv[r][p] == 0; none += jv[r][p] < 0; }
    return 4 * u * u + (z > 1) + 4 * (none > 1);
  };
  uint32_t rng = SEED;
  for (int it = 0; it < 2000000; it++) {
    if ((it & 255) == 0) { int t = 0; for (int p = 0; p < NP; p++) t += cost(p); if (t == 0) break; }
    rng = rng * 1664525u + 1013904223u;
    const int r = (rng >> 8) & 3, a = (rng >> 12) & 63, b = (rng >> 20) & 63, before = cost(a) + cost(b);
    int t = jv[r][a]; jv[r][a] = jv[r][b]; jv[r][b] = t;
    if (cost(a) + cost(b) > before) { jv[r][b] = jv[r][a]; jv[r][a] = t; }
  }
  int fin[256], done[256];
  for (int p = 0; p < NP + 2; p++) {
    Sched::Pair& q = s.pair[p];
    if (p < NP) {
      for (int k = 0; k < 4; k++) q.khead[k] = (uint8_t)(korder[k] * 8 + (p >> 3));
      for (int r = 0; r < 4; r++) {
        if (jv[r][p] < 0) continue;
        q.item[q.nitems++] = (uint8_t)((r * 8 + used[r][jv[r][p]]++) * 8 + jv[r][p]);
      }
    }
    int t = p < NP ? 0 : -3, e = 1;
    for (int i = 0; i < q.nitems; i++) { t += (q.item[i] & 7) + 2; fin[q.item[i]] = t; done[q.item[i]] = t + (i + 1 < q.nitems ? 2 : 0); e += 8 + 4 * ((q.item[i] & 7) + 1); }
    for (int k = 0; k < 3 * MAX_STEPS + 6; k++) {
      const int n = k > 0 ? k - (SPARE_N & 1) : 0, r = n % 7, f = (e + (r < 4 ? r : r - 1)) % 12;
      q.oent[k] = (uint8_t)((r == 4 ? 6 : f >= 6 ? f + 2 : f) ^ (((n / 7) & 1) << 3));
    }
  }
  for (int p = 0; p < NP + 2; p++)
    for (int i = 0; i < s.pair[p].nitems; i++) {
      const int it = s.pair[p].item[i];
      for (int n = 0; n < 2 * (it & 7) + 2; n++) {
        bool last = true;
        for (int j = n >> 1; j < 8; j++) { const int o = (it & ~7) + j; if (o != it && fin[o] + LU_MARGIN > fin[it]) last = false; }
        if (last) s.pair[p].lastuse[i] |= (uint16_t)(1 << n);
      }
    }
  for (int j = 0; j < 8; j++) {
    int order[NH], left[4];
    for (int h = 0; h < NH; h++) { int k = h; for (; k > 0 && done[order[k - 1] * 8 + j] < done[h * 8 + j]; k--) order[k] = order[k - 1]; order[k] = h; }
    for (int kq = 0; kq < 4; kq++) {
      left[kq] = SPARE_N == 0 ? 16 : kq < SPARE_N ? 20 - SPARE_N : 16 - SPARE_N;
      for (int nh = 0; nh < 2; nh++) { Sched::Pair& q = s.pair[kq * 16 + nh * 8 + j]; q.otask = (uint8_t)(kq * 16 + nh * 8 + j); q.nsteps = (uint8_t)((left[kq] + 1) / 2); q.ochunk[0][0] = 255; }
    }
    for (int n = 0, kq = 0, run = 0; n < 64; ) {
      if (left[kq] > 0 && run < 2) {
        const int pos = --left[kq] + (SPARE_N & 1);
        for (int nh = 0; nh < 2; nh++) s.pair[kq * 16 + nh * 8 + j].ochunk[pos >> 1][pos & 1] = (uint8_t)(order[n >> 1] * 2 + 1 - (n & 1));
        n++; run++;
      } else { kq = (kq + 1) & 3; run = 0; }
    }
  }
}

}

extern "C" void kernel_launch(void* const* d_in, const int* in_sizes, int n_in, void* d_out, int out_size) {
  (void)in_sizes; (void)n_in; (void)out_size;
  const __nv_bfloat16* x     = (const __nv_bfloat16*)d_in[0];
  const __nv_bfloat16* ckv   = (const __nv_bfloat16*)d_in[1];
  const __nv_bfloat16* w_q   = (const __nv_bfloat16*)d_in[2];
  const __nv_bfloat16* w_uk  = (const __nv_bfloat16*)d_in[3];
  const __nv_bfloat16* w_uv  = (const __nv_bfloat16*)d_in[4];
  const __nv_bfloat16* w_o   = (const __nv_bfloat16*)d_in[5];
  const __nv_bfloat16* w_r   = (const __nv_bfloat16*)d_in[7];
  const __nv_bfloat16* w_g   = (const __nv_bfloat16*)d_in[8];
  const __nv_bfloat16* w_u   = (const __nv_bfloat16*)d_in[9];
  const __nv_bfloat16* w_d   = (const __nv_bfloat16*)d_in[10];
  const __nv_bfloat16* cvec  = (const __nv_bfloat16*)d_in[11];
  const __nv_bfloat16* w_mod = (const __nv_bfloat16*)d_in[12];
  __nv_bfloat16* out = (__nv_bfloat16*)d_out;

  static HostState st;
  if (!st.ready) {
    void* fn = nullptr; cudaDriverEntryPointQueryResult qr;
    cudaGetDriverEntryPoint("cuTensorMapEncodeTiled", &fn, cudaEnableDefault, &qr);
    st.encode = (EncodeFn)fn;
    cudaFuncSetAttribute(k_fused, cudaFuncAttributeMaxDynamicSharedMemorySize, SMEM);
    build_sched(st.sched);
    void *p_kvc, *p_h1, *p_part;
    cudaGetSymbolAddress(&p_kvc, g_kvc); cudaGetSymbolAddress(&p_h1, g_h1); cudaGetSymbolAddress(&p_part, g_part);
    st.sched.kvc = (__nv_bfloat16*)p_kvc; st.sched.h1 = (__nv_bfloat16*)p_h1;
    make_2d(st.encode, &st.tmH, p_h1, SEQ, DM, 64);
    make_2d(st.encode, &st.tmKV, p_kvc, 192 * SEQ, 64, 128);
    make_3d(st.encode, &st.tmPart, p_part, SEQ, 32, 128, (size_t)SEQ * 128);
    { const cuuint64_t dims[3] = {64, (cuuint64_t)SEQ, 32}, strides[2] = {128, (cuuint64_t)SEQ * 128}; const cuuint32_t box[3] = {64, 16, 4};
      make_map(st.encode, &st.tmPl, p_part, 3, dims, strides, box, false); }
    st.ready = true;
  }
  make_2d(st.encode, &st.tmC, ckv, SEQ, DM, 128);
  make_2d(st.encode, &st.tmWq, w_q, DM, NH * DH, 64);
  make_2d(st.encode, &st.tmWk, w_uk, DM, NH * DH, 64);
  make_2d(st.encode, &st.tmWv, w_uv, DM, NH * DH, 64);
  make_3d(st.encode, &st.tmWo, w_o, NH * DH, DM / 64, (size_t)DM * 2, 128);
  make_3d(st.encode, &st.tmWm, w_mod, DM, 6 * DM / 64, (size_t)6 * DM * 2, 128);
  make_ffn(st.encode, &st.tmWg, w_g);
  make_ffn(st.encode, &st.tmWu, w_u);

  k_fused<<<NGRID, 384, SMEM, cudaStreamPerThread>>>(st.tmC, st.tmH, st.tmWq, st.tmWk, st.tmWv, st.tmKV, st.tmWo, st.tmPart, st.tmWg, st.tmWu, st.tmPl, st.tmWm, st.sched,
                                                     x, cvec, w_o, w_r, w_g, w_u, w_d, out);
}
```

```cpp
#include <cuda_runtime.h>
#include <cuda_bf16.h>
#include <cuda.h>
#include <stdint.h>
#include <string.h>
#include <math.h>

namespace {

constexpr int SEQ = 2048, DM = 512, NH = 32, DH = 128, FF = 1792;
constexpr int NCTA = 128, NGRID = 132;

__device__ __align__(128) __nv_bfloat16 g_kvc[192 * SEQ * 64];
__device__ __nv_bfloat16 g_h1[SEQ * DM];
__device__ __nv_bfloat16 g_part[32 * SEQ * 64];
__device__ __align__(16) __nv_bfloat16 g_mod[6 * DM];
constexpr int C_MOD = 0, C_MOD2 = 16, C_H1 = 32, C_KV = 64, C_CTX = 128, C_END = 384;
__device__ unsigned int g_cnt[C_END];
__device__ unsigned int g_epoch;
__device__ __align__(128) unsigned int g_pflag[32][32];
__device__ __align__(128) uint2 g_keys[128][4];
__device__ __align__(16) uint2 g_row[128][2][DM / 2];
__device__ __align__(16) uint2 g_yll[FF / 16][DM];

#define DBG(i)
#define DBGP(i)

__device__ __forceinline__ uint32_t smem_u32(const void* p) { return (uint32_t)__cvta_generic_to_shared(p); }
__device__ __forceinline__ int wg_tid() { int t; asm volatile("mov.u32 %0, %%tid.x;" : "=r"(t)); return t & 127; }
__device__ __forceinline__ uint32_t clk32() { uint32_t c; asm volatile("mov.u32 %0, %%clock;" : "=r"(c)); return c; }
__device__ __forceinline__ void mbar_arrive(uint32_t bar) { asm volatile("mbarrier.arrive.shared::cta.b64 _, [%0];" :: "r"(bar) : "memory"); }
__device__ __forceinline__ uint32_t mapa(uint32_t addr, uint32_t cta) { uint32_t r; asm("mapa.shared::cluster.u32 %0, %1, %2;" : "=r"(r) : "r"(addr), "r"(cta)); return r; }
__device__ __forceinline__ void mbar_arrive_remote_if(uint32_t cluster_addr, bool pred) {
  asm volatile("{\n.reg .pred p;\nsetp.ne.u32 p, %1, 0;\n@p mbarrier.arrive.shared::cluster.b64 _, [%0];\n}" :: "r"(cluster_addr), "r"((uint32_t)pred) : "memory");
}
__device__ __forceinline__ bool mbar_try(uint32_t bar, uint32_t parity) {
  uint32_t done;
  asm volatile("{\n.reg .pred p;\nmbarrier.try_wait.parity.shared::cta.b64 p, [%1], %2;\nselp.u32 %0, 1, 0, p;\n}" : "=r"(done) : "r"(bar), "r"(parity) : "memory");
  return done;
}
#define WAIT_LIM (1 << 14)
__device__ __forceinline__ void mbar_wait(uint32_t bar, uint32_t parity) {
  #pragma unroll 1
  for (int n = 0; n < WAIT_LIM; n++) { if (mbar_try(bar, parity)) break; }
}
__device__ __forceinline__ unsigned int ld_acquire(const unsigned int* p) {
  unsigned int v; asm volatile("ld.acquire.gpu.global.u32 %0, [%1];" : "=r"(v) : "l"(p) : "memory"); return v;
}
__device__ __forceinline__ unsigned int ld_relaxed(const unsigned int* p) {
  unsigned int v; asm volatile("ld.relaxed.gpu.global.u32 %0, [%1];" : "=r"(v) : "l"(p) : "memory"); return v;
}
__device__ __forceinline__ void wait_count_lazy(int idx, unsigned int target) {
  #pragma unroll 1
  for (int n = 0; n < WAIT_LIM; n++) { if (__all_sync(0xffffffff, (int)(ld_relaxed(&g_cnt[idx]) - target) >= 0)) break; __nanosleep(100); }
  ld_acquire(&g_cnt[idx]);
}
__device__ __forceinline__ uint4 ld_tagged2(const void* p) {
  uint4 v;
  asm volatile("{\n.reg .b64 a, b;\nld.relaxed.gpu.global.v2.u64 {a, b}, [%4];\nmov.b64 {%0, %1}, a;\nmov.b64 {%2, %3}, b;\n}"
    : "=r"(v.x), "=r"(v.y), "=r"(v.z), "=r"(v.w) : "l"(p) : "memory");
  return v;
}
__device__ __forceinline__ uint2 ld_tagged(const void* p) {
  uint2 v; asm volatile("{\n.reg .b64 a;\nld.relaxed.gpu.global.u64 a, [%2];\nmov.b64 {%0, %1}, a;\n}" : "=r"(v.x), "=r"(v.y) : "l"(p) : "memory"); return v;
}
__device__ __forceinline__ void st_tagged2(void* p, uint32_t a, uint32_t b, uint32_t tag) {
  asm volatile("{\n.reg .b64 a, b;\nmov.b64 a, {%1, %3};\nmov.b64 b, {%2, %3};\nst.relaxed.gpu.global.v2.u64 [%0], {a, b};\n}" :: "l"(p), "r"(a), "r"(b), "r"(tag) : "memory");
}
__device__ __forceinline__ void st_tagged(void* p, uint32_t a, uint32_t tag) {
  asm volatile("{\n.reg .b64 a;\nmov.b64 a, {%1, %2};\nst.relaxed.gpu.global.u64 [%0], a;\n}" :: "l"(p), "r"(a), "r"(tag) : "memory");
}
__device__ __forceinline__ void stg_v4(void* p, uint32_t a, uint32_t b, uint32_t c, uint32_t d) {
  asm volatile("st.global.v4.u32 [%0], {%1, %2, %3, %4};" :: "l"(p), "r"(a), "r"(b), "r"(c), "r"(d) : "memory");
}
__device__ __forceinline__ uint4 lds_v4(uint32_t addr) {
  uint4 v; asm volatile("ld.shared.v4.u32 {%0, %1, %2, %3}, [%4];" : "=r"(v.x), "=r"(v.y), "=r"(v.z), "=r"(v.w) : "r"(addr) : "memory"); return v;
}
__device__ __forceinline__ uint32_t lds_u32(uint32_t addr) { uint32_t v; asm volatile("ld.shared.u32 %0, [%1];" : "=r"(v) : "r"(addr) : "memory"); return v; }
__device__ __forceinline__ void sts_v4(uint32_t addr, uint32_t a, uint32_t b, uint32_t c, uint32_t d) {
  asm volatile("st.shared.v4.u32 [%0], {%1, %2, %3, %4};" :: "r"(addr), "r"(a), "r"(b), "r"(c), "r"(d) : "memory");
}
#define ELECT "{\n.reg .pred p;\nelect.sync _|p, 0xffffffff;\n@p "
__device__ __forceinline__ void w_mbar_init(uint32_t bar, uint32_t cnt) { asm volatile(ELECT "mbarrier.init.shared::cta.b64 [%0], %1;\n}" :: "r"(bar), "r"(cnt) : "memory"); }
__device__ __forceinline__ void w_expect_tx(uint32_t bar, uint32_t bytes) { asm volatile(ELECT "mbarrier.arrive.expect_tx.shared::cta.b64 _, [%0], %1;\n}" :: "r"(bar), "r"(bytes) : "memory"); }
__device__ __forceinline__ void w_arrive(uint32_t bar) { asm volatile(ELECT "mbarrier.arrive.shared::cta.b64 _, [%0];\n}" :: "r"(bar) : "memory"); }
__device__ __forceinline__ void tma_load_2d(uint32_t dst, const CUtensorMap* tm, uint32_t bar, int c0, int c1) {
  asm volatile(ELECT "cp.async.bulk.tensor.2d.shared::cluster.global.mbarrier::complete_tx::bytes [%0], [%1, {%3, %4}], [%2];\n}"
    :: "r"(dst), "l"(tm), "r"(bar), "r"(c0), "r"(c1) : "memory");
}
__device__ __forceinline__ void tma_load_2d_mc(uint32_t dst, const CUtensorMap* tm, uint32_t bar, int c0, int c1) {
  asm volatile(ELECT "cp.async.bulk.tensor.2d.shared::cluster.global.mbarrier::complete_tx::bytes.multicast::cluster [%0], [%1, {%3, %4}], [%2], %5;\n}"
    :: "r"(dst), "l"(tm), "r"(bar), "r"(c0), "r"(c1), "h"((uint16_t)3) : "memory");
}
__device__ __forceinline__ void tma_load_3d(uint32_t dst, const CUtensorMap* tm, uint32_t bar, int c0, int c1, int c2) {
  asm volatile(ELECT "cp.async.bulk.tensor.3d.shared::cluster.global.mbarrier::complete_tx::bytes [%0], [%1, {%3, %4, %5}], [%2];\n}"
    :: "r"(dst), "l"(tm), "r"(bar), "r"(c0), "r"(c1), "r"(c2) : "memory");
}
__device__ __forceinline__ void tma_load_3d_mc(uint32_t dst, const CUtensorMap* tm, uint32_t bar, int c0, int c1, int c2) {
  asm volatile(ELECT "cp.async.bulk.tensor.3d.shared::cluster.global.mbarrier::complete_tx::bytes.multicast::cluster [%0], [%1, {%3, %4, %5}], [%2], %6;\n}"
    :: "r"(dst), "l"(tm), "r"(bar), "r"(c0), "r"(c1), "r"(c2), "h"((uint16_t)3) : "memory");
}
__device__ __forceinline__ void bulk_load_mc(uint32_t dst, const void* src, uint32_t bar, bool ef) {
  if (ef) {
    uint64_t pol; asm("createpolicy.fractional.L2::evict_first.b64 %0, 1.0;" : "=l"(pol));
    asm volatile(ELECT "cp.async.bulk.shared::cluster.global.mbarrier::complete_tx::bytes.multicast::cluster.L2::cache_hint [%0], [%1], 16384, [%2], %3, %4;\n}"
      :: "r"(dst), "l"(src), "r"(bar), "h"((uint16_t)3), "l"(pol) : "memory");
  } else
    asm volatile(ELECT "cp.async.bulk.shared::cluster.global.mbarrier::complete_tx::bytes.multicast::cluster [%0], [%1], 16384, [%2], %3;\n}"
      :: "r"(dst), "l"(src), "r"(bar), "h"((uint16_t)3) : "memory");
}
__device__ __forceinline__ void bulk_load(uint32_t dst, const void* src, uint32_t bytes, uint32_t bar) {
  asm volatile(ELECT "cp.async.bulk.shared::cluster.global.mbarrier::complete_tx::bytes [%0], [%1], %2, [%3];\n}" :: "r"(dst), "l"(src), "r"(bytes), "r"(bar) : "memory");
}
__device__ __forceinline__ void tma_prefetch_2d(const CUtensorMap* tm, int c0, int c1) {
  asm volatile(ELECT "cp.async.bulk.prefetch.tensor.2d.L2.global [%0, {%1, %2}];\n}" :: "l"(tm), "r"(c0), "r"(c1) : "memory");
}
__device__ __forceinline__ void bulk_prefetch(const void* p, uint32_t bytes) {
  asm volatile(ELECT "cp.async.bulk.prefetch.L2.global [%0], %1;\n}" :: "l"(p), "r"(bytes) : "memory");
}
__device__ __forceinline__ void tma_store_3d(const CUtensorMap* tm, uint32_t src, int c0, int c1, int c2) {
  asm volatile("cp.async.bulk.tensor.3d.global.shared::cta.bulk_group [%0, {%2, %3, %4}], [%1];"
    :: "l"(tm), "r"(src), "r"(c0), "r"(c1), "r"(c2) : "memory");
}
__device__ __forceinline__ void st_release(unsigned int* p, unsigned int v) { asm volatile("st.release.gpu.global.u32 [%0], %1;" :: "l"(p), "r"(v) : "memory"); }
__device__ __forceinline__ void red_release(int idx) { asm volatile("red.release.gpu.global.add.u32 [%0], 1;" :: "l"(&g_cnt[idx]) : "memory"); }
__device__ __forceinline__ void prefetch_tmap(const CUtensorMap* tm) { asm volatile("prefetch.tensormap [%0];" :: "l"(tm) : "memory"); }
__device__ __forceinline__ void bulk_commit() { asm volatile("cp.async.bulk.commit_group;" ::: "memory"); }
template<int N> __device__ __forceinline__ void bulk_wait() { asm volatile("cp.async.bulk.wait_group %0;" :: "n"(N) : "memory"); }
__device__ __forceinline__ void bar_sync(int id, int n) { asm volatile("bar.sync %0, %1;" :: "r"(id), "r"(n) : "memory"); }
__device__ __forceinline__ void bar_arrive(int id, int n) { asm volatile("bar.arrive %0, %1;" :: "r"(id), "r"(n) : "memory"); }
__device__ __forceinline__ void fence_async_smem() { asm volatile("fence.proxy.async.shared::cta;" ::: "memory"); }
__device__ __forceinline__ void fence_async_global() { asm volatile("fence.proxy.async.global;" ::: "memory"); }
__device__ __forceinline__ void fence_mbar_init() { asm volatile("fence.mbarrier_init.release.cluster;" ::: "memory"); }
__device__ __forceinline__ void cluster_arrive() { asm volatile("barrier.cluster.arrive.relaxed.aligned;" ::: "memory"); }
__device__ __forceinline__ void cluster_wait() { asm volatile("barrier.cluster.wait.aligned;" ::: "memory"); }
__device__ __forceinline__ uint32_t cluster_ctarank() { uint32_t r; asm volatile("mov.u32 %0, %%cluster_ctarank;" : "=r"(r)); return r; }
__device__ __forceinline__ void wgmma_fence() { asm volatile("wgmma.fence.sync.aligned;" ::: "memory"); }
__device__ __forceinline__ void wgmma_commit() { asm volatile("wgmma.commit_group.sync.aligned;" ::: "memory"); }
template<int N> __device__ __forceinline__ void wgmma_wait() { asm volatile("wgmma.wait_group.sync.aligned %0;" :: "n"(N) : "memory"); }
__device__ __forceinline__ float ex2(float x) { float y; asm("ex2.approx.ftz.f32 %0, %1;" : "=f"(y) : "f"(x)); return y; }
__device__ __forceinline__ float rcp_fast(float x) { float y; asm("rcp.approx.ftz.f32 %0, %1;" : "=f"(y) : "f"(x)); return y; }
__device__ __forceinline__ uint32_t pack_bf16(float lo, float hi) { uint32_t r; asm("cvt.rn.bf16x2.f32 %0, %1, %2;" : "=r"(r) : "f"(hi), "f"(lo)); return r; }
__device__ __forceinline__ float rbf(float x) { return __uint_as_float(pack_bf16(0.f, x)); }
__device__ __forceinline__ float bf_lo(uint32_t v) { return __uint_as_float(v << 16); }
__device__ __forceinline__ float bf_hi(uint32_t v) { return __uint_as_float(v & 0xffff0000u); }
__device__ __forceinline__ uint32_t add2(uint32_t a, uint32_t b) { uint32_t r; asm("add.rn.bf16x2 %0, %1, %2;" : "=r"(r) : "r"(a), "r"(b)); return r; }
__device__ __forceinline__ uint32_t fma2(uint32_t a, uint32_t b, uint32_t c) { uint32_t r; asm("fma.rn.bf16x2 %0, %1, %2, %3;" : "=r"(r) : "r"(a), "r"(b), "r"(c)); return r; }
__device__ __forceinline__ uint4 ldsm_x4_t(uint32_t addr) {
  uint4 v; asm volatile("ldmatrix.sync.aligned.m8n8.x4.trans.shared.b16 {%0, %1, %2, %3}, [%4];" : "=r"(v.x), "=r"(v.y), "=r"(v.z), "=r"(v.w) : "r"(addr) : "memory"); return v;
}
__device__ __forceinline__ void mma16816(float (&c)[4], const uint4& a, uint32_t b0, uint32_t b1) {
  asm("mma.sync.aligned.m16n8k16.row.col.f32.bf16.bf16.f32 {%0, %1, %2, %3}, {%4, %5, %6, %7}, {%8, %9}, {%0, %1, %2, %3};"
    : "+f"(c[0]), "+f"(c[1]), "+f"(c[2]), "+f"(c[3]) : "r"(a.x), "r"(a.y), "r"(a.z), "r"(a.w), "r"(b0), "r"(b1));
}
__device__ __forceinline__ void stsm_x4(uint32_t addr, uint32_t r0, uint32_t r1, uint32_t r2, uint32_t r3) {
  asm volatile("stmatrix.sync.aligned.m8n8.x4.shared.b16 [%0], {%1, %2, %3, %4};" :: "r"(addr), "r"(r0), "r"(r1), "r"(r2), "r"(r3) : "memory");
}
template<int N> __device__ __forceinline__ void fence_regs(float (&a)[N]) {
  #pragma unroll
  for (int i = 0; i < N; i++) asm volatile("" : "+f"(a[i]) :: "memory");
}
template<int N> __device__ __forceinline__ void fence_regs_u(uint32_t (&a)[N]) {
  #pragma unroll
  for (int i = 0; i < N; i++) asm volatile("" : "+r"(a[i]) :: "memory");
}
constexpr uint32_t SW128 = 0x40000040u, SW64 = 0x80000020u;
__device__ __forceinline__ uint32_t desc_lo(uint32_t addr, uint32_t lbo) { return ((addr & 0x3FFFF) >> 4) | ((lbo >> 4) << 16); }

template<int TB, int OA, int OB, uint32_t HA, uint32_t HB> __device__ __forceinline__ void wgmma_ss_n128(float (&d)[64], uint32_t da, uint32_t db, int sd) {
  asm volatile("{\n.reg .pred p;\n.reg .b32 ta, tb;\n.reg .b64 da, db;\nsetp.ne.b32 p, %66, 0;\nadd.u32 ta, %64, %68;\nadd.u32 tb, %65, %69;\nmov.b64 da, {ta, %70};\nmov.b64 db, {tb, %71};\n"
    "wgmma.mma_async.sync.aligned.m64n128k16.f32.bf16.bf16 "
    "{%0, %1, %2, %3, %4, %5, %6, %7, %8, %9, %10, %11, %12, %13, %14, %15, %16, %17, %18, %19, %20, %21, %22, %23, %24, %25, %26, %27, %28, %29, %30, %31, %32, %33, %34, %35, %36, %37, %38, %39, %40, %41, %42, %43, %44, %45, %46, %47, %48, %49, %50, %51, %52, %53, %54, %55, %56, %57, %58, %59, %60, %61, %62, %63}, da, db, p, 1, 1, 0, %67;\n}\n"
    : "+f"(d[0]), "+f"(d[1]), "+f"(d[2]), "+f"(d[3]), "+f"(d[4]), "+f"(d[5]), "+f"(d[6]), "+f"(d[7]), "+f"(d[8]), "+f"(d[9]), "+f"(d[10]), "+f"(d[11]), "+f"(d[12]), "+f"(d[13]), "+f"(d[14]), "+f"(d[15]), "+f"(d[16]), "+f"(d[17]), "+f"(d[18]), "+f"(d[19]), "+f"(d[20]), "+f"(d[21]), "+f"(d[22]), "+f"(d[23]), "+f"(d[24]), "+f"(d[25]), "+f"(d[26]), "+f"(d[27]), "+f"(d[28]), "+f"(d[29]), "+f"(d[30]), "+f"(d[31]), "+f"(d[32]), "+f"(d[33]), "+f"(d[34]), "+f"(d[35]), "+f"(d[36]), "+f"(d[37]), "+f"(d[38]), "+f"(d[39]), "+f"(d[40]), "+f"(d[41]), "+f"(d[42]), "+f"(d[43]), "+f"(d[44]), "+f"(d[45]), "+f"(d[46]), "+f"(d[47]), "+f"(d[48]), "+f"(d[49]), "+f"(d[50]), "+f"(d[51]), "+f"(d[52]), "+f"(d[53]), "+f"(d[54]), "+f"(d[55]), "+f"(d[56]), "+f"(d[57]), "+f"(d[58]), "+f"(d[59]), "+f"(d[60]), "+f"(d[61]), "+f"(d[62]), "+f"(d[63])
    : "r"(da), "r"(db), "r"(sd), "n"(TB), "n"(OA), "n"(OB), "n"(HA), "n"(HB));
}
template<int TB, int OB, uint32_t HB> __device__ __forceinline__ void wgmma_rs_n128(float (&d)[64], uint32_t a0, uint32_t a1, uint32_t a2, uint32_t a3, uint32_t db, int sd) {
  asm volatile("{\n.reg .pred p;\n.reg .b32 tb;\n.reg .b64 db;\nsetp.ne.b32 p, %69, 0;\nadd.u32 tb, %68, %71;\nmov.b64 db, {tb, %72};\n"
    "wgmma.mma_async.sync.aligned.m64n128k16.f32.bf16.bf16 "
    "{%0, %1, %2, %3, %4, %5, %6, %7, %8, %9, %10, %11, %12, %13, %14, %15, %16, %17, %18, %19, %20, %21, %22, %23, %24, %25, %26, %27, %28, %29, %30, %31, %32, %33, %34, %35, %36, %37, %38, %39, %40, %41, %42, %43, %44, %45, %46, %47, %48, %49, %50, %51, %52, %53, %54, %55, %56, %57, %58, %59, %60, %61, %62, %63}, {%64,%65,%66,%67}, db, p, 1, 1, %70;\n}\n"
    : "+f"(d[0]), "+f"(d[1]), "+f"(d[2]), "+f"(d[3]), "+f"(d[4]), "+f"(d[5]), "+f"(d[6]), "+f"(d[7]), "+f"(d[8]), "+f"(d[9]), "+f"(d[10]), "+f"(d[11]), "+f"(d[12]), "+f"(d[13]), "+f"(d[14]), "+f"(d[15]), "+f"(d[16]), "+f"(d[17]), "+f"(d[18]), "+f"(d[19]), "+f"(d[20]), "+f"(d[21]), "+f"(d[22]), "+f"(d[23]), "+f"(d[24]), "+f"(d[25]), "+f"(d[26]), "+f"(d[27]), "+f"(d[28]), "+f"(d[29]), "+f"(d[30]), "+f"(d[31]), "+f"(d[32]), "+f"(d[33]), "+f"(d[34]), "+f"(d[35]), "+f"(d[36]), "+f"(d[37]), "+f"(d[38]), "+f"(d[39]), "+f"(d[40]), "+f"(d[41]), "+f"(d[42]), "+f"(d[43]), "+f"(d[44]), "+f"(d[45]), "+f"(d[46]), "+f"(d[47]), "+f"(d[48]), "+f"(d[49]), "+f"(d[50]), "+f"(d[51]), "+f"(d[52]), "+f"(d[53]), "+f"(d[54]), "+f"(d[55]), "+f"(d[56]), "+f"(d[57]), "+f"(d[58]), "+f"(d[59]), "+f"(d[60]), "+f"(d[61]), "+f"(d[62]), "+f"(d[63])
    : "r"(a0), "r"(a1), "r"(a2), "r"(a3), "r"(db), "r"(sd), "n"(TB), "n"(OB), "n"(HB));
}
template<int TB, int OA, int OB, uint32_t HA, uint32_t HB> __device__ __forceinline__ void wgmma_ss_n64(float (&d)[32], uint32_t da, uint32_t db, int sd) {
  asm volatile("{\n.reg .pred p;\n.reg .b32 ta, tb;\n.reg .b64 da, db;\nsetp.ne.b32 p, %34, 0;\nadd.u32 ta, %32, %36;\nadd.u32 tb, %33, %37;\nmov.b64 da, {ta, %38};\nmov.b64 db, {tb, %39};\n"
    "wgmma.mma_async.sync.aligned.m64n64k16.f32.bf16.bf16 "
    "{%0, %1, %2, %3, %4, %5, %6, %7, %8, %9, %10, %11, %12, %13, %14, %15, %16, %17, %18, %19, %20, %21, %22, %23, %24, %25, %26, %27, %28, %29, %30, %31}, da, db, p, 1, 1, 0, %35;\n}\n"
    : "+f"(d[0]), "+f"(d[1]), "+f"(d[2]), "+f"(d[3]), "+f"(d[4]), "+f"(d[5]), "+f"(d[6]), "+f"(d[7]), "+f"(d[8]), "+f"(d[9]), "+f"(d[10]), "+f"(d[11]), "+f"(d[12]), "+f"(d[13]), "+f"(d[14]), "+f"(d[15]), "+f"(d[16]), "+f"(d[17]), "+f"(d[18]), "+f"(d[19]), "+f"(d[20]), "+f"(d[21]), "+f"(d[22]), "+f"(d[23]), "+f"(d[24]), "+f"(d[25]), "+f"(d[26]), "+f"(d[27]), "+f"(d[28]), "+f"(d[29]), "+f"(d[30]), "+f"(d[31])
    : "r"(da), "r"(db), "r"(sd), "n"(TB), "n"(OA), "n"(OB), "n"(HA), "n"(HB));
}
template<int TB, int OA, int OB, uint32_t HA, uint32_t HB> __device__ __forceinline__ void wgmma_ss_n128_new(float (&d)[64], uint32_t da, uint32_t db) {
  asm volatile("{\n.reg .pred p;\n.reg .b32 ta, tb;\n.reg .b64 da, db;\nsetp.ne.b32 p, %66, 0;\nadd.u32 ta, %64, %68;\nadd.u32 tb, %65, %69;\nmov.b64 da, {ta, %70};\nmov.b64 db, {tb, %71};\n"
    "wgmma.mma_async.sync.aligned.m64n128k16.f32.bf16.bf16 "
    "{%0, %1, %2, %3, %4, %5, %6, %7, %8, %9, %10, %11, %12, %13, %14, %15, %16, %17, %18, %19, %20, %21, %22, %23, %24, %25, %26, %27, %28, %29, %30, %31, %32, %33, %34, %35, %36, %37, %38, %39, %40, %41, %42, %43, %44, %45, %46, %47, %48, %49, %50, %51, %52, %53, %54, %55, %56, %57, %58, %59, %60, %61, %62, %63}, da, db, p, 1, 1, 0, %67;\n}\n"
    : "=f"(d[0]), "=f"(d[1]), "=f"(d[2]), "=f"(d[3]), "=f"(d[4]), "=f"(d[5]), "=f"(d[6]), "=f"(d[7]), "=f"(d[8]), "=f"(d[9]), "=f"(d[10]), "=f"(d[11]), "=f"(d[12]), "=f"(d[13]), "=f"(d[14]), "=f"(d[15]), "=f"(d[16]), "=f"(d[17]), "=f"(d[18]), "=f"(d[19]), "=f"(d[20]), "=f"(d[21]), "=f"(d[22]), "=f"(d[23]), "=f"(d[24]), "=f"(d[25]), "=f"(d[26]), "=f"(d[27]), "=f"(d[28]), "=f"(d[29]), "=f"(d[30]), "=f"(d[31]), "=f"(d[32]), "=f"(d[33]), "=f"(d[34]), "=f"(d[35]), "=f"(d[36]), "=f"(d[37]), "=f"(d[38]), "=f"(d[39]), "=f"(d[40]), "=f"(d[41]), "=f"(d[42]), "=f"(d[43]), "=f"(d[44]), "=f"(d[45]), "=f"(d[46]), "=f"(d[47]), "=f"(d[48]), "=f"(d[49]), "=f"(d[50]), "=f"(d[51]), "=f"(d[52]), "=f"(d[53]), "=f"(d[54]), "=f"(d[55]), "=f"(d[56]), "=f"(d[57]), "=f"(d[58]), "=f"(d[59]), "=f"(d[60]), "=f"(d[61]), "=f"(d[62]), "=f"(d[63])
    : "r"(da), "r"(db), "n"(0), "n"(TB), "n"(OA), "n"(OB), "n"(HA), "n"(HB));
}
template<int TB, int OA, int OB, uint32_t HA, uint32_t HB> __device__ __forceinline__ void wgmma_ss_n64_new(float (&d)[32], uint32_t da, uint32_t db) {
  asm volatile("{\n.reg .pred p;\n.reg .b32 ta, tb;\n.reg .b64 da, db;\nsetp.ne.b32 p, %34, 0;\nadd.u32 ta, %32, %36;\nadd.u32 tb, %33, %37;\nmov.b64 da, {ta, %38};\nmov.b64 db, {tb, %39};\n"
    "wgmma.mma_async.sync.aligned.m64n64k16.f32.bf16.bf16 "
    "{%0, %1, %2, %3, %4, %5, %6, %7, %8, %9, %10, %11, %12, %13, %14, %15, %16, %17, %18, %19, %20, %21, %22, %23, %24, %25, %26, %27, %28, %29, %30, %31}, da, db, p, 1, 1, 0, %35;\n}\n"
    : "=f"(d[0]), "=f"(d[1]), "=f"(d[2]), "=f"(d[3]), "=f"(d[4]), "=f"(d[5]), "=f"(d[6]), "=f"(d[7]), "=f"(d[8]), "=f"(d[9]), "=f"(d[10]), "=f"(d[11]), "=f"(d[12]), "=f"(d[13]), "=f"(d[14]), "=f"(d[15]), "=f"(d[16]), "=f"(d[17]), "=f"(d[18]), "=f"(d[19]), "=f"(d[20]), "=f"(d[21]), "=f"(d[22]), "=f"(d[23]), "=f"(d[24]), "=f"(d[25]), "=f"(d[26]), "=f"(d[27]), "=f"(d[28]), "=f"(d[29]), "=f"(d[30]), "=f"(d[31])
    : "r"(da), "r"(db), "n"(0), "n"(TB), "n"(OA), "n"(OB), "n"(HA), "n"(HB));
}
template<int OA, int OB = 0, uint32_t HA = SW128> __device__ __forceinline__ void kblock_n128(float (&d)[64], uint32_t da, uint32_t db, int sd) {
  constexpr int H = HA == SW128 ? 4 : 512;
  wgmma_ss_n128<1, OA, OB, HA, SW128>(d, da, db, sd); wgmma_ss_n128<1, OA + 2, OB + 128, HA, SW128>(d, da, db, 1);
  wgmma_ss_n128<1, OA + H, OB + 256, HA, SW128>(d, da, db, 1); wgmma_ss_n128<1, OA + H + 2, OB + 384, HA, SW128>(d, da, db, 1);
}

__device__ __forceinline__ float quad_sum(float v) {
  v += __shfl_xor_sync(0xffffffff, v, 1);
  v += __shfl_xor_sync(0xffffffff, v, 2);
  return v;
}
struct Row { uint32_t v[8]; };
template<class F> __device__ __forceinline__ Row load_row(const __nv_bfloat16* p, int lane, F ld) {
  const uint4 a = ld(reinterpret_cast<const uint4*>(p) + lane), b = ld(reinterpret_cast<const uint4*>(p) + 32 + lane);
  return Row{{a.x, a.y, a.z, a.w, b.x, b.y, b.z, b.w}};
}
__device__ __forceinline__ Row ldg_row(const __nv_bfloat16* p, int lane) { return load_row(p, lane, [](const uint4* q) { return __ldg(q); }); }
__device__ __forceinline__ Row ldca_row(const __nv_bfloat16* p, int lane) { return load_row(p, lane, [](const uint4* q) { return __ldca(q); }); }
__device__ __forceinline__ Row lds_row(uint32_t addr, int lane) {
  const uint4 a = lds_v4(addr + lane * 16), b = lds_v4(addr + 512 + lane * 16);
  return Row{{a.x, a.y, a.z, a.w, b.x, b.y, b.z, b.w}};
}
__device__ __forceinline__ void store_row(__nv_bfloat16* p, int lane, const Row& r) {
  stg_v4(p + lane * 8, r.v[0], r.v[1], r.v[2], r.v[3]); stg_v4(p + 256 + lane * 8, r.v[4], r.v[5], r.v[6], r.v[7]);
}
__device__ __forceinline__ Row fma_row(const Row& a, const Row& b, const Row& c) {
  Row r;
  #pragma unroll
  for (int i = 0; i < 8; i++) r.v[i] = fma2(a.v[i], b.v[i], c.v[i]);
  return r;
}
__device__ __forceinline__ Row add_row(const Row& a, const Row& b) {
  Row r;
  #pragma unroll
  for (int i = 0; i < 8; i++) r.v[i] = add2(a.v[i], b.v[i]);
  return r;
}
__device__ __forceinline__ Row one_plus(const Row& a) {
  Row r;
  #pragma unroll
  for (int i = 0; i < 8; i++) r.v[i] = add2(a.v[i], 0x3f803f80u);
  return r;
}
__device__ __forceinline__ float row_at(const Row& x, int i) { return (i & 1) ? bf_hi(x.v[i >> 1]) : bf_lo(x.v[i >> 1]); }
template<int N> __device__ __forceinline__ void warp_sums(float (&s)[N]) {
  #pragma unroll
  for (int o = 16; o > 0; o >>= 1) {
    #pragma unroll
    for (int k = 0; k < N; k++) s[k] += __shfl_xor_sync(0xffffffff, s[k], o);
  }
}
__device__ __forceinline__ void ln_stats(float& s1, float& s2) {
  s1 *= 1.f / DM;
  asm("rsqrt.approx.ftz.f32 %0, %1;" : "=f"(s2) : "f"(fmaxf(fmaf(-s1, s1, s2 * (1.f / DM)), 0.f) + 1e-5f));
}
__device__ __forceinline__ Row ln_apply(const Row& x, float mean, float f) {
  Row n;
  const float o = -mean * f;
  #pragma unroll
  for (int i = 0; i < 8; i++) n.v[i] = pack_bf16(fmaf(bf_lo(x.v[i]), f, o), fmaf(bf_hi(x.v[i]), f, o));
  return n;
}

constexpr int SM_Q = 6 * 32768, SM_BAR = 7 * 32768, SM_MAIL = SM_BAR + 640, SM_RED = SM_MAIL + 128, SM_H2 = SM_RED + 1024, SM_KEY = SM_H2 + 1024, SMEM = SM_KEY + 128;
constexpr int B_AF = 0, B_WF = 64, B_RF = 112, B_WE = 168, B_RE = 216, B_PUB = 272, B_RDY = 496;
constexpr int R_MOD = B_RDY, R_H1 = B_RDY + 8, R_ITEM = B_RDY + 16, R_NEAR = B_RDY + 48, R_CTX = B_RDY + 64;
constexpr int R_KEY = B_AF + 8, R_PART = B_AF + 32;
constexpr int NPUB = 14;
__device__ __forceinline__ uint32_t k_addrA(int kb) { return ((0x6310u >> ((kb >> 1) * 4)) & 15u) * 32768u + (kb & 1) * 16384u; }
__device__ __forceinline__ uint32_t k_addrW(int s) { return ((0x254u >> ((s >> 1) * 4)) & 15u) * 32768u + (s & 1) * 16384u; }

#define KORDER 0x2301
constexpr int KHEAD0 = ((KORDER >> 12) & 3) * 8;
constexpr int MAX_ITEMS = 4;
constexpr int MAX_STEPS = 10;
struct Sched {
  __nv_bfloat16 *kvc, *h1;
  struct Pair {
    uint8_t oent[3 * MAX_STEPS + 6];
    uint16_t lastuse[MAX_ITEMS];
    uint8_t khead[4];
    uint8_t nitems, item[MAX_ITEMS];
    uint8_t otask, nsteps;
    uint8_t ochunk[MAX_STEPS][2];
  } pair[NGRID / 2];
};

__device__ __forceinline__ int ring_add(int e, int n) { e += n; return e >= 12 ? e - 12 : e; }
__device__ __forceinline__ int ring_slot(int e) { return e >= 6 ? e - 6 : e; }
__device__ __forceinline__ void ring_wait_full(uint32_t bars, int e) { mbar_wait(bars + B_RF + 8 * ring_slot(e), e >= 6); }

__device__ __forceinline__ void o_wait_full(uint32_t bars, uint32_t v) { mbar_wait(bars + B_RF + 8 * (v & 7), v >> 3); }

struct Ctx {
  uint32_t base, bars;
  uint32_t rel;
  bool rel1;
  int w, nev;
  const Sched* sched;
  uint32_t tr;
};
#define TR(id)
__device__ __forceinline__ void slot_release(const Ctx& x, int s, bool twice) {
  mbar_arrive_remote_if(x.rel + B_RE + 8 * s, twice ? (wg_tid() & 31) == 0 : x.rel1);
}
__device__ __forceinline__ void ring_release(const Ctx& x, int e, bool twice) { slot_release(x, ring_slot(e), twice); }
__device__ __forceinline__ void publish(Ctx& x, int idx) {
  const uint32_t n = x.w * NPUB + x.nev;
  const int t = wg_tid();
  if (t == 0) asm volatile("st.shared.u32 [%0], %1;" :: "r"(x.base + SM_MAIL + 4 * n), "r"(idx) : "memory");
  __syncwarp();
  if ((t & 31) == 0) mbar_arrive(x.bars + B_PUB + 8 * n);
  x.nev++;
}

template<int KK = 0> __device__ __forceinline__ void issue_qk(float (&S)[64], uint32_t dq, uint32_t dk) {
  constexpr int off = (KK >> 1) * 512 + (KK & 1) * 2;
  if constexpr (KK == 0) wgmma_ss_n128_new<0, 0, 0, SW64, SW64>(S, dq, dk); else wgmma_ss_n128<0, off, off, SW64, SW64>(S, dq, dk, 1);
  if constexpr (KK < 7) issue_qk<KK + 1>(S, dq, dk);
}
template<int KK = 0> __device__ __forceinline__ void issue_qk_half(float (&S)[32], uint32_t dq, uint32_t dk) {
  constexpr int off = (KK >> 1) * 512 + (KK & 1) * 2;
  if constexpr (KK == 0) wgmma_ss_n64_new<0, 0, 256, SW64, SW64>(S, dq, dk); else wgmma_ss_n64<0, off, off + 256, SW64, SW64>(S, dq, dk, 1);
  if constexpr (KK < 7) issue_qk_half<KK + 1>(S, dq, dk);
}
template<int NK, int KK = 0>
__device__ __forceinline__ void issue_pv(float (&O)[64], uint32_t (&P)[32], uint32_t dv, int accumulate) {
  wgmma_rs_n128<1, (KK + 8 - NK) * 64, SW64>(O, P[4*KK], P[4*KK+1], P[4*KK+2], P[4*KK+3], dv, accumulate);
  if constexpr (KK + 1 < NK) issue_pv<NK, KK + 1>(O, P, dv, 1);
}
template<int K0, int K1>
__device__ __forceinline__ void exp_pack(const float (&S)[64], uint32_t (&D)[32], float& s0, float& s1) {
  #pragma unroll
  for (int k = K0; k < K1; k++) {
    const float e0 = ex2(S[2*k]), e1 = ex2(S[2*k+1]);
    D[k] = pack_bf16(e0, e1);
    if (k & 1) s1 += e0 + e1; else s0 += e0 + e1;
  }
}
__device__ __forceinline__ int diag_limit() { const int t = wg_tid(); return 16 * (t >> 5) + ((t & 31) >> 2) - 2 * (t & 3); }
__device__ __forceinline__ void exp_pack_diag(const float (&S)[64], uint32_t (&D)[32], int t, float& s0, float& s1) {
  #pragma unroll
  for (int k = 0; k < 16; k++) {
    const int c = 8 * (k >> 1) - 8 * (k & 1);
    const float e0 = ex2((c <= t) ? S[2*k] : -INFINITY), e1 = ex2((c + 1 <= t) ? S[2*k+1] : -INFINITY);
    D[k] = pack_bf16(e0, e1);
    if (k & 1) s1 += e0 + e1; else s0 += e0 + e1;
  }
}
constexpr float SUM_HI = 1.8446744073709552e19f;
constexpr float SUM_LO = 5.421010862427522e-20f;

__device__ __forceinline__ void classic_tile(const float (&S)[64], uint32_t (&P)[32], bool fresh, bool half, bool was_classic, volatile float* mc,
                                             float& l0, float& l1, float& s0, float& s1, float& sc0, float& sc1) {
  const int tmask = diag_limit();
  float4 t[16];
  #pragma unroll
  for (int j = 0; j < 16; j++) t[j] = make_float4(S[4*j], S[4*j+1], S[4*j+2], S[4*j+3]);
  float mx0 = -INFINITY, mx1 = -INFINITY;
  #pragma unroll 1
  for (int j = 0; j < 16; j++) {
    float4 v = t[j];
    const int lim = !fresh ? 1000 : j < 8 ? tmask - 8 * j : half ? -1000 : 1000;
    v.x = 0 <= lim ? v.x : -INFINITY; v.y = 1 <= lim ? v.y : -INFINITY; v.z = -8 <= lim ? v.z : -INFINITY; v.w = -7 <= lim ? v.w : -INFINITY;
    t[j] = v;
    mx0 = fmaxf(mx0, fmaxf(v.x, v.y)); mx1 = fmaxf(mx1, fmaxf(v.z, v.w));
  }
  mx0 = fmaxf(mx0, __shfl_xor_sync(0xffffffff, mx0, 1));
  mx1 = fmaxf(mx1, __shfl_xor_sync(0xffffffff, mx1, 1));
  mx0 = fmaxf(mx0, __shfl_xor_sync(0xffffffff, mx0, 2));
  mx1 = fmaxf(mx1, __shfl_xor_sync(0xffffffff, mx1, 2));
  const float mc0 = was_classic ? mc[0] : 0.f, mc1 = was_classic ? mc[1] : 0.f;
  const float n0 = fresh ? -mx0 : fminf(mc0, -mx0), n1 = fresh ? -mx1 : fminf(mc1, -mx1);
  sc0 = ex2(n0 - mc0); sc1 = ex2(n1 - mc1);
  mc[0] = n0; mc[1] = n1;
  s0 = 0.f; s1 = 0.f;
  #pragma unroll 1
  for (int j = 0; j < 16; j++) {
    const float4 v = t[j];
    const float e0 = ex2(v.x + n0), e1 = ex2(v.y + n0), e2 = ex2(v.z + n1), e3 = ex2(v.w + n1);
    s0 += e0 + e1; s1 += e2 + e3;
    reinterpret_cast<uint2*>(t)[j] = make_uint2(pack_bf16(e0, e1), pack_bf16(e2, e3));
  }
  #pragma unroll
  for (int j = 0; j < 8; j++) { P[4*j] = __float_as_uint(t[j].x); P[4*j+1] = __float_as_uint(t[j].y); P[4*j+2] = __float_as_uint(t[j].z); P[4*j+3] = __float_as_uint(t[j].w); }
  if (!fresh) { l0 *= sc0; l1 *= sc1; }
}
__device__ __forceinline__ void pack_tile(const float (&A)[64], uint32_t (&D)[32], float f0, float f1) {
  #pragma unroll
  for (int j = 0; j < 16; j++) {
    D[8 * (j >> 2) + (j & 3)] = pack_bf16(A[4*j] * f0, A[4*j+1] * f0);
    D[8 * (j >> 2) + 4 + (j & 3)] = pack_bf16(A[4*j+2] * f1, A[4*j+3] * f1);
  }
}
__device__ __forceinline__ int piece0(int t) { return ((t >> 5) * 16 + ((t & 31) >> 2)) * 32 + (((t ^ (t >> 3)) & 3) << 3); }
__device__ __forceinline__ void store_tile(__nv_bfloat16* p, const uint32_t (&D)[32]) {
  #pragma unroll
  for (int i = 0; i < 8; i++) stg_v4(p + (i >> 2) * (SEQ * 64) + ((i >> 1) & 1) * 4096 + (i & 1) * 256, D[4*i], D[4*i+1], D[4*i+2], D[4*i+3]);
}

enum : int { PV_ACC = 0, PV_ZERO = 1, PV_HALF = 2, PV_NONE = 3 };
struct Att {
  float l0, l1, i0, i1;
  bool classic;
  volatile float* mc;
};
__device__ __forceinline__ void store_ctx(Ctx& x, int code, const uint32_t (&D)[32]) {
  store_tile(x.sched->kvc + ((size_t)(128 + (code >> 5) * 2) * SEQ + ((code >> 1) & 15) * 128) * 64 + (code & 1) * 2048 + piece0(wg_tid()), D);
  publish(x, C_CTX + (code >> 2));
}
__device__ __forceinline__ __nv_bfloat16* kv_tile(const Ctx& x, int code) {
  return x.sched->kvc + ((size_t)(x.w * 64 + (code >> 4) * 2) * SEQ + (code & 15) * 128) * 64 + piece0(wg_tid());
}
#define V_AT 3
#define V_AT2 7
#define MERGE1 1
#define NO_CLASSIC 0
__device__ __forceinline__ void q_proj(Ctx& x, int& e, bool isY, const uint32_t (&PA)[32], const uint32_t (&PB)[32], int vtile, bool dbg = false) {
  float S[64];
  bar_sync(1 + x.w, 256);
  if (isY) bar_arrive(1 + (x.w ^ 1), 256);
  if (dbg) DBG(80);
  TR(1);
  #pragma unroll 1
  for (int kb = 0; kb < 8; kb++) {
    ring_wait_full(x.bars, e);
    if (dbg) DBG(81 + kb);
    TR(2);
    const uint32_t da = desc_lo(x.base + x.w * 8192, 16) + ring_slot(e) * 2048, dw = desc_lo(x.base + 16384, 8192) + ring_slot(e) * 2048;
    wgmma_fence();
    kblock_n128<0>(S, da, dw, kb != 0);
    wgmma_commit();
    if (kb == 7 && !isY) bar_arrive(1 + (x.w ^ 1), 256);
    if (kb > 0) { wgmma_wait<1>(); ring_release(x, ring_add(e, 11), false); }
    if (kb == V_AT && vtile >= 0) store_tile(kv_tile(x, vtile) + 2048, PA);
    if (kb == V_AT2 && vtile >= 0) { store_tile(kv_tile(x, vtile), PB); publish(x, C_KV + (vtile >> 4)); }
    e = ring_add(e, 1);
  }
  wgmma_wait<0>();
  fence_regs(S);
  if (dbg) DBG(89);
  TR(3);
  ring_release(x, ring_add(e, 11), false);
  const uint32_t qa = x.base + SM_Q + x.w * 4096 + piece0(wg_tid()) * 2;
  #pragma unroll
  for (int i = 0; i < 8; i++) {
    const int j = 4 * (i >> 1), o = 2 * (i & 1);
    sts_v4(qa + (i >> 1) * 8192 + (i & 1) * 512,
           pack_bf16(S[4*j+o], S[4*j+o+1]), pack_bf16(S[4*j+4+o], S[4*j+5+o]), pack_bf16(S[4*j+8+o], S[4*j+9+o]), pack_bf16(S[4*j+12+o], S[4*j+13+o]));
  }
  fence_async_smem();
  if (dbg) DBG(90);
  TR(4);
  ring_wait_full(x.bars, ring_add(e, isY ? 0 : 2));
  ring_wait_full(x.bars, ring_add(e, 1));
}

template<int KIND>
__device__ __forceinline__ void slot(Ctx& x, Att& a, int& e, float (&O)[64], uint32_t (&Pn)[32], uint32_t (&Po)[32],
                                     bool more, bool isY, bool half, int pv, int pend) {
  float S[64];
  const int w = x.w;
  const bool skip = KIND == 0 && !isY;
  const int en = ring_add(e, skip ? 4 : 2), sn = ring_slot(en), sv = ring_slot(e) + 1, sk = skip ? ring_slot(ring_add(e, 2)) : sv - 1;
  const uint32_t dq = desc_lo(x.base + SM_Q + w * 4096, 16), dk = desc_lo(x.base, 16) + sk * 2048, dv = desc_lo(x.base, 8192) + sv * 2048;
  bar_sync(1 + w, 256);
  TR(5 + KIND);
  if (KIND == 2) {
    wgmma_fence();
    issue_qk(S, dq, dk); wgmma_commit();
    issue_pv<8>(O, Po, dv, 1); wgmma_commit();
    bar_arrive(1 + (w ^ 1), 256);
    wgmma_wait<1>();
  } else if (KIND == 0 && half) {
    float T[32];
    wgmma_fence(); issue_qk_half(T, dq, dk); wgmma_commit();
    a.i0 = rcp_fast(quad_sum(a.l0)); a.i1 = rcp_fast(quad_sum(a.l1));
    if (pv == PV_NONE) { wgmma_fence(); wgmma_commit(); }
    else               { wgmma_fence(); issue_pv<8>(O, Po, dv, pv == PV_ACC); wgmma_commit(); }
    bar_arrive(1 + (w ^ 1), 256);
    wgmma_wait<1>();
    fence_regs(T);
    #pragma unroll
    for (int i = 0; i < 32; i++) { S[i] = T[i]; asm volatile("" : "=f"(S[32 + i])); }
  } else {
    wgmma_fence(); issue_qk(S, dq, dk); wgmma_commit();
    if (KIND == 1 && pend >= 0) { bar_arrive(1 + (w ^ 1), 256); pack_tile(O, Pn, a.i0, a.i1); store_ctx(x, pend, Pn); TR(8); }
    if (KIND == 0) { a.i0 = rcp_fast(quad_sum(a.l0)); a.i1 = rcp_fast(quad_sum(a.l1)); }
    if (KIND == 0 && pv == PV_NONE) { wgmma_fence(); wgmma_commit(); }
    else if (pv == PV_HALF)         { wgmma_fence(); issue_pv<4>(O, Po, dv, 0); wgmma_commit(); }
    else                            { wgmma_fence(); issue_pv<8>(O, Po, dv, pv == PV_ACC); wgmma_commit(); }
    if (KIND == 0 || pend < 0) bar_arrive(1 + (w ^ 1), 256);
    wgmma_wait<1>();
  }
  fence_regs(S);
  fence_regs_u(Pn);
  TR(9);
  slot_release(x, sk, KIND == 0 && isY);
  float s0 = 0.f, s1 = 0.f;
  const bool was_classic = KIND != 0 && a.classic;
  if (KIND == 0) {
    a.l0 = 0.f; a.l1 = 0.f;
    if (!half) exp_pack<16, 32>(S, Pn, s0, s1);
    else {
      #pragma unroll
      for (int i = 16; i < 32; i++) asm volatile("" : "=r"(Pn[i]));
    }
    exp_pack_diag(S, Pn, diag_limit(), s0, s1);
    uint32_t b0 = __ballot_sync(0xffffffff, s0 >= SUM_LO), b1 = __ballot_sync(0xffffffff, s1 >= SUM_LO);
    b0 |= b0 >> 1; b0 |= b0 >> 2; b1 |= b1 >> 1; b1 |= b1 >> 2;
    a.classic = __any_sync(0xffffffff, !(s0 <= SUM_HI && s1 <= SUM_HI)) || (b0 & b1 & 0x11111111u) != 0x11111111u;
  } else {
    exp_pack<0, 32>(S, Pn, s0, s1);
    a.classic = __any_sync(0xffffffff, a.classic || !(s0 <= SUM_HI && s1 <= SUM_HI));
  }
  fence_regs_u(Pn);
  TR(10);
  mbar_wait(x.bars + B_RF + 8 * sn, en >= 6);
  if (more) mbar_wait(x.bars + B_RF + 8 * sn + 8, en >= 6);
  wgmma_wait<0>();
  fence_regs(O);
  fence_regs_u(Po);
  TR(11);
  slot_release(x, sv, KIND == 1 && isY && pv != PV_ACC);
  if (!NO_CLASSIC && __builtin_expect(a.classic, 0)) {
    float sc0, sc1;
    classic_tile(S, Pn, KIND == 0, half, was_classic, a.mc, a.l0, a.l1, s0, s1, sc0, sc1);
    if (KIND != 0) {
      #pragma unroll
      for (int j = 0; j < 16; j++) { O[4*j] *= sc0; O[4*j+1] *= sc0; O[4*j+2] *= sc1; O[4*j+3] *= sc1; }
    }
  }
  a.l0 += s0; a.l1 += s1;
  e = en;
}

__device__ __forceinline__ int attention(Ctx& x, const uint8_t* items, int nitems, int rank, uint32_t (&PA)[32], uint32_t (&PB)[32], int vtile) {
  int e = 0;
  float O[64];
  Att a;
  volatile float mc[2];
  a.l0 = 1.f; a.l1 = 1.f; a.i0 = 0.f; a.i1 = 0.f; a.classic = false; a.mc = mc;
  int pv = PV_NONE, cur = -1;
#define DBGS()
  #pragma unroll 1
  for (int it = 0; ; it++) {
    const bool isY = (it & 1) == x.w;
    int pend = cur;
    if (it < nitems) {
      const int item = items[it];
      const bool half = isY == (rank != 0);
      cur = item * 4 + (isY ? 3 - rank : rank);
      int rem = 2 * (item & 7) + (isY ? 1 : 0);
      DBG(16 + it);
      q_proj(x, e, isY, PA, PB, vtile);
      vtile = -1;
      DBGS();
      slot<0>(x, a, e, O, PA, PB, rem > 0, isY, half, pv, -1);
      pv = half ? PV_HALF : PV_ZERO;
      #pragma unroll 1
      while (rem > 0) {
        DBGS();
        slot<1>(x, a, e, O, PB, PA, rem > 1, isY, false, pv, pend);
        pv = PV_ACC; pend = -1;
        if (rem == 1) break;
        rem -= 2;
        DBGS();
        slot<2>(x, a, e, O, PA, PB, rem > 0, false, false, 0, -1);
      }
    } else {
      DBGS();
      slot_release(x, 6, false);
      const uint32_t dv = desc_lo(x.base, 8192) + ring_slot(e) * 2048;
      bar_sync(1 + x.w, 256);
      if (pv == PV_HALF) { wgmma_fence(); issue_pv<4>(O, PB, dv, 0); wgmma_commit(); }
      else { wgmma_fence(); issue_pv<8>(O, PB, dv, pv == PV_ACC); wgmma_commit(); }
      if (isY) bar_arrive(1 + (x.w ^ 1), 256);
      a.i0 = rcp_fast(quad_sum(a.l0)); a.i1 = rcp_fast(quad_sum(a.l1));
      ring_wait_full(x.bars, e);
      wgmma_wait<0>();
      fence_regs(O);
      fence_regs_u(PB);
      ring_release(x, e, false);
    }
    if (pend >= 0) pack_tile(O, PB, a.i0, a.i1);
    if (it == nitems) return pend;
    if (pend >= 0) store_ctx(x, pend, PB);
    if (!isY) {
      #pragma unroll
      for (int i = 0; i < 32; i++) asm volatile("mov.b32 %0, %1;" : "=r"(PB[i]) : "r"(PA[i]));
    }
  }
}

#define LN_AT 2
#define X_AT 6
#define PERT 0
#define CTX_T 3
#define PF_AT 5
#define PF_N 4
#define PF_MOE 3
constexpr float QSCALE = 0.08838834764831845f * 1.4426950408889634f;
__device__ __forceinline__ void mod_cta(Ctx& x, const __nv_bfloat16* cvec) {
  const int t = wg_tid(), ct = x.w * 128 + t;
  #pragma unroll 1
  for (int k = 0; k < 6; k++) slot_release(x, k, false);
  const uint32_t cv = __ldg(reinterpret_cast<const uint32_t*>(cvec) + ct);
  asm volatile("st.shared.u32 [%0], %1;" :: "r"(x.base + SM_H2 + ct * 4),
               "r"(pack_bf16(__fdividef(bf_lo(cv), 1.f + __expf(-bf_lo(cv))), __fdividef(bf_hi(cv), 1.f + __expf(-bf_hi(cv))))) : "memory");
  bar_sync(5, 256);
  float acc[64];
  int e = 0;
  #pragma unroll 1
  for (int g = 0; g < 24; g++) {
    uint32_t a[8];
    #pragma unroll
    for (int i = 0; i < 8; i++) a[i] = lds_u32(x.base + SM_H2 + (g & 7) * 128 + i * 16 + (t & 3) * 4);
    ring_wait_full(x.bars, e);
    const uint32_t db = desc_lo(x.base + x.w * 16384, 8192) + ring_slot(e) * 2048;
    wgmma_fence();
    wgmma_rs_n128<1, 0, SW128>(acc, a[0], a[0], a[1], a[1], db, g & 7);
    wgmma_rs_n128<1, 128, SW128>(acc, a[2], a[2], a[3], a[3], db, 1);
    wgmma_rs_n128<1, 256, SW128>(acc, a[4], a[4], a[5], a[5], db, 1);
    wgmma_rs_n128<1, 384, SW128>(acc, a[6], a[6], a[7], a[7], db, 1);
    wgmma_commit();
    wgmma_wait<0>();
    fence_regs(acc);
    ring_release(x, e, false);
    e = ring_add(e, 1);
    if ((g & 7) == 7) {
      if (t < 4) {
        const float sc = (g == 7 && blockIdx.x < NCTA + 2) ? QSCALE : 1.f;
        uint32_t* dst = reinterpret_cast<uint32_t*>(g_mod + (g >> 3) * 1024 + (blockIdx.x - NCTA) * 256 + x.w * 128) + t;
        #pragma unroll
        for (int j = 0; j < 16; j++) dst[4 * j] = pack_bf16(rbf(acc[4*j]) * sc, rbf(acc[4*j+1]) * sc);
      }
      publish(x, g == 7 ? C_MOD : C_MOD2);
      DBG(1 + (g >> 3));
    }
  }
}

__global__ void __cluster_dims__(2, 1, 1) __launch_bounds__(384, 1)
k_fused(const __grid_constant__ CUtensorMap tmC, const __grid_constant__ CUtensorMap tmH, const __grid_constant__ CUtensorMap tmWq,
        const __grid_constant__ CUtensorMap tmWk, const __grid_constant__ CUtensorMap tmWv,
        const __grid_constant__ CUtensorMap tmWo, const __grid_constant__ CUtensorMap tmPart, const __grid_constant__ CUtensorMap tmWg,
        const __grid_constant__ CUtensorMap tmWu, const __grid_constant__ CUtensorMap tmPl, const __grid_constant__ CUtensorMap tmWm,
        const __grid_constant__ Sched sched,
        const __nv_bfloat16* __restrict__ xin,
        const __nv_bfloat16* __restrict__ cvec, const __nv_bfloat16* __restrict__ w_o,
        const __nv_bfloat16* __restrict__ w_r, const __nv_bfloat16* __restrict__ w_gate, const __nv_bfloat16* __restrict__ w_up,
        const __nv_bfloat16* __restrict__ w_down, __nv_bfloat16* __restrict__ out) {
  extern __shared__ __align__(1024) uint8_t smem_raw[];
  const uint32_t base = smem_u32(smem_raw), bars = base + SM_BAR;
  const int warp = __shfl_sync(0xffffffff, threadIdx.x >> 5, 0), wg = warp >> 2;
  const int rank = cluster_ctarank(), p = blockIdx.x >> 1;
  const int mt = (p & 7) * 2 + rank;
  const bool spare = blockIdx.x >= NCTA;
  #pragma unroll
  for (int i = 0; i < PERT; i++) { uint32_t d; asm volatile("mov.u32 %0, %%laneid;" : "=r"(d)); }
  {
    const int h0 = KHEAD0 + (p >> 3);
    #pragma unroll 1
    for (int t = warp == 8 ? 0 : warp < 8 ? warp + 1 : warp; t < B_PUB / 8; t += (warp == 8 ? 64 : 11))
      w_mbar_init(bars + 8 * t, t < B_WE / 8 ? 1 : t < B_RE / 8 ? 2 : 4);
    fence_mbar_init();
    cluster_arrive();
    if (warp == 9) prefetch_tmap(&tmWk);
    if (wg == 2) bar_arrive(1, 256);
    if (warp == 8 && !spare) {
      #pragma unroll 1
      for (int kb = 0; kb < 8; kb++) {
        w_expect_tx(bars + B_AF + 8 * kb, 16384);
        tma_load_2d(base + k_addrA(kb), &tmC, bars + B_AF + 8 * kb, kb * 64, mt * 128);
        if (kb == 0) cluster_wait();
        if (kb < 6) {
          w_expect_tx(bars + B_WF + 8 * kb, 16384);
          tma_load_2d_mc(base + k_addrW(kb) + rank * 8192, &tmWk, bars + B_WF + 8 * kb, h0 * 128 + rank * 64, kb * 64);
        }
      }
    }
  }
  const Sched::Pair& sp = sched.pair[p];
  const int nitems = sp.nitems, nsteps = sp.nsteps;
  auto oent = [&](int k) -> uint32_t { return sp.oent[k]; };
  const int ot = sp.otask, m = (ot & 7) * 2 + rank, grp = m * 8 + (ot >> 3);

  if (wg == 0) {
    asm volatile("setmaxnreg.dec.sync.aligned.u32 24;");
    const int lane = threadIdx.x & 31;
    #pragma unroll 1
    for (int t = B_PUB / 8 + warp; t < 80; t += 4) w_mbar_init(bars + 8 * t, t < B_RDY / 8 ? 4 : 1);
    bar_sync(6, 128);
    bar_arrive(7, 256); bar_arrive(8, 256);
    cluster_wait();
    const unsigned int tag = ld_relaxed(&g_epoch) + 1;
    if (warp == 0) {
      if (!spare) {
        int s = 0, ph = 0;
        tma_prefetch_2d(&tmWv, sp.khead[0] * 128 + rank * 64, (p & 7) * 64);
        #pragma unroll 1
        for (int g = 6; g < 64; g++) {
          const int u = g >> 3, kb = g & 7;
          if (kb == 0 && u < 7) tma_prefetch_2d((u & 1) ? &tmWk : &tmWv, sp.khead[(u + 1) >> 1] * 128 + rank * 64, (p & 7) * 64);
          mbar_wait(bars + B_WE + 8 * s, ph);
          w_expect_tx(bars + B_WF + 8 * s, 16384);
          tma_load_2d_mc(base + k_addrW(s) + rank * 8192, (u & 1) ? &tmWv : &tmWk, bars + B_WF + 8 * s, sp.khead[u >> 1] * 128 + rank * 64, kb * 64);
          if (++s == 6) { s = 0; ph ^= 1; }
        }
      }
      int s = 0, ph = 0;
      auto next_entry = [&](int bytes) {
        mbar_wait(bars + B_RE + 8 * s, ph);
        w_expect_tx(bars + B_RF + 8 * s, bytes);
      };
      auto advance = [&]() { if (++s == 6) { s = 0; ph ^= 1; } };
      if (spare) {
        #pragma unroll 1
        for (int g = 0; g < 24; g++) {
          if (g == 8) mbar_wait(bars + R_MOD, 0);
          next_entry(32768);
          for (int k = 0; k < 2; k++) tma_load_3d(base + s * 32768 + k * 16384, &tmWm, bars + B_RF + 8 * s, 0, (g & 7) * 64, (g >> 3) * 16 + (blockIdx.x - NCTA) * 4 + k * 2);
          advance();
        }
      }
      mbar_wait(bars + R_H1, 0);
      fence_async_global();
      int vrow = -1;
      #pragma unroll 1
      for (int i = 0; i <= nitems; i++) {
        const int item = sp.item[i & (MAX_ITEMS - 1)], h = item >> 3, j = item & 7;
        if (i < nitems) {
          const int row0 = j * 256 + ((i & 1) ? rank : 3 - rank) * 64, row1 = j * 256 + ((i & 1) ? 3 - rank : rank) * 64;
          #pragma unroll 1
          for (int kb = 0; kb < 8; kb++) {
            next_entry(32768);
            tma_load_2d_mc(base + s * 32768 + 16384 + rank * 8192, &tmWq, bars + B_RF + 8 * s, h * 128 + rank * 64, kb * 64);
            tma_load_2d(base + s * 32768, &tmH, bars + B_RF + 8 * s, kb * 64, row0);
            tma_load_2d(base + s * 32768 + 8192, &tmH, bars + B_RF + 8 * s, kb * 64, row1);
            advance();
          }
          mbar_wait(bars + R_ITEM + 8 * i, 0);
          fence_async_global();
        }
        #pragma unroll 1
        for (int n = i < nitems ? 4 * j + 3 : 0; n >= 0; n--) {
          const int krow = (h * 2 + rank) * SEQ + (n >> 1) * 128 + ((sp.lastuse[i & (MAX_ITEMS - 1)] >> (n >> 1)) & 1);
          const int row = (n & 1) ? krow : vrow;
          if (i + 1 == nitems && n == min(4 * j + 3, 2 * PF_AT + 1)) w_arrive(bars + R_NEAR);
          next_entry(row >= 0 ? 32768 : 0);
          if (row >= 0) bulk_load_mc(base + s * 32768 + rank * 16384, sched.kvc + (size_t)(row & ~1) * 64, bars + B_RF + 8 * s, row & 1);
          advance();
          if (!(n & 1)) vrow = krow + 64 * SEQ;
        }
      }
      if (!spare) {
      const int oc = ((ot >> 3) & 1) * 4 + rank * 2;
      auto o_next = [&](int k, int bytes) {
        const uint32_t v = oent(k); s = v & 7;
        mbar_wait(bars + B_RE + 8 * s, v >> 3);
        w_expect_tx(bars + B_RF + 8 * s, bytes);
      };
      #pragma unroll 1
      for (int i = 0; i < nsteps; i++) {
        const int c0 = sp.ochunk[i][0], c1 = sp.ochunk[i][1];
        if (i >= PF_MOE && i < PF_MOE + 3)
          bulk_prefetch((i == PF_MOE ? w_gate : i == PF_MOE + 1 ? w_up : w_down) + (size_t)blockIdx.x * (DM * FF / NCTA), DM * FF / NCTA * 2);
        if (c0 < 64) { o_next(3 * i, 32768); tma_load_3d_mc(base + s * 32768 + rank * 16384, &tmWo, bars + B_RF + 8 * s, 0, c0 * 64, oc); }
        mbar_wait(bars + R_CTX + 8 * i, 0);
        fence_async_global();
        o_next(3 * i + 1, c0 < 64 ? 32768 : 16384);
        if (c0 < 64) bulk_load(base + s * 32768, sched.kvc + (size_t)((128 + c0) * SEQ + m * 128) * 64, 16384, bars + B_RF + 8 * s);
        bulk_load(base + s * 32768 + 16384, sched.kvc + (size_t)((128 + c1) * SEQ + m * 128) * 64, 16384, bars + B_RF + 8 * s);
        o_next(3 * i + 2, 32768);
        tma_load_3d_mc(base + s * 32768 + rank * 16384, &tmWo, bars + B_RF + 8 * s, 0, c1 * 64, oc);
      }
      const int f0 = (blockIdx.x < FF / 16 ? blockIdx.x : 0) * 16;
      o_next(3 * nsteps, 32768);
      bulk_load(base + s * 32768, w_down + (size_t)f0 * DM, 16384, bars + B_RF + 8 * s);
      bulk_load(base + s * 32768 + 16384, xin + (size_t)grp * 16 * DM, 16384, bars + B_RF + 8 * s);
      o_next(3 * nsteps + 1, 32768);
      #pragma unroll 1
      for (int k = 0; k < 4; k++) tma_load_2d(base + s * 32768 + k * 8192, (k & 2) ? &tmWu : &tmWg, bars + B_RF + 8 * s, f0, (k & 1) * 256);
      #pragma unroll 1
      for (int k = 0; k < 4; k++) w_expect_tx(bars + R_PART + 8 * k, 16384);
      mbar_wait(bars + B_PUB + 8 * (5 + nitems + 1), 0);
      mbar_wait(bars + B_PUB + 8 * (NPUB + 5 + nitems + 1), 0);
      uint32_t todo = 0xff;
      #pragma unroll 1
      for (int n = 0; n < WAIT_LIM && todo; n++) {
        uint32_t now = __ballot_sync(0xffffffff, ld_acquire(&g_pflag[m * 2 + (ot >> 5)][lane & 7]) == tag) & todo;
        todo &= ~now;
        fence_async_global();
        #pragma unroll 1
        for (; now; now &= now - 1) {
          const int q = __ffs(now) - 1;
          tma_load_3d(base + (oent(3 * nsteps - 3 + (q >> 2)) & 7) * 32768 + (q & 3) * 8192, &tmPl, bars + R_PART + 8 * (q >> 1), 0, grp * 16, q * 4);
        }
      }
      DBGP(11);
      }
    } else if (warp < 3) {
      const int w = warp - 1, n1 = w * NPUB + (spare ? 3 : 5) + nitems;
      #pragma unroll 1
      for (int n = w * NPUB; n < n1 + (spare ? 0 : 2); n++) {
        #pragma unroll 1
        for (int k = 0; k < 8 * WAIT_LIM; k++) { if (mbar_try(bars + B_PUB + 8 * n, 0)) break; }
        const uint32_t msg = lds_u32(base + SM_MAIL + 4 * n);
        if (n < n1) {
          fence_async_global();
          if (lane == 0 && msg < (unsigned)C_END) red_release(msg);
        } else {
          if (lane == 0) { tma_store_3d(&tmPart, base + (msg & 0x3c000), 0, m * 128 + 64 * w, (ot >> 3) * 4 + 2 * (n - n1)); bulk_commit(); }
        }
        __syncwarp();
      }
      bulk_wait<0>();
      fence_async_global();
      if (lane == 0 && !spare) st_release(&g_pflag[m * 2 + w][ot >> 3], tag);
      __syncwarp();
    } else {
      if (!spare) { mbar_wait(bars + B_AF + 8 * X_AT, 0); bulk_prefetch(xin + (size_t)blockIdx.x * 16 * DM, 16 * DM * 2); }
      #pragma unroll 1
      for (int n = 0; n < 8 + nsteps; n++) {
        if (n == 2 + nitems) n = 7;
        int idx = n == 0 ? C_MOD : n == 1 ? C_H1 : C_MOD2, cnt = n == 0 ? 8 : n == 1 ? 256 : 16;
        if (n >= 1 && n <= nitems) { const int item = sp.item[n - 1]; tma_prefetch_2d(&tmWq, (item >> 3) * 128 + rank * 64, (item & 7) * 64); }
        if (n >= 2 && n < 7) { idx = C_KV + (sp.item[n - 2] >> 3); cnt = 32; }
        if (n >= 8) { const int c0 = sp.ochunk[n - 8][0], c1 = sp.ochunk[n - 8][1]; idx = C_CTX + (((lane & 1) && c0 < 64 ? c0 : c1) >> 1) * 8 + (ot & 7); cnt = 4; }
        wait_count_lazy(idx, cnt * tag);
        w_arrive(bars + B_RDY + 8 * n);
        if (n == 0) DBGP(12);
        if (n == 8 + PF_N - 1) {
          #pragma unroll 1
          for (int k = 0; k < 8 * WAIT_LIM; k++) { if (mbar_try(bars + R_NEAR, 0)) break; }
          bulk_prefetch(w_o + (size_t)blockIdx.x * (NH * DH * DM / NCTA), NH * DH * DM / NCTA * 2);
          #pragma unroll 1
          for (int k = 0; k < PF_N; k++) {
            const int cc = sp.ochunk[k][(ot >> 3) & 1];
            if (cc < 64) bulk_prefetch(sched.kvc + ((size_t)(128 + cc) * SEQ + m * 128) * 64, 16384);
          }
        }
      }
    }
    __syncwarp();
    cluster_arrive();
    if (!spare) {
      bar_sync(6, 128);
      asm volatile("setmaxnreg.inc.sync.aligned.u32 88;");
      const int pos = blockIdx.x * 4 + (lane & 1) * 2, col = (blockIdx.x >> 2) * 16 + (blockIdx.x & 3) * 2 + (lane & 1) * 8, src = threadIdx.x >> 1;
      uint32_t gbest = 0, hh = 0, gbf = 0;
      uint2 xx = make_uint2(0, 0);
      uint4 ya = make_uint4(0, 0, 0, 0), yb = make_uint4(0, tag, 0, tag);
      auto poll_y = [&]() {
        if (ya.y != tag || ya.w != tag) ya = ld_tagged2(&g_yll[src][pos]);
        if (yb.y != tag || yb.w != tag) yb = ld_tagged2(&g_yll[src + 64][pos]);
        return __all_sync(0xffffffff, ya.y == tag && ya.w == tag && yb.y == tag && yb.w == tag);
      };
      ya.y = tag - 1; if (src + 64 < FF / 16) yb.y = tag - 1;
      poll_y();
      if (warp == 3) {
        gbf = __ldcg(reinterpret_cast<const uint32_t*>(g_mod + 5 * DM + col));
        uint32_t have = 0;
        uint2 k[4];
        #pragma unroll
        for (int i = 0; i < 4; i++) k[i] = make_uint2(0, tag - 1);
        #pragma unroll 1
        for (int n = 0; n < WAIT_LIM; n++) {
          #pragma unroll
          for (int i = 0; i < 4; i++) if (k[i].y != tag) k[i] = ld_tagged(&g_keys[i * 32 + lane][0]);
          if (gbest != have) {
            const int g = ((0xffffu - gbest) >> 4) & 127;
            uint4 hv[4];
            #pragma unroll
            for (int i = 0; i < 4; i++) hv[i] = ld_tagged2(&g_row[g][0][i * 64 + lane * 2]);
            xx = ld_tagged(&g_row[g][1][col >> 1]);
            bool ok = xx.y == tag;
            #pragma unroll
            for (int i = 0; i < 4; i++) { ok = ok && hv[i].y == tag && hv[i].w == tag; reinterpret_cast<uint2*>(smem_raw + SM_H2)[i * 32 + lane] = make_uint2(hv[i].x, hv[i].z); }
            if (lane == 0) *reinterpret_cast<uint32_t*>(smem_raw + SM_KEY + 32) = gbest;
            have = __all_sync(0xffffffff, ok) ? gbest : 0;
          }
          bool all = true;
          #pragma unroll
          for (int i = 0; i < 4; i++) { all = all && k[i].y == tag; gbest = max(gbest, k[i].y == tag ? k[i].x : 0u); }
          gbest = __reduce_max_sync(0xffffffff, gbest);
          if (__all_sync(0xffffffff, all) && gbest == have) break;
        }
        w_arrive(bars + R_KEY);
        if (blockIdx.x == 0 && lane == 0) g_epoch = tag;
        hh = lds_u32(base + SM_H2 + col * 2);
        DBGP(13);
      }
      const uint32_t sb16 = gbest & 0xffff0000u;
      const float rsel = __uint_as_float((sb16 & 0x80000000u) ? (sb16 & 0x7fffffffu) : (~sb16 & 0xffff0000u));
      const float rs = rbf(__fdividef(1.f, 1.f + __expf(-rsel)));
      mbar_wait(bars + R_KEY, 1);
      #pragma unroll 1
      for (int n = 0; n < WAIT_LIM; n++) { if (poll_y()) break; }
      float y0 = __uint_as_float(ya.x) + __uint_as_float(yb.x), y1 = __uint_as_float(ya.z) + __uint_as_float(yb.z);
      #pragma unroll
      for (int o = 2; o < 32; o <<= 1) { y0 += __shfl_xor_sync(0xffffffff, y0, o); y1 += __shfl_xor_sync(0xffffffff, y1, o); }
      float2* s_y = reinterpret_cast<float2*>(smem_raw + SM_KEY + 64);
      if (lane < 2) s_y[warp * 2 + lane] = make_float2(y0, y1);
      bar_sync(6, 128);
      if (warp == 3 && lane < 2) {
        y0 = 0.f; y1 = 0.f;
        #pragma unroll
        for (int i = 0; i < 4; i++) { y0 += reinterpret_cast<const float*>(s_y)[i * 4 + lane]; y1 += reinterpret_cast<const float*>(s_y)[i * 4 + 2 + lane]; }
        const float o0 = bf_lo(xx.x) + rbf(bf_lo(gbf) * rbf(bf_lo(hh) + rbf(rbf(y0) * rs)));
        const float o1 = bf_hi(xx.x) + rbf(bf_hi(gbf) * rbf(bf_hi(hh) + rbf(rbf(y1) * rs)));
        *reinterpret_cast<uint32_t*>(out + (size_t)((0xffffu - gbest) & (SEQ - 1)) * DM + col) = pack_bf16(o0, o1);
      }
      DBGP(14);
    }
    __syncwarp();
    cluster_wait();
  } else {
    asm volatile("setmaxnreg.inc.sync.aligned.u32 240;");
    Ctx x;
    x.w = wg - 1; x.base = base; x.bars = bars; x.nev = 0; x.sched = &sched;
    const int w = x.w, warp4 = warp & 3;
    x.rel = mapa(bars, (warp4 & 1) ^ 1);
    x.rel1 = (threadIdx.x & 127) == 32 || (threadIdx.x & 127) == 64;
    if (warp != 8 || spare) cluster_wait();
    if (w == 1 || spare) bar_sync(7 + w, 256);
    DBG(1);
    uint32_t PA[32], PB[32];
    int vtile = -1;
    if (spare) {
      mod_cta(x, cvec);
    } else {
      const int lane = wg_tid() & 31;
      Row xn[2];
      float acc0[64], acc1[64];
      int s = 2 * w, ph = w;
      #pragma unroll 1
      for (int u = w; u < 8; u += 2) {
        bar_sync(1 + w, 256);
        DBG(4 + (u >> 1) * 3);
        int ps = 0;
        #pragma unroll 1
        for (int kb = 0; kb < 8; kb++) {
          if (u < 2) mbar_wait(bars + B_AF + 8 * kb, 0);
          mbar_wait(bars + B_WF + 8 * s, ph);
          const uint32_t da = desc_lo(base + k_addrA(kb), 16), dw = desc_lo(base + k_addrW(s), 8192);
          wgmma_fence();
          kblock_n128<0>(acc0, da, dw, kb != 0);
          kblock_n128<512>(acc1, da, dw, kb != 0);
          wgmma_commit();
          if (kb == 7) bar_arrive(1 + (w ^ 1), 256);
          if (kb > 0) {
            wgmma_wait<1>();
            mbar_arrive_remote_if(x.rel + B_WE + 8 * ps, x.rel1);
            if (u == 7 && !(kb & 1)) {
              ring_release(x, kb == 2 ? 0 : kb - 3, false);
              if (kb > 2) ring_release(x, kb - 2, false);
            }
          }
          ps = s;
          if (++s == 6) { s = 0; ph ^= 1; }
        }
        Row t[2];
        const int lrow = blockIdx.x * 16 + w * 8 + warp4 * 2;
        if (u == w) { t[0] = ldg_row(xin + (size_t)lrow * DM, lane); t[1] = ldg_row(xin + (size_t)(lrow + 1) * DM, lane); }
        if (u == LN_AT || u == LN_AT + 1) {
          mbar_wait(bars + R_MOD, 0);
          t[0] = ldca_row(g_mod, lane); t[1] = ldca_row(g_mod + DM, lane);
        }
        wgmma_wait<0>();
        fence_regs(acc0); fence_regs(acc1);
        DBG(5 + (u >> 1) * 3);
        mbar_arrive_remote_if(x.rel + B_WE + 8 * ps, x.rel1);
        if (u == 6) { for (int k = 0; k < 5; k++) ring_release(x, k, false); }
        if (u >= 6) ring_release(x, 5, false);
        if (V_AT >= 0 && u == 7) {
          pack_tile(acc0, PA, 1.f, 1.f); pack_tile(acc1, PB, 1.f, 1.f);
          vtile = sp.khead[3] * 16 + mt;
          break;
        }
        s += 2; ph ^= 1; if (s >= 6) { s -= 6; ph ^= 1; }
        if (u == 0) bar_sync(7, 256);
        if (u == w) {
          float st[4] = {0.f, 0.f, 0.f, 0.f};
          #pragma unroll
          for (int i = 0; i < 32; i++) { const float v = row_at(t[i >> 4], i & 15); st[(i >> 4) * 2] += v; st[(i >> 4) * 2 + 1] = fmaf(v, v, st[(i >> 4) * 2 + 1]); }
          warp_sums(st);
          #pragma unroll
          for (int r = 0; r < 2; r++) { ln_stats(st[2*r], st[2*r+1]); xn[r] = ln_apply(t[r], st[2*r], st[2*r+1] * QSCALE); }
        }
        if ((u == LN_AT || u == LN_AT + 1)) {
          #pragma unroll
          for (int r = 0; r < 2; r++) store_row(sched.h1 + (size_t)(lrow + r) * DM, lane, fma_row(xn[r], one_plus(t[1]), t[0]));
        }
        const int tile = sp.khead[u >> 1] * 16 + mt;
        __nv_bfloat16* dst = kv_tile(x, tile);
        uint32_t D[32];
        pack_tile(acc0, D, 1.f, 1.f); store_tile(dst + 2048, D);
        pack_tile(acc1, D, 1.f, 1.f); store_tile(dst, D);
        if (u == LN_AT || u == LN_AT + 1) publish(x, C_H1);
        publish(x, C_KV + (tile >> 4));
        DBG(6 + (u >> 1) * 3);
      }
    }
    x.tr = base + SM_RED + w * 1024;
    const int last = attention(x, sp.item, nitems, rank, PA, PB, vtile);
    DBG(100);
    const int lane = wg_tid() & 31, cw = w * 4 + warp4, ct = cw * 32 + lane;
    const int row0 = grp * 16 + cw * 2;
    const bool moe_cta = blockIdx.x < FF / 16;
    const unsigned int tag = ld_relaxed(&g_epoch) + 1;
    if (spare) { store_ctx(x, last, PB); __syncwarp(); cluster_arrive(); cluster_wait(); return; }
    const int kl = 3 * nsteps - 3;
    {
      float accA[64], accB[64];
      const int t0 = oent(0) == oent(1);
      uint32_t pa = 0, pb = 0;
      #pragma unroll 1
      for (int t = t0; t < 2 * nsteps - 2; t++) {
        const uint32_t eb = oent(3 * (t >> 1) + 2 * (t & 1)), ea = oent(3 * (t >> 1) + 1);
        o_wait_full(bars, eb);
        o_wait_full(bars, ea);
        const uint32_t da = desc_lo(base + w * 4096, 16) + (ea & 7) * 2048 + (t & 1) * 1024, db = desc_lo(base, 8192) + (eb & 7) * 2048;
        wgmma_fence();
        kblock_n128<0, 0, SW64>(accA, da, db, t != t0); kblock_n128<0, 1024, SW64>(accB, da, db, t != t0);
        wgmma_commit();
        if (t == CTX_T) store_ctx(x, last, PB);
        if (t > t0) { wgmma_wait<1>(); slot_release(x, pb, false); if (!(t & 1)) slot_release(x, pa, false); }
        pa = ea & 7; pb = eb & 7;
      }
      const uint32_t e0 = oent(kl), ea = oent(kl + 1), eb = oent(kl + 2);
      const uint32_t da = desc_lo(base + w * 4096, 16) + (ea & 7) * 2048;
      const uint32_t db0 = desc_lo(base, 8192) + (e0 & 7) * 2048, db1 = desc_lo(base, 8192) + (eb & 7) * 2048;
      o_wait_full(bars, e0);
      o_wait_full(bars, ea);
      o_wait_full(bars, eb);
      wgmma_fence();
      kblock_n128<0, 0, SW64>(accA, da, db0, 1); kblock_n128<1024, 0, SW64>(accA, da, db1, 1);
      wgmma_commit();
      kblock_n128<0, 1024, SW64>(accB, da, db0, 1); kblock_n128<1024, 1024, SW64>(accB, da, db1, 1);
      wgmma_commit();
      wgmma_wait<2>();
      slot_release(x, pa, false); slot_release(x, pb, false);
      __syncwarp();
      cluster_arrive();
      const int srow = 16 * warp4 + (lane & 7) + 8 * ((lane >> 3) & 1);
      const uint32_t swz = (((lane >> 4) ^ (srow & 7)) << 4);
      auto stage = [&](const float (&acc)[64], uint32_t off) {
        #pragma unroll
        for (int j = 0; j < 16; j += 2)
          stsm_x4(base + off + srow * 128 + (j >> 3) * 8192 + (((j & 7) << 4) ^ swz),
                  pack_bf16(acc[4*j+0], acc[4*j+1]), pack_bf16(acc[4*j+2], acc[4*j+3]), pack_bf16(acc[4*j+4], acc[4*j+5]), pack_bf16(acc[4*j+6], acc[4*j+7]));
        fence_async_smem();
        publish(x, off);
      };
      mbar_wait(bars + B_RE + 8 * pa, oent(kl + 5) >> 3);
      wgmma_wait<1>();
      fence_regs(accA);
      stage(accA, pa * 32768 + w * 16384);
      mbar_wait(bars + B_RE + 8 * pb, oent(kl + 6) >> 3);
      wgmma_wait<0>();
      fence_regs(accB);
      DBG(101);
      stage(accB, pb * 32768 + w * 16384);
      DBG(102);
    }
    asm volatile("setmaxnreg.dec.sync.aligned.u32 208;");
    const Row ga = ldca_row(g_mod + 2 * DM, lane), sb = ldca_row(g_mod + 3 * DM, lane), cb = ldca_row(g_mod + 4 * DM, lane), gb = ldca_row(g_mod + 5 * DM, lane);
    const Row wr = ldca_row(w_r, lane);
    const uint32_t sD = base + (oent(kl + 3) & 7) * 32768, sW = base + (oent(kl + 4) & 7) * 32768;
    o_wait_full(bars, oent(kl + 3)); o_wait_full(bars, oent(kl + 4));
    Row x1[2];
    #pragma unroll
    for (int r = 0; r < 2; r++) x1[r] = lds_row(sD + 16384 + (cw * 2 + r) * 1024, lane);
    uint4 wgv[4], wuv[4], wdv[4];
    #pragma unroll
    for (int r = 0; r < 4; r++) {
      const uint32_t k = (lane & 7) + ((lane >> 4) << 3), h = (lane & 8) * 2;
      wgv[r] = ldsm_x4_t(sW + (cw * 64 + r * 16 + k) * 32 + h);
      wuv[r] = ldsm_x4_t(sW + 16384 + (cw * 64 + r * 16 + k) * 32 + h);
      wdv[r] = ldsm_x4_t(sD + k * 1024 + (cw * 64 + r * 16) * 2 + h);
    }
    const Row cb1 = one_plus(cb);
    DBG(103);
    float u[16], ub[2] = {0.f, 0.f};
    #pragma unroll
    for (int i = 0; i < 16; i++) { u[i] = row_at(cb1, i) * row_at(wr, i); ub[0] += u[i]; ub[1] = fmaf(row_at(sb, i), row_at(wr, i), ub[1]); }
    warp_sums(ub);
    float st[6] = {0.f, 0.f, 0.f, 0.f, 0.f, 0.f};
    uint32_t key[2];
    {
      const uint32_t po = base + (lane >> 3) * 2048 + cw * 256 + (lane & 7) * 16;
      Row av[2][2];
      #pragma unroll
      for (int k = 0; k < 4; k++) {
        mbar_wait(bars + R_PART + 8 * k, 1);
        const uint32_t pa = po + (oent(kl + (k >> 1)) & 7) * 32768 + (k & 1) * 16384;
        #pragma unroll
        for (int r = 0; r < 2; r++) {
          const uint4 lo = lds_v4(pa + r * 128), hi = lds_v4(pa + 8192 + r * 128);
          const Row v{{lo.x, lo.y, lo.z, lo.w, hi.x, hi.y, hi.z, hi.w}};
          av[r][k >> 1] = (k & 1) ? add_row(av[r][k >> 1], v) : v;
        }
      }
      DBG(104);
      #pragma unroll
      for (int r = 0; r < 2; r++) {
        x1[r] = fma_row(ga, add_row(av[r][0], av[r][1]), x1[r]);
        #pragma unroll
        for (int i = 0; i < 16; i++) { const float v = row_at(x1[r], i); st[3*r] += v; st[3*r+1] = fmaf(v, v, st[3*r+1]); st[3*r+2] = fmaf(v, u[i], st[3*r+2]); }
      }
      warp_sums(st);
      #pragma unroll
      for (int r = 0; r < 2; r++) {
        ln_stats(st[3*r], st[3*r+1]);
        const uint32_t rb = pack_bf16(0.f, fmaf(st[3*r+1], fmaf(-st[3*r], ub[0], st[3*r+2]), ub[1]));
        key[r] = (((rb & 0x80000000u) ? ~rb : (rb | 0x80000000u)) & 0xffff0000u) | (0xffffu - (uint32_t)(row0 + r));
      }
    }
    DBG(105);
    float* s_red = reinterpret_cast<float*>(smem_raw + SM_RED);
    uint32_t* s_key = reinterpret_cast<uint32_t*>(smem_raw + SM_KEY);
    const int rb = key[1] > key[0];
    const uint32_t wbest = rb ? key[1] : key[0];
    if (lane == 0) s_key[cw] = wbest;
    bar_sync(5, 256);
    const uint32_t cbest = __reduce_max_sync(0xffffffff, s_key[lane & 7]);
    if (wbest == cbest && lane == 0) st_tagged(&g_keys[grp][0], cbest, tag);
    Row xb, xo;
    #pragma unroll
    for (int i = 0; i < 8; i++) { xb.v[i] = rb ? x1[1].v[i] : x1[0].v[i]; xo.v[i] = rb ? x1[0].v[i] : x1[1].v[i]; }
    const Row hb = fma_row(ln_apply(xb, rb ? st[3] : st[0], rb ? st[4] : st[1]), cb1, sb);
    if (wbest == cbest) {
      #pragma unroll
      for (int i = 0; i < 4; i++) st_tagged2(&g_row[grp][0][(i >> 1) * 128 + lane * 4 + (i & 1) * 2], hb.v[2*i], hb.v[2*i+1], tag);
      #pragma unroll
      for (int i = 0; i < 4; i++) st_tagged2(&g_row[grp][1][(i >> 1) * 128 + lane * 4 + (i & 1) * 2], xb.v[2*i], xb.v[2*i+1], tag);
    }
    DBG(106);
    const Row ob = fma_row(gb, hb, xb);
    if (wbest != cbest) store_row(out + (size_t)(row0 + rb) * DM, lane, ob);
    store_row(out + (size_t)(row0 + 1 - rb) * DM, lane, fma_row(gb, fma_row(ln_apply(xo, rb ? st[0] : st[3], rb ? st[1] : st[4]), cb1, sb), xo));
    mbar_wait(bars + R_KEY, 1);
    DBG(107);
    if (moe_cta) {
      float cg[4] = {0, 0, 0, 0}, cu[4] = {0, 0, 0, 0};
      #pragma unroll
      for (int r = 0; r < 4; r++) {
        const uint32_t b0 = lds_u32(base + SM_H2 + (cw * 64 + r * 16) * 2 + (lane & 3) * 4), b1 = lds_u32(base + SM_H2 + (cw * 64 + r * 16) * 2 + 16 + (lane & 3) * 4);
        mma16816(cg, wgv[r], b0, b1); mma16816(cu, wuv[r], b0, b1);
      }
      s_red[cw * 32 + (lane & 3) * 8 + (lane >> 2)] = (lane & 2) ? ((lane & 1) ? cu[2] : cu[0]) : ((lane & 1) ? cg[2] : cg[0]);
      bar_sync(5, 256);
      float g = 0.f;
      #pragma unroll
      for (int i = 0; i < 8; i++) g += s_red[i * 32 + lane];
      g = rbf(g);
      const float act = rbf(__fdividef(g, 1.f + __expf(-g))) * __shfl_down_sync(0xffffffff, g, 16);
      const uint32_t a2 = pack_bf16(act, __shfl_down_sync(0xffffffff, act, 1));
      const uint32_t b0 = __shfl_sync(0xffffffff, a2, (lane & 3) * 2), b1 = __shfl_sync(0xffffffff, a2, (lane & 3) * 2 + 8);
      float y0 = 0.f, y1 = 0.f;
      #pragma unroll
      for (int r = 0; r < 4; r++) {
        float c[4] = {0, 0, 0, 0};
        mma16816(c, wdv[r], b0, b1);
        if ((lane & 3) == r) { y0 = c[0]; y1 = c[2]; }
      }
      st_tagged2(&g_yll[blockIdx.x][cw * 64 + (lane & 3) * 16 + (lane >> 2) * 2], __float_as_uint(y0), __float_as_uint(y1), tag);
    }
    DBG(108);
    if (wbest == cbest && wbest != s_key[8]) store_row(out + (size_t)(row0 + rb) * DM, lane, ob);
    DBG(109);
    __syncwarp();
    cluster_wait();
  }
}

typedef CUresult (*EncodeFn)(CUtensorMap*, CUtensorMapDataType, cuuint32_t, void*, const cuuint64_t*, const cuuint64_t*, const cuuint32_t*,
                             const cuuint32_t*, CUtensorMapInterleave, CUtensorMapSwizzle, CUtensorMapL2promotion, CUtensorMapFloatOOBfill);

struct HostState {
  bool ready = false;
  EncodeFn encode = nullptr;
  CUtensorMap tmC, tmH, tmWq, tmWk, tmWv, tmWo, tmPart, tmWg, tmWu, tmPl, tmWm;
  Sched sched;
};

void make_map(EncodeFn enc, CUtensorMap* m, const void* ptr, int rank, const cuuint64_t* dims, const cuuint64_t* strides, const cuuint32_t* box, bool swizzle = true) {
  const cuuint32_t es[3] = {1, 1, 1};
  enc(m, CU_TENSOR_MAP_DATA_TYPE_BFLOAT16, rank, const_cast<void*>(ptr), dims, strides, box, es, CU_TENSOR_MAP_INTERLEAVE_NONE,
      swizzle ? CU_TENSOR_MAP_SWIZZLE_128B : CU_TENSOR_MAP_SWIZZLE_NONE, swizzle ? CU_TENSOR_MAP_L2_PROMOTION_L2_128B : CU_TENSOR_MAP_L2_PROMOTION_NONE, CU_TENSOR_MAP_FLOAT_OOB_FILL_NONE);
}
void make_2d(EncodeFn enc, CUtensorMap* m, const void* ptr, int rows, int cols, int box_rows) {
  const cuuint64_t dims[2] = {(cuuint64_t)cols, (cuuint64_t)rows}, strides[1] = {(cuuint64_t)cols * 2};
  const cuuint32_t box[2] = {64, (cuuint32_t)box_rows};
  make_map(enc, m, ptr, 2, dims, strides, box);
}
void make_3d(EncodeFn enc, CUtensorMap* m, const void* ptr, int rows, int chunks, size_t row_stride, size_t chunk_stride) {
  const cuuint64_t dims[3] = {64, (cuuint64_t)rows, (cuuint64_t)chunks}, strides[2] = {row_stride, chunk_stride};
  const cuuint32_t box[3] = {64, 64, 2};
  make_map(enc, m, ptr, 3, dims, strides, box);
}

void make_ffn(EncodeFn enc, CUtensorMap* m, const void* ptr) {
  const cuuint64_t dims[2] = {(cuuint64_t)FF, (cuuint64_t)DM}, strides[1] = {(cuuint64_t)FF * 2};
  const cuuint32_t box[2] = {16, 256};
  make_map(enc, m, ptr, 2, dims, strides, box, false);
}

#define SR 0x213312
#define SEED 12345
#define LU_MARGIN 0
#define SPARE_N 3
void build_sched(Sched& s) {
  memset(&s, 0, sizeof(s));
  const int NP = NCTA / 2, korder[4] = {(KORDER >> 12) & 3, (KORDER >> 8) & 3, (KORDER >> 4) & 3, KORDER & 3};
  const int sround[4][2][3] = {{}, {{1}, {2}}, {{1, 2}, {1, 2}}, {{(SR >> 20) & 3, (SR >> 16) & 3, (SR >> 12) & 3}, {(SR >> 8) & 3, (SR >> 4) & 3, SR & 3}}};
  int jv[4][NP], used[4][8] = {};
  for (int r = 0; r < 4; r++) for (int p = 0; p < NP; p++) jv[r][p] = (r & 2) ? 7 - ((p + 4 * (r & 1)) & 7) : (p + 4 * (r & 1)) & 7;
  for (int q = 0; q < 2; q++) {
    s.pair[NP + q].nitems = SPARE_N;
    for (int i = 0; i < SPARE_N; i++) {
      const int r = sround[SPARE_N][q][i];
      s.pair[NP + q].item[i] = (uint8_t)((r * 8 + used[r][6]++) * 8 + 6);
      for (int p = 0; p < NP; p++) if (jv[r][p] == 6) { jv[r][p] = -2; break; }
    }
  }
  auto cost = [&](int p) {
    int u = 8 - ((p >> 4) < SPARE_N ? 21 : 22), z = 0, none = 0;
    for (int r = 0; r < 4; r++) { u += jv[r][p]; z += jv[r][p] == 0; none += jv[r][p] < 0; }
    return 4 * u * u + (z > 1) + 4 * (none > 1);
  };
  uint32_t rng = SEED;
  for (int it = 0; it < 2000000; it++) {
    if ((it & 255) == 0) { int t = 0; for (int p = 0; p < NP; p++) t += cost(p); if (t == 0) break; }
    rng = rng * 1664525u + 1013904223u;
    const int r = (rng >> 8) & 3, a = (rng >> 12) & 63, b = (rng >> 20) & 63, before = cost(a) + cost(b);
    int t = jv[r][a]; jv[r][a] = jv[r][b]; jv[r][b] = t;
    if (cost(a) + cost(b) > before) { jv[r][b] = jv[r][a]; jv[r][a] = t; }
  }
  int fin[256], done[256];
  for (int p = 0; p < NP + 2; p++) {
    Sched::Pair& q = s.pair[p];
    if (p < NP) {
      for (int k = 0; k < 4; k++) q.khead[k] = (uint8_t)(korder[k] * 8 + (p >> 3));
      for (int r = 0; r < 4; r++) {
        if (jv[r][p] < 0) continue;
        q.item[q.nitems++] = (uint8_t)((r * 8 + used[r][jv[r][p]]++) * 8 + jv[r][p]);
      }
    }
    int t = p < NP ? 0 : -3, e = 1;
    for (int i = 0; i < q.nitems; i++) { t += (q.item[i] & 7) + 2; fin[q.item[i]] = t; done[q.item[i]] = t + (i + 1 < q.nitems ? 2 : 0); e += 8 + 4 * ((q.item[i] & 7) + 1); }
    for (int k = 0; k < 3 * MAX_STEPS + 6; k++) {
      const int n = k > 0 ? k - (SPARE_N & 1) : 0, r = n % 7, f = (e + (r < 4 ? r : r - 1)) % 12;
      q.oent[k] = (uint8_t)((r == 4 ? 6 : f >= 6 ? f + 2 : f) ^ (((n / 7) & 1) << 3));
    }
  }
  for (int p = 0; p < NP + 2; p++)
    for (int i = 0; i < s.pair[p].nitems; i++) {
      const int it = s.pair[p].item[i];
      for (int n = 0; n < 2 * (it & 7) + 2; n++) {
        bool last = true;
        for (int j = n >> 1; j < 8; j++) { const int o = (it & ~7) + j; if (o != it && fin[o] + LU_MARGIN > fin[it]) last = false; }
        if (last) s.pair[p].lastuse[i] |= (uint16_t)(1 << n);
      }
    }
  for (int j = 0; j < 8; j++) {
    int order[NH], left[4];
    for (int h = 0; h < NH; h++) { int k = h; for (; k > 0 && done[order[k - 1] * 8 + j] < done[h * 8 + j]; k--) order[k] = order[k - 1]; order[k] = h; }
    for (int kq = 0; kq < 4; kq++) {
      left[kq] = SPARE_N == 0 ? 16 : kq < SPARE_N ? 20 - SPARE_N : 16 - SPARE_N;
      for (int nh = 0; nh < 2; nh++) { Sched::Pair& q = s.pair[kq * 16 + nh * 8 + j]; q.otask = (uint8_t)(kq * 16 + nh * 8 + j); q.nsteps = (uint8_t)((left[kq] + 1) / 2); q.ochunk[0][0] = 255; }
    }
    for (int n = 0, kq = 0, run = 0; n < 64; ) {
      if (left[kq] > 0 && run < 2) {
        const int pos = --left[kq] + (SPARE_N & 1);
        for (int nh = 0; nh < 2; nh++) s.pair[kq * 16 + nh * 8 + j].ochunk[pos >> 1][pos & 1] = (uint8_t)(order[n >> 1] * 2 + 1 - (n & 1));
        n++; run++;
      } else { kq = (kq + 1) & 3; run = 0; }
    }
  }
}

}

extern "C" void kernel_launch(void* const* d_in, const int* in_sizes, int n_in, void* d_out, int out_size) {
  (void)in_sizes; (void)n_in; (void)out_size;
  const __nv_bfloat16* x     = (const __nv_bfloat16*)d_in[0];
  const __nv_bfloat16* ckv   = (const __nv_bfloat16*)d_in[1];
  const __nv_bfloat16* w_q   = (const __nv_bfloat16*)d_in[2];
  const __nv_bfloat16* w_uk  = (const __nv_bfloat16*)d_in[3];
  const __nv_bfloat16* w_uv  = (const __nv_bfloat16*)d_in[4];
  const __nv_bfloat16* w_o   = (const __nv_bfloat16*)d_in[5];
  const __nv_bfloat16* w_r   = (const __nv_bfloat16*)d_in[7];
  const __nv_bfloat16* w_g   = (const __nv_bfloat16*)d_in[8];
  const __nv_bfloat16* w_u   = (const __nv_bfloat16*)d_in[9];
  const __nv_bfloat16* w_d   = (const __nv_bfloat16*)d_in[10];
  const __nv_bfloat16* cvec  = (const __nv_bfloat16*)d_in[11];
  const __nv_bfloat16* w_mod = (const __nv_bfloat16*)d_in[12];
  __nv_bfloat16* out = (__nv_bfloat16*)d_out;

  static HostState st;
  if (!st.ready) {
    void* fn = nullptr; cudaDriverEntryPointQueryResult qr;
    cudaGetDriverEntryPoint("cuTensorMapEncodeTiled", &fn, cudaEnableDefault, &qr);
    st.encode = (EncodeFn)fn;
    cudaFuncSetAttribute(k_fused, cudaFuncAttributeMaxDynamicSharedMemorySize, SMEM);
    build_sched(st.sched);
    void *p_kvc, *p_h1, *p_part;
    cudaGetSymbolAddress(&p_kvc, g_kvc); cudaGetSymbolAddress(&p_h1, g_h1); cudaGetSymbolAddress(&p_part, g_part);
    st.sched.kvc = (__nv_bfloat16*)p_kvc; st.sched.h1 = (__nv_bfloat16*)p_h1;
    make_2d(st.encode, &st.tmH, p_h1, SEQ, DM, 64);
    make_3d(st.encode, &st.tmPart, p_part, SEQ, 32, 128, (size_t)SEQ * 128);
    { const cuuint64_t dims[3] = {64, (cuuint64_t)SEQ, 32}, strides[2] = {128, (cuuint64_t)SEQ * 128}; const cuuint32_t box[3] = {64, 16, 4};
      make_map(st.encode, &st.tmPl, p_part, 3, dims, strides, box, false); }
    st.ready = true;
  }
  make_2d(st.encode, &st.tmC, ckv, SEQ, DM, 128);
  make_2d(st.encode, &st.tmWq, w_q, DM, NH * DH, 64);
  make_2d(st.encode, &st.tmWk, w_uk, DM, NH * DH, 64);
  make_2d(st.encode, &st.tmWv, w_uv, DM, NH * DH, 64);
  make_3d(st.encode, &st.tmWo, w_o, NH * DH, DM / 64, (size_t)DM * 2, 128);
  make_3d(st.encode, &st.tmWm, w_mod, DM, 6 * DM / 64, (size_t)6 * DM * 2, 128);
  make_ffn(st.encode, &st.tmWg, w_g);
  make_ffn(st.encode, &st.tmWu, w_u);

  k_fused<<<NGRID, 384, SMEM, cudaStreamPerThread>>>(st.tmC, st.tmH, st.tmWq, st.tmWk, st.tmWv, st.tmWo, st.tmPart, st.tmWg, st.tmWu, st.tmPl, st.tmWm, st.sched,
                                                     x, cvec, w_o, w_r, w_g, w_u, w_d, out);
}
```

```cpp
#include <cuda_runtime.h>
#include <cuda_bf16.h>
#include <cuda.h>
#include <stdint.h>
#include <string.h>
#include <math.h>

namespace {

constexpr int SEQ = 2048, DM = 512, NH = 32, DH = 128, FF = 1792;
constexpr int NCTA = 128, NGRID = 132;

__device__ __align__(128) __nv_bfloat16 g_kvc[192 * SEQ * 64];
__device__ __nv_bfloat16 g_h1[SEQ * DM];
__device__ __align__(128) __nv_bfloat16 g_part[128 * 8 * 4096];
__device__ __align__(16) __nv_bfloat16 g_mod[6 * DM];
constexpr int C_MOD = 0, C_MOD2 = 16, C_H1 = 32, C_KV = 64, C_CTX = 128, C_PART = 384, C_END = C_PART + 32 * 32;
__device__ __align__(128) unsigned int g_cnt[C_END];
__device__ unsigned int g_epoch;
__device__ __align__(128) uint2 g_keys[128][4];
__device__ __align__(16) uint2 g_row[128][2][DM / 2];
__device__ __align__(16) uint2 g_yll[FF / 16][DM];

#define DBG(i)
#define DBGP(i)

__device__ __forceinline__ uint32_t smem_u32(const void* p) { return (uint32_t)__cvta_generic_to_shared(p); }
__device__ __forceinline__ int wg_tid() { int t; asm volatile("mov.u32 %0, %%tid.x;" : "=r"(t)); return t & 127; }
__device__ __forceinline__ uint32_t clk32() { uint32_t c; asm volatile("mov.u32 %0, %%clock;" : "=r"(c)); return c; }
__device__ __forceinline__ void mbar_arrive(uint32_t bar) { asm volatile("mbarrier.arrive.shared::cta.b64 _, [%0];" :: "r"(bar) : "memory"); }
__device__ __forceinline__ uint32_t mapa(uint32_t addr, uint32_t cta) { uint32_t r; asm("mapa.shared::cluster.u32 %0, %1, %2;" : "=r"(r) : "r"(addr), "r"(cta)); return r; }
__device__ __forceinline__ void mbar_arrive_remote_if(uint32_t cluster_addr, bool pred) {
  asm volatile("{\n.reg .pred p;\nsetp.ne.u32 p, %1, 0;\n@p mbarrier.arrive.shared::cluster.b64 _, [%0];\n}" :: "r"(cluster_addr), "r"((uint32_t)pred) : "memory");
}
__device__ __forceinline__ bool mbar_try(uint32_t bar, uint32_t parity) {
  uint32_t done;
  asm volatile("{\n.reg .pred p;\nmbarrier.try_wait.parity.shared::cta.b64 p, [%1], %2;\nselp.u32 %0, 1, 0, p;\n}" : "=r"(done) : "r"(bar), "r"(parity) : "memory");
  return done;
}
__device__ __forceinline__ bool mbar_test2(uint32_t bar, uint32_t parity) {
  uint32_t done;
  asm volatile("{\n.reg .pred p, q;\nmbarrier.test_wait.parity.shared::cta.b64 p, [%1], %2;\nmbarrier.test_wait.parity.shared::cta.b64 q, [%1 + 8], %2;\n"
               "and.pred p, p, q;\nselp.u32 %0, 1, 0, p;\n}" : "=r"(done) : "r"(bar), "r"(parity) : "memory");
  return done;
}
#define WAIT_LIM (1 << 14)
__device__ __forceinline__ void mbar_wait(uint32_t bar, uint32_t parity) {
  #pragma unroll 1
  for (int n = 0; n < WAIT_LIM; n++) { if (mbar_try(bar, parity)) break; }
}
__device__ __forceinline__ unsigned int ld_acquire(const unsigned int* p) {
  unsigned int v; asm volatile("ld.acquire.gpu.global.u32 %0, [%1];" : "=r"(v) : "l"(p) : "memory"); return v;
}
__device__ __forceinline__ unsigned int ld_relaxed(const unsigned int* p) {
  unsigned int v; asm volatile("ld.relaxed.gpu.global.u32 %0, [%1];" : "=r"(v) : "l"(p) : "memory"); return v;
}
__device__ __forceinline__ void wait_count_lazy(int idx, unsigned int target) {
  #pragma unroll 1
  for (int n = 0; n < WAIT_LIM; n++) { if (__all_sync(0xffffffff, (int)(ld_relaxed(&g_cnt[idx]) - target) >= 0)) break; __nanosleep(100); }
  ld_acquire(&g_cnt[idx]);
}
__device__ __forceinline__ uint4 ld_tagged2(const void* p) {
  uint4 v;
  asm volatile("{\n.reg .b64 a, b;\nld.relaxed.gpu.global.v2.u64 {a, b}, [%4];\nmov.b64 {%0, %1}, a;\nmov.b64 {%2, %3}, b;\n}"
    : "=r"(v.x), "=r"(v.y), "=r"(v.z), "=r"(v.w) : "l"(p) : "memory");
  return v;
}
__device__ __forceinline__ uint2 ld_tagged(const void* p) {
  uint2 v; asm volatile("{\n.reg .b64 a;\nld.relaxed.gpu.global.u64 a, [%2];\nmov.b64 {%0, %1}, a;\n}" : "=r"(v.x), "=r"(v.y) : "l"(p) : "memory"); return v;
}
__device__ __forceinline__ void st_tagged2(void* p, uint32_t a, uint32_t b, uint32_t tag) {
  asm volatile("{\n.reg .b64 a, b;\nmov.b64 a, {%1, %3};\nmov.b64 b, {%2, %3};\nst.relaxed.gpu.global.v2.u64 [%0], {a, b};\n}" :: "l"(p), "r"(a), "r"(b), "r"(tag) : "memory");
}
__device__ __forceinline__ void st_tagged(void* p, uint32_t a, uint32_t tag) {
  asm volatile("{\n.reg .b64 a;\nmov.b64 a, {%1, %2};\nst.relaxed.gpu.global.u64 [%0], a;\n}" :: "l"(p), "r"(a), "r"(tag) : "memory");
}
__device__ __forceinline__ void stg_v4(void* p, uint32_t a, uint32_t b, uint32_t c, uint32_t d) {
  asm volatile("st.global.v4.u32 [%0], {%1, %2, %3, %4};" :: "l"(p), "r"(a), "r"(b), "r"(c), "r"(d) : "memory");
}
__device__ __forceinline__ uint4 lds_v4(uint32_t addr) {
  uint4 v; asm volatile("ld.shared.v4.u32 {%0, %1, %2, %3}, [%4];" : "=r"(v.x), "=r"(v.y), "=r"(v.z), "=r"(v.w) : "r"(addr) : "memory"); return v;
}
__device__ __forceinline__ uint32_t lds_u32(uint32_t addr) { uint32_t v; asm volatile("ld.shared.u32 %0, [%1];" : "=r"(v) : "r"(addr) : "memory"); return v; }
__device__ __forceinline__ void sts_v4(uint32_t addr, uint32_t a, uint32_t b, uint32_t c, uint32_t d) {
  asm volatile("st.shared.v4.u32 [%0], {%1, %2, %3, %4};" :: "r"(addr), "r"(a), "r"(b), "r"(c), "r"(d) : "memory");
}
#define ELECT "{\n.reg .pred p;\nelect.sync _|p, 0xffffffff;\n@p "
__device__ __forceinline__ void w_mbar_init(uint32_t bar, uint32_t cnt) { asm volatile(ELECT "mbarrier.init.shared::cta.b64 [%0], %1;\n}" :: "r"(bar), "r"(cnt) : "memory"); }
__device__ __forceinline__ void w_expect_tx(uint32_t bar, uint32_t bytes) { asm volatile(ELECT "mbarrier.arrive.expect_tx.shared::cta.b64 _, [%0], %1;\n}" :: "r"(bar), "r"(bytes) : "memory"); }
__device__ __forceinline__ void w_arrive(uint32_t bar) { asm volatile(ELECT "mbarrier.arrive.shared::cta.b64 _, [%0];\n}" :: "r"(bar) : "memory"); }
__device__ __forceinline__ void tma_load_2d(uint32_t dst, const CUtensorMap* tm, uint32_t bar, int c0, int c1) {
  asm volatile(ELECT "cp.async.bulk.tensor.2d.shared::cluster.global.mbarrier::complete_tx::bytes [%0], [%1, {%3, %4}], [%2];\n}"
    :: "r"(dst), "l"(tm), "r"(bar), "r"(c0), "r"(c1) : "memory");
}
__device__ __forceinline__ void tma_load_2d_mc(uint32_t dst, const CUtensorMap* tm, uint32_t bar, int c0, int c1) {
  asm volatile(ELECT "cp.async.bulk.tensor.2d.shared::cluster.global.mbarrier::complete_tx::bytes.multicast::cluster [%0], [%1, {%3, %4}], [%2], %5;\n}"
    :: "r"(dst), "l"(tm), "r"(bar), "r"(c0), "r"(c1), "h"((uint16_t)3) : "memory");
}
__device__ __forceinline__ void tma_load_3d(uint32_t dst, const CUtensorMap* tm, uint32_t bar, int c0, int c1, int c2) {
  asm volatile(ELECT "cp.async.bulk.tensor.3d.shared::cluster.global.mbarrier::complete_tx::bytes [%0], [%1, {%3, %4, %5}], [%2];\n}"
    :: "r"(dst), "l"(tm), "r"(bar), "r"(c0), "r"(c1), "r"(c2) : "memory");
}
__device__ __forceinline__ void tma_load_3d_mc(uint32_t dst, const CUtensorMap* tm, uint32_t bar, int c0, int c1, int c2) {
  asm volatile(ELECT "cp.async.bulk.tensor.3d.shared::cluster.global.mbarrier::complete_tx::bytes.multicast::cluster [%0], [%1, {%3, %4, %5}], [%2], %6;\n}"
    :: "r"(dst), "l"(tm), "r"(bar), "r"(c0), "r"(c1), "r"(c2), "h"((uint16_t)3) : "memory");
}
__device__ __forceinline__ void bulk_load_mc(uint32_t dst, const void* src, uint32_t bar, bool ef) {
  if (ef) {
    uint64_t pol; asm("createpolicy.fractional.L2::evict_first.b64 %0, 1.0;" : "=l"(pol));
    asm volatile(ELECT "cp.async.bulk.shared::cluster.global.mbarrier::complete_tx::bytes.multicast::cluster.L2::cache_hint [%0], [%1], 16384, [%2], %3, %4;\n}"
      :: "r"(dst), "l"(src), "r"(bar), "h"((uint16_t)3), "l"(pol) : "memory");
  } else
    asm volatile(ELECT "cp.async.bulk.shared::cluster.global.mbarrier::complete_tx::bytes.multicast::cluster [%0], [%1], 16384, [%2], %3;\n}"
      :: "r"(dst), "l"(src), "r"(bar), "h"((uint16_t)3) : "memory");
}
__device__ __forceinline__ void bulk_load(uint32_t dst, const void* src, uint32_t bytes, uint32_t bar) {
  asm volatile(ELECT "cp.async.bulk.shared::cluster.global.mbarrier::complete_tx::bytes [%0], [%1], %2, [%3];\n}" :: "r"(dst), "l"(src), "r"(bytes), "r"(bar) : "memory");
}
__device__ __forceinline__ void tma_prefetch_2d(const CUtensorMap* tm, int c0, int c1) {
  asm volatile(ELECT "cp.async.bulk.prefetch.tensor.2d.L2.global [%0, {%1, %2}];\n}" :: "l"(tm), "r"(c0), "r"(c1) : "memory");
}
__device__ __forceinline__ void bulk_prefetch(const void* p, uint32_t bytes) {
  asm volatile(ELECT "cp.async.bulk.prefetch.L2.global [%0], %1;\n}" :: "l"(p), "r"(bytes) : "memory");
}
__device__ __forceinline__ void red_release(int idx) { asm volatile("red.release.gpu.global.add.u32 [%0], 1;" :: "l"(&g_cnt[idx]) : "memory"); }
__device__ __forceinline__ void prefetch_tmap(const CUtensorMap* tm) { asm volatile("prefetch.tensormap [%0];" :: "l"(tm) : "memory"); }
__device__ __forceinline__ void bar_sync(int id, int n) { asm volatile("bar.sync %0, %1;" :: "r"(id), "r"(n) : "memory"); }
__device__ __forceinline__ void bar_arrive(int id, int n) { asm volatile("bar.arrive %0, %1;" :: "r"(id), "r"(n) : "memory"); }
__device__ __forceinline__ void fence_async_smem() { asm volatile("fence.proxy.async.shared::cta;" ::: "memory"); }
__device__ __forceinline__ void fence_async_global() { asm volatile("fence.proxy.async.global;" ::: "memory"); }
__device__ __forceinline__ void fence_mbar_init() { asm volatile("fence.mbarrier_init.release.cluster;" ::: "memory"); }
__device__ __forceinline__ void cluster_arrive() { asm volatile("barrier.cluster.arrive.relaxed.aligned;" ::: "memory"); }
__device__ __forceinline__ void cluster_wait() { asm volatile("barrier.cluster.wait.aligned;" ::: "memory"); }
__device__ __forceinline__ uint32_t cluster_ctarank() { uint32_t r; asm volatile("mov.u32 %0, %%cluster_ctarank;" : "=r"(r)); return r; }
__device__ __forceinline__ void wgmma_fence() { asm volatile("wgmma.fence.sync.aligned;" ::: "memory"); }
__device__ __forceinline__ void wgmma_commit() { asm volatile("wgmma.commit_group.sync.aligned;" ::: "memory"); }
template<int N> __device__ __forceinline__ void wgmma_wait() { asm volatile("wgmma.wait_group.sync.aligned %0;" :: "n"(N) : "memory"); }
__device__ __forceinline__ float ex2(float x) { float y; asm("ex2.approx.ftz.f32 %0, %1;" : "=f"(y) : "f"(x)); return y; }
__device__ __forceinline__ float rcp_fast(float x) { float y; asm("rcp.approx.ftz.f32 %0, %1;" : "=f"(y) : "f"(x)); return y; }
__device__ __forceinline__ uint32_t pack_bf16(float lo, float hi) { uint32_t r; asm("cvt.rn.bf16x2.f32 %0, %1, %2;" : "=r"(r) : "f"(hi), "f"(lo)); return r; }
__device__ __forceinline__ float rbf(float x) { return __uint_as_float(pack_bf16(0.f, x)); }
__device__ __forceinline__ float bf_lo(uint32_t v) { return __uint_as_float(v << 16); }
__device__ __forceinline__ float bf_hi(uint32_t v) { return __uint_as_float(v & 0xffff0000u); }
__device__ __forceinline__ uint32_t add2(uint32_t a, uint32_t b) { uint32_t r; asm("add.rn.bf16x2 %0, %1, %2;" : "=r"(r) : "r"(a), "r"(b)); return r; }
__device__ __forceinline__ uint32_t fma2(uint32_t a, uint32_t b, uint32_t c) { uint32_t r; asm("fma.rn.bf16x2 %0, %1, %2, %3;" : "=r"(r) : "r"(a), "r"(b), "r"(c)); return r; }
__device__ __forceinline__ uint4 ldsm_x4_t(uint32_t addr) {
  uint4 v; asm volatile("ldmatrix.sync.aligned.m8n8.x4.trans.shared.b16 {%0, %1, %2, %3}, [%4];" : "=r"(v.x), "=r"(v.y), "=r"(v.z), "=r"(v.w) : "r"(addr) : "memory"); return v;
}
__device__ __forceinline__ uint4 ldsm_x4(uint32_t addr) {
  uint4 v; asm volatile("ldmatrix.sync.aligned.m8n8.x4.shared.b16 {%0, %1, %2, %3}, [%4];" : "=r"(v.x), "=r"(v.y), "=r"(v.z), "=r"(v.w) : "r"(addr) : "memory"); return v;
}
__device__ __forceinline__ void mma16816(float (&c)[4], const uint4& a, uint32_t b0, uint32_t b1) {
  asm("mma.sync.aligned.m16n8k16.row.col.f32.bf16.bf16.f32 {%0, %1, %2, %3}, {%4, %5, %6, %7}, {%8, %9}, {%0, %1, %2, %3};"
    : "+f"(c[0]), "+f"(c[1]), "+f"(c[2]), "+f"(c[3]) : "r"(a.x), "r"(a.y), "r"(a.z), "r"(a.w), "r"(b0), "r"(b1));
}
template<int N> __device__ __forceinline__ void fence_regs(float (&a)[N]) {
  #pragma unroll
  for (int i = 0; i < N; i++) asm volatile("" : "+f"(a[i]) :: "memory");
}
template<int N> __device__ __forceinline__ void fence_regs_u(uint32_t (&a)[N]) {
  #pragma unroll
  for (int i = 0; i < N; i++) asm volatile("" : "+r"(a[i]) :: "memory");
}
constexpr uint32_t SW128 = 0x40000040u, SW64 = 0x80000020u;
__device__ __forceinline__ uint32_t desc_lo(uint32_t addr, uint32_t lbo) { return ((addr & 0x3FFFF) >> 4) | ((lbo >> 4) << 16); }

template<int TB, int OA, int OB, uint32_t HA, uint32_t HB> __device__ __forceinline__ void wgmma_ss_n128(float (&d)[64], uint32_t da, uint32_t db, int sd) {
  asm volatile("{\n.reg .pred p;\n.reg .b32 ta, tb;\n.reg .b64 da, db;\nsetp.ne.b32 p, %66, 0;\nadd.u32 ta, %64, %68;\nadd.u32 tb, %65, %69;\nmov.b64 da, {ta, %70};\nmov.b64 db, {tb, %71};\n"
    "wgmma.mma_async.sync.aligned.m64n128k16.f32.bf16.bf16 "
    "{%0, %1, %2, %3, %4, %5, %6, %7, %8, %9, %10, %11, %12, %13, %14, %15, %16, %17, %18, %19, %20, %21, %22, %23, %24, %25, %26, %27, %28, %29, %30, %31, %32, %33, %34, %35, %36, %37, %38, %39, %40, %41, %42, %43, %44, %45, %46, %47, %48, %49, %50, %51, %52, %53, %54, %55, %56, %57, %58, %59, %60, %61, %62, %63}, da, db, p, 1, 1, 0, %67;\n}\n"
    : "+f"(d[0]), "+f"(d[1]), "+f"(d[2]), "+f"(d[3]), "+f"(d[4]), "+f"(d[5]), "+f"(d[6]), "+f"(d[7]), "+f"(d[8]), "+f"(d[9]), "+f"(d[10]), "+f"(d[11]), "+f"(d[12]), "+f"(d[13]), "+f"(d[14]), "+f"(d[15]), "+f"(d[16]), "+f"(d[17]), "+f"(d[18]), "+f"(d[19]), "+f"(d[20]), "+f"(d[21]), "+f"(d[22]), "+f"(d[23]), "+f"(d[24]), "+f"(d[25]), "+f"(d[26]), "+f"(d[27]), "+f"(d[28]), "+f"(d[29]), "+f"(d[30]), "+f"(d[31]), "+f"(d[32]), "+f"(d[33]), "+f"(d[34]), "+f"(d[35]), "+f"(d[36]), "+f"(d[37]), "+f"(d[38]), "+f"(d[39]), "+f"(d[40]), "+f"(d[41]), "+f"(d[42]), "+f"(d[43]), "+f"(d[44]), "+f"(d[45]), "+f"(d[46]), "+f"(d[47]), "+f"(d[48]), "+f"(d[49]), "+f"(d[50]), "+f"(d[51]), "+f"(d[52]), "+f"(d[53]), "+f"(d[54]), "+f"(d[55]), "+f"(d[56]), "+f"(d[57]), "+f"(d[58]), "+f"(d[59]), "+f"(d[60]), "+f"(d[61]), "+f"(d[62]), "+f"(d[63])
    : "r"(da), "r"(db), "r"(sd), "n"(TB), "n"(OA), "n"(OB), "n"(HA), "n"(HB));
}
template<int TB, int OB, uint32_t HB> __device__ __forceinline__ void wgmma_rs_n128(float (&d)[64], uint32_t a0, uint32_t a1, uint32_t a2, uint32_t a3, uint32_t db, int sd) {
  asm volatile("{\n.reg .pred p;\n.reg .b32 tb;\n.reg .b64 db;\nsetp.ne.b32 p, %69, 0;\nadd.u32 tb, %68, %71;\nmov.b64 db, {tb, %72};\n"
    "wgmma.mma_async.sync.aligned.m64n128k16.f32.bf16.bf16 "
    "{%0, %1, %2, %3, %4, %5, %6, %7, %8, %9, %10, %11, %12, %13, %14, %15, %16, %17, %18, %19, %20, %21, %22, %23, %24, %25, %26, %27, %28, %29, %30, %31, %32, %33, %34, %35, %36, %37, %38, %39, %40, %41, %42, %43, %44, %45, %46, %47, %48, %49, %50, %51, %52, %53, %54, %55, %56, %57, %58, %59, %60, %61, %62, %63}, {%64,%65,%66,%67}, db, p, 1, 1, %70;\n}\n"
    : "+f"(d[0]), "+f"(d[1]), "+f"(d[2]), "+f"(d[3]), "+f"(d[4]), "+f"(d[5]), "+f"(d[6]), "+f"(d[7]), "+f"(d[8]), "+f"(d[9]), "+f"(d[10]), "+f"(d[11]), "+f"(d[12]), "+f"(d[13]), "+f"(d[14]), "+f"(d[15]), "+f"(d[16]), "+f"(d[17]), "+f"(d[18]), "+f"(d[19]), "+f"(d[20]), "+f"(d[21]), "+f"(d[22]), "+f"(d[23]), "+f"(d[24]), "+f"(d[25]), "+f"(d[26]), "+f"(d[27]), "+f"(d[28]), "+f"(d[29]), "+f"(d[30]), "+f"(d[31]), "+f"(d[32]), "+f"(d[33]), "+f"(d[34]), "+f"(d[35]), "+f"(d[36]), "+f"(d[37]), "+f"(d[38]), "+f"(d[39]), "+f"(d[40]), "+f"(d[41]), "+f"(d[42]), "+f"(d[43]), "+f"(d[44]), "+f"(d[45]), "+f"(d[46]), "+f"(d[47]), "+f"(d[48]), "+f"(d[49]), "+f"(d[50]), "+f"(d[51]), "+f"(d[52]), "+f"(d[53]), "+f"(d[54]), "+f"(d[55]), "+f"(d[56]), "+f"(d[57]), "+f"(d[58]), "+f"(d[59]), "+f"(d[60]), "+f"(d[61]), "+f"(d[62]), "+f"(d[63])
    : "r"(a0), "r"(a1), "r"(a2), "r"(a3), "r"(db), "r"(sd), "n"(TB), "n"(OB), "n"(HB));
}
template<int TB, int OA, int OB, uint32_t HA, uint32_t HB> __device__ __forceinline__ void wgmma_ss_n64(float (&d)[32], uint32_t da, uint32_t db, int sd) {
  asm volatile("{\n.reg .pred p;\n.reg .b32 ta, tb;\n.reg .b64 da, db;\nsetp.ne.b32 p, %34, 0;\nadd.u32 ta, %32, %36;\nadd.u32 tb, %33, %37;\nmov.b64 da, {ta, %38};\nmov.b64 db, {tb, %39};\n"
    "wgmma.mma_async.sync.aligned.m64n64k16.f32.bf16.bf16 "
    "{%0, %1, %2, %3, %4, %5, %6, %7, %8, %9, %10, %11, %12, %13, %14, %15, %16, %17, %18, %19, %20, %21, %22, %23, %24, %25, %26, %27, %28, %29, %30, %31}, da, db, p, 1, 1, 0, %35;\n}\n"
    : "+f"(d[0]), "+f"(d[1]), "+f"(d[2]), "+f"(d[3]), "+f"(d[4]), "+f"(d[5]), "+f"(d[6]), "+f"(d[7]), "+f"(d[8]), "+f"(d[9]), "+f"(d[10]), "+f"(d[11]), "+f"(d[12]), "+f"(d[13]), "+f"(d[14]), "+f"(d[15]), "+f"(d[16]), "+f"(d[17]), "+f"(d[18]), "+f"(d[19]), "+f"(d[20]), "+f"(d[21]), "+f"(d[22]), "+f"(d[23]), "+f"(d[24]), "+f"(d[25]), "+f"(d[26]), "+f"(d[27]), "+f"(d[28]), "+f"(d[29]), "+f"(d[30]), "+f"(d[31])
    : "r"(da), "r"(db), "r"(sd), "n"(TB), "n"(OA), "n"(OB), "n"(HA), "n"(HB));
}
template<int TB, int OA, int OB, uint32_t HA, uint32_t HB> __device__ __forceinline__ void wgmma_ss_n128_new(float (&d)[64], uint32_t da, uint32_t db) {
  asm volatile("{\n.reg .pred p;\n.reg .b32 ta, tb;\n.reg .b64 da, db;\nsetp.ne.b32 p, %66, 0;\nadd.u32 ta, %64, %68;\nadd.u32 tb, %65, %69;\nmov.b64 da, {ta, %70};\nmov.b64 db, {tb, %71};\n"
    "wgmma.mma_async.sync.aligned.m64n128k16.f32.bf16.bf16 "
    "{%0, %1, %2, %3, %4, %5, %6, %7, %8, %9, %10, %11, %12, %13, %14, %15, %16, %17, %18, %19, %20, %21, %22, %23, %24, %25, %26, %27, %28, %29, %30, %31, %32, %33, %34, %35, %36, %37, %38, %39, %40, %41, %42, %43, %44, %45, %46, %47, %48, %49, %50, %51, %52, %53, %54, %55, %56, %57, %58, %59, %60, %61, %62, %63}, da, db, p, 1, 1, 0, %67;\n}\n"
    : "=f"(d[0]), "=f"(d[1]), "=f"(d[2]), "=f"(d[3]), "=f"(d[4]), "=f"(d[5]), "=f"(d[6]), "=f"(d[7]), "=f"(d[8]), "=f"(d[9]), "=f"(d[10]), "=f"(d[11]), "=f"(d[12]), "=f"(d[13]), "=f"(d[14]), "=f"(d[15]), "=f"(d[16]), "=f"(d[17]), "=f"(d[18]), "=f"(d[19]), "=f"(d[20]), "=f"(d[21]), "=f"(d[22]), "=f"(d[23]), "=f"(d[24]), "=f"(d[25]), "=f"(d[26]), "=f"(d[27]), "=f"(d[28]), "=f"(d[29]), "=f"(d[30]), "=f"(d[31]), "=f"(d[32]), "=f"(d[33]), "=f"(d[34]), "=f"(d[35]), "=f"(d[36]), "=f"(d[37]), "=f"(d[38]), "=f"(d[39]), "=f"(d[40]), "=f"(d[41]), "=f"(d[42]), "=f"(d[43]), "=f"(d[44]), "=f"(d[45]), "=f"(d[46]), "=f"(d[47]), "=f"(d[48]), "=f"(d[49]), "=f"(d[50]), "=f"(d[51]), "=f"(d[52]), "=f"(d[53]), "=f"(d[54]), "=f"(d[55]), "=f"(d[56]), "=f"(d[57]), "=f"(d[58]), "=f"(d[59]), "=f"(d[60]), "=f"(d[61]), "=f"(d[62]), "=f"(d[63])
    : "r"(da), "r"(db), "n"(0), "n"(TB), "n"(OA), "n"(OB), "n"(HA), "n"(HB));
}
template<int TB, int OA, int OB, uint32_t HA, uint32_t HB> __device__ __forceinline__ void wgmma_ss_n64_new(float (&d)[32], uint32_t da, uint32_t db) {
  asm volatile("{\n.reg .pred p;\n.reg .b32 ta, tb;\n.reg .b64 da, db;\nsetp.ne.b32 p, %34, 0;\nadd.u32 ta, %32, %36;\nadd.u32 tb, %33, %37;\nmov.b64 da, {ta, %38};\nmov.b64 db, {tb, %39};\n"
    "wgmma.mma_async.sync.aligned.m64n64k16.f32.bf16.bf16 "
    "{%0, %1, %2, %3, %4, %5, %6, %7, %8, %9, %10, %11, %12, %13, %14, %15, %16, %17, %18, %19, %20, %21, %22, %23, %24, %25, %26, %27, %28, %29, %30, %31}, da, db, p, 1, 1, 0, %35;\n}\n"
    : "=f"(d[0]), "=f"(d[1]), "=f"(d[2]), "=f"(d[3]), "=f"(d[4]), "=f"(d[5]), "=f"(d[6]), "=f"(d[7]), "=f"(d[8]), "=f"(d[9]), "=f"(d[10]), "=f"(d[11]), "=f"(d[12]), "=f"(d[13]), "=f"(d[14]), "=f"(d[15]), "=f"(d[16]), "=f"(d[17]), "=f"(d[18]), "=f"(d[19]), "=f"(d[20]), "=f"(d[21]), "=f"(d[22]), "=f"(d[23]), "=f"(d[24]), "=f"(d[25]), "=f"(d[26]), "=f"(d[27]), "=f"(d[28]), "=f"(d[29]), "=f"(d[30]), "=f"(d[31])
    : "r"(da), "r"(db), "n"(0), "n"(TB), "n"(OA), "n"(OB), "n"(HA), "n"(HB));
}
template<int OA, int OB = 0, uint32_t HA = SW128> __device__ __forceinline__ void kblock_n128(float (&d)[64], uint32_t da, uint32_t db, int sd) {
  constexpr int H = HA == SW128 ? 4 : 512;
  wgmma_ss_n128<1, OA, OB, HA, SW128>(d, da, db, sd); wgmma_ss_n128<1, OA + 2, OB + 128, HA, SW128>(d, da, db, 1);
  wgmma_ss_n128<1, OA + H, OB + 256, HA, SW128>(d, da, db, 1); wgmma_ss_n128<1, OA + H + 2, OB + 384, HA, SW128>(d, da, db, 1);
}

__device__ __forceinline__ float quad_sum(float v) {
  v += __shfl_xor_sync(0xffffffff, v, 1);
  v += __shfl_xor_sync(0xffffffff, v, 2);
  return v;
}
struct Row { uint32_t v[8]; };
template<class F> __device__ __forceinline__ Row load_row(const __nv_bfloat16* p, int lane, F ld) {
  const uint4 a = ld(reinterpret_cast<const uint4*>(p) + lane), b = ld(reinterpret_cast<const uint4*>(p) + 32 + lane);
  return Row{{a.x, a.y, a.z, a.w, b.x, b.y, b.z, b.w}};
}
__device__ __forceinline__ Row ldg_row(const __nv_bfloat16* p, int lane) { return load_row(p, lane, [](const uint4* q) { return __ldg(q); }); }
__device__ __forceinline__ Row ldca_row(const __nv_bfloat16* p, int lane) { return load_row(p, lane, [](const uint4* q) { return __ldca(q); }); }
__device__ __forceinline__ Row lds_row(uint32_t addr, int lane) {
  const uint4 a = lds_v4(addr + lane * 16), b = lds_v4(addr + 512 + lane * 16);
  return Row{{a.x, a.y, a.z, a.w, b.x, b.y, b.z, b.w}};
}
__device__ __forceinline__ void store_row(__nv_bfloat16* p, int lane, const Row& r) {
  stg_v4(p + lane * 8, r.v[0], r.v[1], r.v[2], r.v[3]); stg_v4(p + 256 + lane * 8, r.v[4], r.v[5], r.v[6], r.v[7]);
}
__device__ __forceinline__ Row fma_row(const Row& a, const Row& b, const Row& c) {
  Row r;
  #pragma unroll
  for (int i = 0; i < 8; i++) r.v[i] = fma2(a.v[i], b.v[i], c.v[i]);
  return r;
}
__device__ __forceinline__ Row add_row(const Row& a, const Row& b) {
  Row r;
  #pragma unroll
  for (int i = 0; i < 8; i++) r.v[i] = add2(a.v[i], b.v[i]);
  return r;
}
__device__ __forceinline__ Row one_plus(const Row& a) {
  Row r;
  #pragma unroll
  for (int i = 0; i < 8; i++) r.v[i] = add2(a.v[i], 0x3f803f80u);
  return r;
}
__device__ __forceinline__ float row_at(const Row& x, int i) { return (i & 1) ? bf_hi(x.v[i >> 1]) : bf_lo(x.v[i >> 1]); }
template<int N> __device__ __forceinline__ void warp_sums(float (&s)[N]) {
  #pragma unroll
  for (int o = 16; o > 0; o >>= 1) {
    #pragma unroll
    for (int k = 0; k < N; k++) s[k] += __shfl_xor_sync(0xffffffff, s[k], o);
  }
}
__device__ __forceinline__ void ln_stats(float& s1, float& s2) {
  s1 *= 1.f / DM;
  asm("rsqrt.approx.ftz.f32 %0, %1;" : "=f"(s2) : "f"(fmaxf(fmaf(-s1, s1, s2 * (1.f / DM)), 0.f) + 1e-5f));
}
__device__ __forceinline__ Row ln_apply(const Row& x, float mean, float f) {
  Row n;
  const float o = -mean * f;
  #pragma unroll
  for (int i = 0; i < 8; i++) n.v[i] = pack_bf16(fmaf(bf_lo(x.v[i]), f, o), fmaf(bf_hi(x.v[i]), f, o));
  return n;
}

constexpr int SM_Q = 6 * 32768, SM_BAR = 7 * 32768, SM_MAIL = SM_BAR + 640, SM_RED = SM_MAIL + 128, SM_H2 = SM_RED + 1024, SM_KEY = SM_H2 + 1024, SMEM = SM_KEY + 128;
constexpr int B_AF = 0, B_WF = 64, B_RF = 112, B_WE = 168, B_RE = 216, B_PUB = 272, B_RDY = 496;
constexpr int R_MOD = B_RDY, R_H1 = B_RDY + 8, R_ITEM = B_RDY + 16, R_NEAR = B_RDY + 48, R_CTX = B_RDY + 64;
constexpr int R_KEY = B_AF + 8, R_PART = B_AF + 32;
constexpr int NPUB = 14;
__device__ __forceinline__ uint32_t k_addrA(int kb) { return ((0x6310u >> ((kb >> 1) * 4)) & 15u) * 32768u + (kb & 1) * 16384u; }
__device__ __forceinline__ uint32_t k_addrW(int s) { return ((0x254u >> ((s >> 1) * 4)) & 15u) * 32768u + (s & 1) * 16384u; }

#define KORDER 0x2301
constexpr int KHEAD0 = ((KORDER >> 12) & 3) * 8;
constexpr int MAX_ITEMS = 4;
constexpr int MAX_STEPS = 10;
struct Sched {
  __nv_bfloat16 *kvc, *h1, *part;
  struct Pair {
    uint8_t oent[3 * MAX_STEPS + 6];
    uint16_t lastuse[MAX_ITEMS];
    uint8_t khead[4];
    uint8_t nitems, item[MAX_ITEMS];
    uint8_t otask, nsteps;
    uint8_t ochunk[MAX_STEPS][2];
  } pair[NGRID / 2];
};

__device__ __forceinline__ int ring_add(int e, int n) { e += n; return e >= 12 ? e - 12 : e; }
__device__ __forceinline__ int ring_slot(int e) { return e >= 6 ? e - 6 : e; }
__device__ __forceinline__ void ring_wait_full(uint32_t bars, int e) { mbar_wait(bars + B_RF + 8 * ring_slot(e), e >= 6); }

__device__ __forceinline__ void o_wait_full(uint32_t bars, uint32_t v) { mbar_wait(bars + B_RF + 8 * (v & 7), v >> 3); }

struct Ctx {
  uint32_t base, bars;
  uint32_t rel;
  bool rel1;
  int w, nev;
  const Sched* sched;
  uint32_t tr;
};
#define TR(id)
__device__ __forceinline__ void slot_release(const Ctx& x, int s, bool twice) {
  mbar_arrive_remote_if(x.rel + B_RE + 8 * s, twice ? (wg_tid() & 31) == 0 : x.rel1);
}
__device__ __forceinline__ void ring_release(const Ctx& x, int e, bool twice) { slot_release(x, ring_slot(e), twice); }
__device__ __forceinline__ void publish(Ctx& x, int idx) {
  const uint32_t n = x.w * NPUB + x.nev;
  const int t = wg_tid();
  if (t == 0) asm volatile("st.shared.u32 [%0], %1;" :: "r"(x.base + SM_MAIL + 4 * n), "r"(idx) : "memory");
  __syncwarp();
  if ((t & 31) == 0) mbar_arrive(x.bars + B_PUB + 8 * n);
  x.nev++;
}

template<int KK = 0> __device__ __forceinline__ void issue_qk(float (&S)[64], uint32_t dq, uint32_t dk) {
  constexpr int off = (KK >> 1) * 512 + (KK & 1) * 2;
  if constexpr (KK == 0) wgmma_ss_n128_new<0, 0, 0, SW64, SW64>(S, dq, dk); else wgmma_ss_n128<0, off, off, SW64, SW64>(S, dq, dk, 1);
  if constexpr (KK < 7) issue_qk<KK + 1>(S, dq, dk);
}
template<int KK = 0> __device__ __forceinline__ void issue_qk_half(float (&S)[32], uint32_t dq, uint32_t dk) {
  constexpr int off = (KK >> 1) * 512 + (KK & 1) * 2;
  if constexpr (KK == 0) wgmma_ss_n64_new<0, 0, 256, SW64, SW64>(S, dq, dk); else wgmma_ss_n64<0, off, off + 256, SW64, SW64>(S, dq, dk, 1);
  if constexpr (KK < 7) issue_qk_half<KK + 1>(S, dq, dk);
}
template<int NK, int KK = 0>
__device__ __forceinline__ void issue_pv(float (&O)[64], uint32_t (&P)[32], uint32_t dv, int accumulate) {
  wgmma_rs_n128<1, (KK + 8 - NK) * 64, SW64>(O, P[4*KK], P[4*KK+1], P[4*KK+2], P[4*KK+3], dv, accumulate);
  if constexpr (KK + 1 < NK) issue_pv<NK, KK + 1>(O, P, dv, 1);
}
template<int K0, int K1>
__device__ __forceinline__ void exp_pack(const float (&S)[64], uint32_t (&D)[32], float& s0, float& s1) {
  #pragma unroll
  for (int k = K0; k < K1; k++) {
    const float e0 = ex2(S[2*k]), e1 = ex2(S[2*k+1]);
    D[k] = pack_bf16(e0, e1);
    if (k & 1) s1 += e0 + e1; else s0 += e0 + e1;
  }
}
__device__ __forceinline__ int diag_limit() { const int t = wg_tid(); return 16 * (t >> 5) + ((t & 31) >> 2) - 2 * (t & 3); }
__device__ __forceinline__ void exp_pack_diag(const float (&S)[64], uint32_t (&D)[32], int t, float& s0, float& s1) {
  #pragma unroll
  for (int k = 0; k < 16; k++) {
    const int c = 8 * (k >> 1) - 8 * (k & 1);
    const float e0 = ex2((c <= t) ? S[2*k] : -INFINITY), e1 = ex2((c + 1 <= t) ? S[2*k+1] : -INFINITY);
    D[k] = pack_bf16(e0, e1);
    if (k & 1) s1 += e0 + e1; else s0 += e0 + e1;
  }
}
constexpr float SUM_HI = 1.8446744073709552e19f;
constexpr float SUM_LO = 5.421010862427522e-20f;

__device__ __forceinline__ void classic_tile(const float (&S)[64], uint32_t (&P)[32], bool fresh, bool half, bool was_classic, volatile float* mc,
                                             float& l0, float& l1, float& s0, float& s1, float& sc0, float& sc1) {
  const int tmask = diag_limit();
  float4 t[16];
  #pragma unroll
  for (int j = 0; j < 16; j++) t[j] = make_float4(S[4*j], S[4*j+1], S[4*j+2], S[4*j+3]);
  float mx0 = -INFINITY, mx1 = -INFINITY;
  #pragma unroll 1
  for (int j = 0; j < 16; j++) {
    float4 v = t[j];
    const int lim = !fresh ? 1000 : j < 8 ? tmask - 8 * j : half ? -1000 : 1000;
    v.x = 0 <= lim ? v.x : -INFINITY; v.y = 1 <= lim ? v.y : -INFINITY; v.z = -8 <= lim ? v.z : -INFINITY; v.w = -7 <= lim ? v.w : -INFINITY;
    t[j] = v;
    mx0 = fmaxf(mx0, fmaxf(v.x, v.y)); mx1 = fmaxf(mx1, fmaxf(v.z, v.w));
  }
  mx0 = fmaxf(mx0, __shfl_xor_sync(0xffffffff, mx0, 1));
  mx1 = fmaxf(mx1, __shfl_xor_sync(0xffffffff, mx1, 1));
  mx0 = fmaxf(mx0, __shfl_xor_sync(0xffffffff, mx0, 2));
  mx1 = fmaxf(mx1, __shfl_xor_sync(0xffffffff, mx1, 2));
  const float mc0 = was_classic ? mc[0] : 0.f, mc1 = was_classic ? mc[1] : 0.f;
  const float n0 = fresh ? -mx0 : fminf(mc0, -mx0), n1 = fresh ? -mx1 : fminf(mc1, -mx1);
  sc0 = ex2(n0 - mc0); sc1 = ex2(n1 - mc1);
  mc[0] = n0; mc[1] = n1;
  s0 = 0.f; s1 = 0.f;
  #pragma unroll 1
  for (int j = 0; j < 16; j++) {
    const float4 v = t[j];
    const float e0 = ex2(v.x + n0), e1 = ex2(v.y + n0), e2 = ex2(v.z + n1), e3 = ex2(v.w + n1);
    s0 += e0 + e1; s1 += e2 + e3;
    reinterpret_cast<uint2*>(t)[j] = make_uint2(pack_bf16(e0, e1), pack_bf16(e2, e3));
  }
  #pragma unroll
  for (int j = 0; j < 8; j++) { P[4*j] = __float_as_uint(t[j].x); P[4*j+1] = __float_as_uint(t[j].y); P[4*j+2] = __float_as_uint(t[j].z); P[4*j+3] = __float_as_uint(t[j].w); }
  if (!fresh) { l0 *= sc0; l1 *= sc1; }
}
__device__ __forceinline__ void pack_tile(const float (&A)[64], uint32_t (&D)[32], float f0, float f1) {
  #pragma unroll
  for (int j = 0; j < 16; j++) {
    D[8 * (j >> 2) + (j & 3)] = pack_bf16(A[4*j] * f0, A[4*j+1] * f0);
    D[8 * (j >> 2) + 4 + (j & 3)] = pack_bf16(A[4*j+2] * f1, A[4*j+3] * f1);
  }
}
__device__ __forceinline__ int piece0(int t) { return ((t >> 5) * 16 + ((t & 31) >> 2)) * 32 + (((t ^ (t >> 3)) & 3) << 3); }
__device__ __forceinline__ void store_tile(__nv_bfloat16* p, const uint32_t (&D)[32]) {
  #pragma unroll
  for (int i = 0; i < 8; i++) stg_v4(p + (i >> 2) * (SEQ * 64) + ((i >> 1) & 1) * 4096 + (i & 1) * 256, D[4*i], D[4*i+1], D[4*i+2], D[4*i+3]);
}

enum : int { PV_ACC = 0, PV_ZERO = 1, PV_HALF = 2, PV_NONE = 3 };
struct Att {
  float l0, l1, i0, i1;
  bool classic;
  volatile float* mc;
};
__device__ __forceinline__ void store_ctx(Ctx& x, int code, const uint32_t (&D)[32]) {
  store_tile(x.sched->kvc + ((size_t)(128 + (code >> 5) * 2) * SEQ + ((code >> 1) & 15) * 128) * 64 + (code & 1) * 2048 + piece0(wg_tid()), D);
  publish(x, C_CTX + (code >> 2));
}
__device__ __forceinline__ __nv_bfloat16* kv_tile(const Ctx& x, int code) {
  return x.sched->kvc + ((size_t)(x.w * 64 + (code >> 4) * 2) * SEQ + (code & 15) * 128) * 64 + piece0(wg_tid());
}
#define V_AT 3
#define V_AT2 7
#define MERGE1 1
#define NO_CLASSIC 0
__device__ __forceinline__ void q_proj(Ctx& x, int& e, bool isY, const uint32_t (&PA)[32], const uint32_t (&PB)[32], int vtile, bool first, bool dbg = false) {
  float S[64];
  if (isY) bar_sync(1 + x.w, 256);
  if (dbg) DBG(80);
  TR(1);
  #pragma unroll 1
  for (int kb = 0; kb < 8; kb++) {
    if (kb > 0 || first) ring_wait_full(x.bars, e);
    if (dbg) DBG(81 + kb);
    TR(2);
    const uint32_t da = desc_lo(x.base + x.w * 8192, 16) + ring_slot(e) * 2048, dw = desc_lo(x.base + 16384, 8192) + ring_slot(e) * 2048;
    wgmma_fence();
    kblock_n128<0>(S, da, dw, kb != 0);
    wgmma_commit();
    if (kb == 7 && !isY) bar_arrive(1 + (x.w ^ 1), 256);
    if (kb > 0) { wgmma_wait<1>(); ring_release(x, ring_add(e, 11), false); }
    if (kb == V_AT && vtile >= 0) store_tile(kv_tile(x, vtile) + 2048, PA);
    if (kb == V_AT2 && vtile >= 0) { store_tile(kv_tile(x, vtile), PB); publish(x, C_KV + (vtile >> 4)); }
    e = ring_add(e, 1);
  }
  wgmma_wait<0>();
  fence_regs(S);
  if (dbg) DBG(89);
  TR(3);
  ring_release(x, ring_add(e, 11), false);
  const uint32_t qa = x.base + SM_Q + x.w * 4096 + piece0(wg_tid()) * 2;
  #pragma unroll
  for (int i = 0; i < 8; i++) {
    const int j = 4 * (i >> 1), o = 2 * (i & 1);
    sts_v4(qa + (i >> 1) * 8192 + (i & 1) * 512,
           pack_bf16(S[4*j+o], S[4*j+o+1]), pack_bf16(S[4*j+4+o], S[4*j+5+o]), pack_bf16(S[4*j+8+o], S[4*j+9+o]), pack_bf16(S[4*j+12+o], S[4*j+13+o]));
  }
  fence_async_smem();
  if (dbg) DBG(90);
  TR(4);
  ring_wait_full(x.bars, ring_add(e, isY ? 0 : 2));
  ring_wait_full(x.bars, e + 1);
}

template<int KIND>
__device__ __forceinline__ void slot(Ctx& x, Att& a, int& e, float (&O)[64], uint32_t (&Pn)[32], uint32_t (&Po)[32],
                                     bool more, bool isY, bool half, int pv, int pend) {
  float S[64];
  const int w = x.w;
  const bool skip = KIND == 0 && !isY;
  const int en = ring_add(e, skip ? 4 : 2), sn = ring_slot(en), sv = ring_slot(e) + 1, sk = skip ? ring_slot(ring_add(e, 2)) : sv - 1;
  const uint32_t dq = desc_lo(x.base + SM_Q + w * 4096, 16), dk = desc_lo(x.base, 16) + sk * 2048, dv = desc_lo(x.base, 8192) + sv * 2048;
  bar_sync(1 + w, 256);
  TR(5 + KIND);
  if (KIND == 2) {
    wgmma_fence();
    issue_qk(S, dq, dk); wgmma_commit();
    issue_pv<8>(O, Po, dv, 1); wgmma_commit();
    bar_arrive(1 + (w ^ 1), 256);
    wgmma_wait<1>();
  } else if (KIND == 0 && half) {
    float T[32];
    wgmma_fence(); issue_qk_half(T, dq, dk); wgmma_commit();
    a.i0 = rcp_fast(quad_sum(a.l0)); a.i1 = rcp_fast(quad_sum(a.l1));
    if (pv == PV_NONE) { wgmma_fence(); wgmma_commit(); }
    else               { wgmma_fence(); issue_pv<8>(O, Po, dv, pv == PV_ACC); wgmma_commit(); }
    bar_arrive(1 + (w ^ 1), 256);
    wgmma_wait<1>();
    fence_regs(T);
    #pragma unroll
    for (int i = 0; i < 32; i++) { S[i] = T[i]; asm volatile("" : "=f"(S[32 + i])); }
  } else {
    wgmma_fence(); issue_qk(S, dq, dk); wgmma_commit();
    if (KIND == 1 && pend >= 0) { bar_arrive(1 + (w ^ 1), 256); pack_tile(O, Pn, a.i0, a.i1); store_ctx(x, pend, Pn); TR(8); }
    if (KIND == 0) { a.i0 = rcp_fast(quad_sum(a.l0)); a.i1 = rcp_fast(quad_sum(a.l1)); }
    if (KIND == 0 && pv == PV_NONE) { wgmma_fence(); wgmma_commit(); }
    else if (pv == PV_HALF)         { wgmma_fence(); issue_pv<4>(O, Po, dv, 0); wgmma_commit(); }
    else                            { wgmma_fence(); issue_pv<8>(O, Po, dv, pv == PV_ACC); wgmma_commit(); }
    if (KIND == 0 || pend < 0) bar_arrive(1 + (w ^ 1), 256);
    wgmma_wait<1>();
  }
  fence_regs(S);
  fence_regs_u(Pn);
  TR(9);
  slot_release(x, sk, KIND == 0 && isY);
  const bool landed = KIND != 0 && mbar_test2(x.bars + B_RF + 8 * sn, en >= 6);
  float s0 = 0.f, s1 = 0.f;
  const bool was_classic = KIND != 0 && a.classic;
  if (KIND == 0) {
    a.l0 = 0.f; a.l1 = 0.f;
    if (!half) exp_pack<16, 32>(S, Pn, s0, s1);
    else {
      #pragma unroll
      for (int i = 16; i < 32; i++) asm volatile("" : "=r"(Pn[i]));
    }
    exp_pack_diag(S, Pn, diag_limit(), s0, s1);
    uint32_t b0 = __ballot_sync(0xffffffff, s0 >= SUM_LO), b1 = __ballot_sync(0xffffffff, s1 >= SUM_LO);
    b0 |= b0 >> 1; b0 |= b0 >> 2; b1 |= b1 >> 1; b1 |= b1 >> 2;
    a.classic = __any_sync(0xffffffff, !(s0 <= SUM_HI && s1 <= SUM_HI)) || (b0 & b1 & 0x11111111u) != 0x11111111u;
  } else {
    exp_pack<0, 32>(S, Pn, s0, s1);
    a.classic = __any_sync(0xffffffff, a.classic || !(s0 <= SUM_HI && s1 <= SUM_HI));
  }
  fence_regs_u(Pn);
  TR(10);
  if (!landed) {
    mbar_wait(x.bars + B_RF + 8 * sn, en >= 6);
    if (more) mbar_wait(x.bars + B_RF + 8 * sn + 8, en >= 6);
  }
  wgmma_wait<0>();
  fence_regs(O);
  fence_regs_u(Po);
  TR(11);
  slot_release(x, sv, KIND == 1 && isY && pv != PV_ACC);
  if (!NO_CLASSIC && __builtin_expect(a.classic, 0)) {
    float sc0, sc1;
    classic_tile(S, Pn, KIND == 0, half, was_classic, a.mc, a.l0, a.l1, s0, s1, sc0, sc1);
    if (KIND != 0) {
      #pragma unroll
      for (int j = 0; j < 16; j++) { O[4*j] *= sc0; O[4*j+1] *= sc0; O[4*j+2] *= sc1; O[4*j+3] *= sc1; }
    }
  }
  a.l0 += s0; a.l1 += s1;
  e = en;
}

__device__ __forceinline__ int attention(Ctx& x, const uint8_t* items, int nitems, int rank, uint32_t (&PA)[32], uint32_t (&PB)[32], int vtile) {
  int e = 0;
  float O[64];
  Att a;
  volatile float mc[2];
  a.l0 = 1.f; a.l1 = 1.f; a.i0 = 0.f; a.i1 = 0.f; a.classic = false; a.mc = mc;
  int pv = PV_NONE, cur = -1;
#define DBGS()
  #pragma unroll 1
  for (int it = 0; ; it++) {
    const bool isY = (it & 1) == x.w;
    int pend = cur;
    if (it < nitems) {
      const int item = items[it];
      const bool half = isY == (rank != 0);
      cur = item * 4 + (isY ? 3 - rank : rank);
      int rem = 2 * (item & 7) + (isY ? 1 : 0);
      DBG(16 + it);
      q_proj(x, e, isY, PA, PB, vtile, it == 0);
      vtile = -1;
      DBGS();
      slot<0>(x, a, e, O, PA, PB, rem > 0, isY, half, pv, -1);
      pv = half ? PV_HALF : PV_ZERO;
      #pragma unroll 1
      while (rem > 0) {
        DBGS();
        slot<1>(x, a, e, O, PB, PA, rem > 1, isY, false, pv, pend);
        pv = PV_ACC; pend = -1;
        if (rem == 1) break;
        rem -= 2;
        DBGS();
        slot<2>(x, a, e, O, PA, PB, rem > 0, false, false, 0, -1);
      }
      if (isY) continue;
    } else {
      DBGS();
      slot_release(x, 6, false);
      const uint32_t dv = desc_lo(x.base, 8192) + ring_slot(e) * 2048;
      bar_sync(1 + x.w, 256);
      if (pv == PV_HALF) { wgmma_fence(); issue_pv<4>(O, PB, dv, 0); wgmma_commit(); }
      else { wgmma_fence(); issue_pv<8>(O, PB, dv, pv == PV_ACC); wgmma_commit(); }
      if (isY) bar_arrive(1 + (x.w ^ 1), 256);
      a.i0 = rcp_fast(quad_sum(a.l0)); a.i1 = rcp_fast(quad_sum(a.l1));
      ring_wait_full(x.bars, e);
      wgmma_wait<0>();
      fence_regs(O);
      fence_regs_u(PB);
      ring_release(x, e, false);
    }
    if (pend >= 0) {
      pack_tile(O, PB, a.i0, a.i1);
      if (it == nitems) return pend;
      store_ctx(x, pend, PB);
    }
    #pragma unroll
    for (int i = 0; i < 32; i++) asm volatile("mov.b32 %0, %1;" : "=r"(PB[i]) : "r"(PA[i]));
  }
}

#define LN_AT 2
#define X_AT 6
#define PERT 0
#define CTX_T 3
#define PF_AT 5
#define PF_N 4
#define PF_MOE 3
constexpr float QSCALE = 0.08838834764831845f * 1.4426950408889634f;
__device__ __forceinline__ void mod_cta(Ctx& x, const __nv_bfloat16* cvec) {
  const int t = wg_tid(), ct = x.w * 128 + t;
  #pragma unroll 1
  for (int k = 0; k < 6; k++) slot_release(x, k, false);
  const uint32_t cv = __ldg(reinterpret_cast<const uint32_t*>(cvec) + ct);
  asm volatile("st.shared.u32 [%0], %1;" :: "r"(x.base + SM_H2 + ct * 4),
               "r"(pack_bf16(__fdividef(bf_lo(cv), 1.f + __expf(-bf_lo(cv))), __fdividef(bf_hi(cv), 1.f + __expf(-bf_hi(cv))))) : "memory");
  bar_sync(5, 256);
  float acc[64];
  int e = 0;
  #pragma unroll 1
  for (int g = 0; g < 24; g++) {
    uint32_t a[8];
    #pragma unroll
    for (int i = 0; i < 8; i++) a[i] = lds_u32(x.base + SM_H2 + (g & 7) * 128 + i * 16 + (t & 3) * 4);
    ring_wait_full(x.bars, e);
    const uint32_t db = desc_lo(x.base + x.w * 16384, 8192) + ring_slot(e) * 2048;
    wgmma_fence();
    wgmma_rs_n128<1, 0, SW128>(acc, a[0], a[0], a[1], a[1], db, g & 7);
    wgmma_rs_n128<1, 128, SW128>(acc, a[2], a[2], a[3], a[3], db, 1);
    wgmma_rs_n128<1, 256, SW128>(acc, a[4], a[4], a[5], a[5], db, 1);
    wgmma_rs_n128<1, 384, SW128>(acc, a[6], a[6], a[7], a[7], db, 1);
    wgmma_commit();
    wgmma_wait<0>();
    fence_regs(acc);
    ring_release(x, e, false);
    e = ring_add(e, 1);
    if ((g & 7) == 7) {
      if (t < 4) {
        const float sc = (g == 7 && blockIdx.x < NCTA + 2) ? QSCALE : 1.f;
        uint32_t* dst = reinterpret_cast<uint32_t*>(g_mod + (g >> 3) * 1024 + (blockIdx.x - NCTA) * 256 + x.w * 128) + t;
        #pragma unroll
        for (int j = 0; j < 16; j++) dst[4 * j] = pack_bf16(rbf(acc[4*j]) * sc, rbf(acc[4*j+1]) * sc);
      }
      publish(x, g == 7 ? C_MOD : C_MOD2);
      DBG(1 + (g >> 3));
    }
  }
}

__global__ void __cluster_dims__(2, 1, 1) __launch_bounds__(384, 1)
k_fused(const __grid_constant__ CUtensorMap tmC, const __grid_constant__ CUtensorMap tmH, const __grid_constant__ CUtensorMap tmWq,
        const __grid_constant__ CUtensorMap tmWk, const __grid_constant__ CUtensorMap tmWv,
        const __grid_constant__ CUtensorMap tmWo, const __grid_constant__ CUtensorMap tmWg,
        const __grid_constant__ CUtensorMap tmWu, const __grid_constant__ CUtensorMap tmWm,
        const __grid_constant__ Sched sched,
        const __nv_bfloat16* __restrict__ xin,
        const __nv_bfloat16* __restrict__ cvec, const __nv_bfloat16* __restrict__ w_o,
        const __nv_bfloat16* __restrict__ w_r, const __nv_bfloat16* __restrict__ w_gate, const __nv_bfloat16* __restrict__ w_up,
        const __nv_bfloat16* __restrict__ w_down, __nv_bfloat16* __restrict__ out) {
  extern __shared__ __align__(1024) uint8_t smem_raw[];
  const uint32_t base = smem_u32(smem_raw), bars = base + SM_BAR;
  const int warp = __shfl_sync(0xffffffff, threadIdx.x >> 5, 0), wg = warp >> 2;
  const int rank = cluster_ctarank(), p = blockIdx.x >> 1;
  const int mt = (p & 7) * 2 + rank;
  const bool spare = blockIdx.x >= NCTA;
  #pragma unroll
  for (int i = 0; i < PERT; i++) { uint32_t d; asm volatile("mov.u32 %0, %%laneid;" : "=r"(d)); }
  {
    const int h0 = KHEAD0 + (p >> 3);
    #pragma unroll 1
    for (int t = warp == 8 ? 0 : warp < 8 ? warp + 1 : warp; t < B_PUB / 8; t += (warp == 8 ? 64 : 11))
      w_mbar_init(bars + 8 * t, t < B_WE / 8 ? 1 : t < B_RE / 8 ? 2 : 4);
    fence_mbar_init();
    cluster_arrive();
    if (warp == 9) prefetch_tmap(&tmWk);
    if (wg == 2) bar_arrive(1, 256);
    if (warp == 8 && !spare) {
      #pragma unroll 1
      for (int kb = 0; kb < 8; kb++) {
        w_expect_tx(bars + B_AF + 8 * kb, 16384);
        tma_load_2d(base + k_addrA(kb), &tmC, bars + B_AF + 8 * kb, kb * 64, mt * 128);
        if (kb == 0) cluster_wait();
        if (kb < 6) {
          w_expect_tx(bars + B_WF + 8 * kb, 16384);
          tma_load_2d_mc(base + k_addrW(kb) + rank * 8192, &tmWk, bars + B_WF + 8 * kb, h0 * 128 + rank * 64, kb * 64);
        }
      }
    }
  }
  const Sched::Pair& sp = sched.pair[p];
  const int nitems = sp.nitems, nsteps = sp.nsteps;
  auto oent = [&](int k) -> uint32_t { return sp.oent[k]; };
  const int ot = sp.otask, m = (ot & 7) * 2 + rank, grp = m * 8 + (ot >> 3);

  if (wg == 0) {
    asm volatile("setmaxnreg.dec.sync.aligned.u32 24;");
    const int lane = threadIdx.x & 31;
    #pragma unroll 1
    for (int t = B_PUB / 8 + warp; t < 80; t += 4) w_mbar_init(bars + 8 * t, t < B_RDY / 8 ? 4 : 1);
    bar_sync(6, 128);
    bar_arrive(7, 256); bar_arrive(8, 256);
    cluster_wait();
    const unsigned int tag = ld_relaxed(&g_epoch) + 1;
    if (warp == 0) {
      if (!spare) {
        int s = 0, ph = 0;
        tma_prefetch_2d(&tmWv, sp.khead[0] * 128 + rank * 64, (p & 7) * 64);
        #pragma unroll 1
        for (int g = 6; g < 64; g++) {
          const int u = g >> 3, kb = g & 7;
          if (kb == 0 && u < 7) tma_prefetch_2d((u & 1) ? &tmWk : &tmWv, sp.khead[(u + 1) >> 1] * 128 + rank * 64, (p & 7) * 64);
          mbar_wait(bars + B_WE + 8 * s, ph);
          w_expect_tx(bars + B_WF + 8 * s, 16384);
          tma_load_2d_mc(base + k_addrW(s) + rank * 8192, (u & 1) ? &tmWv : &tmWk, bars + B_WF + 8 * s, sp.khead[u >> 1] * 128 + rank * 64, kb * 64);
          if (++s == 6) { s = 0; ph ^= 1; }
        }
      }
      int s = 0, ph = 0;
      auto next_entry = [&](int bytes) {
        mbar_wait(bars + B_RE + 8 * s, ph);
        w_expect_tx(bars + B_RF + 8 * s, bytes);
      };
      auto advance = [&]() { if (++s == 6) { s = 0; ph ^= 1; } };
      if (spare) {
        #pragma unroll 1
        for (int g = 0; g < 24; g++) {
          if (g == 8) mbar_wait(bars + R_MOD, 0);
          next_entry(32768);
          for (int k = 0; k < 2; k++) tma_load_3d(base + s * 32768 + k * 16384, &tmWm, bars + B_RF + 8 * s, 0, (g & 7) * 64, (g >> 3) * 16 + (blockIdx.x - NCTA) * 4 + k * 2);
          advance();
        }
      }
      mbar_wait(bars + R_H1, 0);
      fence_async_global();
      int vrow = -1;
      #pragma unroll 1
      for (int i = 0; i <= nitems; i++) {
        const int item = sp.item[i & (MAX_ITEMS - 1)], h = item >> 3, j = item & 7;
        if (i < nitems) {
          const int row0 = j * 256 + ((i & 1) ? rank : 3 - rank) * 64, row1 = j * 256 + ((i & 1) ? 3 - rank : rank) * 64;
          #pragma unroll 1
          for (int kb = 0; kb < 8; kb++) {
            next_entry(32768);
            tma_load_2d_mc(base + s * 32768 + 16384 + rank * 8192, &tmWq, bars + B_RF + 8 * s, h * 128 + rank * 64, kb * 64);
            tma_load_2d(base + s * 32768, &tmH, bars + B_RF + 8 * s, kb * 64, row0);
            tma_load_2d(base + s * 32768 + 8192, &tmH, bars + B_RF + 8 * s, kb * 64, row1);
            advance();
          }
          mbar_wait(bars + R_ITEM + 8 * i, 0);
          fence_async_global();
        }
        #pragma unroll 1
        for (int n = i < nitems ? 4 * j + 3 : 0; n >= 0; n--) {
          const int krow = (h * 2 + rank) * SEQ + (n >> 1) * 128 + ((sp.lastuse[i & (MAX_ITEMS - 1)] >> (n >> 1)) & 1);
          const int row = (n & 1) ? krow : vrow;
          if (i + 1 == nitems && n == min(4 * j + 3, 2 * PF_AT + 1)) w_arrive(bars + R_NEAR);
          next_entry(row >= 0 ? 32768 : 0);
          if (row >= 0) bulk_load_mc(base + s * 32768 + rank * 16384, sched.kvc + (size_t)(row & ~1) * 64, bars + B_RF + 8 * s, row & 1);
          advance();
          if (!(n & 1)) vrow = krow + 64 * SEQ;
        }
      }
      if (!spare) {
      const int oc = ((ot >> 3) & 1) * 4 + rank * 2;
      auto o_next = [&](int k, int bytes) {
        const uint32_t v = oent(k); s = v & 7;
        mbar_wait(bars + B_RE + 8 * s, v >> 3);
        w_expect_tx(bars + B_RF + 8 * s, bytes);
      };
      #pragma unroll 1
      for (int i = 0; i < nsteps; i++) {
        const int c0 = sp.ochunk[i][0], c1 = sp.ochunk[i][1];
        if (i >= PF_MOE && i < PF_MOE + 3)
          bulk_prefetch((i == PF_MOE ? w_gate : i == PF_MOE + 1 ? w_up : w_down) + (size_t)blockIdx.x * (DM * FF / NCTA), DM * FF / NCTA * 2);
        if (c0 < 64) { o_next(3 * i, 32768); tma_load_3d_mc(base + s * 32768 + rank * 16384, &tmWo, bars + B_RF + 8 * s, 0, c0 * 64, oc); }
        mbar_wait(bars + R_CTX + 8 * i, 0);
        fence_async_global();
        o_next(3 * i + 1, c0 < 64 ? 32768 : 16384);
        if (c0 < 64) bulk_load(base + s * 32768, sched.kvc + (size_t)((128 + c0) * SEQ + m * 128) * 64, 16384, bars + B_RF + 8 * s);
        bulk_load(base + s * 32768 + 16384, sched.kvc + (size_t)((128 + c1) * SEQ + m * 128) * 64, 16384, bars + B_RF + 8 * s);
        o_next(3 * i + 2, 32768);
        tma_load_3d_mc(base + s * 32768 + rank * 16384, &tmWo, bars + B_RF + 8 * s, 0, c1 * 64, oc);
      }
      const int f0 = (blockIdx.x < FF / 16 ? blockIdx.x : 0) * 16;
      o_next(3 * nsteps, 32768);
      bulk_load(base + s * 32768, w_down + (size_t)f0 * DM, 16384, bars + B_RF + 8 * s);
      bulk_load(base + s * 32768 + 16384, xin + (size_t)grp * 16 * DM, 16384, bars + B_RF + 8 * s);
      o_next(3 * nsteps + 1, 32768);
      #pragma unroll 1
      for (int k = 0; k < 4; k++) tma_load_2d(base + s * 32768 + k * 8192, (k & 2) ? &tmWu : &tmWg, bars + B_RF + 8 * s, f0, (k & 1) * 256);
      #pragma unroll 1
      for (int k = 0; k < 4; k++) w_expect_tx(bars + R_PART + 8 * k, 16384);
      mbar_wait(bars + B_PUB + 8 * (5 + nitems), 0);
      mbar_wait(bars + B_PUB + 8 * (NPUB + 5 + nitems), 0);
      uint32_t todo = 0xff;
      #pragma unroll 1
      for (int n = 0; n < WAIT_LIM && todo; n++) {
        uint32_t now = __ballot_sync(0xffffffff, ld_acquire(&g_cnt[C_PART + (m * 2 + (ot >> 5)) * 32 + (lane & 7)]) == tag) & todo;
        todo &= ~now;
        fence_async_global();
        #pragma unroll 1
        for (; now; now &= now - 1) {
          const int q = __ffs(now) - 1;
          bulk_load(base + (oent(3 * nsteps - 3 + (q >> 2)) & 7) * 32768 + (q & 3) * 8192, sched.part + (grp * 8 + q) * 4096, 8192, bars + R_PART + 8 * (q >> 1));
        }
      }
      DBGP(11);
      }
    } else if (warp < 3) {
      const int w = warp - 1, n1 = w * NPUB + (spare ? 3 : 6) + nitems;
      #pragma unroll 1
      for (int n = w * NPUB; n < n1; n++) {
        #pragma unroll 1
        for (int k = 0; k < 8 * WAIT_LIM; k++) { if (mbar_try(bars + B_PUB + 8 * n, 0)) break; }
        const uint32_t idx = lds_u32(base + SM_MAIL + 4 * n);
        fence_async_global();
        if (lane == 0 && idx < (unsigned)C_END) red_release(idx);
        __syncwarp();
      }
    } else {
      *reinterpret_cast<volatile uint32_t*>(smem_raw + SM_KEY + 48) = tag;
      if (!spare) { mbar_wait(bars + B_AF + 8 * X_AT, 0); bulk_prefetch(xin + (size_t)blockIdx.x * 16 * DM, 16 * DM * 2); }
      #pragma unroll 1
      for (int n = 0; n < 8 + nsteps; n++) {
        if (n == 2 + nitems) n = 7;
        int idx = n == 0 ? C_MOD : n == 1 ? C_H1 : C_MOD2, cnt = n == 0 ? 8 : n == 1 ? 256 : 16;
        if (n >= 1 && n <= nitems) { const int item = sp.item[n - 1]; tma_prefetch_2d(&tmWq, (item >> 3) * 128 + rank * 64, (item & 7) * 64); }
        if (n >= 2 && n < 7) { idx = C_KV + (sp.item[n - 2] >> 3); cnt = 32; }
        if (n >= 8) { const int c0 = sp.ochunk[n - 8][0], c1 = sp.ochunk[n - 8][1]; idx = C_CTX + (((lane & 1) && c0 < 64 ? c0 : c1) >> 1) * 8 + (ot & 7); cnt = 4; }
        wait_count_lazy(idx, cnt * tag);
        w_arrive(bars + B_RDY + 8 * n);
        if (n == 0) DBGP(12);
        if (n == 8 + PF_N - 1) {
          #pragma unroll 1
          for (int k = 0; k < 8 * WAIT_LIM; k++) { if (mbar_try(bars + R_NEAR, 0)) break; }
          bulk_prefetch(w_o + (size_t)blockIdx.x * (NH * DH * DM / NCTA), NH * DH * DM / NCTA * 2);
          #pragma unroll 1
          for (int k = 0; k < PF_N; k++) {
            const int cc = sp.ochunk[k][(ot >> 3) & 1];
            if (cc < 64) bulk_prefetch(sched.kvc + ((size_t)(128 + cc) * SEQ + m * 128) * 64, 16384);
          }
        }
      }
    }
    __syncwarp();
    cluster_arrive();
    if (!spare) {
      bar_sync(6, 128);
      asm volatile("setmaxnreg.inc.sync.aligned.u32 88;");
      const int pos = blockIdx.x * 4 + (lane & 1) * 2, col = (blockIdx.x >> 2) * 16 + (blockIdx.x & 3) * 2 + (lane & 1) * 8, src = threadIdx.x >> 1;
      uint32_t gbest = 0, hh = 0, gbf = 0;
      uint2 xx = make_uint2(0, 0);
      uint4 ya = make_uint4(0, 0, 0, 0), yb = make_uint4(0, tag, 0, tag);
      auto poll_y = [&]() {
        if (ya.y != tag || ya.w != tag) ya = ld_tagged2(&g_yll[src][pos]);
        if (yb.y != tag || yb.w != tag) yb = ld_tagged2(&g_yll[src + 64][pos]);
        return __all_sync(0xffffffff, ya.y == tag && ya.w == tag && yb.y == tag && yb.w == tag);
      };
      ya.y = tag - 1; if (src + 64 < FF / 16) yb.y = tag - 1;
      poll_y();
      if (warp == 3) {
        gbf = __ldcg(reinterpret_cast<const uint32_t*>(g_mod + 5 * DM + col));
        uint32_t have = 0;
        uint2 k[4];
        #pragma unroll
        for (int i = 0; i < 4; i++) k[i] = make_uint2(0, tag - 1);
        #pragma unroll 1
        for (int n = 0; n < WAIT_LIM; n++) {
          #pragma unroll
          for (int i = 0; i < 4; i++) if (k[i].y != tag) k[i] = ld_tagged(&g_keys[i * 32 + lane][0]);
          if (gbest != have) {
            const int g = ((0xffffu - gbest) >> 4) & 127;
            uint4 hv[4];
            #pragma unroll
            for (int i = 0; i < 4; i++) hv[i] = ld_tagged2(&g_row[g][0][i * 64 + lane * 2]);
            xx = ld_tagged(&g_row[g][1][col >> 1]);
            bool ok = xx.y == tag;
            #pragma unroll
            for (int i = 0; i < 4; i++) { ok = ok && hv[i].y == tag && hv[i].w == tag; reinterpret_cast<uint2*>(smem_raw + SM_H2)[i * 32 + lane] = make_uint2(hv[i].x, hv[i].z); }
            if (lane == 0) *reinterpret_cast<uint32_t*>(smem_raw + SM_KEY + 32) = gbest;
            have = __all_sync(0xffffffff, ok) ? gbest : 0;
          }
          bool all = true;
          #pragma unroll
          for (int i = 0; i < 4; i++) { all = all && k[i].y == tag; gbest = max(gbest, k[i].y == tag ? k[i].x : 0u); }
          gbest = __reduce_max_sync(0xffffffff, gbest);
          if (__all_sync(0xffffffff, all) && gbest == have) break;
        }
        w_arrive(bars + R_KEY);
        if (blockIdx.x == 0 && lane == 0) g_epoch = tag;
        hh = lds_u32(base + SM_H2 + col * 2);
        DBGP(13);
      }
      const uint32_t sb16 = gbest & 0xffff0000u;
      const float rsel = __uint_as_float((sb16 & 0x80000000u) ? (sb16 & 0x7fffffffu) : (~sb16 & 0xffff0000u));
      const float rs = rbf(__fdividef(1.f, 1.f + __expf(-rsel)));
      mbar_wait(bars + R_KEY, 1);
      #pragma unroll 1
      for (int n = 0; n < WAIT_LIM; n++) { if (poll_y()) break; }
      float y0 = __uint_as_float(ya.x) + __uint_as_float(yb.x), y1 = __uint_as_float(ya.z) + __uint_as_float(yb.z);
      #pragma unroll
      for (int o = 2; o < 32; o <<= 1) { y0 += __shfl_xor_sync(0xffffffff, y0, o); y1 += __shfl_xor_sync(0xffffffff, y1, o); }
      float2* s_y = reinterpret_cast<float2*>(smem_raw + SM_KEY + 64);
      if (lane < 2) s_y[warp * 2 + lane] = make_float2(y0, y1);
      bar_sync(6, 128);
      if (warp == 3 && lane < 2) {
        y0 = 0.f; y1 = 0.f;
        #pragma unroll
        for (int i = 0; i < 4; i++) { y0 += reinterpret_cast<const float*>(s_y)[i * 4 + lane]; y1 += reinterpret_cast<const float*>(s_y)[i * 4 + 2 + lane]; }
        const float o0 = bf_lo(xx.x) + rbf(bf_lo(gbf) * rbf(bf_lo(hh) + rbf(rbf(y0) * rs)));
        const float o1 = bf_hi(xx.x) + rbf(bf_hi(gbf) * rbf(bf_hi(hh) + rbf(rbf(y1) * rs)));
        *reinterpret_cast<uint32_t*>(out + (size_t)((0xffffu - gbest) & (SEQ - 1)) * DM + col) = pack_bf16(o0, o1);
      }
      DBGP(14);
    }
    __syncwarp();
    cluster_wait();
  } else {
    asm volatile("setmaxnreg.inc.sync.aligned.u32 240;");
    Ctx x;
    x.w = wg - 1; x.base = base; x.bars = bars; x.nev = 0; x.sched = &sched;
    const int w = x.w, warp4 = warp & 3;
    x.rel = mapa(bars, (warp4 & 1) ^ 1);
    x.rel1 = (threadIdx.x & 127) == 32 || (threadIdx.x & 127) == 64;
    if (warp != 8 || spare) cluster_wait();
    if (w == 1 || spare) bar_sync(7 + w, 256);
    DBG(1);
    uint32_t PA[32], PB[32];
    int vtile = -1;
    if (spare) {
      mod_cta(x, cvec);
    } else {
      const int lane = wg_tid() & 31;
      Row xn[2];
      float acc0[64], acc1[64];
      int s = 2 * w, ph = w;
      #pragma unroll 1
      for (int u = w; u < 8; u += 2) {
        bar_sync(1 + w, 256);
        DBG(4 + (u >> 1) * 3);
        int ps = 0;
        #pragma unroll 1
        for (int kb = 0; kb < 8; kb++) {
          if (u < 2) mbar_wait(bars + B_AF + 8 * kb, 0);
          mbar_wait(bars + B_WF + 8 * s, ph);
          const uint32_t da = desc_lo(base + k_addrA(kb), 16), dw = desc_lo(base + k_addrW(s), 8192);
          wgmma_fence();
          kblock_n128<0>(acc0, da, dw, kb != 0);
          kblock_n128<512>(acc1, da, dw, kb != 0);
          wgmma_commit();
          if (kb == 7) bar_arrive(1 + (w ^ 1), 256);
          if (kb > 0) {
            wgmma_wait<1>();
            mbar_arrive_remote_if(x.rel + B_WE + 8 * ps, x.rel1);
            if (u == 7 && !(kb & 1)) {
              ring_release(x, kb == 2 ? 0 : kb - 3, false);
              if (kb > 2) ring_release(x, kb - 2, false);
            }
          }
          ps = s;
          if (++s == 6) { s = 0; ph ^= 1; }
        }
        Row t[2];
        const int lrow = blockIdx.x * 16 + w * 8 + warp4 * 2;
        if (u == w) { t[0] = ldg_row(xin + (size_t)lrow * DM, lane); t[1] = ldg_row(xin + (size_t)(lrow + 1) * DM, lane); }
        if (u == LN_AT || u == LN_AT + 1) {
          mbar_wait(bars + R_MOD, 0);
          t[0] = ldca_row(g_mod, lane); t[1] = ldca_row(g_mod + DM, lane);
        }
        wgmma_wait<0>();
        fence_regs(acc0); fence_regs(acc1);
        DBG(5 + (u >> 1) * 3);
        mbar_arrive_remote_if(x.rel + B_WE + 8 * ps, x.rel1);
        if (u == 6) { for (int k = 0; k < 5; k++) ring_release(x, k, false); }
        if (u >= 6) ring_release(x, 5, false);
        if (V_AT >= 0 && u == 7) {
          pack_tile(acc0, PA, 1.f, 1.f); pack_tile(acc1, PB, 1.f, 1.f);
          vtile = sp.khead[3] * 16 + mt;
          break;
        }
        s += 2; ph ^= 1; if (s >= 6) { s -= 6; ph ^= 1; }
        if (u == 0) bar_sync(7, 256);
        if (u == w) {
          float st[4] = {0.f, 0.f, 0.f, 0.f};
          #pragma unroll
          for (int i = 0; i < 32; i++) { const float v = row_at(t[i >> 4], i & 15); st[(i >> 4) * 2] += v; st[(i >> 4) * 2 + 1] = fmaf(v, v, st[(i >> 4) * 2 + 1]); }
          warp_sums(st);
          #pragma unroll
          for (int r = 0; r < 2; r++) { ln_stats(st[2*r], st[2*r+1]); xn[r] = ln_apply(t[r], st[2*r], st[2*r+1] * QSCALE); }
        }
        if ((u == LN_AT || u == LN_AT + 1)) {
          #pragma unroll
          for (int r = 0; r < 2; r++) store_row(sched.h1 + (size_t)(lrow + r) * DM, lane, fma_row(xn[r], one_plus(t[1]), t[0]));
        }
        const int tile = sp.khead[u >> 1] * 16 + mt;
        __nv_bfloat16* dst = kv_tile(x, tile);
        uint32_t D[32];
        pack_tile(acc0, D, 1.f, 1.f); store_tile(dst + 2048, D);
        pack_tile(acc1, D, 1.f, 1.f); store_tile(dst, D);
        if (u == LN_AT || u == LN_AT + 1) publish(x, C_H1);
        publish(x, C_KV + (tile >> 4));
        DBG(6 + (u >> 1) * 3);
      }
    }
    x.tr = base + SM_RED + w * 1024;
    const int last = attention(x, sp.item, nitems, rank, PA, PB, vtile);
    DBG(100);
    const int lane = wg_tid() & 31, cw = w * 4 + warp4, ct = cw * 32 + lane;
    const int row0 = grp * 16 + cw * 2;
    const bool moe_cta = blockIdx.x < FF / 16;
    if (spare) { store_ctx(x, last, PB); __syncwarp(); cluster_arrive(); cluster_wait(); return; }
    const int kl = 3 * nsteps - 3;
    {
      float accA[64], accB[64];
      const int t0 = oent(0) == oent(1);
      uint32_t pa = 0, pb = 0;
      #pragma unroll 1
      for (int t = t0; t < 2 * nsteps - 2; t++) {
        const uint32_t eb = oent(3 * (t >> 1) + 2 * (t & 1)), ea = oent(3 * (t >> 1) + 1);
        o_wait_full(bars, eb);
        o_wait_full(bars, ea);
        const uint32_t da = desc_lo(base + w * 4096, 16) + (ea & 7) * 2048 + (t & 1) * 1024, db = desc_lo(base, 8192) + (eb & 7) * 2048;
        wgmma_fence();
        kblock_n128<0, 0, SW64>(accA, da, db, t != t0); kblock_n128<0, 1024, SW64>(accB, da, db, t != t0);
        wgmma_commit();
        if (t == CTX_T) store_ctx(x, last, PB);
        if (t > t0) { wgmma_wait<1>(); slot_release(x, pb, false); if (!(t & 1)) slot_release(x, pa, false); }
        pa = ea & 7; pb = eb & 7;
      }
      const uint32_t e0 = oent(kl), ea = oent(kl + 1), eb = oent(kl + 2);
      const uint32_t da = desc_lo(base + w * 4096, 16) + (ea & 7) * 2048;
      const uint32_t db0 = desc_lo(base, 8192) + (e0 & 7) * 2048, db1 = desc_lo(base, 8192) + (eb & 7) * 2048;
      o_wait_full(bars, e0);
      o_wait_full(bars, ea);
      o_wait_full(bars, eb);
      wgmma_fence();
      kblock_n128<0, 0, SW64>(accA, da, db0, 1); kblock_n128<1024, 0, SW64>(accA, da, db1, 1);
      wgmma_commit();
      kblock_n128<0, 1024, SW64>(accB, da, db0, 1); kblock_n128<1024, 1024, SW64>(accB, da, db1, 1);
      wgmma_commit();
      __syncwarp();
      cluster_arrive();
      __nv_bfloat16* dst = sched.part + ((m * 8 + cw) * 8 + (ot >> 3)) * 4096;
      auto send = [&](const float (&acc)[64], int h) {
        uint32_t D[32];
        pack_tile(acc, D, 1.f, 1.f);
        #pragma unroll
        for (int i = 0; i < 8; i++) stg_v4(dst + (h * 8 + i) * 256 + ((lane ^ (h * 4 + (i >> 1))) << 3), D[4*i], D[4*i+1], D[4*i+2], D[4*i+3]);
      };
      wgmma_wait<1>();
      fence_regs(accA);
      DBG(120);
      send(accA, 0);
      o_wait_full(bars, eb);
      wgmma_wait<0>();
      fence_regs(accB);
      DBG(101);
      send(accB, 1);
      publish(x, C_PART + (m * 2 + w) * 32 + (ot >> 3));
      DBG(121);
      DBG(102);
    }
    asm volatile("setmaxnreg.dec.sync.aligned.u32 208;");
    const Row ga = ldca_row(g_mod + 2 * DM, lane), sb = ldca_row(g_mod + 3 * DM, lane), cb = ldca_row(g_mod + 4 * DM, lane), gb = ldca_row(g_mod + 5 * DM, lane);
    const Row wr = ldca_row(w_r, lane);
    const uint32_t sD = base + (oent(kl + 3) & 7) * 32768, sW = base + (oent(kl + 4) & 7) * 32768;
    o_wait_full(bars, oent(kl + 3)); o_wait_full(bars, oent(kl + 4));
    Row x1[2];
    #pragma unroll
    for (int r = 0; r < 2; r++) x1[r] = lds_row(sD + 16384 + (cw * 2 + r) * 1024, lane);
    uint4 wgv[4], wuv[4], wdv[4];
    #pragma unroll
    for (int r = 0; r < 4; r++) {
      const uint32_t k = (lane & 7) + ((lane >> 4) << 3), h = (lane & 8) * 2;
      wgv[r] = ldsm_x4_t(sW + (cw * 64 + r * 16 + k) * 32 + h);
      wuv[r] = ldsm_x4_t(sW + 16384 + (cw * 64 + r * 16 + k) * 32 + h);
      wdv[r] = ldsm_x4_t(sD + k * 1024 + (cw * 64 + r * 16) * 2 + h);
    }
    const Row cb1 = one_plus(cb);
    const unsigned int tag = lds_u32(base + SM_KEY + 48);
    DBG(103);
    float u[16], ub[2] = {0.f, 0.f};
    #pragma unroll
    for (int i = 0; i < 16; i++) { u[i] = row_at(cb1, i) * row_at(wr, i); ub[0] += u[i]; ub[1] = fmaf(row_at(sb, i), row_at(wr, i), ub[1]); }
    warp_sums(ub);
    float st[6] = {0.f, 0.f, 0.f, 0.f, 0.f, 0.f};
    uint32_t key[2];
    {
      const uint32_t po = base + ((lane & 7) * 2 + (cw >> 2)) * 512 + (cw & 3) * 128;
      Row av[2][2];
      #pragma unroll
      for (int k = 0; k < 4; k++) {
        mbar_wait(bars + R_PART + 8 * k, 1);
        const uint32_t pa = po + (oent(kl + (k >> 1)) & 7) * 32768 + (k & 1) * 16384;
        #pragma unroll
        for (int r = 0; r < 2; r++) {
          const uint32_t sw = ((r * 4 + (lane >> 3)) ^ (lane & 7)) << 4;
          const uint4 lo = ldsm_x4(pa + sw), hi = ldsm_x4(pa + 8192 + sw);
          const Row v{{lo.x, lo.y, lo.z, lo.w, hi.x, hi.y, hi.z, hi.w}};
          av[r][k >> 1] = (k & 1) ? add_row(av[r][k >> 1], v) : v;
        }
      }
      DBG(104);
      #pragma unroll
      for (int r = 0; r < 2; r++) {
        x1[r] = fma_row(ga, add_row(av[r][0], av[r][1]), x1[r]);
        #pragma unroll
        for (int i = 0; i < 16; i++) { const float v = row_at(x1[r], i); st[3*r] += v; st[3*r+1] = fmaf(v, v, st[3*r+1]); st[3*r+2] = fmaf(v, u[i], st[3*r+2]); }
      }
      warp_sums(st);
      #pragma unroll
      for (int r = 0; r < 2; r++) {
        ln_stats(st[3*r], st[3*r+1]);
        const uint32_t rb = pack_bf16(0.f, fmaf(st[3*r+1], fmaf(-st[3*r], ub[0], st[3*r+2]), ub[1]));
        key[r] = (((rb & 0x80000000u) ? ~rb : (rb | 0x80000000u)) & 0xffff0000u) | (0xffffu - (uint32_t)(row0 + r));
      }
    }
    DBG(105);
    float* s_red = reinterpret_cast<float*>(smem_raw + SM_RED);
    uint32_t* s_key = reinterpret_cast<uint32_t*>(smem_raw + SM_KEY);
    const int rb = key[1] > key[0];
    const uint32_t wbest = rb ? key[1] : key[0];
    if (lane == 0) s_key[cw] = wbest;
    bar_sync(5, 256);
    const uint32_t cbest = __reduce_max_sync(0xffffffff, s_key[lane & 7]);
    if (wbest == cbest && lane == 0) st_tagged(&g_keys[grp][0], cbest, tag);
    Row xb, xo;
    #pragma unroll
    for (int i = 0; i < 8; i++) { xb.v[i] = rb ? x1[1].v[i] : x1[0].v[i]; xo.v[i] = rb ? x1[0].v[i] : x1[1].v[i]; }
    const Row hb = fma_row(ln_apply(xb, rb ? st[3] : st[0], rb ? st[4] : st[1]), cb1, sb);
    if (wbest == cbest) {
      #pragma unroll
      for (int i = 0; i < 4; i++) st_tagged2(&g_row[grp][0][(i >> 1) * 128 + lane * 4 + (i & 1) * 2], hb.v[2*i], hb.v[2*i+1], tag);
      #pragma unroll
      for (int i = 0; i < 4; i++) st_tagged2(&g_row[grp][1][(i >> 1) * 128 + lane * 4 + (i & 1) * 2], xb.v[2*i], xb.v[2*i+1], tag);
    }
    DBG(106);
    const Row ob = fma_row(gb, hb, xb);
    if (wbest != cbest) store_row(out + (size_t)(row0 + rb) * DM, lane, ob);
    store_row(out + (size_t)(row0 + 1 - rb) * DM, lane, fma_row(gb, fma_row(ln_apply(xo, rb ? st[0] : st[3], rb ? st[1] : st[4]), cb1, sb), xo));
    mbar_wait(bars + R_KEY, 1);
    DBG(107);
    if (moe_cta) {
      float cg[4] = {0, 0, 0, 0}, cu[4] = {0, 0, 0, 0};
      #pragma unroll
      for (int r = 0; r < 4; r++) {
        const uint32_t b0 = lds_u32(base + SM_H2 + (cw * 64 + r * 16) * 2 + (lane & 3) * 4), b1 = lds_u32(base + SM_H2 + (cw * 64 + r * 16) * 2 + 16 + (lane & 3) * 4);
        mma16816(cg, wgv[r], b0, b1); mma16816(cu, wuv[r], b0, b1);
      }
      s_red[cw * 32 + (lane & 3) * 8 + (lane >> 2)] = (lane & 2) ? ((lane & 1) ? cu[2] : cu[0]) : ((lane & 1) ? cg[2] : cg[0]);
      bar_sync(5, 256);
      float g = 0.f;
      #pragma unroll
      for (int i = 0; i < 8; i++) g += s_red[i * 32 + lane];
      g = rbf(g);
      const float act = rbf(__fdividef(g, 1.f + __expf(-g))) * __shfl_down_sync(0xffffffff, g, 16);
      const uint32_t a2 = pack_bf16(act, __shfl_down_sync(0xffffffff, act, 1));
      const uint32_t b0 = __shfl_sync(0xffffffff, a2, (lane & 3) * 2), b1 = __shfl_sync(0xffffffff, a2, (lane & 3) * 2 + 8);
      float y0 = 0.f, y1 = 0.f;
      #pragma unroll
      for (int r = 0; r < 4; r++) {
        float c[4] = {0, 0, 0, 0};
        mma16816(c, wdv[r], b0, b1);
        if ((lane & 3) == r) { y0 = c[0]; y1 = c[2]; }
      }
      st_tagged2(&g_yll[blockIdx.x][cw * 64 + (lane & 3) * 16 + (lane >> 2) * 2], __float_as_uint(y0), __float_as_uint(y1), tag);
    }
    DBG(108);
    if (wbest == cbest && wbest != s_key[8]) store_row(out + (size_t)(row0 + rb) * DM, lane, ob);
    DBG(109);
    __syncwarp();
    cluster_wait();
  }
}

typedef CUresult (*EncodeFn)(CUtensorMap*, CUtensorMapDataType, cuuint32_t, void*, const cuuint64_t*, const cuuint64_t*, const cuuint32_t*,
                             const cuuint32_t*, CUtensorMapInterleave, CUtensorMapSwizzle, CUtensorMapL2promotion, CUtensorMapFloatOOBfill);

struct HostState {
  bool ready = false;
  EncodeFn encode = nullptr;
  CUtensorMap tmC, tmH, tmWq, tmWk, tmWv, tmWo, tmWg, tmWu, tmWm;
  Sched sched;
};

void make_map(EncodeFn enc, CUtensorMap* m, const void* ptr, int rank, const cuuint64_t* dims, const cuuint64_t* strides, const cuuint32_t* box, bool swizzle = true) {
  const cuuint32_t es[3] = {1, 1, 1};
  enc(m, CU_TENSOR_MAP_DATA_TYPE_BFLOAT16, rank, const_cast<void*>(ptr), dims, strides, box, es, CU_TENSOR_MAP_INTERLEAVE_NONE,
      swizzle ? CU_TENSOR_MAP_SWIZZLE_128B : CU_TENSOR_MAP_SWIZZLE_NONE, swizzle ? CU_TENSOR_MAP_L2_PROMOTION_L2_128B : CU_TENSOR_MAP_L2_PROMOTION_NONE, CU_TENSOR_MAP_FLOAT_OOB_FILL_NONE);
}
void make_2d(EncodeFn enc, CUtensorMap* m, const void* ptr, int rows, int cols, int box_rows) {
  const cuuint64_t dims[2] = {(cuuint64_t)cols, (cuuint64_t)rows}, strides[1] = {(cuuint64_t)cols * 2};
  const cuuint32_t box[2] = {64, (cuuint32_t)box_rows};
  make_map(enc, m, ptr, 2, dims, strides, box);
}
void make_3d(EncodeFn enc, CUtensorMap* m, const void* ptr, int rows, int chunks, size_t row_stride, size_t chunk_stride) {
  const cuuint64_t dims[3] = {64, (cuuint64_t)rows, (cuuint64_t)chunks}, strides[2] = {row_stride, chunk_stride};
  const cuuint32_t box[3] = {64, 64, 2};
  make_map(enc, m, ptr, 3, dims, strides, box);
}

void make_ffn(EncodeFn enc, CUtensorMap* m, const void* ptr) {
  const cuuint64_t dims[2] = {(cuuint64_t)FF, (cuuint64_t)DM}, strides[1] = {(cuuint64_t)FF * 2};
  const cuuint32_t box[2] = {16, 256};
  make_map(enc, m, ptr, 2, dims, strides, box, false);
}

#define SR 0x213312
#define SEED 12345
#define LU_MARGIN 0
#define SPARE_N 3
void build_sched(Sched& s) {
  memset(&s, 0, sizeof(s));
  const int NP = NCTA / 2, korder[4] = {(KORDER >> 12) & 3, (KORDER >> 8) & 3, (KORDER >> 4) & 3, KORDER & 3};
  const int sround[4][2][3] = {{}, {{1}, {2}}, {{1, 2}, {1, 2}}, {{(SR >> 20) & 3, (SR >> 16) & 3, (SR >> 12) & 3}, {(SR >> 8) & 3, (SR >> 4) & 3, SR & 3}}};
  int jv[4][NP], used[4][8] = {};
  for (int r = 0; r < 4; r++) for (int p = 0; p < NP; p++) jv[r][p] = (r & 2) ? 7 - ((p + 4 * (r & 1)) & 7) : (p + 4 * (r & 1)) & 7;
  for (int q = 0; q < 2; q++) {
    s.pair[NP + q].nitems = SPARE_N;
    for (int i = 0; i < SPARE_N; i++) {
      const int r = sround[SPARE_N][q][i];
      s.pair[NP + q].item[i] = (uint8_t)((r * 8 + used[r][6]++) * 8 + 6);
      for (int p = 0; p < NP; p++) if (jv[r][p] == 6) { jv[r][p] = -2; break; }
    }
  }
  auto cost = [&](int p) {
    int u = 8 - ((p >> 4) < SPARE_N ? 21 : 22), z = 0, none = 0;
    for (int r = 0; r < 4; r++) { u += jv[r][p]; z += jv[r][p] == 0; none += jv[r][p] < 0; }
    return 4 * u * u + (z > 1) + 4 * (none > 1);
  };
  uint32_t rng = SEED;
  for (int it = 0; it < 2000000; it++) {
    if ((it & 255) == 0) { int t = 0; for (int p = 0; p < NP; p++) t += cost(p); if (t == 0) break; }
    rng = rng * 1664525u + 1013904223u;
    const int r = (rng >> 8) & 3, a = (rng >> 12) & 63, b = (rng >> 20) & 63, before = cost(a) + cost(b);
    int t = jv[r][a]; jv[r][a] = jv[r][b]; jv[r][b] = t;
    if (cost(a) + cost(b) > before) { jv[r][b] = jv[r][a]; jv[r][a] = t; }
  }
  int fin[256], done[256];
  for (int p = 0; p < NP + 2; p++) {
    Sched::Pair& q = s.pair[p];
    if (p < NP) {
      for (int k = 0; k < 4; k++) q.khead[k] = (uint8_t)(korder[k] * 8 + (p >> 3));
      for (int r = 0; r < 4; r++) {
        if (jv[r][p] < 0) continue;
        q.item[q.nitems++] = (uint8_t)((r * 8 + used[r][jv[r][p]]++) * 8 + jv[r][p]);
      }
    }
    int t = p < NP ? 0 : -3, e = 1;
    for (int i = 0; i < q.nitems; i++) { t += (q.item[i] & 7) + 2; fin[q.item[i]] = t; done[q.item[i]] = t + (i + 1 < q.nitems ? 2 : 0); e += 8 + 4 * ((q.item[i] & 7) + 1); }
    for (int k = 0; k < 3 * MAX_STEPS + 6; k++) {
      const int n = k > 0 ? k - (SPARE_N & 1) : 0, r = n % 7, f = (e + (r < 4 ? r : r - 1)) % 12;
      q.oent[k] = (uint8_t)((r == 4 ? 6 : f >= 6 ? f + 2 : f) ^ (((n / 7) & 1) << 3));
    }
  }
  for (int p = 0; p < NP + 2; p++)
    for (int i = 0; i < s.pair[p].nitems; i++) {
      const int it = s.pair[p].item[i];
      for (int n = 0; n < 2 * (it & 7) + 2; n++) {
        bool last = true;
        for (int j = n >> 1; j < 8; j++) { const int o = (it & ~7) + j; if (o != it && fin[o] + LU_MARGIN > fin[it]) last = false; }
        if (last) s.pair[p].lastuse[i] |= (uint16_t)(1 << n);
      }
    }
  for (int j = 0; j < 8; j++) {
    int order[NH], left[4];
    for (int h = 0; h < NH; h++) { int k = h; for (; k > 0 && done[order[k - 1] * 8 + j] < done[h * 8 + j]; k--) order[k] = order[k - 1]; order[k] = h; }
    for (int kq = 0; kq < 4; kq++) {
      left[kq] = SPARE_N == 0 ? 16 : kq < SPARE_N ? 20 - SPARE_N : 16 - SPARE_N;
      for (int nh = 0; nh < 2; nh++) { Sched::Pair& q = s.pair[kq * 16 + nh * 8 + j]; q.otask = (uint8_t)(kq * 16 + nh * 8 + j); q.nsteps = (uint8_t)((left[kq] + 1) / 2); q.ochunk[0][0] = 255; }
    }
    for (int n = 0, kq = 0, run = 0; n < 64; ) {
      if (left[kq] > 0 && run < 2) {
        const int pos = --left[kq] + (SPARE_N & 1);
        for (int nh = 0; nh < 2; nh++) s.pair[kq * 16 + nh * 8 + j].ochunk[pos >> 1][pos & 1] = (uint8_t)(order[n >> 1] * 2 + 1 - (n & 1));
        n++; run++;
      } else { kq = (kq + 1) & 3; run = 0; }
    }
  }
}

}

extern "C" void kernel_launch(void* const* d_in, const int* in_sizes, int n_in, void* d_out, int out_size) {
  (void)in_sizes; (void)n_in; (void)out_size;
  const __nv_bfloat16* x     = (const __nv_bfloat16*)d_in[0];
  const __nv_bfloat16* ckv   = (const __nv_bfloat16*)d_in[1];
  const __nv_bfloat16* w_q   = (const __nv_bfloat16*)d_in[2];
  const __nv_bfloat16* w_uk  = (const __nv_bfloat16*)d_in[3];
  const __nv_bfloat16* w_uv  = (const __nv_bfloat16*)d_in[4];
  const __nv_bfloat16* w_o   = (const __nv_bfloat16*)d_in[5];
  const __nv_bfloat16* w_r   = (const __nv_bfloat16*)d_in[7];
  const __nv_bfloat16* w_g   = (const __nv_bfloat16*)d_in[8];
  const __nv_bfloat16* w_u   = (const __nv_bfloat16*)d_in[9];
  const __nv_bfloat16* w_d   = (const __nv_bfloat16*)d_in[10];
  const __nv_bfloat16* cvec  = (const __nv_bfloat16*)d_in[11];
  const __nv_bfloat16* w_mod = (const __nv_bfloat16*)d_in[12];
  __nv_bfloat16* out = (__nv_bfloat16*)d_out;

  static HostState st;
  if (!st.ready) {
    void* fn = nullptr; cudaDriverEntryPointQueryResult qr;
    cudaGetDriverEntryPoint("cuTensorMapEncodeTiled", &fn, cudaEnableDefault, &qr);
    st.encode = (EncodeFn)fn;
    cudaFuncSetAttribute(k_fused, cudaFuncAttributeMaxDynamicSharedMemorySize, SMEM);
    build_sched(st.sched);
    void *p_kvc, *p_h1, *p_part;
    cudaGetSymbolAddress(&p_kvc, g_kvc); cudaGetSymbolAddress(&p_h1, g_h1); cudaGetSymbolAddress(&p_part, g_part);
    st.sched.kvc = (__nv_bfloat16*)p_kvc; st.sched.h1 = (__nv_bfloat16*)p_h1; st.sched.part = (__nv_bfloat16*)p_part;
    make_2d(st.encode, &st.tmH, p_h1, SEQ, DM, 64);
    st.ready = true;
  }
  make_2d(st.encode, &st.tmC, ckv, SEQ, DM, 128);
  make_2d(st.encode, &st.tmWq, w_q, DM, NH * DH, 64);
  make_2d(st.encode, &st.tmWk, w_uk, DM, NH * DH, 64);
  make_2d(st.encode, &st.tmWv, w_uv, DM, NH * DH, 64);
  make_3d(st.encode, &st.tmWo, w_o, NH * DH, DM / 64, (size_t)DM * 2, 128);
  make_3d(st.encode, &st.tmWm, w_mod, DM, 6 * DM / 64, (size_t)6 * DM * 2, 128);
  make_ffn(st.encode, &st.tmWg, w_g);
  make_ffn(st.encode, &st.tmWu, w_u);

  k_fused<<<NGRID, 384, SMEM, cudaStreamPerThread>>>(st.tmC, st.tmH, st.tmWq, st.tmWk, st.tmWv, st.tmWo, st.tmWg, st.tmWu, st.tmWm, st.sched,
                                                     x, cvec, w_o, w_r, w_g, w_u, w_d, out);
}
```

```cpp
#include <cuda_runtime.h>
#include <cuda_bf16.h>
#include <cuda.h>
#include <stdint.h>
#include <string.h>
#include <math.h>

namespace {

constexpr int SEQ = 2048, DM = 512, NH = 32, DH = 128, FF = 1792;
constexpr int NCTA = 128, NGRID = 132;

__device__ __align__(128) __nv_bfloat16 g_kvc[192 * SEQ * 64];
__device__ __align__(128) __nv_bfloat16 g_h1[SEQ * DM];
__device__ __align__(128) __nv_bfloat16 g_part[128 * 8 * 4096];
__device__ __align__(16) __nv_bfloat16 g_mod[6 * DM];
constexpr int C_MOD = 0, C_MOD2 = 16, C_H1 = 32, C_KV = 64, C_CTX = 128, C_PART = 384, C_END = C_PART + 32 * 32;
__device__ __align__(128) unsigned int g_cnt[C_END];
__device__ unsigned int g_epoch;
__device__ __align__(128) uint2 g_keys[128][4];
__device__ __align__(16) uint2 g_row[128][2][DM / 2];
__device__ __align__(16) uint2 g_yll[FF / 16][DM];

#define DBG(i)
#define DBGP(i)

__device__ __forceinline__ uint32_t smem_u32(const void* p) { return (uint32_t)__cvta_generic_to_shared(p); }
__device__ __forceinline__ int wg_tid() { int t; asm volatile("mov.u32 %0, %%tid.x;" : "=r"(t)); return t & 127; }
__device__ __forceinline__ uint32_t clk32() { uint32_t c; asm volatile("mov.u32 %0, %%clock;" : "=r"(c)); return c; }
__device__ __forceinline__ void mbar_arrive(uint32_t bar) { asm volatile("mbarrier.arrive.shared::cta.b64 _, [%0];" :: "r"(bar) : "memory"); }
__device__ __forceinline__ uint32_t mapa(uint32_t addr, uint32_t cta) { uint32_t r; asm("mapa.shared::cluster.u32 %0, %1, %2;" : "=r"(r) : "r"(addr), "r"(cta)); return r; }
__device__ __forceinline__ void mbar_arrive_remote_if(uint32_t cluster_addr, bool pred) {
  asm volatile("{\n.reg .pred p;\nsetp.ne.u32 p, %1, 0;\n@p mbarrier.arrive.shared::cluster.b64 _, [%0];\n}" :: "r"(cluster_addr), "r"((uint32_t)pred) : "memory");
}
__device__ __forceinline__ bool mbar_try(uint32_t bar, uint32_t parity) {
  uint32_t done;
  asm volatile("{\n.reg .pred p;\nmbarrier.try_wait.parity.shared::cta.b64 p, [%1], %2;\nselp.u32 %0, 1, 0, p;\n}" : "=r"(done) : "r"(bar), "r"(parity) : "memory");
  return done;
}
__device__ __forceinline__ bool mbar_test2(uint32_t bar, uint32_t parity) {
  uint32_t done;
  asm volatile("{\n.reg .pred p, q;\nmbarrier.test_wait.parity.shared::cta.b64 p, [%1], %2;\nmbarrier.test_wait.parity.shared::cta.b64 q, [%1 + 8], %2;\n"
               "and.pred p, p, q;\nselp.u32 %0, 1, 0, p;\n}" : "=r"(done) : "r"(bar), "r"(parity) : "memory");
  return done;
}
#define WAIT_LIM (1 << 14)
__device__ __forceinline__ void mbar_wait(uint32_t bar, uint32_t parity) {
  #pragma unroll 1
  for (int n = 0; n < WAIT_LIM; n++) { if (mbar_try(bar, parity)) break; }
}
__device__ __forceinline__ unsigned int ld_acquire(const unsigned int* p) {
  unsigned int v; asm volatile("ld.acquire.gpu.global.u32 %0, [%1];" : "=r"(v) : "l"(p) : "memory"); return v;
}
__device__ __forceinline__ unsigned int ld_relaxed(const unsigned int* p) {
  unsigned int v; asm volatile("ld.relaxed.gpu.global.u32 %0, [%1];" : "=r"(v) : "l"(p) : "memory"); return v;
}
__device__ __forceinline__ void wait_count_lazy(int idx, unsigned int target) {
  #pragma unroll 1
  for (int n = 0; n < WAIT_LIM; n++) { if (__all_sync(0xffffffff, (int)(ld_relaxed(&g_cnt[idx]) - target) >= 0)) break; __nanosleep(100); }
  ld_acquire(&g_cnt[idx]);
}
__device__ __forceinline__ uint4 ld_tagged2(const void* p) {
  uint4 v;
  asm volatile("{\n.reg .b64 a, b;\nld.relaxed.gpu.global.v2.u64 {a, b}, [%4];\nmov.b64 {%0, %1}, a;\nmov.b64 {%2, %3}, b;\n}"
    : "=r"(v.x), "=r"(v.y), "=r"(v.z), "=r"(v.w) : "l"(p) : "memory");
  return v;
}
__device__ __forceinline__ uint2 ld_tagged(const void* p) {
  uint2 v; asm volatile("{\n.reg .b64 a;\nld.relaxed.gpu.global.u64 a, [%2];\nmov.b64 {%0, %1}, a;\n}" : "=r"(v.x), "=r"(v.y) : "l"(p) : "memory"); return v;
}
__device__ __forceinline__ void st_tagged2(void* p, uint32_t a, uint32_t b, uint32_t tag) {
  asm volatile("{\n.reg .b64 a, b;\nmov.b64 a, {%1, %3};\nmov.b64 b, {%2, %3};\nst.relaxed.gpu.global.v2.u64 [%0], {a, b};\n}" :: "l"(p), "r"(a), "r"(b), "r"(tag) : "memory");
}
__device__ __forceinline__ void st_tagged(void* p, uint32_t a, uint32_t tag) {
  asm volatile("{\n.reg .b64 a;\nmov.b64 a, {%1, %2};\nst.relaxed.gpu.global.u64 [%0], a;\n}" :: "l"(p), "r"(a), "r"(tag) : "memory");
}
__device__ __forceinline__ void stg_v4(void* p, uint32_t a, uint32_t b, uint32_t c, uint32_t d) {
  asm volatile("st.global.v4.u32 [%0], {%1, %2, %3, %4};" :: "l"(p), "r"(a), "r"(b), "r"(c), "r"(d) : "memory");
}
__device__ __forceinline__ uint4 lds_v4(uint32_t addr) {
  uint4 v; asm volatile("ld.shared.v4.u32 {%0, %1, %2, %3}, [%4];" : "=r"(v.x), "=r"(v.y), "=r"(v.z), "=r"(v.w) : "r"(addr) : "memory"); return v;
}
__device__ __forceinline__ uint32_t lds_u32(uint32_t addr) { uint32_t v; asm volatile("ld.shared.u32 %0, [%1];" : "=r"(v) : "r"(addr) : "memory"); return v; }
__device__ __forceinline__ void sts_v4(uint32_t addr, uint32_t a, uint32_t b, uint32_t c, uint32_t d) {
  asm volatile("st.shared.v4.u32 [%0], {%1, %2, %3, %4};" :: "r"(addr), "r"(a), "r"(b), "r"(c), "r"(d) : "memory");
}
#define ELECT "{\n.reg .pred p;\nelect.sync _|p, 0xffffffff;\n@p "
__device__ __forceinline__ void w_mbar_init(uint32_t bar, uint32_t cnt) { asm volatile(ELECT "mbarrier.init.shared::cta.b64 [%0], %1;\n}" :: "r"(bar), "r"(cnt) : "memory"); }
__device__ __forceinline__ void w_expect_tx(uint32_t bar, uint32_t bytes) { asm volatile(ELECT "mbarrier.arrive.expect_tx.shared::cta.b64 _, [%0], %1;\n}" :: "r"(bar), "r"(bytes) : "memory"); }
__device__ __forceinline__ void w_arrive(uint32_t bar) { asm volatile(ELECT "mbarrier.arrive.shared::cta.b64 _, [%0];\n}" :: "r"(bar) : "memory"); }
__device__ __forceinline__ void tma_load_2d(uint32_t dst, const CUtensorMap* tm, uint32_t bar, int c0, int c1) {
  asm volatile(ELECT "cp.async.bulk.tensor.2d.shared::cluster.global.mbarrier::complete_tx::bytes [%0], [%1, {%3, %4}], [%2];\n}"
    :: "r"(dst), "l"(tm), "r"(bar), "r"(c0), "r"(c1) : "memory");
}
__device__ __forceinline__ void tma_load_2d_mc(uint32_t dst, const CUtensorMap* tm, uint32_t bar, int c0, int c1) {
  asm volatile(ELECT "cp.async.bulk.tensor.2d.shared::cluster.global.mbarrier::complete_tx::bytes.multicast::cluster [%0], [%1, {%3, %4}], [%2], %5;\n}"
    :: "r"(dst), "l"(tm), "r"(bar), "r"(c0), "r"(c1), "h"((uint16_t)3) : "memory");
}
__device__ __forceinline__ void tma_load_3d(uint32_t dst, const CUtensorMap* tm, uint32_t bar, int c0, int c1, int c2) {
  asm volatile(ELECT "cp.async.bulk.tensor.3d.shared::cluster.global.mbarrier::complete_tx::bytes [%0], [%1, {%3, %4, %5}], [%2];\n}"
    :: "r"(dst), "l"(tm), "r"(bar), "r"(c0), "r"(c1), "r"(c2) : "memory");
}
__device__ __forceinline__ void tma_load_3d_mc(uint32_t dst, const CUtensorMap* tm, uint32_t bar, int c0, int c1, int c2) {
  asm volatile(ELECT "cp.async.bulk.tensor.3d.shared::cluster.global.mbarrier::complete_tx::bytes.multicast::cluster [%0], [%1, {%3, %4, %5}], [%2], %6;\n}"
    :: "r"(dst), "l"(tm), "r"(bar), "r"(c0), "r"(c1), "r"(c2), "h"((uint16_t)3) : "memory");
}
__device__ __forceinline__ void bulk_load_mc(uint32_t dst, const void* src, uint32_t bar, bool ef) {
  if (ef) {
    uint64_t pol; asm("createpolicy.fractional.L2::evict_first.b64 %0, 1.0;" : "=l"(pol));
    asm volatile(ELECT "cp.async.bulk.shared::cluster.global.mbarrier::complete_tx::bytes.multicast::cluster.L2::cache_hint [%0], [%1], 16384, [%2], %3, %4;\n}"
      :: "r"(dst), "l"(src), "r"(bar), "h"((uint16_t)3), "l"(pol) : "memory");
  } else
    asm volatile(ELECT "cp.async.bulk.shared::cluster.global.mbarrier::complete_tx::bytes.multicast::cluster [%0], [%1], 16384, [%2], %3;\n}"
      :: "r"(dst), "l"(src), "r"(bar), "h"((uint16_t)3) : "memory");
}
__device__ __forceinline__ void bulk_load(uint32_t dst, const void* src, uint32_t bytes, uint32_t bar) {
  asm volatile(ELECT "cp.async.bulk.shared::cluster.global.mbarrier::complete_tx::bytes [%0], [%1], %2, [%3];\n}" :: "r"(dst), "l"(src), "r"(bytes), "r"(bar) : "memory");
}
__device__ __forceinline__ void tma_prefetch_2d(const CUtensorMap* tm, int c0, int c1) {
  asm volatile(ELECT "cp.async.bulk.prefetch.tensor.2d.L2.global [%0, {%1, %2}];\n}" :: "l"(tm), "r"(c0), "r"(c1) : "memory");
}
__device__ __forceinline__ void bulk_prefetch(const void* p, uint32_t bytes) {
  asm volatile(ELECT "cp.async.bulk.prefetch.L2.global [%0], %1;\n}" :: "l"(p), "r"(bytes) : "memory");
}
__device__ __forceinline__ void red_release(int idx) { asm volatile("red.release.gpu.global.add.u32 [%0], 1;" :: "l"(&g_cnt[idx]) : "memory"); }
__device__ __forceinline__ void prefetch_tmap(const CUtensorMap* tm) { asm volatile("prefetch.tensormap [%0];" :: "l"(tm) : "memory"); }
__device__ __forceinline__ void bar_sync(int id, int n) { asm volatile("bar.sync %0, %1;" :: "r"(id), "r"(n) : "memory"); }
__device__ __forceinline__ void bar_arrive(int id, int n) { asm volatile("bar.arrive %0, %1;" :: "r"(id), "r"(n) : "memory"); }
__device__ __forceinline__ void fence_async_smem() { asm volatile("fence.proxy.async.shared::cta;" ::: "memory"); }
__device__ __forceinline__ void fence_async_global() { asm volatile("fence.proxy.async.global;" ::: "memory"); }
__device__ __forceinline__ void fence_mbar_init() { asm volatile("fence.mbarrier_init.release.cluster;" ::: "memory"); }
__device__ __forceinline__ void cluster_arrive() { asm volatile("barrier.cluster.arrive.relaxed.aligned;" ::: "memory"); }
__device__ __forceinline__ void cluster_wait() { asm volatile("barrier.cluster.wait.aligned;" ::: "memory"); }
__device__ __forceinline__ uint32_t cluster_ctarank() { uint32_t r; asm volatile("mov.u32 %0, %%cluster_ctarank;" : "=r"(r)); return r; }
__device__ __forceinline__ void wgmma_fence() { asm volatile("wgmma.fence.sync.aligned;" ::: "memory"); }
__device__ __forceinline__ void wgmma_commit() { asm volatile("wgmma.commit_group.sync.aligned;" ::: "memory"); }
template<int N> __device__ __forceinline__ void wgmma_wait() { asm volatile("wgmma.wait_group.sync.aligned %0;" :: "n"(N) : "memory"); }
__device__ __forceinline__ float ex2(float x) { float y; asm("ex2.approx.ftz.f32 %0, %1;" : "=f"(y) : "f"(x)); return y; }
__device__ __forceinline__ float rcp_fast(float x) { float y; asm("rcp.approx.ftz.f32 %0, %1;" : "=f"(y) : "f"(x)); return y; }
__device__ __forceinline__ uint32_t pack_bf16(float lo, float hi) { uint32_t r; asm("cvt.rn.bf16x2.f32 %0, %1, %2;" : "=r"(r) : "f"(hi), "f"(lo)); return r; }
__device__ __forceinline__ float rbf(float x) { return __uint_as_float(pack_bf16(0.f, x)); }
__device__ __forceinline__ float bf_lo(uint32_t v) { return __uint_as_float(v << 16); }
__device__ __forceinline__ float bf_hi(uint32_t v) { return __uint_as_float(v & 0xffff0000u); }
__device__ __forceinline__ uint32_t add2(uint32_t a, uint32_t b) { uint32_t r; asm("add.rn.bf16x2 %0, %1, %2;" : "=r"(r) : "r"(a), "r"(b)); return r; }
__device__ __forceinline__ uint32_t fma2(uint32_t a, uint32_t b, uint32_t c) { uint32_t r; asm("fma.rn.bf16x2 %0, %1, %2, %3;" : "=r"(r) : "r"(a), "r"(b), "r"(c)); return r; }
__device__ __forceinline__ uint4 ldsm_x4_t(uint32_t addr) {
  uint4 v; asm volatile("ldmatrix.sync.aligned.m8n8.x4.trans.shared.b16 {%0, %1, %2, %3}, [%4];" : "=r"(v.x), "=r"(v.y), "=r"(v.z), "=r"(v.w) : "r"(addr) : "memory"); return v;
}
__device__ __forceinline__ uint4 ldsm_x4(uint32_t addr) {
  uint4 v; asm volatile("ldmatrix.sync.aligned.m8n8.x4.shared.b16 {%0, %1, %2, %3}, [%4];" : "=r"(v.x), "=r"(v.y), "=r"(v.z), "=r"(v.w) : "r"(addr) : "memory"); return v;
}
__device__ __forceinline__ void mma16816(float (&c)[4], const uint4& a, uint32_t b0, uint32_t b1) {
  asm("mma.sync.aligned.m16n8k16.row.col.f32.bf16.bf16.f32 {%0, %1, %2, %3}, {%4, %5, %6, %7}, {%8, %9}, {%0, %1, %2, %3};"
    : "+f"(c[0]), "+f"(c[1]), "+f"(c[2]), "+f"(c[3]) : "r"(a.x), "r"(a.y), "r"(a.z), "r"(a.w), "r"(b0), "r"(b1));
}
template<int N> __device__ __forceinline__ void fence_regs(float (&a)[N]) {
  #pragma unroll
  for (int i = 0; i < N; i++) asm volatile("" : "+f"(a[i]) :: "memory");
}
template<int N> __device__ __forceinline__ void fence_regs_u(uint32_t (&a)[N]) {
  #pragma unroll
  for (int i = 0; i < N; i++) asm volatile("" : "+r"(a[i]) :: "memory");
}
constexpr uint32_t SW128 = 0x40000040u, SW64 = 0x80000020u;
__device__ __forceinline__ uint32_t desc_lo(uint32_t addr, uint32_t lbo) { return ((addr & 0x3FFFF) >> 4) | ((lbo >> 4) << 16); }

template<int TB, int OA, int OB, uint32_t HA, uint32_t HB> __device__ __forceinline__ void wgmma_ss_n128(float (&d)[64], uint32_t da, uint32_t db, int sd) {
  asm volatile("{\n.reg .pred p;\n.reg .b32 ta, tb;\n.reg .b64 da, db;\nsetp.ne.b32 p, %66, 0;\nadd.u32 ta, %64, %68;\nadd.u32 tb, %65, %69;\nmov.b64 da, {ta, %70};\nmov.b64 db, {tb, %71};\n"
    "wgmma.mma_async.sync.aligned.m64n128k16.f32.bf16.bf16 "
    "{%0, %1, %2, %3, %4, %5, %6, %7, %8, %9, %10, %11, %12, %13, %14, %15, %16, %17, %18, %19, %20, %21, %22, %23, %24, %25, %26, %27, %28, %29, %30, %31, %32, %33, %34, %35, %36, %37, %38, %39, %40, %41, %42, %43, %44, %45, %46, %47, %48, %49, %50, %51, %52, %53, %54, %55, %56, %57, %58, %59, %60, %61, %62, %63}, da, db, p, 1, 1, 0, %67;\n}\n"
    : "+f"(d[0]), "+f"(d[1]), "+f"(d[2]), "+f"(d[3]), "+f"(d[4]), "+f"(d[5]), "+f"(d[6]), "+f"(d[7]), "+f"(d[8]), "+f"(d[9]), "+f"(d[10]), "+f"(d[11]), "+f"(d[12]), "+f"(d[13]), "+f"(d[14]), "+f"(d[15]), "+f"(d[16]), "+f"(d[17]), "+f"(d[18]), "+f"(d[19]), "+f"(d[20]), "+f"(d[21]), "+f"(d[22]), "+f"(d[23]), "+f"(d[24]), "+f"(d[25]), "+f"(d[26]), "+f"(d[27]), "+f"(d[28]), "+f"(d[29]), "+f"(d[30]), "+f"(d[31]), "+f"(d[32]), "+f"(d[33]), "+f"(d[34]), "+f"(d[35]), "+f"(d[36]), "+f"(d[37]), "+f"(d[38]), "+f"(d[39]), "+f"(d[40]), "+f"(d[41]), "+f"(d[42]), "+f"(d[43]), "+f"(d[44]), "+f"(d[45]), "+f"(d[46]), "+f"(d[47]), "+f"(d[48]), "+f"(d[49]), "+f"(d[50]), "+f"(d[51]), "+f"(d[52]), "+f"(d[53]), "+f"(d[54]), "+f"(d[55]), "+f"(d[56]), "+f"(d[57]), "+f"(d[58]), "+f"(d[59]), "+f"(d[60]), "+f"(d[61]), "+f"(d[62]), "+f"(d[63])
    : "r"(da), "r"(db), "r"(sd), "n"(TB), "n"(OA), "n"(OB), "n"(HA), "n"(HB));
}
template<int TB, int OB, uint32_t HB> __device__ __forceinline__ void wgmma_rs_n128(float (&d)[64], uint32_t a0, uint32_t a1, uint32_t a2, uint32_t a3, uint32_t db, int sd) {
  asm volatile("{\n.reg .pred p;\n.reg .b32 tb;\n.reg .b64 db;\nsetp.ne.b32 p, %69, 0;\nadd.u32 tb, %68, %71;\nmov.b64 db, {tb, %72};\n"
    "wgmma.mma_async.sync.aligned.m64n128k16.f32.bf16.bf16 "
    "{%0, %1, %2, %3, %4, %5, %6, %7, %8, %9, %10, %11, %12, %13, %14, %15, %16, %17, %18, %19, %20, %21, %22, %23, %24, %25, %26, %27, %28, %29, %30, %31, %32, %33, %34, %35, %36, %37, %38, %39, %40, %41, %42, %43, %44, %45, %46, %47, %48, %49, %50, %51, %52, %53, %54, %55, %56, %57, %58, %59, %60, %61, %62, %63}, {%64,%65,%66,%67}, db, p, 1, 1, %70;\n}\n"
    : "+f"(d[0]), "+f"(d[1]), "+f"(d[2]), "+f"(d[3]), "+f"(d[4]), "+f"(d[5]), "+f"(d[6]), "+f"(d[7]), "+f"(d[8]), "+f"(d[9]), "+f"(d[10]), "+f"(d[11]), "+f"(d[12]), "+f"(d[13]), "+f"(d[14]), "+f"(d[15]), "+f"(d[16]), "+f"(d[17]), "+f"(d[18]), "+f"(d[19]), "+f"(d[20]), "+f"(d[21]), "+f"(d[22]), "+f"(d[23]), "+f"(d[24]), "+f"(d[25]), "+f"(d[26]), "+f"(d[27]), "+f"(d[28]), "+f"(d[29]), "+f"(d[30]), "+f"(d[31]), "+f"(d[32]), "+f"(d[33]), "+f"(d[34]), "+f"(d[35]), "+f"(d[36]), "+f"(d[37]), "+f"(d[38]), "+f"(d[39]), "+f"(d[40]), "+f"(d[41]), "+f"(d[42]), "+f"(d[43]), "+f"(d[44]), "+f"(d[45]), "+f"(d[46]), "+f"(d[47]), "+f"(d[48]), "+f"(d[49]), "+f"(d[50]), "+f"(d[51]), "+f"(d[52]), "+f"(d[53]), "+f"(d[54]), "+f"(d[55]), "+f"(d[56]), "+f"(d[57]), "+f"(d[58]), "+f"(d[59]), "+f"(d[60]), "+f"(d[61]), "+f"(d[62]), "+f"(d[63])
    : "r"(a0), "r"(a1), "r"(a2), "r"(a3), "r"(db), "r"(sd), "n"(TB), "n"(OB), "n"(HB));
}
template<int TB, int OA, int OB, uint32_t HA, uint32_t HB> __device__ __forceinline__ void wgmma_ss_n64(float (&d)[32], uint32_t da, uint32_t db, int sd) {
  asm volatile("{\n.reg .pred p;\n.reg .b32 ta, tb;\n.reg .b64 da, db;\nsetp.ne.b32 p, %34, 0;\nadd.u32 ta, %32, %36;\nadd.u32 tb, %33, %37;\nmov.b64 da, {ta, %38};\nmov.b64 db, {tb, %39};\n"
    "wgmma.mma_async.sync.aligned.m64n64k16.f32.bf16.bf16 "
    "{%0, %1, %2, %3, %4, %5, %6, %7, %8, %9, %10, %11, %12, %13, %14, %15, %16, %17, %18, %19, %20, %21, %22, %23, %24, %25, %26, %27, %28, %29, %30, %31}, da, db, p, 1, 1, 0, %35;\n}\n"
    : "+f"(d[0]), "+f"(d[1]), "+f"(d[2]), "+f"(d[3]), "+f"(d[4]), "+f"(d[5]), "+f"(d[6]), "+f"(d[7]), "+f"(d[8]), "+f"(d[9]), "+f"(d[10]), "+f"(d[11]), "+f"(d[12]), "+f"(d[13]), "+f"(d[14]), "+f"(d[15]), "+f"(d[16]), "+f"(d[17]), "+f"(d[18]), "+f"(d[19]), "+f"(d[20]), "+f"(d[21]), "+f"(d[22]), "+f"(d[23]), "+f"(d[24]), "+f"(d[25]), "+f"(d[26]), "+f"(d[27]), "+f"(d[28]), "+f"(d[29]), "+f"(d[30]), "+f"(d[31])
    : "r"(da), "r"(db), "r"(sd), "n"(TB), "n"(OA), "n"(OB), "n"(HA), "n"(HB));
}
template<int TB, int OA, int OB, uint32_t HA, uint32_t HB> __device__ __forceinline__ void wgmma_ss_n128_new(float (&d)[64], uint32_t da, uint32_t db) {
  asm volatile("{\n.reg .pred p;\n.reg .b32 ta, tb;\n.reg .b64 da, db;\nsetp.ne.b32 p, %66, 0;\nadd.u32 ta, %64, %68;\nadd.u32 tb, %65, %69;\nmov.b64 da, {ta, %70};\nmov.b64 db, {tb, %71};\n"
    "wgmma.mma_async.sync.aligned.m64n128k16.f32.bf16.bf16 "
    "{%0, %1, %2, %3, %4, %5, %6, %7, %8, %9, %10, %11, %12, %13, %14, %15, %16, %17, %18, %19, %20, %21, %22, %23, %24, %25, %26, %27, %28, %29, %30, %31, %32, %33, %34, %35, %36, %37, %38, %39, %40, %41, %42, %43, %44, %45, %46, %47, %48, %49, %50, %51, %52, %53, %54, %55, %56, %57, %58, %59, %60, %61, %62, %63}, da, db, p, 1, 1, 0, %67;\n}\n"
    : "=f"(d[0]), "=f"(d[1]), "=f"(d[2]), "=f"(d[3]), "=f"(d[4]), "=f"(d[5]), "=f"(d[6]), "=f"(d[7]), "=f"(d[8]), "=f"(d[9]), "=f"(d[10]), "=f"(d[11]), "=f"(d[12]), "=f"(d[13]), "=f"(d[14]), "=f"(d[15]), "=f"(d[16]), "=f"(d[17]), "=f"(d[18]), "=f"(d[19]), "=f"(d[20]), "=f"(d[21]), "=f"(d[22]), "=f"(d[23]), "=f"(d[24]), "=f"(d[25]), "=f"(d[26]), "=f"(d[27]), "=f"(d[28]), "=f"(d[29]), "=f"(d[30]), "=f"(d[31]), "=f"(d[32]), "=f"(d[33]), "=f"(d[34]), "=f"(d[35]), "=f"(d[36]), "=f"(d[37]), "=f"(d[38]), "=f"(d[39]), "=f"(d[40]), "=f"(d[41]), "=f"(d[42]), "=f"(d[43]), "=f"(d[44]), "=f"(d[45]), "=f"(d[46]), "=f"(d[47]), "=f"(d[48]), "=f"(d[49]), "=f"(d[50]), "=f"(d[51]), "=f"(d[52]), "=f"(d[53]), "=f"(d[54]), "=f"(d[55]), "=f"(d[56]), "=f"(d[57]), "=f"(d[58]), "=f"(d[59]), "=f"(d[60]), "=f"(d[61]), "=f"(d[62]), "=f"(d[63])
    : "r"(da), "r"(db), "n"(0), "n"(TB), "n"(OA), "n"(OB), "n"(HA), "n"(HB));
}
template<int TB, int OA, int OB, uint32_t HA, uint32_t HB> __device__ __forceinline__ void wgmma_ss_n64_new(float (&d)[32], uint32_t da, uint32_t db) {
  asm volatile("{\n.reg .pred p;\n.reg .b32 ta, tb;\n.reg .b64 da, db;\nsetp.ne.b32 p, %34, 0;\nadd.u32 ta, %32, %36;\nadd.u32 tb, %33, %37;\nmov.b64 da, {ta, %38};\nmov.b64 db, {tb, %39};\n"
    "wgmma.mma_async.sync.aligned.m64n64k16.f32.bf16.bf16 "
    "{%0, %1, %2, %3, %4, %5, %6, %7, %8, %9, %10, %11, %12, %13, %14, %15, %16, %17, %18, %19, %20, %21, %22, %23, %24, %25, %26, %27, %28, %29, %30, %31}, da, db, p, 1, 1, 0, %35;\n}\n"
    : "=f"(d[0]), "=f"(d[1]), "=f"(d[2]), "=f"(d[3]), "=f"(d[4]), "=f"(d[5]), "=f"(d[6]), "=f"(d[7]), "=f"(d[8]), "=f"(d[9]), "=f"(d[10]), "=f"(d[11]), "=f"(d[12]), "=f"(d[13]), "=f"(d[14]), "=f"(d[15]), "=f"(d[16]), "=f"(d[17]), "=f"(d[18]), "=f"(d[19]), "=f"(d[20]), "=f"(d[21]), "=f"(d[22]), "=f"(d[23]), "=f"(d[24]), "=f"(d[25]), "=f"(d[26]), "=f"(d[27]), "=f"(d[28]), "=f"(d[29]), "=f"(d[30]), "=f"(d[31])
    : "r"(da), "r"(db), "n"(0), "n"(TB), "n"(OA), "n"(OB), "n"(HA), "n"(HB));
}
template<int OA, int OB = 0, uint32_t HA = SW128> __device__ __forceinline__ void kblock_n128(float (&d)[64], uint32_t da, uint32_t db, int sd) {
  constexpr int H = HA == SW128 ? 4 : 512;
  wgmma_ss_n128<1, OA, OB, HA, SW128>(d, da, db, sd); wgmma_ss_n128<1, OA + 2, OB + 128, HA, SW128>(d, da, db, 1);
  wgmma_ss_n128<1, OA + H, OB + 256, HA, SW128>(d, da, db, 1); wgmma_ss_n128<1, OA + H + 2, OB + 384, HA, SW128>(d, da, db, 1);
}

__device__ __forceinline__ float quad_sum(float v) {
  v += __shfl_xor_sync(0xffffffff, v, 1);
  v += __shfl_xor_sync(0xffffffff, v, 2);
  return v;
}
struct Row { uint32_t v[8]; };
template<class F> __device__ __forceinline__ Row load_row(const __nv_bfloat16* p, int lane, F ld) {
  const uint4 a = ld(reinterpret_cast<const uint4*>(p) + lane), b = ld(reinterpret_cast<const uint4*>(p) + 32 + lane);
  return Row{{a.x, a.y, a.z, a.w, b.x, b.y, b.z, b.w}};
}
__device__ __forceinline__ Row ldg_row(const __nv_bfloat16* p, int lane) { return load_row(p, lane, [](const uint4* q) { return __ldg(q); }); }
__device__ __forceinline__ Row ldca_row(const __nv_bfloat16* p, int lane) { return load_row(p, lane, [](const uint4* q) { return __ldca(q); }); }
__device__ __forceinline__ Row lds_row(uint32_t addr, int lane) {
  const uint4 a = lds_v4(addr + lane * 16), b = lds_v4(addr + 512 + lane * 16);
  return Row{{a.x, a.y, a.z, a.w, b.x, b.y, b.z, b.w}};
}
__device__ __forceinline__ void store_row(__nv_bfloat16* p, int lane, const Row& r) {
  stg_v4(p + lane * 8, r.v[0], r.v[1], r.v[2], r.v[3]); stg_v4(p + 256 + lane * 8, r.v[4], r.v[5], r.v[6], r.v[7]);
}
__device__ __forceinline__ Row fma_row(const Row& a, const Row& b, const Row& c) {
  Row r;
  #pragma unroll
  for (int i = 0; i < 8; i++) r.v[i] = fma2(a.v[i], b.v[i], c.v[i]);
  return r;
}
__device__ __forceinline__ Row add_row(const Row& a, const Row& b) {
  Row r;
  #pragma unroll
  for (int i = 0; i < 8; i++) r.v[i] = add2(a.v[i], b.v[i]);
  return r;
}
__device__ __forceinline__ Row one_plus(const Row& a) {
  Row r;
  #pragma unroll
  for (int i = 0; i < 8; i++) r.v[i] = add2(a.v[i], 0x3f803f80u);
  return r;
}
__device__ __forceinline__ float row_at(const Row& x, int i) { return (i & 1) ? bf_hi(x.v[i >> 1]) : bf_lo(x.v[i >> 1]); }
template<int N> __device__ __forceinline__ void warp_sums(float (&s)[N]) {
  #pragma unroll
  for (int o = 16; o > 0; o >>= 1) {
    #pragma unroll
    for (int k = 0; k < N; k++) s[k] += __shfl_xor_sync(0xffffffff, s[k], o);
  }
}
__device__ __forceinline__ void ln_stats(float& s1, float& s2) {
  s1 *= 1.f / DM;
  asm("rsqrt.approx.ftz.f32 %0, %1;" : "=f"(s2) : "f"(fmaxf(fmaf(-s1, s1, s2 * (1.f / DM)), 0.f) + 1e-5f));
}
__device__ __forceinline__ Row ln_apply(const Row& x, float mean, float f) {
  Row n;
  const float o = -mean * f;
  #pragma unroll
  for (int i = 0; i < 8; i++) n.v[i] = pack_bf16(fmaf(bf_lo(x.v[i]), f, o), fmaf(bf_hi(x.v[i]), f, o));
  return n;
}

constexpr int SM_Q = 6 * 32768, SM_BAR = 7 * 32768, SM_MAIL = SM_BAR + 640, SM_RED = SM_MAIL + 128, SM_H2 = SM_RED + 1024, SM_KEY = SM_H2 + 1024, SMEM = SM_KEY + 128;
constexpr int B_AF = 0, B_WF = 64, B_RF = 112, B_WE = 168, B_RE = 216, B_PUB = 272, B_RDY = 496;
constexpr int R_MOD = B_RDY, R_H1 = B_RDY + 8, R_ITEM = B_RDY + 16, R_NEAR = B_RDY + 48, R_CTX = B_RDY + 64;
constexpr int R_KEY = B_AF + 8, R_PART = B_AF + 32;
constexpr int NPUB = 14;
__device__ __forceinline__ uint32_t k_addrA(int kb) { return ((0x6310u >> ((kb >> 1) * 4)) & 15u) * 32768u + (kb & 1) * 16384u; }
__device__ __forceinline__ uint32_t k_addrW(int s) { return ((0x254u >> ((s >> 1) * 4)) & 15u) * 32768u + (s & 1) * 16384u; }

#define KORDER 0x3201
constexpr int KHEAD0 = ((KORDER >> 12) & 3) * 8;
constexpr int MAX_ITEMS = 4;
constexpr int MAX_STEPS = 10;
struct Sched {
  __nv_bfloat16 *kvc, *h1, *part;
  struct Pair {
    uint8_t oent[3 * MAX_STEPS + 6];
    uint16_t lastuse[MAX_ITEMS];
    uint8_t khead[4];
    uint8_t nitems, item[MAX_ITEMS];
    uint8_t otask, nsteps;
    uint8_t ochunk[MAX_STEPS][2];
  } pair[NGRID / 2];
};

__device__ __forceinline__ int ring_add(int e, int n) { e += n; return e >= 12 ? e - 12 : e; }
__device__ __forceinline__ int ring_slot(int e) { return e >= 6 ? e - 6 : e; }
__device__ __forceinline__ void ring_wait_full(uint32_t bars, int e) { mbar_wait(bars + B_RF + 8 * ring_slot(e), e >= 6); }

__device__ __forceinline__ void o_wait_full(uint32_t bars, uint32_t v) { mbar_wait(bars + B_RF + 8 * (v & 7), v >> 3); }

struct Ctx {
  uint32_t base, bars;
  uint32_t rel;
  bool rel1;
  int w, nev;
  const Sched* sched;
  uint32_t tr;
};
#define TR(id)
__device__ __forceinline__ void slot_release(const Ctx& x, int s, bool twice) {
  mbar_arrive_remote_if(x.rel + B_RE + 8 * s, twice ? (wg_tid() & 31) == 0 : x.rel1);
}
__device__ __forceinline__ void ring_release(const Ctx& x, int e, bool twice) { slot_release(x, ring_slot(e), twice); }
__device__ __forceinline__ void publish(Ctx& x, int idx) {
  const uint32_t n = x.w * NPUB + x.nev;
  const int t = wg_tid();
  if (t == 0) asm volatile("st.shared.u32 [%0], %1;" :: "r"(x.base + SM_MAIL + 4 * n), "r"(idx) : "memory");
  __syncwarp();
  if ((t & 31) == 0) mbar_arrive(x.bars + B_PUB + 8 * n);
  x.nev++;
}

template<int KK = 0> __device__ __forceinline__ void issue_qk(float (&S)[64], uint32_t dq, uint32_t dk) {
  constexpr int off = (KK >> 1) * 512 + (KK & 1) * 2;
  if constexpr (KK == 0) wgmma_ss_n128_new<0, 0, 0, SW64, SW64>(S, dq, dk); else wgmma_ss_n128<0, off, off, SW64, SW64>(S, dq, dk, 1);
  if constexpr (KK < 7) issue_qk<KK + 1>(S, dq, dk);
}
template<int KK = 0> __device__ __forceinline__ void issue_qk_half(float (&S)[32], uint32_t dq, uint32_t dk) {
  constexpr int off = (KK >> 1) * 512 + (KK & 1) * 2;
  if constexpr (KK == 0) wgmma_ss_n64_new<0, 0, 256, SW64, SW64>(S, dq, dk); else wgmma_ss_n64<0, off, off + 256, SW64, SW64>(S, dq, dk, 1);
  if constexpr (KK < 7) issue_qk_half<KK + 1>(S, dq, dk);
}
template<int NK, int KK = 0>
__device__ __forceinline__ void issue_pv(float (&O)[64], uint32_t (&P)[32], uint32_t dv, int accumulate) {
  wgmma_rs_n128<1, (KK + 8 - NK) * 64, SW64>(O, P[4*KK], P[4*KK+1], P[4*KK+2], P[4*KK+3], dv, accumulate);
  if constexpr (KK + 1 < NK) issue_pv<NK, KK + 1>(O, P, dv, 1);
}
template<int K0, int K1>
__device__ __forceinline__ void exp_pack(const float (&S)[64], uint32_t (&D)[32], float& s0, float& s1) {
  #pragma unroll
  for (int k = K0; k < K1; k++) {
    const float e0 = ex2(S[2*k]), e1 = ex2(S[2*k+1]);
    D[k] = pack_bf16(e0, e1);
    if (k & 1) s1 += e0 + e1; else s0 += e0 + e1;
  }
}
__device__ __forceinline__ int diag_limit() { const int t = wg_tid(); return 16 * (t >> 5) + ((t & 31) >> 2) - 2 * (t & 3); }
__device__ __forceinline__ void exp_pack_diag(const float (&S)[64], uint32_t (&D)[32], int t, float& s0, float& s1) {
  #pragma unroll
  for (int k = 0; k < 16; k++) {
    const int c = 8 * (k >> 1) - 8 * (k & 1);
    const float e0 = ex2((c <= t) ? S[2*k] : -INFINITY), e1 = ex2((c + 1 <= t) ? S[2*k+1] : -INFINITY);
    D[k] = pack_bf16(e0, e1);
    if (k & 1) s1 += e0 + e1; else s0 += e0 + e1;
  }
}
constexpr float SUM_HI = 1.8446744073709552e19f;
constexpr float SUM_LO = 5.421010862427522e-20f;

__device__ __forceinline__ void classic_tile(const float (&S)[64], uint32_t (&P)[32], bool fresh, bool half, bool was_classic, volatile float* mc,
                                             float& l0, float& l1, float& s0, float& s1, float& sc0, float& sc1) {
  const int tmask = diag_limit();
  float4 t[16];
  #pragma unroll
  for (int j = 0; j < 16; j++) t[j] = make_float4(S[4*j], S[4*j+1], S[4*j+2], S[4*j+3]);
  float mx0 = -INFINITY, mx1 = -INFINITY;
  #pragma unroll 1
  for (int j = 0; j < 16; j++) {
    float4 v = t[j];
    const int lim = !fresh ? 1000 : j < 8 ? tmask - 8 * j : half ? -1000 : 1000;
    v.x = 0 <= lim ? v.x : -INFINITY; v.y = 1 <= lim ? v.y : -INFINITY; v.z = -8 <= lim ? v.z : -INFINITY; v.w = -7 <= lim ? v.w : -INFINITY;
    t[j] = v;
    mx0 = fmaxf(mx0, fmaxf(v.x, v.y)); mx1 = fmaxf(mx1, fmaxf(v.z, v.w));
  }
  mx0 = fmaxf(mx0, __shfl_xor_sync(0xffffffff, mx0, 1));
  mx1 = fmaxf(mx1, __shfl_xor_sync(0xffffffff, mx1, 1));
  mx0 = fmaxf(mx0, __shfl_xor_sync(0xffffffff, mx0, 2));
  mx1 = fmaxf(mx1, __shfl_xor_sync(0xffffffff, mx1, 2));
  const float mc0 = was_classic ? mc[0] : 0.f, mc1 = was_classic ? mc[1] : 0.f;
  const float n0 = fresh ? -mx0 : fminf(mc0, -mx0), n1 = fresh ? -mx1 : fminf(mc1, -mx1);
  sc0 = ex2(n0 - mc0); sc1 = ex2(n1 - mc1);
  mc[0] = n0; mc[1] = n1;
  s0 = 0.f; s1 = 0.f;
  #pragma unroll 1
  for (int j = 0; j < 16; j++) {
    const float4 v = t[j];
    const float e0 = ex2(v.x + n0), e1 = ex2(v.y + n0), e2 = ex2(v.z + n1), e3 = ex2(v.w + n1);
    s0 += e0 + e1; s1 += e2 + e3;
    reinterpret_cast<uint2*>(t)[j] = make_uint2(pack_bf16(e0, e1), pack_bf16(e2, e3));
  }
  #pragma unroll
  for (int j = 0; j < 8; j++) { P[4*j] = __float_as_uint(t[j].x); P[4*j+1] = __float_as_uint(t[j].y); P[4*j+2] = __float_as_uint(t[j].z); P[4*j+3] = __float_as_uint(t[j].w); }
  if (!fresh) { l0 *= sc0; l1 *= sc1; }
}
__device__ __forceinline__ void pack_tile(const float (&A)[64], uint32_t (&D)[32], float f0, float f1) {
  #pragma unroll
  for (int j = 0; j < 16; j++) {
    D[8 * (j >> 2) + (j & 3)] = pack_bf16(A[4*j] * f0, A[4*j+1] * f0);
    D[8 * (j >> 2) + 4 + (j & 3)] = pack_bf16(A[4*j+2] * f1, A[4*j+3] * f1);
  }
}
__device__ __forceinline__ int piece0(int t) { return ((t >> 5) * 16 + ((t & 31) >> 2)) * 32 + (((t ^ (t >> 3)) & 3) << 3); }
__device__ __forceinline__ void store_tile(__nv_bfloat16* p, const uint32_t (&D)[32]) {
  #pragma unroll
  for (int i = 0; i < 8; i++) stg_v4(p + (i >> 2) * (SEQ * 64) + ((i >> 1) & 1) * 4096 + (i & 1) * 256, D[4*i], D[4*i+1], D[4*i+2], D[4*i+3]);
}

enum : int { PV_ACC = 0, PV_ZERO = 1, PV_HALF = 2, PV_NONE = 3 };
struct Att {
  float l0, l1, i0, i1;
  bool classic;
  volatile float* mc;
};
__device__ __forceinline__ void store_ctx(Ctx& x, int code, const uint32_t (&D)[32]) {
  store_tile(x.sched->kvc + ((size_t)(128 + (code >> 5) * 2) * SEQ + ((code >> 1) & 15) * 128) * 64 + (code & 1) * 2048 + piece0(wg_tid()), D);
  publish(x, C_CTX + (code >> 2));
}
__device__ __forceinline__ __nv_bfloat16* kv_tile(const Ctx& x, int code) {
  return x.sched->kvc + ((size_t)(x.w * 64 + (code >> 4) * 2) * SEQ + (code & 15) * 128) * 64 + piece0(wg_tid());
}
#define V_AT 3
#define V_AT2 7
#define MERGE1 1
#define NO_CLASSIC 0
__device__ __forceinline__ void q_proj(Ctx& x, int& e, bool isY, const uint32_t (&PA)[32], const uint32_t (&PB)[32], int vtile, bool first, bool dbg = false) {
  float S[64];
  if (isY) bar_sync(1 + x.w, 256);
  if (dbg) DBG(80);
  TR(1);
  #pragma unroll 1
  for (int kb = 0; kb < 8; kb++) {
    if (kb > 0 || first) ring_wait_full(x.bars, e);
    if (dbg) DBG(81 + kb);
    TR(2);
    const uint32_t da = desc_lo(x.base + x.w * 8192, 16) + ring_slot(e) * 2048, dw = desc_lo(x.base + 16384, 8192) + ring_slot(e) * 2048;
    wgmma_fence();
    kblock_n128<0>(S, da, dw, kb != 0);
    wgmma_commit();
    if (kb == 7 && !isY) bar_arrive(1 + (x.w ^ 1), 256);
    if (kb > 0) { wgmma_wait<1>(); ring_release(x, ring_add(e, 11), false); }
    if (kb == V_AT && vtile >= 0) store_tile(kv_tile(x, vtile) + 2048, PA);
    if (kb == V_AT2 && vtile >= 0) { store_tile(kv_tile(x, vtile), PB); publish(x, C_KV + (vtile >> 4)); }
    e = ring_add(e, 1);
  }
  wgmma_wait<0>();
  fence_regs(S);
  if (dbg) DBG(89);
  TR(3);
  ring_release(x, ring_add(e, 11), false);
  const uint32_t qa = x.base + SM_Q + x.w * 4096 + piece0(wg_tid()) * 2;
  #pragma unroll
  for (int i = 0; i < 8; i++) {
    const int j = 4 * (i >> 1), o = 2 * (i & 1);
    sts_v4(qa + (i >> 1) * 8192 + (i & 1) * 512,
           pack_bf16(S[4*j+o], S[4*j+o+1]), pack_bf16(S[4*j+4+o], S[4*j+5+o]), pack_bf16(S[4*j+8+o], S[4*j+9+o]), pack_bf16(S[4*j+12+o], S[4*j+13+o]));
  }
  fence_async_smem();
  if (dbg) DBG(90);
  TR(4);
  ring_wait_full(x.bars, ring_add(e, isY ? 0 : 2));
  ring_wait_full(x.bars, e + 1);
}

template<int KIND>
__device__ __forceinline__ void slot(Ctx& x, Att& a, int& e, float (&O)[64], uint32_t (&Pn)[32], uint32_t (&Po)[32],
                                     bool more, bool isY, bool half, int pv, int pend) {
  float S[64];
  const int w = x.w;
  const bool skip = KIND == 0 && !isY;
  const int en = ring_add(e, skip ? 4 : 2), sn = ring_slot(en), sv = ring_slot(e) + 1, sk = skip ? ring_slot(ring_add(e, 2)) : sv - 1;
  const uint32_t dq = desc_lo(x.base + SM_Q + w * 4096, 16), dk = desc_lo(x.base, 16) + sk * 2048, dv = desc_lo(x.base, 8192) + sv * 2048;
  bar_sync(1 + w, 256);
  TR(5 + KIND);
  if (KIND == 2) {
    wgmma_fence();
    issue_qk(S, dq, dk); wgmma_commit();
    issue_pv<8>(O, Po, dv, 1); wgmma_commit();
    bar_arrive(1 + (w ^ 1), 256);
    wgmma_wait<1>();
  } else if (KIND == 0 && half) {
    float T[32];
    wgmma_fence(); issue_qk_half(T, dq, dk); wgmma_commit();
    a.i0 = rcp_fast(quad_sum(a.l0)); a.i1 = rcp_fast(quad_sum(a.l1));
    if (pv == PV_NONE) { wgmma_fence(); wgmma_commit(); }
    else               { wgmma_fence(); issue_pv<8>(O, Po, dv, pv == PV_ACC); wgmma_commit(); }
    bar_arrive(1 + (w ^ 1), 256);
    wgmma_wait<1>();
    fence_regs(T);
    #pragma unroll
    for (int i = 0; i < 32; i++) { S[i] = T[i]; asm volatile("" : "=f"(S[32 + i])); }
  } else {
    wgmma_fence(); issue_qk(S, dq, dk); wgmma_commit();
    if (KIND == 1 && pend >= 0) { bar_arrive(1 + (w ^ 1), 256); pack_tile(O, Pn, a.i0, a.i1); store_ctx(x, pend, Pn); TR(8); }
    if (KIND == 0) { a.i0 = rcp_fast(quad_sum(a.l0)); a.i1 = rcp_fast(quad_sum(a.l1)); }
    if (KIND == 0 && pv == PV_NONE) { wgmma_fence(); wgmma_commit(); }
    else if (pv == PV_HALF)         { wgmma_fence(); issue_pv<4>(O, Po, dv, 0); wgmma_commit(); }
    else                            { wgmma_fence(); issue_pv<8>(O, Po, dv, pv == PV_ACC); wgmma_commit(); }
    if (KIND == 0 || pend < 0) bar_arrive(1 + (w ^ 1), 256);
    wgmma_wait<1>();
  }
  fence_regs(S);
  fence_regs_u(Pn);
  TR(9);
  slot_release(x, sk, KIND == 0 && isY);
  const bool landed = KIND != 0 && mbar_test2(x.bars + B_RF + 8 * sn, en >= 6);
  float s0 = 0.f, s1 = 0.f;
  const bool was_classic = KIND != 0 && a.classic;
  if (KIND == 0) {
    a.l0 = 0.f; a.l1 = 0.f;
    if (!half) exp_pack<16, 32>(S, Pn, s0, s1);
    else {
      #pragma unroll
      for (int i = 16; i < 32; i++) asm volatile("" : "=r"(Pn[i]));
    }
    exp_pack_diag(S, Pn, diag_limit(), s0, s1);
    uint32_t b0 = __ballot_sync(0xffffffff, s0 >= SUM_LO), b1 = __ballot_sync(0xffffffff, s1 >= SUM_LO);
    b0 |= b0 >> 1; b0 |= b0 >> 2; b1 |= b1 >> 1; b1 |= b1 >> 2;
    a.classic = __any_sync(0xffffffff, !(s0 <= SUM_HI && s1 <= SUM_HI)) || (b0 & b1 & 0x11111111u) != 0x11111111u;
  } else {
    exp_pack<0, 32>(S, Pn, s0, s1);
    a.classic = __any_sync(0xffffffff, a.classic || !(s0 <= SUM_HI && s1 <= SUM_HI));
  }
  fence_regs_u(Pn);
  TR(10);
  if (!landed) {
    mbar_wait(x.bars + B_RF + 8 * sn, en >= 6);
    if (more) mbar_wait(x.bars + B_RF + 8 * sn + 8, en >= 6);
  }
  wgmma_wait<0>();
  fence_regs(O);
  fence_regs_u(Po);
  TR(11);
  slot_release(x, sv, KIND == 1 && isY && pv != PV_ACC);
  if (!NO_CLASSIC && __builtin_expect(a.classic, 0)) {
    float sc0, sc1;
    classic_tile(S, Pn, KIND == 0, half, was_classic, a.mc, a.l0, a.l1, s0, s1, sc0, sc1);
    if (KIND != 0) {
      #pragma unroll
      for (int j = 0; j < 16; j++) { O[4*j] *= sc0; O[4*j+1] *= sc0; O[4*j+2] *= sc1; O[4*j+3] *= sc1; }
    }
  }
  a.l0 += s0; a.l1 += s1;
  e = en;
}

__device__ __forceinline__ int attention(Ctx& x, const uint8_t* items, int nitems, int rank, uint32_t (&PA)[32], uint32_t (&PB)[32], int vtile) {
  int e = 0;
  float O[64];
  Att a;
  volatile float mc[2];
  a.l0 = 1.f; a.l1 = 1.f; a.i0 = 0.f; a.i1 = 0.f; a.classic = false; a.mc = mc;
  int pv = PV_NONE, cur = -1;
#define DBGS()
  #pragma unroll 1
  for (int it = 0; ; it++) {
    const bool isY = (it & 1) == x.w;
    int pend = cur;
    if (it < nitems) {
      const int item = items[it];
      const bool half = isY == (rank != 0);
      cur = item * 4 + (isY ? 3 - rank : rank);
      int rem = 2 * (item & 7) + (isY ? 1 : 0);
      DBG(16 + it);
      q_proj(x, e, isY, PA, PB, vtile, it == 0);
      vtile = -1;
      DBGS();
      slot<0>(x, a, e, O, PA, PB, rem > 0, isY, half, pv, -1);
      pv = half ? PV_HALF : PV_ZERO;
      #pragma unroll 1
      while (rem > 0) {
        DBGS();
        slot<1>(x, a, e, O, PB, PA, rem > 1, isY, false, pv, pend);
        pv = PV_ACC; pend = -1;
        if (rem == 1) break;
        rem -= 2;
        DBGS();
        slot<2>(x, a, e, O, PA, PB, rem > 0, false, false, 0, -1);
      }
      if (isY) continue;
    } else {
      DBGS();
      slot_release(x, 6, false);
      const uint32_t dv = desc_lo(x.base, 8192) + ring_slot(e) * 2048;
      bar_sync(1 + x.w, 256);
      if (pv == PV_HALF) { wgmma_fence(); issue_pv<4>(O, PB, dv, 0); wgmma_commit(); }
      else { wgmma_fence(); issue_pv<8>(O, PB, dv, pv == PV_ACC); wgmma_commit(); }
      if (isY) bar_arrive(1 + (x.w ^ 1), 256);
      a.i0 = rcp_fast(quad_sum(a.l0)); a.i1 = rcp_fast(quad_sum(a.l1));
      ring_wait_full(x.bars, e);
      wgmma_wait<0>();
      fence_regs(O);
      fence_regs_u(PB);
      ring_release(x, e, false);
    }
    if (pend >= 0) {
      pack_tile(O, PB, a.i0, a.i1);
      if (it == nitems) return pend;
      store_ctx(x, pend, PB);
    }
    #pragma unroll
    for (int i = 0; i < 32; i++) asm volatile("mov.b32 %0, %1;" : "=r"(PB[i]) : "r"(PA[i]));
  }
}

#define LN_AT 2
#define X_AT 6
#define PERT 0
#define CTX_T 3
#define PF_AT 5
#define PF_N 4
#define PF_MOE -3
constexpr float QSCALE = 0.08838834764831845f * 1.4426950408889634f;
__device__ __forceinline__ void mod_cta(Ctx& x, const __nv_bfloat16* cvec) {
  const int t = wg_tid(), ct = x.w * 128 + t;
  #pragma unroll 1
  for (int k = 0; k < 6; k++) slot_release(x, k, false);
  const uint32_t cv = __ldg(reinterpret_cast<const uint32_t*>(cvec) + ct);
  asm volatile("st.shared.u32 [%0], %1;" :: "r"(x.base + SM_H2 + ct * 4),
               "r"(pack_bf16(__fdividef(bf_lo(cv), 1.f + __expf(-bf_lo(cv))), __fdividef(bf_hi(cv), 1.f + __expf(-bf_hi(cv))))) : "memory");
  bar_sync(5, 256);
  float acc[64];
  int e = 0;
  #pragma unroll 1
  for (int g = 0; g < 24; g++) {
    uint32_t a[8];
    #pragma unroll
    for (int i = 0; i < 8; i++) a[i] = lds_u32(x.base + SM_H2 + (g & 7) * 128 + i * 16 + (t & 3) * 4);
    ring_wait_full(x.bars, e);
    const uint32_t db = desc_lo(x.base + x.w * 16384, 8192) + ring_slot(e) * 2048;
    wgmma_fence();
    wgmma_rs_n128<1, 0, SW128>(acc, a[0], a[0], a[1], a[1], db, g & 7);
    wgmma_rs_n128<1, 128, SW128>(acc, a[2], a[2], a[3], a[3], db, 1);
    wgmma_rs_n128<1, 256, SW128>(acc, a[4], a[4], a[5], a[5], db, 1);
    wgmma_rs_n128<1, 384, SW128>(acc, a[6], a[6], a[7], a[7], db, 1);
    wgmma_commit();
    wgmma_wait<0>();
    fence_regs(acc);
    ring_release(x, e, false);
    e = ring_add(e, 1);
    if ((g & 7) == 7) {
      if (t < 4) {
        const float sc = (g == 7 && blockIdx.x < NCTA + 2) ? QSCALE : 1.f;
        uint32_t* dst = reinterpret_cast<uint32_t*>(g_mod + (g >> 3) * 1024 + (blockIdx.x - NCTA) * 256 + x.w * 128) + t;
        #pragma unroll
        for (int j = 0; j < 16; j++) dst[4 * j] = pack_bf16(rbf(acc[4*j]) * sc, rbf(acc[4*j+1]) * sc);
      }
      publish(x, g == 7 ? C_MOD : C_MOD2);
      DBG(1 + (g >> 3));
    }
  }
}

__global__ void __cluster_dims__(2, 1, 1) __launch_bounds__(384, 1)
k_fused(const __grid_constant__ CUtensorMap tmC, const __grid_constant__ CUtensorMap tmWq,
        const __grid_constant__ CUtensorMap tmWk, const __grid_constant__ CUtensorMap tmWv,
        const __grid_constant__ CUtensorMap tmWo, const __grid_constant__ CUtensorMap tmWg,
        const __grid_constant__ CUtensorMap tmWu, const __grid_constant__ CUtensorMap tmWm,
        const __grid_constant__ Sched sched,
        const __nv_bfloat16* __restrict__ xin,
        const __nv_bfloat16* __restrict__ cvec, const __nv_bfloat16* __restrict__ w_o,
        const __nv_bfloat16* __restrict__ w_r, const __nv_bfloat16* __restrict__ w_gate, const __nv_bfloat16* __restrict__ w_up,
        const __nv_bfloat16* __restrict__ w_down, __nv_bfloat16* __restrict__ out) {
  extern __shared__ __align__(1024) uint8_t smem_raw[];
  const uint32_t base = smem_u32(smem_raw), bars = base + SM_BAR;
  const int warp = __shfl_sync(0xffffffff, threadIdx.x >> 5, 0), wg = warp >> 2;
  const int rank = cluster_ctarank(), p = blockIdx.x >> 1;
  const int mt = (p & 7) * 2 + rank;
  const bool spare = blockIdx.x >= NCTA;
  #pragma unroll
  for (int i = 0; i < PERT; i++) { uint32_t d; asm volatile("mov.u32 %0, %%laneid;" : "=r"(d)); }
  {
    const int h0 = KHEAD0 + (p >> 3);
    if (warp == 11) { prefetch_tmap(&tmC); prefetch_tmap(&tmWk); }
    #pragma unroll 1
    for (int t = warp == 8 ? 0 : warp < 8 ? warp + 1 : warp == 11 ? 64 : warp; t < B_PUB / 8; t += (warp == 8 ? 64 : 10))
      w_mbar_init(bars + 8 * t, t < B_WE / 8 ? 1 : t < B_RE / 8 ? 2 : 4);
    fence_mbar_init();
    cluster_arrive();
    if (warp == 9) prefetch_tmap(&tmWv);
    if (wg == 2) bar_arrive(1, 256);
    if (warp == 8 && !spare) {
      #pragma unroll 1
      for (int kb = 0; kb < 8; kb++) {
        w_expect_tx(bars + B_AF + 8 * kb, 16384);
        tma_load_2d(base + k_addrA(kb), &tmC, bars + B_AF + 8 * kb, kb * 64, mt * 128);
        if (kb == 0) cluster_wait();
        if (kb < 6) {
          w_expect_tx(bars + B_WF + 8 * kb, 16384);
          tma_load_2d_mc(base + k_addrW(kb) + rank * 8192, &tmWk, bars + B_WF + 8 * kb, h0 * 128 + rank * 64, kb * 64);
        }
      }
    }
  }
  const Sched::Pair& sp = sched.pair[p];
  const int nitems = sp.nitems, nsteps = sp.nsteps;
  auto oent = [&](int k) -> uint32_t { return sp.oent[k]; };
  const int ot = sp.otask, m = (ot & 7) * 2 + rank, grp = m * 8 + (ot >> 3);

  if (wg == 0) {
    asm volatile("setmaxnreg.dec.sync.aligned.u32 24;");
    const int lane = threadIdx.x & 31;
    #pragma unroll 1
    for (int t = B_PUB / 8 + warp; t < 80; t += 4) w_mbar_init(bars + 8 * t, t < B_RDY / 8 ? 4 : 1);
    bar_sync(6, 128);
    bar_arrive(7, 256); bar_arrive(8, 256);
    cluster_wait();
    const unsigned int tag = ld_relaxed(&g_epoch) + 1;
    if (warp == 0) {
      if (!spare) {
        int s = 0, ph = 0;
        tma_prefetch_2d(&tmWv, sp.khead[0] * 128 + rank * 64, (p & 7) * 64);
        #pragma unroll 1
        for (int g = 6; g < 64; g++) {
          const int u = g >> 3, kb = g & 7;
          if (kb == 0 && u < 7) tma_prefetch_2d((u & 1) ? &tmWk : &tmWv, sp.khead[(u + 1) >> 1] * 128 + rank * 64, (p & 7) * 64);
          mbar_wait(bars + B_WE + 8 * s, ph);
          w_expect_tx(bars + B_WF + 8 * s, 16384);
          tma_load_2d_mc(base + k_addrW(s) + rank * 8192, (u & 1) ? &tmWv : &tmWk, bars + B_WF + 8 * s, sp.khead[u >> 1] * 128 + rank * 64, kb * 64);
          if (++s == 6) { s = 0; ph ^= 1; }
        }
      }
      int s = 0, ph = 0;
      auto next_entry = [&](int bytes) {
        mbar_wait(bars + B_RE + 8 * s, ph);
        w_expect_tx(bars + B_RF + 8 * s, bytes);
      };
      auto advance = [&]() { if (++s == 6) { s = 0; ph ^= 1; } };
      if (spare) {
        #pragma unroll 1
        for (int g = 0; g < 24; g++) {
          if (g == 8) mbar_wait(bars + R_MOD, 0);
          next_entry(32768);
          for (int k = 0; k < 2; k++) tma_load_3d(base + s * 32768 + k * 16384, &tmWm, bars + B_RF + 8 * s, 0, (g & 7) * 64, (g >> 3) * 16 + (blockIdx.x - NCTA) * 4 + k * 2);
          advance();
        }
      }
      mbar_wait(bars + R_H1, 0);
      fence_async_global();
      int vrow = -1;
      #pragma unroll 1
      for (int i = 0; i <= nitems; i++) {
        const int item = sp.item[i & (MAX_ITEMS - 1)], h = item >> 3, j = item & 7;
        if (i < nitems) {
          const int row0 = j * 256 + ((i & 1) ? rank : 3 - rank) * 64, row1 = j * 256 + ((i & 1) ? 3 - rank : rank) * 64;
          #pragma unroll 1
          for (int kb = 0; kb < 8; kb++) {
            next_entry(32768);
            tma_load_2d_mc(base + s * 32768 + 16384 + rank * 8192, &tmWq, bars + B_RF + 8 * s, h * 128 + rank * 64, kb * 64);
            bulk_load(base + s * 32768, sched.h1 + row0 * DM + kb * 4096, 8192, bars + B_RF + 8 * s);
            bulk_load(base + s * 32768 + 8192, sched.h1 + row1 * DM + kb * 4096, 8192, bars + B_RF + 8 * s);
            advance();
          }
          mbar_wait(bars + R_ITEM + 8 * i, 0);
          fence_async_global();
        }
        #pragma unroll 1
        for (int n = i < nitems ? 4 * j + 3 : 0; n >= 0; n--) {
          const int krow = (h * 2 + rank) * SEQ + (n >> 1) * 128 + ((sp.lastuse[i & (MAX_ITEMS - 1)] >> (n >> 1)) & 1);
          const int row = (n & 1) ? krow : vrow;
          if (i + 1 == nitems && n == min(4 * j + 3, 2 * PF_AT + 1)) w_arrive(bars + R_NEAR);
          next_entry(row >= 0 ? 32768 : 0);
          if (row >= 0) bulk_load_mc(base + s * 32768 + rank * 16384, sched.kvc + (size_t)(row & ~1) * 64, bars + B_RF + 8 * s, row & 1);
          advance();
          if (!(n & 1)) vrow = krow + 64 * SEQ;
        }
      }
      if (!spare) {
      const int oc = ((ot >> 3) & 1) * 4 + rank * 2;
      auto o_next = [&](int k, int bytes) {
        const uint32_t v = oent(k); s = v & 7;
        mbar_wait(bars + B_RE + 8 * s, v >> 3);
        w_expect_tx(bars + B_RF + 8 * s, bytes);
      };
      #pragma unroll 1
      for (int i = 0; i < nsteps; i++) {
        const int c0 = sp.ochunk[i][0], c1 = sp.ochunk[i][1];
        const int pf = PF_MOE > 0 ? i - PF_MOE : i - nsteps - PF_MOE;
        if (pf >= 0 && pf < 3)
          bulk_prefetch((pf == 0 ? w_gate : pf == 1 ? w_up : w_down) + (size_t)blockIdx.x * (DM * FF / NCTA), DM * FF / NCTA * 2);
        if (c0 < 64) { o_next(3 * i, 32768); tma_load_3d_mc(base + s * 32768 + rank * 16384, &tmWo, bars + B_RF + 8 * s, 0, c0 * 64, oc); }
        mbar_wait(bars + R_CTX + 8 * i, 0);
        fence_async_global();
        o_next(3 * i + 1, c0 < 64 ? 32768 : 16384);
        if (c0 < 64) bulk_load(base + s * 32768, sched.kvc + (size_t)((128 + c0) * SEQ + m * 128) * 64, 16384, bars + B_RF + 8 * s);
        bulk_load(base + s * 32768 + 16384, sched.kvc + (size_t)((128 + c1) * SEQ + m * 128) * 64, 16384, bars + B_RF + 8 * s);
        o_next(3 * i + 2, 32768);
        tma_load_3d_mc(base + s * 32768 + rank * 16384, &tmWo, bars + B_RF + 8 * s, 0, c1 * 64, oc);
      }
      const int f0 = (blockIdx.x < FF / 16 ? blockIdx.x : 0) * 16;
      o_next(3 * nsteps, 32768);
      bulk_load(base + s * 32768, w_down + (size_t)f0 * DM, 16384, bars + B_RF + 8 * s);
      bulk_load(base + s * 32768 + 16384, xin + (size_t)grp * 16 * DM, 16384, bars + B_RF + 8 * s);
      o_next(3 * nsteps + 1, 32768);
      #pragma unroll 1
      for (int k = 0; k < 4; k++) tma_load_2d(base + s * 32768 + k * 8192, (k & 2) ? &tmWu : &tmWg, bars + B_RF + 8 * s, f0, (k & 1) * 256);
      #pragma unroll 1
      for (int k = 0; k < 4; k++) w_expect_tx(bars + R_PART + 8 * k, 16384);
      mbar_wait(bars + B_PUB + 8 * (5 + nitems), 0);
      mbar_wait(bars + B_PUB + 8 * (NPUB + 5 + nitems), 0);
      uint32_t todo = 0xff;
      #pragma unroll 1
      for (int n = 0; n < WAIT_LIM && todo; n++) {
        uint32_t now = __ballot_sync(0xffffffff, ld_acquire(&g_cnt[C_PART + (m * 2 + (ot >> 5)) * 32 + (lane & 7)]) == tag) & todo;
        todo &= ~now;
        if (now) fence_async_global();
        #pragma unroll 1
        for (; now; now &= now - 1) {
          const int q = __ffs(now) - 1;
          bulk_load(base + (oent(3 * nsteps - 3 + (q >> 2)) & 7) * 32768 + (q & 3) * 8192, sched.part + (grp * 8 + q) * 4096, 8192, bars + R_PART + 8 * (q >> 1));
        }
      }
      DBGP(11);
      }
    } else if (warp < 3) {
      const int w = warp - 1, n1 = w * NPUB + (spare ? 3 : 6) + nitems;
      #pragma unroll 1
      for (int n = w * NPUB; n < n1; n++) {
        #pragma unroll 1
        for (int k = 0; k < 8 * WAIT_LIM; k++) { if (mbar_try(bars + B_PUB + 8 * n, 0)) break; }
        const uint32_t idx = lds_u32(base + SM_MAIL + 4 * n);
        fence_async_global();
        if (lane == 0 && idx < (unsigned)C_END) red_release(idx);
        __syncwarp();
      }
    } else {
      *reinterpret_cast<volatile uint32_t*>(smem_raw + SM_KEY + 48) = tag;
      if (!spare) { mbar_wait(bars + B_AF + 8 * X_AT, 0); bulk_prefetch(xin + (size_t)blockIdx.x * 16 * DM, 16 * DM * 2); }
      #pragma unroll 1
      for (int n = 0; n < 8 + nsteps; n++) {
        if (n == 2 + nitems) n = 7;
        int idx = n == 0 ? C_MOD : n == 1 ? C_H1 : C_MOD2, cnt = n == 0 ? 8 : n == 1 ? 256 : 16;
        if (n >= 1 && n <= nitems) { const int item = sp.item[n - 1]; tma_prefetch_2d(&tmWq, (item >> 3) * 128 + rank * 64, (item & 7) * 64); }
        if (n >= 2 && n < 7) { idx = C_KV + (sp.item[n - 2] >> 3); cnt = 32; }
        if (n >= 8) { const int c0 = sp.ochunk[n - 8][0], c1 = sp.ochunk[n - 8][1]; idx = C_CTX + (((lane & 1) && c0 < 64 ? c0 : c1) >> 1) * 8 + (ot & 7); cnt = 4; }
        wait_count_lazy(idx, cnt * tag);
        w_arrive(bars + B_RDY + 8 * n);
        if (n == 0) DBGP(12);
        if (n == 8 + PF_N - 1) {
          #pragma unroll 1
          for (int k = 0; k < 8 * WAIT_LIM; k++) { if (mbar_try(bars + R_NEAR, 0)) break; }
          bulk_prefetch(w_o + (size_t)blockIdx.x * (NH * DH * DM / NCTA), NH * DH * DM / NCTA * 2);
          #pragma unroll 1
          for (int k = 0; k < PF_N; k++) {
            const int cc = sp.ochunk[k][(ot >> 3) & 1];
            if (cc < 64) bulk_prefetch(sched.kvc + ((size_t)(128 + cc) * SEQ + m * 128) * 64, 16384);
          }
        }
      }
    }
    __syncwarp();
    cluster_arrive();
    if (!spare) {
      bar_sync(6, 128);
      asm volatile("setmaxnreg.inc.sync.aligned.u32 88;");
      const int pos = blockIdx.x * 4 + (lane & 1) * 2, col = (blockIdx.x >> 2) * 16 + (blockIdx.x & 3) * 2 + (lane & 1) * 8, src = threadIdx.x >> 1;
      uint32_t gbest = 0, hh = 0, gbf = 0;
      uint2 xx = make_uint2(0, 0);
      uint4 ya = make_uint4(0, 0, 0, 0), yb = make_uint4(0, tag, 0, tag);
      auto poll_y = [&]() {
        if (ya.y != tag || ya.w != tag) ya = ld_tagged2(&g_yll[src][pos]);
        if (yb.y != tag || yb.w != tag) yb = ld_tagged2(&g_yll[src + 64][pos]);
        return __all_sync(0xffffffff, ya.y == tag && ya.w == tag && yb.y == tag && yb.w == tag);
      };
      ya.y = tag - 1; if (src + 64 < FF / 16) yb.y = tag - 1;
      poll_y();
      if (warp == 3) {
        gbf = __ldcg(reinterpret_cast<const uint32_t*>(g_mod + 5 * DM + col));
        uint32_t have = 0;
        uint2 k[4];
        #pragma unroll
        for (int i = 0; i < 4; i++) k[i] = make_uint2(0, tag - 1);
        #pragma unroll 1
        for (int n = 0; n < WAIT_LIM; n++) {
          #pragma unroll
          for (int i = 0; i < 4; i++) if (k[i].y != tag) k[i] = ld_tagged(&g_keys[i * 32 + lane][0]);
          if (gbest != have) {
            const int g = ((0xffffu - gbest) >> 4) & 127;
            uint4 hv[4];
            #pragma unroll
            for (int i = 0; i < 4; i++) hv[i] = ld_tagged2(&g_row[g][0][i * 64 + lane * 2]);
            xx = ld_tagged(&g_row[g][1][col >> 1]);
            bool ok = xx.y == tag;
            #pragma unroll
            for (int i = 0; i < 4; i++) { ok = ok && hv[i].y == tag && hv[i].w == tag; reinterpret_cast<uint2*>(smem_raw + SM_H2)[i * 32 + lane] = make_uint2(hv[i].x, hv[i].z); }
            if (lane == 0) *reinterpret_cast<uint32_t*>(smem_raw + SM_KEY + 32) = gbest;
            have = __all_sync(0xffffffff, ok) ? gbest : 0;
          }
          bool all = true;
          #pragma unroll
          for (int i = 0; i < 4; i++) { all = all && k[i].y == tag; gbest = max(gbest, k[i].y == tag ? k[i].x : 0u); }
          gbest = __reduce_max_sync(0xffffffff, gbest);
          if (__all_sync(0xffffffff, all) && gbest == have) break;
        }
        w_arrive(bars + R_KEY);
        if (blockIdx.x == 0 && lane == 0) g_epoch = tag;
        hh = lds_u32(base + SM_H2 + col * 2);
        DBGP(13);
      }
      const uint32_t sb16 = gbest & 0xffff0000u;
      const float rsel = __uint_as_float((sb16 & 0x80000000u) ? (sb16 & 0x7fffffffu) : (~sb16 & 0xffff0000u));
      const float rs = rbf(__fdividef(1.f, 1.f + __expf(-rsel)));
      mbar_wait(bars + R_KEY, 1);
      #pragma unroll 1
      for (int n = 0; n < WAIT_LIM; n++) { if (poll_y()) break; }
      float y0 = __uint_as_float(ya.x) + __uint_as_float(yb.x), y1 = __uint_as_float(ya.z) + __uint_as_float(yb.z);
      #pragma unroll
      for (int o = 2; o < 32; o <<= 1) { y0 += __shfl_xor_sync(0xffffffff, y0, o); y1 += __shfl_xor_sync(0xffffffff, y1, o); }
      float2* s_y = reinterpret_cast<float2*>(smem_raw + SM_KEY + 64);
      if (lane < 2) s_y[warp * 2 + lane] = make_float2(y0, y1);
      bar_sync(6, 128);
      if (warp == 3 && lane < 2) {
        y0 = 0.f; y1 = 0.f;
        #pragma unroll
        for (int i = 0; i < 4; i++) { y0 += reinterpret_cast<const float*>(s_y)[i * 4 + lane]; y1 += reinterpret_cast<const float*>(s_y)[i * 4 + 2 + lane]; }
        const float o0 = bf_lo(xx.x) + rbf(bf_lo(gbf) * rbf(bf_lo(hh) + rbf(rbf(y0) * rs)));
        const float o1 = bf_hi(xx.x) + rbf(bf_hi(gbf) * rbf(bf_hi(hh) + rbf(rbf(y1) * rs)));
        *reinterpret_cast<uint32_t*>(out + (size_t)((0xffffu - gbest) & (SEQ - 1)) * DM + col) = pack_bf16(o0, o1);
      }
      DBGP(14);
    }
    __syncwarp();
    cluster_wait();
  } else {
    asm volatile("setmaxnreg.inc.sync.aligned.u32 240;");
    Ctx x;
    x.w = wg - 1; x.base = base; x.bars = bars; x.nev = 0; x.sched = &sched;
    const int w = x.w, warp4 = warp & 3;
    x.rel = mapa(bars, (warp4 & 1) ^ 1);
    x.rel1 = (threadIdx.x & 127) == 32 || (threadIdx.x & 127) == 64;
    if (warp != 8 || spare) cluster_wait();
    if (w == 1 || spare) bar_sync(7 + w, 256);
    DBG(1);
    uint32_t PA[32], PB[32];
    int vtile = -1;
    if (spare) {
      mod_cta(x, cvec);
    } else {
      const int lane = wg_tid() & 31;
      Row xn[2];
      float acc0[64], acc1[64];
      int s = 2 * w, ph = w;
      #pragma unroll 1
      for (int u = w; u < 8; u += 2) {
        bar_sync(1 + w, 256);
        DBG(4 + (u >> 1) * 3);
        int ps = 0;
        #pragma unroll 1
        for (int kb = 0; kb < 8; kb++) {
          if (u < 2) mbar_wait(bars + B_AF + 8 * kb, 0);
          mbar_wait(bars + B_WF + 8 * s, ph);
          const uint32_t da = desc_lo(base + k_addrA(kb), 16), dw = desc_lo(base + k_addrW(s), 8192);
          wgmma_fence();
          kblock_n128<0>(acc0, da, dw, kb != 0);
          kblock_n128<512>(acc1, da, dw, kb != 0);
          wgmma_commit();
          if (kb == 7) bar_arrive(1 + (w ^ 1), 256);
          if (kb > 0) {
            wgmma_wait<1>();
            mbar_arrive_remote_if(x.rel + B_WE + 8 * ps, x.rel1);
            if (u == 7 && !(kb & 1)) {
              ring_release(x, kb == 2 ? 0 : kb - 3, false);
              if (kb > 2) ring_release(x, kb - 2, false);
            }
          }
          ps = s;
          if (++s == 6) { s = 0; ph ^= 1; }
        }
        Row t[2];
        const int lrow = blockIdx.x * 16 + w * 8 + warp4 * 2;
        if (u == w) { t[0] = ldg_row(xin + (size_t)lrow * DM, lane); t[1] = ldg_row(xin + (size_t)(lrow + 1) * DM, lane); }
        if (u == LN_AT || u == LN_AT + 1) {
          mbar_wait(bars + R_MOD, 0);
          t[0] = ldca_row(g_mod, lane); t[1] = ldca_row(g_mod + DM, lane);
        }
        wgmma_wait<0>();
        fence_regs(acc0); fence_regs(acc1);
        DBG(5 + (u >> 1) * 3);
        mbar_arrive_remote_if(x.rel + B_WE + 8 * ps, x.rel1);
        if (u == 6) { for (int k = 0; k < 5; k++) ring_release(x, k, false); }
        if (u >= 6) ring_release(x, 5, false);
        if (V_AT >= 0 && u == 7) {
          pack_tile(acc0, PA, 1.f, 1.f); pack_tile(acc1, PB, 1.f, 1.f);
          vtile = sp.khead[3] * 16 + mt;
          break;
        }
        s += 2; ph ^= 1; if (s >= 6) { s -= 6; ph ^= 1; }
        if (u == 0) bar_sync(7, 256);
        if (u == w) {
          float st[4] = {0.f, 0.f, 0.f, 0.f};
          #pragma unroll
          for (int i = 0; i < 32; i++) { const float v = row_at(t[i >> 4], i & 15); st[(i >> 4) * 2] += v; st[(i >> 4) * 2 + 1] = fmaf(v, v, st[(i >> 4) * 2 + 1]); }
          warp_sums(st);
          #pragma unroll
          for (int r = 0; r < 2; r++) { ln_stats(st[2*r], st[2*r+1]); xn[r] = ln_apply(t[r], st[2*r], st[2*r+1] * QSCALE); }
        }
        if ((u == LN_AT || u == LN_AT + 1)) {
          #pragma unroll
          for (int r = 0; r < 2; r++) {
            const Row hr = fma_row(xn[r], one_plus(t[1]), t[0]);
            __nv_bfloat16* hp = sched.h1 + (lrow & ~63) * DM + (lane >> 3) * 4096 + ((lrow + r) & 63) * 64 + (((lane ^ (lrow + r)) & 7) << 3);
            stg_v4(hp, hr.v[0], hr.v[1], hr.v[2], hr.v[3]); stg_v4(hp + 4 * 4096, hr.v[4], hr.v[5], hr.v[6], hr.v[7]);
          }
        }
        const int tile = sp.khead[u >> 1] * 16 + mt;
        __nv_bfloat16* dst = kv_tile(x, tile);
        uint32_t D[32];
        pack_tile(acc0, D, 1.f, 1.f); store_tile(dst + 2048, D);
        pack_tile(acc1, D, 1.f, 1.f); store_tile(dst, D);
        if (u == LN_AT || u == LN_AT + 1) publish(x, C_H1);
        publish(x, C_KV + (tile >> 4));
        DBG(6 + (u >> 1) * 3);
      }
    }
    x.tr = base + SM_RED + w * 1024;
    const int last = attention(x, sp.item, nitems, rank, PA, PB, vtile);
    DBG(100);
    const int lane = wg_tid() & 31, cw = w * 4 + warp4, ct = cw * 32 + lane;
    const int row0 = grp * 16 + cw * 2;
    const bool moe_cta = blockIdx.x < FF / 16;
    if (spare) { store_ctx(x, last, PB); __syncwarp(); cluster_arrive(); cluster_wait(); return; }
    const int kl = 3 * nsteps - 3;
    {
      float accA[64], accB[64];
      const int t0 = oent(0) == oent(1);
      uint32_t pa = 0, pb = 0;
      #pragma unroll 1
      for (int t = t0; t < 2 * nsteps - 2; t++) {
        const uint32_t eb = oent(3 * (t >> 1) + 2 * (t & 1)), ea = oent(3 * (t >> 1) + 1);
        o_wait_full(bars, eb);
        o_wait_full(bars, ea);
        const uint32_t da = desc_lo(base + w * 4096, 16) + (ea & 7) * 2048 + (t & 1) * 1024, db = desc_lo(base, 8192) + (eb & 7) * 2048;
        wgmma_fence();
        kblock_n128<0, 0, SW64>(accA, da, db, t != t0); kblock_n128<0, 1024, SW64>(accB, da, db, t != t0);
        wgmma_commit();
        if (t == CTX_T) store_ctx(x, last, PB);
        if (t > t0) { wgmma_wait<1>(); slot_release(x, pb, false); if (!(t & 1)) slot_release(x, pa, false); }
        pa = ea & 7; pb = eb & 7;
      }
      const uint32_t e0 = oent(kl), ea = oent(kl + 1), eb = oent(kl + 2);
      const uint32_t da = desc_lo(base + w * 4096, 16) + (ea & 7) * 2048;
      const uint32_t db0 = desc_lo(base, 8192) + (e0 & 7) * 2048, db1 = desc_lo(base, 8192) + (eb & 7) * 2048;
      o_wait_full(bars, e0);
      o_wait_full(bars, ea);
      o_wait_full(bars, eb);
      wgmma_fence();
      kblock_n128<0, 0, SW64>(accA, da, db0, 1); kblock_n128<1024, 0, SW64>(accA, da, db1, 1);
      wgmma_commit();
      kblock_n128<0, 1024, SW64>(accB, da, db0, 1); kblock_n128<1024, 1024, SW64>(accB, da, db1, 1);
      wgmma_commit();
      __syncwarp();
      cluster_arrive();
      __nv_bfloat16* dst = sched.part + ((m * 8 + cw) * 8 + (ot >> 3)) * 4096;
      auto send = [&](const float (&acc)[64], int h) {
        uint32_t D[32];
        pack_tile(acc, D, 1.f, 1.f);
        #pragma unroll
        for (int i = 0; i < 8; i++) stg_v4(dst + (h * 8 + i) * 256 + ((lane ^ (h * 4 + (i >> 1))) << 3), D[4*i], D[4*i+1], D[4*i+2], D[4*i+3]);
      };
      wgmma_wait<1>();
      fence_regs(accA);
      DBG(120);
      send(accA, 0);
      o_wait_full(bars, eb);
      wgmma_wait<0>();
      fence_regs(accB);
      DBG(101);
      send(accB, 1);
      publish(x, C_PART + (m * 2 + w) * 32 + (ot >> 3));
      DBG(121);
      DBG(102);
    }
    asm volatile("setmaxnreg.dec.sync.aligned.u32 208;");
    const Row ga = ldca_row(g_mod + 2 * DM, lane), sb = ldca_row(g_mod + 3 * DM, lane), cb = ldca_row(g_mod + 4 * DM, lane), gb = ldca_row(g_mod + 5 * DM, lane);
    const Row wr = ldca_row(w_r, lane);
    const uint32_t sD = base + (oent(kl + 3) & 7) * 32768, sW = base + (oent(kl + 4) & 7) * 32768;
    o_wait_full(bars, oent(kl + 3)); o_wait_full(bars, oent(kl + 4));
    Row x1[2];
    #pragma unroll
    for (int r = 0; r < 2; r++) x1[r] = lds_row(sD + 16384 + (cw * 2 + r) * 1024, lane);
    uint4 wgv[4], wuv[4], wdv[4];
    #pragma unroll
    for (int r = 0; r < 4; r++) {
      const uint32_t k = (lane & 7) + ((lane >> 4) << 3), h = (lane & 8) * 2;
      wgv[r] = ldsm_x4_t(sW + (cw * 64 + r * 16 + k) * 32 + h);
      wuv[r] = ldsm_x4_t(sW + 16384 + (cw * 64 + r * 16 + k) * 32 + h);
      wdv[r] = ldsm_x4_t(sD + k * 1024 + (cw * 64 + r * 16) * 2 + h);
    }
    const Row cb1 = one_plus(cb);
    const unsigned int tag = lds_u32(base + SM_KEY + 48);
    DBG(103);
    float u[16], ub[2] = {0.f, 0.f};
    #pragma unroll
    for (int i = 0; i < 16; i++) { u[i] = row_at(cb1, i) * row_at(wr, i); ub[0] += u[i]; ub[1] = fmaf(row_at(sb, i), row_at(wr, i), ub[1]); }
    warp_sums(ub);
    float st[6] = {0.f, 0.f, 0.f, 0.f, 0.f, 0.f};
    uint32_t key[2];
    {
      const uint32_t po = base + ((lane & 7) * 2 + (cw >> 2)) * 512 + (cw & 3) * 128;
      Row av[2][2];
      #pragma unroll
      for (int k = 0; k < 4; k++) {
        mbar_wait(bars + R_PART + 8 * k, 1);
        const uint32_t pa = po + (oent(kl + (k >> 1)) & 7) * 32768 + (k & 1) * 16384;
        #pragma unroll
        for (int r = 0; r < 2; r++) {
          const uint32_t sw = ((r * 4 + (lane >> 3)) ^ (lane & 7)) << 4;
          const uint4 lo = ldsm_x4(pa + sw), hi = ldsm_x4(pa + 8192 + sw);
          const Row v{{lo.x, lo.y, lo.z, lo.w, hi.x, hi.y, hi.z, hi.w}};
          av[r][k >> 1] = (k & 1) ? add_row(av[r][k >> 1], v) : v;
        }
      }
      DBG(104);
      #pragma unroll
      for (int r = 0; r < 2; r++) {
        x1[r] = fma_row(ga, add_row(av[r][0], av[r][1]), x1[r]);
        #pragma unroll
        for (int i = 0; i < 16; i++) { const float v = row_at(x1[r], i); st[3*r] += v; st[3*r+1] = fmaf(v, v, st[3*r+1]); st[3*r+2] = fmaf(v, u[i], st[3*r+2]); }
      }
      warp_sums(st);
      #pragma unroll
      for (int r = 0; r < 2; r++) {
        ln_stats(st[3*r], st[3*r+1]);
        const uint32_t rb = pack_bf16(0.f, fmaf(st[3*r+1], fmaf(-st[3*r], ub[0], st[3*r+2]), ub[1]));
        key[r] = (((rb & 0x80000000u) ? ~rb : (rb | 0x80000000u)) & 0xffff0000u) | (0xffffu - (uint32_t)(row0 + r));
      }
    }
    DBG(105);
    float* s_red = reinterpret_cast<float*>(smem_raw + SM_RED);
    uint32_t* s_key = reinterpret_cast<uint32_t*>(smem_raw + SM_KEY);
    const int rb = key[1] > key[0];
    const uint32_t wbest = rb ? key[1] : key[0];
    if (lane == 0) s_key[cw] = wbest;
    bar_sync(5, 256);
    const uint32_t cbest = __reduce_max_sync(0xffffffff, s_key[lane & 7]);
    if (wbest == cbest && lane == 0) st_tagged(&g_keys[grp][0], cbest, tag);
    Row xb, xo;
    #pragma unroll
    for (int i = 0; i < 8; i++) { xb.v[i] = rb ? x1[1].v[i] : x1[0].v[i]; xo.v[i] = rb ? x1[0].v[i] : x1[1].v[i]; }
    const Row hb = fma_row(ln_apply(xb, rb ? st[3] : st[0], rb ? st[4] : st[1]), cb1, sb);
    if (wbest == cbest) {
      #pragma unroll
      for (int i = 0; i < 4; i++) st_tagged2(&g_row[grp][0][(i >> 1) * 128 + lane * 4 + (i & 1) * 2], hb.v[2*i], hb.v[2*i+1], tag);
      #pragma unroll
      for (int i = 0; i < 4; i++) st_tagged2(&g_row[grp][1][(i >> 1) * 128 + lane * 4 + (i & 1) * 2], xb.v[2*i], xb.v[2*i+1], tag);
    }
    DBG(106);
    const Row ob = fma_row(gb, hb, xb);
    if (wbest != cbest) store_row(out + (size_t)(row0 + rb) * DM, lane, ob);
    store_row(out + (size_t)(row0 + 1 - rb) * DM, lane, fma_row(gb, fma_row(ln_apply(xo, rb ? st[0] : st[3], rb ? st[1] : st[4]), cb1, sb), xo));
    mbar_wait(bars + R_KEY, 1);
    DBG(107);
    if (moe_cta) {
      float cg[4] = {0, 0, 0, 0}, cu[4] = {0, 0, 0, 0};
      #pragma unroll
      for (int r = 0; r < 4; r++) {
        const uint32_t b0 = lds_u32(base + SM_H2 + (cw * 64 + r * 16) * 2 + (lane & 3) * 4), b1 = lds_u32(base + SM_H2 + (cw * 64 + r * 16) * 2 + 16 + (lane & 3) * 4);
        mma16816(cg, wgv[r], b0, b1); mma16816(cu, wuv[r], b0, b1);
      }
      s_red[cw * 32 + (lane & 3) * 8 + (lane >> 2)] = (lane & 2) ? ((lane & 1) ? cu[2] : cu[0]) : ((lane & 1) ? cg[2] : cg[0]);
      bar_sync(5, 256);
      float g = 0.f;
      #pragma unroll
      for (int i = 0; i < 8; i++) g += s_red[i * 32 + lane];
      g = rbf(g);
      const float act = rbf(__fdividef(g, 1.f + __expf(-g))) * __shfl_down_sync(0xffffffff, g, 16);
      const uint32_t a2 = pack_bf16(act, __shfl_down_sync(0xffffffff, act, 1));
      const uint32_t b0 = __shfl_sync(0xffffffff, a2, (lane & 3) * 2), b1 = __shfl_sync(0xffffffff, a2, (lane & 3) * 2 + 8);
      float y0 = 0.f, y1 = 0.f;
      #pragma unroll
      for (int r = 0; r < 4; r++) {
        float c[4] = {0, 0, 0, 0};
        mma16816(c, wdv[r], b0, b1);
        if ((lane & 3) == r) { y0 = c[0]; y1 = c[2]; }
      }
      st_tagged2(&g_yll[blockIdx.x][cw * 64 + (lane & 3) * 16 + (lane >> 2) * 2], __float_as_uint(y0), __float_as_uint(y1), tag);
    }
    DBG(108);
    if (wbest == cbest && wbest != s_key[8]) store_row(out + (size_t)(row0 + rb) * DM, lane, ob);
    DBG(109);
    __syncwarp();
    cluster_wait();
  }
}

typedef CUresult (*EncodeFn)(CUtensorMap*, CUtensorMapDataType, cuuint32_t, void*, const cuuint64_t*, const cuuint64_t*, const cuuint32_t*,
                             const cuuint32_t*, CUtensorMapInterleave, CUtensorMapSwizzle, CUtensorMapL2promotion, CUtensorMapFloatOOBfill);

struct HostState {
  bool ready = false;
  EncodeFn encode = nullptr;
  CUtensorMap tmC, tmWq, tmWk, tmWv, tmWo, tmWg, tmWu, tmWm;
  Sched sched;
};

void make_map(EncodeFn enc, CUtensorMap* m, const void* ptr, int rank, const cuuint64_t* dims, const cuuint64_t* strides, const cuuint32_t* box, bool swizzle = true) {
  const cuuint32_t es[3] = {1, 1, 1};
  enc(m, CU_TENSOR_MAP_DATA_TYPE_BFLOAT16, rank, const_cast<void*>(ptr), dims, strides, box, es, CU_TENSOR_MAP_INTERLEAVE_NONE,
      swizzle ? CU_TENSOR_MAP_SWIZZLE_128B : CU_TENSOR_MAP_SWIZZLE_NONE, swizzle ? CU_TENSOR_MAP_L2_PROMOTION_L2_128B : CU_TENSOR_MAP_L2_PROMOTION_NONE, CU_TENSOR_MAP_FLOAT_OOB_FILL_NONE);
}
void make_2d(EncodeFn enc, CUtensorMap* m, const void* ptr, int rows, int cols, int box_rows) {
  const cuuint64_t dims[2] = {(cuuint64_t)cols, (cuuint64_t)rows}, strides[1] = {(cuuint64_t)cols * 2};
  const cuuint32_t box[2] = {64, (cuuint32_t)box_rows};
  make_map(enc, m, ptr, 2, dims, strides, box);
}
void make_3d(EncodeFn enc, CUtensorMap* m, const void* ptr, int rows, int chunks, size_t row_stride, size_t chunk_stride) {
  const cuuint64_t dims[3] = {64, (cuuint64_t)rows, (cuuint64_t)chunks}, strides[2] = {row_stride, chunk_stride};
  const cuuint32_t box[3] = {64, 64, 2};
  make_map(enc, m, ptr, 3, dims, strides, box);
}

void make_ffn(EncodeFn enc, CUtensorMap* m, const void* ptr) {
  const cuuint64_t dims[2] = {(cuuint64_t)FF, (cuuint64_t)DM}, strides[1] = {(cuuint64_t)FF * 2};
  const cuuint32_t box[2] = {16, 256};
  make_map(enc, m, ptr, 2, dims, strides, box, false);
}

#define SR 0x213312
#define SEED 12345
#define LU_MARGIN 0
#define SPARE_N 3
void build_sched(Sched& s) {
  memset(&s, 0, sizeof(s));
  const int NP = NCTA / 2, korder[4] = {(KORDER >> 12) & 3, (KORDER >> 8) & 3, (KORDER >> 4) & 3, KORDER & 3};
  const int sround[4][2][3] = {{}, {{1}, {2}}, {{1, 2}, {1, 2}}, {{(SR >> 20) & 3, (SR >> 16) & 3, (SR >> 12) & 3}, {(SR >> 8) & 3, (SR >> 4) & 3, SR & 3}}};
  int jv[4][NP], used[4][8] = {};
  for (int r = 0; r < 4; r++) for (int p = 0; p < NP; p++) jv[r][p] = (r & 2) ? 7 - ((p + 4 * (r & 1)) & 7) : (p + 4 * (r & 1)) & 7;
  for (int q = 0; q < 2; q++) {
    s.pair[NP + q].nitems = SPARE_N;
    for (int i = 0; i < SPARE_N; i++) {
      const int r = sround[SPARE_N][q][i];
      s.pair[NP + q].item[i] = (uint8_t)((r * 8 + used[r][6]++) * 8 + 6);
      for (int p = 0; p < NP; p++) if (jv[r][p] == 6) { jv[r][p] = -2; break; }
    }
  }
  auto cost = [&](int p) {
    int u = 8 - ((p >> 4) < SPARE_N ? 21 : 22), z = 0, none = 0;
    for (int r = 0; r < 4; r++) { u += jv[r][p]; z += jv[r][p] == 0; none += jv[r][p] < 0; }
    return 4 * u * u + (z > 1) + 4 * (none > 1);
  };
  uint32_t rng = SEED;
  for (int it = 0; it < 2000000; it++) {
    if ((it & 255) == 0) { int t = 0; for (int p = 0; p < NP; p++) t += cost(p); if (t == 0) break; }
    rng = rng * 1664525u + 1013904223u;
    const int r = (rng >> 8) & 3, a = (rng >> 12) & 63, b = (rng >> 20) & 63, before = cost(a) + cost(b);
    int t = jv[r][a]; jv[r][a] = jv[r][b]; jv[r][b] = t;
    if (cost(a) + cost(b) > before) { jv[r][b] = jv[r][a]; jv[r][a] = t; }
  }
  int fin[256], done[256];
  for (int p = 0; p < NP + 2; p++) {
    Sched::Pair& q = s.pair[p];
    if (p < NP) {
      for (int k = 0; k < 4; k++) q.khead[k] = (uint8_t)(korder[k] * 8 + (p >> 3));
      for (int r = 0; r < 4; r++) {
        if (jv[r][p] < 0) continue;
        q.item[q.nitems++] = (uint8_t)((r * 8 + used[r][jv[r][p]]++) * 8 + jv[r][p]);
      }
    }
    int t = p < NP ? 0 : -3, e = 1;
    for (int i = 0; i < q.nitems; i++) { t += (q.item[i] & 7) + 2; fin[q.item[i]] = t; done[q.item[i]] = t + (i + 1 < q.nitems ? 2 : 0); e += 8 + 4 * ((q.item[i] & 7) + 1); }
    for (int k = 0; k < 3 * MAX_STEPS + 6; k++) {
      const int n = k > 0 ? k - (SPARE_N & 1) : 0, r = n % 7, f = (e + (r < 4 ? r : r - 1)) % 12;
      q.oent[k] = (uint8_t)((r == 4 ? 6 : f >= 6 ? f + 2 : f) ^ (((n / 7) & 1) << 3));
    }
  }
  for (int p = 0; p < NP + 2; p++)
    for (int i = 0; i < s.pair[p].nitems; i++) {
      const int it = s.pair[p].item[i];
      for (int n = 0; n < 2 * (it & 7) + 2; n++) {
        bool last = true;
        for (int j = n >> 1; j < 8; j++) { const int o = (it & ~7) + j; if (o != it && fin[o] + LU_MARGIN > fin[it]) last = false; }
        if (last) s.pair[p].lastuse[i] |= (uint16_t)(1 << n);
      }
    }
  for (int j = 0; j < 8; j++) {
    int order[NH], left[4];
    for (int h = 0; h < NH; h++) { int k = h; for (; k > 0 && done[order[k - 1] * 8 + j] < done[h * 8 + j]; k--) order[k] = order[k - 1]; order[k] = h; }
    for (int kq = 0; kq < 4; kq++) {
      left[kq] = SPARE_N == 0 ? 16 : kq < SPARE_N ? 20 - SPARE_N : 16 - SPARE_N;
      for (int nh = 0; nh < 2; nh++) { Sched::Pair& q = s.pair[kq * 16 + nh * 8 + j]; q.otask = (uint8_t)(kq * 16 + nh * 8 + j); q.nsteps = (uint8_t)((left[kq] + 1) / 2); q.ochunk[0][0] = 255; }
    }
    for (int n = 0, kq = 0, run = 0; n < 64; ) {
      if (left[kq] > 0 && run < 2) {
        const int pos = --left[kq] + (SPARE_N & 1);
        for (int nh = 0; nh < 2; nh++) s.pair[kq * 16 + nh * 8 + j].ochunk[pos >> 1][pos & 1] = (uint8_t)(order[n >> 1] * 2 + 1 - (n & 1));
        n++; run++;
      } else { kq = (kq + 1) & 3; run = 0; }
    }
  }
}

}

extern "C" void kernel_launch(void* const* d_in, const int* in_sizes, int n_in, void* d_out, int out_size) {
  (void)in_sizes; (void)n_in; (void)out_size;
  const __nv_bfloat16* x     = (const __nv_bfloat16*)d_in[0];
  const __nv_bfloat16* ckv   = (const __nv_bfloat16*)d_in[1];
  const __nv_bfloat16* w_q   = (const __nv_bfloat16*)d_in[2];
  const __nv_bfloat16* w_uk  = (const __nv_bfloat16*)d_in[3];
  const __nv_bfloat16* w_uv  = (const __nv_bfloat16*)d_in[4];
  const __nv_bfloat16* w_o   = (const __nv_bfloat16*)d_in[5];
  const __nv_bfloat16* w_r   = (const __nv_bfloat16*)d_in[7];
  const __nv_bfloat16* w_g   = (const __nv_bfloat16*)d_in[8];
  const __nv_bfloat16* w_u   = (const __nv_bfloat16*)d_in[9];
  const __nv_bfloat16* w_d   = (const __nv_bfloat16*)d_in[10];
  const __nv_bfloat16* cvec  = (const __nv_bfloat16*)d_in[11];
  const __nv_bfloat16* w_mod = (const __nv_bfloat16*)d_in[12];
  __nv_bfloat16* out = (__nv_bfloat16*)d_out;

  static HostState st;
  if (!st.ready) {
    void* fn = nullptr; cudaDriverEntryPointQueryResult qr;
    cudaGetDriverEntryPoint("cuTensorMapEncodeTiled", &fn, cudaEnableDefault, &qr);
    st.encode = (EncodeFn)fn;
    cudaFuncSetAttribute(k_fused, cudaFuncAttributeMaxDynamicSharedMemorySize, SMEM);
    build_sched(st.sched);
    void *p_kvc, *p_h1, *p_part;
    cudaGetSymbolAddress(&p_kvc, g_kvc); cudaGetSymbolAddress(&p_h1, g_h1); cudaGetSymbolAddress(&p_part, g_part);
    st.sched.kvc = (__nv_bfloat16*)p_kvc; st.sched.h1 = (__nv_bfloat16*)p_h1; st.sched.part = (__nv_bfloat16*)p_part;
    st.ready = true;
  }
  make_2d(st.encode, &st.tmC, ckv, SEQ, DM, 128);
  make_2d(st.encode, &st.tmWq, w_q, DM, NH * DH, 64);
  make_2d(st.encode, &st.tmWk, w_uk, DM, NH * DH, 64);
  make_2d(st.encode, &st.tmWv, w_uv, DM, NH * DH, 64);
  make_3d(st.encode, &st.tmWo, w_o, NH * DH, DM / 64, (size_t)DM * 2, 128);
  make_3d(st.encode, &st.tmWm, w_mod, DM, 6 * DM / 64, (size_t)6 * DM * 2, 128);
  make_ffn(st.encode, &st.tmWg, w_g);
  make_ffn(st.encode, &st.tmWu, w_u);

  k_fused<<<NGRID, 384, SMEM, cudaStreamPerThread>>>(st.tmC, st.tmWq, st.tmWk, st.tmWv, st.tmWo, st.tmWg, st.tmWu, st.tmWm, st.sched,
                                                     x, cvec, w_o, w_r, w_g, w_u, w_d, out);
}
```

```cpp
#include <cuda_runtime.h>
#include <cuda_bf16.h>
#include <cuda.h>
#include <stdint.h>
#include <string.h>
#include <math.h>

namespace {

constexpr int SEQ = 2048, DM = 512, NH = 32, DH = 128, FF = 1792;
constexpr int NCTA = 128, NGRID = 132;

__device__ __align__(128) __nv_bfloat16 g_kvc[192 * SEQ * 64];
__device__ __align__(128) __nv_bfloat16 g_h1[SEQ * DM];
__device__ __align__(128) __nv_bfloat16 g_part[128 * 8 * 4096];
__device__ __align__(16) __nv_bfloat16 g_mod[6 * DM];
constexpr int C_MOD = 0, C_MOD2 = 16, C_H1 = 32, C_KV = 64, C_CTX = 128, C_PART = 384, C_END = C_PART + 32 * 32;
__device__ __align__(128) unsigned int g_cnt[C_END];
__device__ unsigned int g_epoch;
__device__ __align__(128) uint2 g_keys[128][4];
__device__ __align__(16) uint2 g_row[128][2][DM / 2];
__device__ __align__(16) uint2 g_yll[FF / 16][DM];

#define DBG(i)
#define DBGP(i)

__device__ __forceinline__ uint32_t smem_u32(const void* p) { return (uint32_t)__cvta_generic_to_shared(p); }
__device__ __forceinline__ int wg_tid() { int t; asm volatile("mov.u32 %0, %%tid.x;" : "=r"(t)); return t & 127; }
__device__ __forceinline__ uint32_t clk32() { uint32_t c; asm volatile("mov.u32 %0, %%clock;" : "=r"(c)); return c; }
__device__ __forceinline__ void mbar_arrive(uint32_t bar) { asm volatile("mbarrier.arrive.shared::cta.b64 _, [%0];" :: "r"(bar) : "memory"); }
__device__ __forceinline__ uint32_t mapa(uint32_t addr, uint32_t cta) { uint32_t r; asm("mapa.shared::cluster.u32 %0, %1, %2;" : "=r"(r) : "r"(addr), "r"(cta)); return r; }
__device__ __forceinline__ void mbar_arrive_remote_if(uint32_t cluster_addr, bool pred) {
  asm volatile("{\n.reg .pred p;\nsetp.ne.u32 p, %1, 0;\n@p mbarrier.arrive.shared::cluster.b64 _, [%0];\n}" :: "r"(cluster_addr), "r"((uint32_t)pred) : "memory");
}
__device__ __forceinline__ bool mbar_try(uint32_t bar, uint32_t parity) {
  uint32_t done;
  asm volatile("{\n.reg .pred p;\nmbarrier.try_wait.parity.shared::cta.b64 p, [%1], %2;\nselp.u32 %0, 1, 0, p;\n}" : "=r"(done) : "r"(bar), "r"(parity) : "memory");
  return done;
}
__device__ __forceinline__ bool mbar_test2(uint32_t bar, uint32_t parity) {
  uint32_t done;
  asm volatile("{\n.reg .pred p, q;\nmbarrier.test_wait.parity.shared::cta.b64 p, [%1], %2;\nmbarrier.test_wait.parity.shared::cta.b64 q, [%1 + 8], %2;\n"
               "and.pred p, p, q;\nselp.u32 %0, 1, 0, p;\n}" : "=r"(done) : "r"(bar), "r"(parity) : "memory");
  return done;
}
#define WAIT_LIM (1 << 14)
__device__ __forceinline__ void mbar_wait(uint32_t bar, uint32_t parity) {
  #pragma unroll 1
  for (int n = 0; n < WAIT_LIM; n++) { if (mbar_try(bar, parity)) break; }
}
__device__ __forceinline__ unsigned int ld_acquire(const unsigned int* p) {
  unsigned int v; asm volatile("ld.acquire.gpu.global.u32 %0, [%1];" : "=r"(v) : "l"(p) : "memory"); return v;
}
__device__ __forceinline__ unsigned int ld_relaxed(const unsigned int* p) {
  unsigned int v; asm volatile("ld.relaxed.gpu.global.u32 %0, [%1];" : "=r"(v) : "l"(p) : "memory"); return v;
}
__device__ __forceinline__ void wait_count_lazy(int idx, unsigned int target) {
  #pragma unroll 1
  for (int n = 0; n < WAIT_LIM; n++) { if (__all_sync(0xffffffff, (int)(ld_relaxed(&g_cnt[idx]) - target) >= 0)) break; __nanosleep(100); }
  ld_acquire(&g_cnt[idx]);
}
__device__ __forceinline__ uint4 ld_tagged2(const void* p) {
  uint4 v;
  asm volatile("{\n.reg .b64 a, b;\nld.relaxed.gpu.global.v2.u64 {a, b}, [%4];\nmov.b64 {%0, %1}, a;\nmov.b64 {%2, %3}, b;\n}"
    : "=r"(v.x), "=r"(v.y), "=r"(v.z), "=r"(v.w) : "l"(p) : "memory");
  return v;
}
__device__ __forceinline__ uint2 ld_tagged(const void* p) {
  uint2 v; asm volatile("{\n.reg .b64 a;\nld.relaxed.gpu.global.u64 a, [%2];\nmov.b64 {%0, %1}, a;\n}" : "=r"(v.x), "=r"(v.y) : "l"(p) : "memory"); return v;
}
__device__ __forceinline__ void st_tagged2(void* p, uint32_t a, uint32_t b, uint32_t tag) {
  asm volatile("{\n.reg .b64 a, b;\nmov.b64 a, {%1, %3};\nmov.b64 b, {%2, %3};\nst.relaxed.gpu.global.v2.u64 [%0], {a, b};\n}" :: "l"(p), "r"(a), "r"(b), "r"(tag) : "memory");
}
__device__ __forceinline__ void st_tagged(void* p, uint32_t a, uint32_t tag) {
  asm volatile("{\n.reg .b64 a;\nmov.b64 a, {%1, %2};\nst.relaxed.gpu.global.u64 [%0], a;\n}" :: "l"(p), "r"(a), "r"(tag) : "memory");
}
__device__ __forceinline__ void stg_v4(void* p, uint32_t a, uint32_t b, uint32_t c, uint32_t d) {
  asm volatile("st.global.v4.u32 [%0], {%1, %2, %3, %4};" :: "l"(p), "r"(a), "r"(b), "r"(c), "r"(d) : "memory");
}
__device__ __forceinline__ uint4 lds_v4(uint32_t addr) {
  uint4 v; asm volatile("ld.shared.v4.u32 {%0, %1, %2, %3}, [%4];" : "=r"(v.x), "=r"(v.y), "=r"(v.z), "=r"(v.w) : "r"(addr) : "memory"); return v;
}
__device__ __forceinline__ uint32_t lds_u32(uint32_t addr) { uint32_t v; asm volatile("ld.shared.u32 %0, [%1];" : "=r"(v) : "r"(addr) : "memory"); return v; }
__device__ __forceinline__ void sts_v4(uint32_t addr, uint32_t a, uint32_t b, uint32_t c, uint32_t d) {
  asm volatile("st.shared.v4.u32 [%0], {%1, %2, %3, %4};" :: "r"(addr), "r"(a), "r"(b), "r"(c), "r"(d) : "memory");
}
#define ELECT "{\n.reg .pred p;\nelect.sync _|p, 0xffffffff;\n@p "
__device__ __forceinline__ void w_mbar_init(uint32_t bar, uint32_t cnt) { asm volatile(ELECT "mbarrier.init.shared::cta.b64 [%0], %1;\n}" :: "r"(bar), "r"(cnt) : "memory"); }
__device__ __forceinline__ void w_expect_tx(uint32_t bar, uint32_t bytes) { asm volatile(ELECT "mbarrier.arrive.expect_tx.shared::cta.b64 _, [%0], %1;\n}" :: "r"(bar), "r"(bytes) : "memory"); }
__device__ __forceinline__ void w_arrive(uint32_t bar) { asm volatile(ELECT "mbarrier.arrive.shared::cta.b64 _, [%0];\n}" :: "r"(bar) : "memory"); }
__device__ __forceinline__ void tma_load_2d(uint32_t dst, const CUtensorMap* tm, uint32_t bar, int c0, int c1) {
  asm volatile(ELECT "cp.async.bulk.tensor.2d.shared::cluster.global.mbarrier::complete_tx::bytes [%0], [%1, {%3, %4}], [%2];\n}"
    :: "r"(dst), "l"(tm), "r"(bar), "r"(c0), "r"(c1) : "memory");
}
__device__ __forceinline__ void tma_load_2d_mc(uint32_t dst, const CUtensorMap* tm, uint32_t bar, int c0, int c1) {
  asm volatile(ELECT "cp.async.bulk.tensor.2d.shared::cluster.global.mbarrier::complete_tx::bytes.multicast::cluster [%0], [%1, {%3, %4}], [%2], %5;\n}"
    :: "r"(dst), "l"(tm), "r"(bar), "r"(c0), "r"(c1), "h"((uint16_t)3) : "memory");
}
__device__ __forceinline__ void tma_load_3d(uint32_t dst, const CUtensorMap* tm, uint32_t bar, int c0, int c1, int c2) {
  asm volatile(ELECT "cp.async.bulk.tensor.3d.shared::cluster.global.mbarrier::complete_tx::bytes [%0], [%1, {%3, %4, %5}], [%2];\n}"
    :: "r"(dst), "l"(tm), "r"(bar), "r"(c0), "r"(c1), "r"(c2) : "memory");
}
__device__ __forceinline__ void tma_load_3d_mc(uint32_t dst, const CUtensorMap* tm, uint32_t bar, int c0, int c1, int c2) {
  asm volatile(ELECT "cp.async.bulk.tensor.3d.shared::cluster.global.mbarrier::complete_tx::bytes.multicast::cluster [%0], [%1, {%3, %4, %5}], [%2], %6;\n}"
    :: "r"(dst), "l"(tm), "r"(bar), "r"(c0), "r"(c1), "r"(c2), "h"((uint16_t)3) : "memory");
}
__device__ __forceinline__ void bulk_load_mc(uint32_t dst, const void* src, uint32_t bar, bool ef) {
  if (ef) {
    uint64_t pol; asm("createpolicy.fractional.L2::evict_first.b64 %0, 1.0;" : "=l"(pol));
    asm volatile(ELECT "cp.async.bulk.shared::cluster.global.mbarrier::complete_tx::bytes.multicast::cluster.L2::cache_hint [%0], [%1], 16384, [%2], %3, %4;\n}"
      :: "r"(dst), "l"(src), "r"(bar), "h"((uint16_t)3), "l"(pol) : "memory");
  } else
    asm volatile(ELECT "cp.async.bulk.shared::cluster.global.mbarrier::complete_tx::bytes.multicast::cluster [%0], [%1], 16384, [%2], %3;\n}"
      :: "r"(dst), "l"(src), "r"(bar), "h"((uint16_t)3) : "memory");
}
__device__ __forceinline__ void bulk_load(uint32_t dst, const void* src, uint32_t bytes, uint32_t bar) {
  asm volatile(ELECT "cp.async.bulk.shared::cluster.global.mbarrier::complete_tx::bytes [%0], [%1], %2, [%3];\n}" :: "r"(dst), "l"(src), "r"(bytes), "r"(bar) : "memory");
}
__device__ __forceinline__ void tma_prefetch_2d(const CUtensorMap* tm, int c0, int c1) {
  asm volatile(ELECT "cp.async.bulk.prefetch.tensor.2d.L2.global [%0, {%1, %2}];\n}" :: "l"(tm), "r"(c0), "r"(c1) : "memory");
}
__device__ __forceinline__ void bulk_prefetch(const void* p, uint32_t bytes) {
  asm volatile(ELECT "cp.async.bulk.prefetch.L2.global [%0], %1;\n}" :: "l"(p), "r"(bytes) : "memory");
}
__device__ __forceinline__ void red_release(int idx) { asm volatile("red.release.gpu.global.add.u32 [%0], 1;" :: "l"(&g_cnt[idx]) : "memory"); }
__device__ __forceinline__ void prefetch_tmap(const CUtensorMap* tm) { asm volatile("prefetch.tensormap [%0];" :: "l"(tm) : "memory"); }
__device__ __forceinline__ void bar_sync(int id, int n) { asm volatile("bar.sync %0, %1;" :: "r"(id), "r"(n) : "memory"); }
__device__ __forceinline__ void bar_arrive(int id, int n) { asm volatile("bar.arrive %0, %1;" :: "r"(id), "r"(n) : "memory"); }
__device__ __forceinline__ void fence_async_smem() { asm volatile("fence.proxy.async.shared::cta;" ::: "memory"); }
__device__ __forceinline__ void fence_async_global() { asm volatile("fence.proxy.async.global;" ::: "memory"); }
__device__ __forceinline__ void fence_mbar_init() { asm volatile("fence.mbarrier_init.release.cluster;" ::: "memory"); }
__device__ __forceinline__ void cluster_arrive() { asm volatile("barrier.cluster.arrive.relaxed.aligned;" ::: "memory"); }
__device__ __forceinline__ void cluster_wait() { asm volatile("barrier.cluster.wait.aligned;" ::: "memory"); }
__device__ __forceinline__ uint32_t cluster_ctarank() { uint32_t r; asm volatile("mov.u32 %0, %%cluster_ctarank;" : "=r"(r)); return r; }
__device__ __forceinline__ void wgmma_fence() { asm volatile("wgmma.fence.sync.aligned;" ::: "memory"); }
__device__ __forceinline__ void wgmma_commit() { asm volatile("wgmma.commit_group.sync.aligned;" ::: "memory"); }
template<int N> __device__ __forceinline__ void wgmma_wait() { asm volatile("wgmma.wait_group.sync.aligned %0;" :: "n"(N) : "memory"); }
__device__ __forceinline__ float ex2(float x) { float y; asm("ex2.approx.ftz.f32 %0, %1;" : "=f"(y) : "f"(x)); return y; }
__device__ __forceinline__ float rcp_fast(float x) { float y; asm("rcp.approx.ftz.f32 %0, %1;" : "=f"(y) : "f"(x)); return y; }
__device__ __forceinline__ uint32_t pack_bf16(float lo, float hi) { uint32_t r; asm("cvt.rn.bf16x2.f32 %0, %1, %2;" : "=r"(r) : "f"(hi), "f"(lo)); return r; }
__device__ __forceinline__ float rbf(float x) { return __uint_as_float(pack_bf16(0.f, x)); }
__device__ __forceinline__ float bf_lo(uint32_t v) { return __uint_as_float(v << 16); }
__device__ __forceinline__ float bf_hi(uint32_t v) { return __uint_as_float(v & 0xffff0000u); }
__device__ __forceinline__ uint32_t add2(uint32_t a, uint32_t b) { uint32_t r; asm("add.rn.bf16x2 %0, %1, %2;" : "=r"(r) : "r"(a), "r"(b)); return r; }
__device__ __forceinline__ uint32_t fma2(uint32_t a, uint32_t b, uint32_t c) { uint32_t r; asm("fma.rn.bf16x2 %0, %1, %2, %3;" : "=r"(r) : "r"(a), "r"(b), "r"(c)); return r; }
__device__ __forceinline__ uint4 ldsm_x4_t(uint32_t addr) {
  uint4 v; asm volatile("ldmatrix.sync.aligned.m8n8.x4.trans.shared.b16 {%0, %1, %2, %3}, [%4];" : "=r"(v.x), "=r"(v.y), "=r"(v.z), "=r"(v.w) : "r"(addr) : "memory"); return v;
}
__device__ __forceinline__ uint4 ldsm_x4(uint32_t addr) {
  uint4 v; asm volatile("ldmatrix.sync.aligned.m8n8.x4.shared.b16 {%0, %1, %2, %3}, [%4];" : "=r"(v.x), "=r"(v.y), "=r"(v.z), "=r"(v.w) : "r"(addr) : "memory"); return v;
}
__device__ __forceinline__ void mma16816(float (&c)[4], const uint4& a, uint32_t b0, uint32_t b1) {
  asm("mma.sync.aligned.m16n8k16.row.col.f32.bf16.bf16.f32 {%0, %1, %2, %3}, {%4, %5, %6, %7}, {%8, %9}, {%0, %1, %2, %3};"
    : "+f"(c[0]), "+f"(c[1]), "+f"(c[2]), "+f"(c[3]) : "r"(a.x), "r"(a.y), "r"(a.z), "r"(a.w), "r"(b0), "r"(b1));
}
template<int N> __device__ __forceinline__ void fence_regs(float (&a)[N]) {
  #pragma unroll
  for (int i = 0; i < N; i++) asm volatile("" : "+f"(a[i]) :: "memory");
}
template<int N> __device__ __forceinline__ void fence_regs_u(uint32_t (&a)[N]) {
  #pragma unroll
  for (int i = 0; i < N; i++) asm volatile("" : "+r"(a[i]) :: "memory");
}
constexpr uint32_t SW128 = 0x40000040u, SW64 = 0x80000020u;
__device__ __forceinline__ uint32_t desc_lo(uint32_t addr, uint32_t lbo) { return ((addr & 0x3FFFF) >> 4) | ((lbo >> 4) << 16); }

template<int TB, int OA, int OB, uint32_t HA, uint32_t HB> __device__ __forceinline__ void wgmma_ss_n128(float (&d)[64], uint32_t da, uint32_t db, int sd) {
  asm volatile("{\n.reg .pred p;\n.reg .b32 ta, tb;\n.reg .b64 da, db;\nsetp.ne.b32 p, %66, 0;\nadd.u32 ta, %64, %68;\nadd.u32 tb, %65, %69;\nmov.b64 da, {ta, %70};\nmov.b64 db, {tb, %71};\n"
    "wgmma.mma_async.sync.aligned.m64n128k16.f32.bf16.bf16 "
    "{%0, %1, %2, %3, %4, %5, %6, %7, %8, %9, %10, %11, %12, %13, %14, %15, %16, %17, %18, %19, %20, %21, %22, %23, %24, %25, %26, %27, %28, %29, %30, %31, %32, %33, %34, %35, %36, %37, %38, %39, %40, %41, %42, %43, %44, %45, %46, %47, %48, %49, %50, %51, %52, %53, %54, %55, %56, %57, %58, %59, %60, %61, %62, %63}, da, db, p, 1, 1, 0, %67;\n}\n"
    : "+f"(d[0]), "+f"(d[1]), "+f"(d[2]), "+f"(d[3]), "+f"(d[4]), "+f"(d[5]), "+f"(d[6]), "+f"(d[7]), "+f"(d[8]), "+f"(d[9]), "+f"(d[10]), "+f"(d[11]), "+f"(d[12]), "+f"(d[13]), "+f"(d[14]), "+f"(d[15]), "+f"(d[16]), "+f"(d[17]), "+f"(d[18]), "+f"(d[19]), "+f"(d[20]), "+f"(d[21]), "+f"(d[22]), "+f"(d[23]), "+f"(d[24]), "+f"(d[25]), "+f"(d[26]), "+f"(d[27]), "+f"(d[28]), "+f"(d[29]), "+f"(d[30]), "+f"(d[31]), "+f"(d[32]), "+f"(d[33]), "+f"(d[34]), "+f"(d[35]), "+f"(d[36]), "+f"(d[37]), "+f"(d[38]), "+f"(d[39]), "+f"(d[40]), "+f"(d[41]), "+f"(d[42]), "+f"(d[43]), "+f"(d[44]), "+f"(d[45]), "+f"(d[46]), "+f"(d[47]), "+f"(d[48]), "+f"(d[49]), "+f"(d[50]), "+f"(d[51]), "+f"(d[52]), "+f"(d[53]), "+f"(d[54]), "+f"(d[55]), "+f"(d[56]), "+f"(d[57]), "+f"(d[58]), "+f"(d[59]), "+f"(d[60]), "+f"(d[61]), "+f"(d[62]), "+f"(d[63])
    : "r"(da), "r"(db), "r"(sd), "n"(TB), "n"(OA), "n"(OB), "n"(HA), "n"(HB));
}
template<int TB, int OB, uint32_t HB> __device__ __forceinline__ void wgmma_rs_n128(float (&d)[64], uint32_t a0, uint32_t a1, uint32_t a2, uint32_t a3, uint32_t db, int sd) {
  asm volatile("{\n.reg .pred p;\n.reg .b32 tb;\n.reg .b64 db;\nsetp.ne.b32 p, %69, 0;\nadd.u32 tb, %68, %71;\nmov.b64 db, {tb, %72};\n"
    "wgmma.mma_async.sync.aligned.m64n128k16.f32.bf16.bf16 "
    "{%0, %1, %2, %3, %4, %5, %6, %7, %8, %9, %10, %11, %12, %13, %14, %15, %16, %17, %18, %19, %20, %21, %22, %23, %24, %25, %26, %27, %28, %29, %30, %31, %32, %33, %34, %35, %36, %37, %38, %39, %40, %41, %42, %43, %44, %45, %46, %47, %48, %49, %50, %51, %52, %53, %54, %55, %56, %57, %58, %59, %60, %61, %62, %63}, {%64,%65,%66,%67}, db, p, 1, 1, %70;\n}\n"
    : "+f"(d[0]), "+f"(d[1]), "+f"(d[2]), "+f"(d[3]), "+f"(d[4]), "+f"(d[5]), "+f"(d[6]), "+f"(d[7]), "+f"(d[8]), "+f"(d[9]), "+f"(d[10]), "+f"(d[11]), "+f"(d[12]), "+f"(d[13]), "+f"(d[14]), "+f"(d[15]), "+f"(d[16]), "+f"(d[17]), "+f"(d[18]), "+f"(d[19]), "+f"(d[20]), "+f"(d[21]), "+f"(d[22]), "+f"(d[23]), "+f"(d[24]), "+f"(d[25]), "+f"(d[26]), "+f"(d[27]), "+f"(d[28]), "+f"(d[29]), "+f"(d[30]), "+f"(d[31]), "+f"(d[32]), "+f"(d[33]), "+f"(d[34]), "+f"(d[35]), "+f"(d[36]), "+f"(d[37]), "+f"(d[38]), "+f"(d[39]), "+f"(d[40]), "+f"(d[41]), "+f"(d[42]), "+f"(d[43]), "+f"(d[44]), "+f"(d[45]), "+f"(d[46]), "+f"(d[47]), "+f"(d[48]), "+f"(d[49]), "+f"(d[50]), "+f"(d[51]), "+f"(d[52]), "+f"(d[53]), "+f"(d[54]), "+f"(d[55]), "+f"(d[56]), "+f"(d[57]), "+f"(d[58]), "+f"(d[59]), "+f"(d[60]), "+f"(d[61]), "+f"(d[62]), "+f"(d[63])
    : "r"(a0), "r"(a1), "r"(a2), "r"(a3), "r"(db), "r"(sd), "n"(TB), "n"(OB), "n"(HB));
}
template<int TB, int OA, int OB, uint32_t HA, uint32_t HB> __device__ __forceinline__ void wgmma_ss_n64(float (&d)[32], uint32_t da, uint32_t db, int sd) {
  asm volatile("{\n.reg .pred p;\n.reg .b32 ta, tb;\n.reg .b64 da, db;\nsetp.ne.b32 p, %34, 0;\nadd.u32 ta, %32, %36;\nadd.u32 tb, %33, %37;\nmov.b64 da, {ta, %38};\nmov.b64 db, {tb, %39};\n"
    "wgmma.mma_async.sync.aligned.m64n64k16.f32.bf16.bf16 "
    "{%0, %1, %2, %3, %4, %5, %6, %7, %8, %9, %10, %11, %12, %13, %14, %15, %16, %17, %18, %19, %20, %21, %22, %23, %24, %25, %26, %27, %28, %29, %30, %31}, da, db, p, 1, 1, 0, %35;\n}\n"
    : "+f"(d[0]), "+f"(d[1]), "+f"(d[2]), "+f"(d[3]), "+f"(d[4]), "+f"(d[5]), "+f"(d[6]), "+f"(d[7]), "+f"(d[8]), "+f"(d[9]), "+f"(d[10]), "+f"(d[11]), "+f"(d[12]), "+f"(d[13]), "+f"(d[14]), "+f"(d[15]), "+f"(d[16]), "+f"(d[17]), "+f"(d[18]), "+f"(d[19]), "+f"(d[20]), "+f"(d[21]), "+f"(d[22]), "+f"(d[23]), "+f"(d[24]), "+f"(d[25]), "+f"(d[26]), "+f"(d[27]), "+f"(d[28]), "+f"(d[29]), "+f"(d[30]), "+f"(d[31])
    : "r"(da), "r"(db), "r"(sd), "n"(TB), "n"(OA), "n"(OB), "n"(HA), "n"(HB));
}
template<int TB, int OA, int OB, uint32_t HA, uint32_t HB> __device__ __forceinline__ void wgmma_ss_n128_new(float (&d)[64], uint32_t da, uint32_t db) {
  asm volatile("{\n.reg .pred p;\n.reg .b32 ta, tb;\n.reg .b64 da, db;\nsetp.ne.b32 p, %66, 0;\nadd.u32 ta, %64, %68;\nadd.u32 tb, %65, %69;\nmov.b64 da, {ta, %70};\nmov.b64 db, {tb, %71};\n"
    "wgmma.mma_async.sync.aligned.m64n128k16.f32.bf16.bf16 "
    "{%0, %1, %2, %3, %4, %5, %6, %7, %8, %9, %10, %11, %12, %13, %14, %15, %16, %17, %18, %19, %20, %21, %22, %23, %24, %25, %26, %27, %28, %29, %30, %31, %32, %33, %34, %35, %36, %37, %38, %39, %40, %41, %42, %43, %44, %45, %46, %47, %48, %49, %50, %51, %52, %53, %54, %55, %56, %57, %58, %59, %60, %61, %62, %63}, da, db, p, 1, 1, 0, %67;\n}\n"
    : "=f"(d[0]), "=f"(d[1]), "=f"(d[2]), "=f"(d[3]), "=f"(d[4]), "=f"(d[5]), "=f"(d[6]), "=f"(d[7]), "=f"(d[8]), "=f"(d[9]), "=f"(d[10]), "=f"(d[11]), "=f"(d[12]), "=f"(d[13]), "=f"(d[14]), "=f"(d[15]), "=f"(d[16]), "=f"(d[17]), "=f"(d[18]), "=f"(d[19]), "=f"(d[20]), "=f"(d[21]), "=f"(d[22]), "=f"(d[23]), "=f"(d[24]), "=f"(d[25]), "=f"(d[26]), "=f"(d[27]), "=f"(d[28]), "=f"(d[29]), "=f"(d[30]), "=f"(d[31]), "=f"(d[32]), "=f"(d[33]), "=f"(d[34]), "=f"(d[35]), "=f"(d[36]), "=f"(d[37]), "=f"(d[38]), "=f"(d[39]), "=f"(d[40]), "=f"(d[41]), "=f"(d[42]), "=f"(d[43]), "=f"(d[44]), "=f"(d[45]), "=f"(d[46]), "=f"(d[47]), "=f"(d[48]), "=f"(d[49]), "=f"(d[50]), "=f"(d[51]), "=f"(d[52]), "=f"(d[53]), "=f"(d[54]), "=f"(d[55]), "=f"(d[56]), "=f"(d[57]), "=f"(d[58]), "=f"(d[59]), "=f"(d[60]), "=f"(d[61]), "=f"(d[62]), "=f"(d[63])
    : "r"(da), "r"(db), "n"(0), "n"(TB), "n"(OA), "n"(OB), "n"(HA), "n"(HB));
}
template<int TB, int OA, int OB, uint32_t HA, uint32_t HB> __device__ __forceinline__ void wgmma_ss_n64_new(float (&d)[32], uint32_t da, uint32_t db) {
  asm volatile("{\n.reg .pred p;\n.reg .b32 ta, tb;\n.reg .b64 da, db;\nsetp.ne.b32 p, %34, 0;\nadd.u32 ta, %32, %36;\nadd.u32 tb, %33, %37;\nmov.b64 da, {ta, %38};\nmov.b64 db, {tb, %39};\n"
    "wgmma.mma_async.sync.aligned.m64n64k16.f32.bf16.bf16 "
    "{%0, %1, %2, %3, %4, %5, %6, %7, %8, %9, %10, %11, %12, %13, %14, %15, %16, %17, %18, %19, %20, %21, %22, %23, %24, %25, %26, %27, %28, %29, %30, %31}, da, db, p, 1, 1, 0, %35;\n}\n"
    : "=f"(d[0]), "=f"(d[1]), "=f"(d[2]), "=f"(d[3]), "=f"(d[4]), "=f"(d[5]), "=f"(d[6]), "=f"(d[7]), "=f"(d[8]), "=f"(d[9]), "=f"(d[10]), "=f"(d[11]), "=f"(d[12]), "=f"(d[13]), "=f"(d[14]), "=f"(d[15]), "=f"(d[16]), "=f"(d[17]), "=f"(d[18]), "=f"(d[19]), "=f"(d[20]), "=f"(d[21]), "=f"(d[22]), "=f"(d[23]), "=f"(d[24]), "=f"(d[25]), "=f"(d[26]), "=f"(d[27]), "=f"(d[28]), "=f"(d[29]), "=f"(d[30]), "=f"(d[31])
    : "r"(da), "r"(db), "n"(0), "n"(TB), "n"(OA), "n"(OB), "n"(HA), "n"(HB));
}
template<int OA, int OB = 0, uint32_t HA = SW128> __device__ __forceinline__ void kblock_n128(float (&d)[64], uint32_t da, uint32_t db, int sd) {
  constexpr int H = HA == SW128 ? 4 : 512;
  wgmma_ss_n128<1, OA, OB, HA, SW128>(d, da, db, sd); wgmma_ss_n128<1, OA + 2, OB + 128, HA, SW128>(d, da, db, 1);
  wgmma_ss_n128<1, OA + H, OB + 256, HA, SW128>(d, da, db, 1); wgmma_ss_n128<1, OA + H + 2, OB + 384, HA, SW128>(d, da, db, 1);
}

__device__ __forceinline__ float quad_sum(float v) {
  v += __shfl_xor_sync(0xffffffff, v, 1);
  v += __shfl_xor_sync(0xffffffff, v, 2);
  return v;
}
struct Row { uint32_t v[8]; };
template<class F> __device__ __forceinline__ Row load_row(const __nv_bfloat16* p, int lane, F ld) {
  const uint4 a = ld(reinterpret_cast<const uint4*>(p) + lane), b = ld(reinterpret_cast<const uint4*>(p) + 32 + lane);
  return Row{{a.x, a.y, a.z, a.w, b.x, b.y, b.z, b.w}};
}
__device__ __forceinline__ Row ldg_row(const __nv_bfloat16* p, int lane) { return load_row(p, lane, [](const uint4* q) { return __ldg(q); }); }
__device__ __forceinline__ Row ldca_row(const __nv_bfloat16* p, int lane) { return load_row(p, lane, [](const uint4* q) { return __ldca(q); }); }
__device__ __forceinline__ Row lds_row(uint32_t addr, int lane) {
  const uint4 a = lds_v4(addr + lane * 16), b = lds_v4(addr + 512 + lane * 16);
  return Row{{a.x, a.y, a.z, a.w, b.x, b.y, b.z, b.w}};
}
__device__ __forceinline__ void store_row(__nv_bfloat16* p, int lane, const Row& r) {
  stg_v4(p + lane * 8, r.v[0], r.v[1], r.v[2], r.v[3]); stg_v4(p + 256 + lane * 8, r.v[4], r.v[5], r.v[6], r.v[7]);
}
__device__ __forceinline__ Row fma_row(const Row& a, const Row& b, const Row& c) {
  Row r;
  #pragma unroll
  for (int i = 0; i < 8; i++) r.v[i] = fma2(a.v[i], b.v[i], c.v[i]);
  return r;
}
__device__ __forceinline__ Row add_row(const Row& a, const Row& b) {
  Row r;
  #pragma unroll
  for (int i = 0; i < 8; i++) r.v[i] = add2(a.v[i], b.v[i]);
  return r;
}
__device__ __forceinline__ Row one_plus(const Row& a) {
  Row r;
  #pragma unroll
  for (int i = 0; i < 8; i++) r.v[i] = add2(a.v[i], 0x3f803f80u);
  return r;
}
__device__ __forceinline__ float row_at(const Row& x, int i) { return (i & 1) ? bf_hi(x.v[i >> 1]) : bf_lo(x.v[i >> 1]); }
template<int N> __device__ __forceinline__ void warp_sums(float (&s)[N]) {
  #pragma unroll
  for (int o = 16; o > 0; o >>= 1) {
    #pragma unroll
    for (int k = 0; k < N; k++) s[k] += __shfl_xor_sync(0xffffffff, s[k], o);
  }
}
__device__ __forceinline__ void ln_stats(float& s1, float& s2) {
  s1 *= 1.f / DM;
  asm("rsqrt.approx.ftz.f32 %0, %1;" : "=f"(s2) : "f"(fmaxf(fmaf(-s1, s1, s2 * (1.f / DM)), 0.f) + 1e-5f));
}
__device__ __forceinline__ Row ln_apply(const Row& x, float mean, float f) {
  Row n;
  const float o = -mean * f;
  #pragma unroll
  for (int i = 0; i < 8; i++) n.v[i] = pack_bf16(fmaf(bf_lo(x.v[i]), f, o), fmaf(bf_hi(x.v[i]), f, o));
  return n;
}

constexpr int SM_Q = 6 * 32768, SM_BAR = 7 * 32768, SM_MAIL = SM_BAR + 640, SM_RED = SM_MAIL + 128, SM_H2 = SM_RED + 1024, SM_KEY = SM_H2 + 1024, SMEM = SM_KEY + 128;
constexpr int B_AF = 0, B_WF = 64, B_RF = 112, B_WE = 168, B_RE = 216, B_PUB = 272, B_RDY = 496;
constexpr int R_MOD = B_RDY, R_H1 = B_RDY + 8, R_ITEM = B_RDY + 16, R_NEAR = B_RDY + 48, R_CTX = B_RDY + 64;
constexpr int R_KEY = B_AF + 8, R_PART = B_AF + 32;
constexpr int NPUB = 14;
__device__ __forceinline__ uint32_t k_addrA(int kb) { return ((0x6310u >> ((kb >> 1) * 4)) & 15u) * 32768u + (kb & 1) * 16384u; }
__device__ __forceinline__ uint32_t k_addrW(int s) { return ((0x254u >> ((s >> 1) * 4)) & 15u) * 32768u + (s & 1) * 16384u; }

#define KORDER 0x3201
constexpr int KHEAD0 = ((KORDER >> 12) & 3) * 8;
constexpr int MAX_ITEMS = 4;
constexpr int MAX_STEPS = 10;
struct Sched {
  __nv_bfloat16 *kvc, *h1, *part;
  struct Pair {
    uint8_t oent[3 * MAX_STEPS + 6];
    uint16_t lastuse[MAX_ITEMS];
    uint8_t khead[4];
    uint8_t nitems, item[MAX_ITEMS];
    uint8_t otask, nsteps;
    uint8_t ochunk[MAX_STEPS][2];
  } pair[NGRID / 2];
};

__device__ __forceinline__ int ring_add(int e, int n) { e += n; return e >= 12 ? e - 12 : e; }
__device__ __forceinline__ int ring_slot(int e) { return e >= 6 ? e - 6 : e; }
__device__ __forceinline__ void ring_wait_full(uint32_t bars, int e) { mbar_wait(bars + B_RF + 8 * ring_slot(e), e >= 6); }

__device__ __forceinline__ void o_wait_full(uint32_t bars, uint32_t v) { mbar_wait(bars + B_RF + 8 * (v & 7), v >> 3); }

struct Ctx {
  uint32_t base, bars;
  uint32_t rel;
  bool rel1;
  int w, nev;
  const Sched* sched;
  uint32_t tr;
};
#define TR(id)
__device__ __forceinline__ void slot_release(const Ctx& x, int s, bool twice) {
  mbar_arrive_remote_if(x.rel + B_RE + 8 * s, twice ? (wg_tid() & 31) == 0 : x.rel1);
}
__device__ __forceinline__ void ring_release(const Ctx& x, int e, bool twice) { slot_release(x, ring_slot(e), twice); }
__device__ __forceinline__ void publish(Ctx& x, int idx) {
  const uint32_t n = x.w * NPUB + x.nev;
  const int t = wg_tid();
  if (t == 0) asm volatile("st.shared.u32 [%0], %1;" :: "r"(x.base + SM_MAIL + 4 * n), "r"(idx) : "memory");
  __syncwarp();
  if ((t & 31) == 0) mbar_arrive(x.bars + B_PUB + 8 * n);
  x.nev++;
}

template<int KK = 0> __device__ __forceinline__ void issue_qk(float (&S)[64], uint32_t dq, uint32_t dk) {
  constexpr int off = (KK >> 1) * 512 + (KK & 1) * 2;
  if constexpr (KK == 0) wgmma_ss_n128_new<0, 0, 0, SW64, SW64>(S, dq, dk); else wgmma_ss_n128<0, off, off, SW64, SW64>(S, dq, dk, 1);
  if constexpr (KK < 7) issue_qk<KK + 1>(S, dq, dk);
}
template<int KK = 0> __device__ __forceinline__ void issue_qk_half(float (&S)[32], uint32_t dq, uint32_t dk) {
  constexpr int off = (KK >> 1) * 512 + (KK & 1) * 2;
  if constexpr (KK == 0) wgmma_ss_n64_new<0, 0, 256, SW64, SW64>(S, dq, dk); else wgmma_ss_n64<0, off, off + 256, SW64, SW64>(S, dq, dk, 1);
  if constexpr (KK < 7) issue_qk_half<KK + 1>(S, dq, dk);
}
template<int NK, int KK = 0>
__device__ __forceinline__ void issue_pv(float (&O)[64], uint32_t (&P)[32], uint32_t dv, int accumulate) {
  wgmma_rs_n128<1, (KK + 8 - NK) * 64, SW64>(O, P[4*KK], P[4*KK+1], P[4*KK+2], P[4*KK+3], dv, accumulate);
  if constexpr (KK + 1 < NK) issue_pv<NK, KK + 1>(O, P, dv, 1);
}
template<int K0, int K1>
__device__ __forceinline__ void exp_pack(const float (&S)[64], uint32_t (&D)[32], float& s0, float& s1) {
  #pragma unroll
  for (int k = K0; k < K1; k++) {
    const float e0 = ex2(S[2*k]), e1 = ex2(S[2*k+1]);
    D[k] = pack_bf16(e0, e1);
    if (k & 1) s1 += e0 + e1; else s0 += e0 + e1;
  }
}
__device__ __forceinline__ int diag_limit() { const int t = wg_tid(); return 16 * (t >> 5) + ((t & 31) >> 2) - 2 * (t & 3); }
__device__ __forceinline__ void exp_pack_diag(const float (&S)[64], uint32_t (&D)[32], int t, float& s0, float& s1) {
  #pragma unroll
  for (int k = 0; k < 16; k++) {
    const int c = 8 * (k >> 1) - 8 * (k & 1);
    const float e0 = ex2((c <= t) ? S[2*k] : -INFINITY), e1 = ex2((c + 1 <= t) ? S[2*k+1] : -INFINITY);
    D[k] = pack_bf16(e0, e1);
    if (k & 1) s1 += e0 + e1; else s0 += e0 + e1;
  }
}
constexpr float SUM_HI = 1.8446744073709552e19f;
constexpr float SUM_LO = 5.421010862427522e-20f;

__device__ __forceinline__ void classic_tile(const float (&S)[64], uint32_t (&P)[32], bool fresh, bool half, bool was_classic, volatile float* mc,
                                             float& l0, float& l1, float& s0, float& s1, float& sc0, float& sc1) {
  const int tmask = diag_limit();
  float4 t[16];
  #pragma unroll
  for (int j = 0; j < 16; j++) t[j] = make_float4(S[4*j], S[4*j+1], S[4*j+2], S[4*j+3]);
  float mx0 = -INFINITY, mx1 = -INFINITY;
  #pragma unroll 1
  for (int j = 0; j < 16; j++) {
    float4 v = t[j];
    const int lim = !fresh ? 1000 : j < 8 ? tmask - 8 * j : half ? -1000 : 1000;
    v.x = 0 <= lim ? v.x : -INFINITY; v.y = 1 <= lim ? v.y : -INFINITY; v.z = -8 <= lim ? v.z : -INFINITY; v.w = -7 <= lim ? v.w : -INFINITY;
    t[j] = v;
    mx0 = fmaxf(mx0, fmaxf(v.x, v.y)); mx1 = fmaxf(mx1, fmaxf(v.z, v.w));
  }
  mx0 = fmaxf(mx0, __shfl_xor_sync(0xffffffff, mx0, 1));
  mx1 = fmaxf(mx1, __shfl_xor_sync(0xffffffff, mx1, 1));
  mx0 = fmaxf(mx0, __shfl_xor_sync(0xffffffff, mx0, 2));
  mx1 = fmaxf(mx1, __shfl_xor_sync(0xffffffff, mx1, 2));
  const float mc0 = was_classic ? mc[0] : 0.f, mc1 = was_classic ? mc[1] : 0.f;
  const float n0 = fresh ? -mx0 : fminf(mc0, -mx0), n1 = fresh ? -mx1 : fminf(mc1, -mx1);
  sc0 = ex2(n0 - mc0); sc1 = ex2(n1 - mc1);
  mc[0] = n0; mc[1] = n1;
  s0 = 0.f; s1 = 0.f;
  #pragma unroll 1
  for (int j = 0; j < 16; j++) {
    const float4 v = t[j];
    const float e0 = ex2(v.x + n0), e1 = ex2(v.y + n0), e2 = ex2(v.z + n1), e3 = ex2(v.w + n1);
    s0 += e0 + e1; s1 += e2 + e3;
    reinterpret_cast<uint2*>(t)[j] = make_uint2(pack_bf16(e0, e1), pack_bf16(e2, e3));
  }
  #pragma unroll
  for (int j = 0; j < 8; j++) { P[4*j] = __float_as_uint(t[j].x); P[4*j+1] = __float_as_uint(t[j].y); P[4*j+2] = __float_as_uint(t[j].z); P[4*j+3] = __float_as_uint(t[j].w); }
  if (!fresh) { l0 *= sc0; l1 *= sc1; }
}
__device__ __forceinline__ void pack_tile(const float (&A)[64], uint32_t (&D)[32], float f0, float f1) {
  #pragma unroll
  for (int j = 0; j < 16; j++) {
    D[8 * (j >> 2) + (j & 3)] = pack_bf16(A[4*j] * f0, A[4*j+1] * f0);
    D[8 * (j >> 2) + 4 + (j & 3)] = pack_bf16(A[4*j+2] * f1, A[4*j+3] * f1);
  }
}
__device__ __forceinline__ int piece0(int t) { return ((t >> 5) * 16 + ((t & 31) >> 2)) * 32 + (((t ^ (t >> 3)) & 3) << 3); }
__device__ __forceinline__ void store_tile(__nv_bfloat16* p, const uint32_t (&D)[32]) {
  #pragma unroll
  for (int i = 0; i < 8; i++) stg_v4(p + (i >> 2) * (SEQ * 64) + ((i >> 1) & 1) * 4096 + (i & 1) * 256, D[4*i], D[4*i+1], D[4*i+2], D[4*i+3]);
}

enum : int { PV_ACC = 0, PV_ZERO = 1, PV_HALF = 2, PV_NONE = 3 };
struct Att {
  float l0, l1, i0, i1;
  bool classic;
  volatile float* mc;
};
__device__ __forceinline__ void store_ctx(Ctx& x, int code, const uint32_t (&D)[32]) {
  store_tile(x.sched->kvc + ((size_t)(128 + (code >> 5) * 2) * SEQ + ((code >> 1) & 15) * 128) * 64 + (code & 1) * 2048 + piece0(wg_tid()), D);
  publish(x, C_CTX + (code >> 2));
}
__device__ __forceinline__ __nv_bfloat16* kv_tile(const Ctx& x, int code) {
  return x.sched->kvc + ((size_t)(x.w * 64 + (code >> 4) * 2) * SEQ + (code & 15) * 128) * 64 + piece0(wg_tid());
}
#define V_AT 3
#define V_AT2 7
#define MERGE1 1
#define NO_CLASSIC 0
__device__ __forceinline__ void q_proj(Ctx& x, int& e, bool isY, const uint32_t (&PA)[32], const uint32_t (&PB)[32], int vtile, bool first, bool dbg = false) {
  float S[64];
  if (isY) bar_sync(1 + x.w, 256);
  if (dbg) DBG(80);
  TR(1);
  #pragma unroll 1
  for (int kb = 0; kb < 8; kb++) {
    if (kb > 0 || first) ring_wait_full(x.bars, e);
    if (dbg) DBG(81 + kb);
    TR(2);
    const uint32_t da = desc_lo(x.base + x.w * 8192, 16) + ring_slot(e) * 2048, dw = desc_lo(x.base + 16384, 8192) + ring_slot(e) * 2048;
    wgmma_fence();
    kblock_n128<0>(S, da, dw, kb != 0);
    wgmma_commit();
    if (kb == 7 && !isY) bar_arrive(1 + (x.w ^ 1), 256);
    if (kb > 0) { wgmma_wait<1>(); ring_release(x, ring_add(e, 11), false); }
    if (kb == V_AT && vtile >= 0) store_tile(kv_tile(x, vtile) + 2048, PA);
    if (kb == V_AT2 && vtile >= 0) { store_tile(kv_tile(x, vtile), PB); publish(x, C_KV + (vtile >> 4)); }
    e = ring_add(e, 1);
  }
  wgmma_wait<0>();
  fence_regs(S);
  if (dbg) DBG(89);
  TR(3);
  ring_release(x, ring_add(e, 11), false);
  const uint32_t qa = x.base + SM_Q + x.w * 4096 + piece0(wg_tid()) * 2;
  #pragma unroll
  for (int i = 0; i < 8; i++) {
    const int j = 4 * (i >> 1), o = 2 * (i & 1);
    sts_v4(qa + (i >> 1) * 8192 + (i & 1) * 512,
           pack_bf16(S[4*j+o], S[4*j+o+1]), pack_bf16(S[4*j+4+o], S[4*j+5+o]), pack_bf16(S[4*j+8+o], S[4*j+9+o]), pack_bf16(S[4*j+12+o], S[4*j+13+o]));
  }
  fence_async_smem();
  if (dbg) DBG(90);
  TR(4);
  ring_wait_full(x.bars, ring_add(e, isY ? 0 : 2));
  ring_wait_full(x.bars, e + 1);
}

template<int KIND>
__device__ __forceinline__ void slot(Ctx& x, Att& a, int& e, float (&O)[64], uint32_t (&Pn)[32], uint32_t (&Po)[32],
                                     bool more, bool isY, bool half, int pv, int pend) {
  float S[64];
  const int w = x.w;
  const bool skip = KIND == 0 && !isY;
  const int en = ring_add(e, skip ? 4 : 2), sn = ring_slot(en), sv = ring_slot(e) + 1, sk = skip ? ring_slot(ring_add(e, 2)) : sv - 1;
  const uint32_t dq = desc_lo(x.base + SM_Q + w * 4096, 16), dk = desc_lo(x.base, 16) + sk * 2048, dv = desc_lo(x.base, 8192) + sv * 2048;
  bar_sync(1 + w, 256);
  TR(5 + KIND);
  if (KIND == 2) {
    wgmma_fence();
    issue_qk(S, dq, dk); wgmma_commit();
    issue_pv<8>(O, Po, dv, 1); wgmma_commit();
    bar_arrive(1 + (w ^ 1), 256);
    wgmma_wait<1>();
  } else if (KIND == 0 && half) {
    float T[32];
    wgmma_fence(); issue_qk_half(T, dq, dk); wgmma_commit();
    a.i0 = rcp_fast(quad_sum(a.l0)); a.i1 = rcp_fast(quad_sum(a.l1));
    if (pv == PV_NONE) { wgmma_fence(); wgmma_commit(); }
    else               { wgmma_fence(); issue_pv<8>(O, Po, dv, pv == PV_ACC); wgmma_commit(); }
    bar_arrive(1 + (w ^ 1), 256);
    wgmma_wait<1>();
    fence_regs(T);
    #pragma unroll
    for (int i = 0; i < 32; i++) { S[i] = T[i]; asm volatile("" : "=f"(S[32 + i])); }
  } else {
    wgmma_fence(); issue_qk(S, dq, dk); wgmma_commit();
    if (KIND == 1 && pend >= 0) { bar_arrive(1 + (w ^ 1), 256); pack_tile(O, Pn, a.i0, a.i1); store_ctx(x, pend, Pn); TR(8); }
    if (KIND == 0) { a.i0 = rcp_fast(quad_sum(a.l0)); a.i1 = rcp_fast(quad_sum(a.l1)); }
    if (KIND == 0 && pv == PV_NONE) { wgmma_fence(); wgmma_commit(); }
    else if (pv == PV_HALF)         { wgmma_fence(); issue_pv<4>(O, Po, dv, 0); wgmma_commit(); }
    else                            { wgmma_fence(); issue_pv<8>(O, Po, dv, pv == PV_ACC); wgmma_commit(); }
    if (KIND == 0 || pend < 0) bar_arrive(1 + (w ^ 1), 256);
    wgmma_wait<1>();
  }
  fence_regs(S);
  fence_regs_u(Pn);
  TR(9);
  slot_release(x, sk, KIND == 0 && isY);
  const bool landed = KIND != 0 && mbar_test2(x.bars + B_RF + 8 * sn, en >= 6);
  float s0 = 0.f, s1 = 0.f;
  const bool was_classic = KIND != 0 && a.classic;
  if (KIND == 0) {
    a.l0 = 0.f; a.l1 = 0.f;
    if (!half) exp_pack<16, 32>(S, Pn, s0, s1);
    else {
      #pragma unroll
      for (int i = 16; i < 32; i++) asm volatile("" : "=r"(Pn[i]));
    }
    exp_pack_diag(S, Pn, diag_limit(), s0, s1);
    uint32_t b0 = __ballot_sync(0xffffffff, s0 >= SUM_LO), b1 = __ballot_sync(0xffffffff, s1 >= SUM_LO);
    b0 |= b0 >> 1; b0 |= b0 >> 2; b1 |= b1 >> 1; b1 |= b1 >> 2;
    a.classic = __any_sync(0xffffffff, !(s0 <= SUM_HI && s1 <= SUM_HI)) || (b0 & b1 & 0x11111111u) != 0x11111111u;
  } else {
    exp_pack<0, 32>(S, Pn, s0, s1);
    a.classic = __any_sync(0xffffffff, a.classic || !(s0 <= SUM_HI && s1 <= SUM_HI));
  }
  fence_regs_u(Pn);
  TR(10);
  if (!landed) {
    mbar_wait(x.bars + B_RF + 8 * sn, en >= 6);
    if (more) mbar_wait(x.bars + B_RF + 8 * sn + 8, en >= 6);
  }
  wgmma_wait<0>();
  fence_regs(O);
  fence_regs_u(Po);
  TR(11);
  slot_release(x, sv, KIND == 1 && isY && pv != PV_ACC);
  if (!NO_CLASSIC && __builtin_expect(a.classic, 0)) {
    float sc0, sc1;
    classic_tile(S, Pn, KIND == 0, half, was_classic, a.mc, a.l0, a.l1, s0, s1, sc0, sc1);
    if (KIND != 0) {
      #pragma unroll
      for (int j = 0; j < 16; j++) { O[4*j] *= sc0; O[4*j+1] *= sc0; O[4*j+2] *= sc1; O[4*j+3] *= sc1; }
    }
  }
  a.l0 += s0; a.l1 += s1;
  e = en;
}

__device__ __forceinline__ int attention(Ctx& x, const uint8_t* items, int nitems, int rank, uint32_t (&PA)[32], uint32_t (&PB)[32], int vtile) {
  int e = 0;
  float O[64];
  Att a;
  volatile float mc[2];
  a.l0 = 1.f; a.l1 = 1.f; a.i0 = 0.f; a.i1 = 0.f; a.classic = false; a.mc = mc;
  int pv = PV_NONE, cur = -1;
#define DBGS()
  #pragma unroll 1
  for (int it = 0; ; it++) {
    const bool isY = (it & 1) == x.w;
    int pend = cur;
    if (it < nitems) {
      const int item = items[it];
      const bool half = isY == (rank != 0);
      cur = item * 4 + (isY ? 3 - rank : rank);
      int rem = 2 * (item & 7) + (isY ? 1 : 0);
      DBG(16 + it);
      q_proj(x, e, isY, PA, PB, vtile, it == 0);
      vtile = -1;
      DBGS();
      slot<0>(x, a, e, O, PA, PB, rem > 0, isY, half, pv, -1);
      pv = half ? PV_HALF : PV_ZERO;
      #pragma unroll 1
      while (rem > 0) {
        DBGS();
        slot<1>(x, a, e, O, PB, PA, rem > 1, isY, false, pv, pend);
        pv = PV_ACC; pend = -1;
        if (rem == 1) break;
        rem -= 2;
        DBGS();
        slot<2>(x, a, e, O, PA, PB, rem > 0, false, false, 0, -1);
      }
      if (isY) continue;
    } else {
      DBGS();
      slot_release(x, 6, false);
      const uint32_t dv = desc_lo(x.base, 8192) + ring_slot(e) * 2048;
      bar_sync(1 + x.w, 256);
      if (pv == PV_HALF) { wgmma_fence(); issue_pv<4>(O, PB, dv, 0); wgmma_commit(); }
      else { wgmma_fence(); issue_pv<8>(O, PB, dv, pv == PV_ACC); wgmma_commit(); }
      if (isY) bar_arrive(1 + (x.w ^ 1), 256);
      a.i0 = rcp_fast(quad_sum(a.l0)); a.i1 = rcp_fast(quad_sum(a.l1));
      ring_wait_full(x.bars, e);
      wgmma_wait<0>();
      fence_regs(O);
      fence_regs_u(PB);
      ring_release(x, e, false);
    }
    if (pend >= 0) {
      pack_tile(O, PB, a.i0, a.i1);
      if (it == nitems) return pend;
      store_ctx(x, pend, PB);
    }
    #pragma unroll
    for (int i = 0; i < 32; i++) asm volatile("mov.b32 %0, %1;" : "=r"(PB[i]) : "r"(PA[i]));
  }
}

#define LN_AT 2
#define X_AT 6
#define PERT 0
#define CTX_T 3
#define PF_AT 5
#define PF_N 4
#define PF_MOE -3
constexpr float QSCALE = 0.08838834764831845f * 1.4426950408889634f;
__device__ __forceinline__ void mod_cta(Ctx& x, const __nv_bfloat16* cvec) {
  const int t = wg_tid(), ct = x.w * 128 + t;
  #pragma unroll 1
  for (int k = 0; k < 6; k++) slot_release(x, k, false);
  const uint32_t cv = __ldg(reinterpret_cast<const uint32_t*>(cvec) + ct);
  asm volatile("st.shared.u32 [%0], %1;" :: "r"(x.base + SM_H2 + ct * 4),
               "r"(pack_bf16(__fdividef(bf_lo(cv), 1.f + __expf(-bf_lo(cv))), __fdividef(bf_hi(cv), 1.f + __expf(-bf_hi(cv))))) : "memory");
  bar_sync(5, 256);
  float acc[64];
  int e = 0;
  #pragma unroll 1
  for (int g = 0; g < 24; g++) {
    uint32_t a[8];
    #pragma unroll
    for (int i = 0; i < 8; i++) a[i] = lds_u32(x.base + SM_H2 + (g & 7) * 128 + i * 16 + (t & 3) * 4);
    ring_wait_full(x.bars, e);
    const uint32_t db = desc_lo(x.base + x.w * 16384, 8192) + ring_slot(e) * 2048;
    wgmma_fence();
    wgmma_rs_n128<1, 0, SW128>(acc, a[0], a[0], a[1], a[1], db, g & 7);
    wgmma_rs_n128<1, 128, SW128>(acc, a[2], a[2], a[3], a[3], db, 1);
    wgmma_rs_n128<1, 256, SW128>(acc, a[4], a[4], a[5], a[5], db, 1);
    wgmma_rs_n128<1, 384, SW128>(acc, a[6], a[6], a[7], a[7], db, 1);
    wgmma_commit();
    wgmma_wait<0>();
    fence_regs(acc);
    ring_release(x, e, false);
    e = ring_add(e, 1);
    if ((g & 7) == 7) {
      if (t < 4) {
        const float sc = (g == 7 && blockIdx.x < NCTA + 2) ? QSCALE : 1.f;
        uint32_t* dst = reinterpret_cast<uint32_t*>(g_mod + (g >> 3) * 1024 + (blockIdx.x - NCTA) * 256 + x.w * 128) + t;
        #pragma unroll
        for (int j = 0; j < 16; j++) dst[4 * j] = pack_bf16(rbf(acc[4*j]) * sc, rbf(acc[4*j+1]) * sc);
      }
      publish(x, g == 7 ? C_MOD : C_MOD2);
      DBG(1 + (g >> 3));
    }
  }
}

__global__ void __cluster_dims__(2, 1, 1) __launch_bounds__(384, 1)
k_fused(const __grid_constant__ CUtensorMap tmC, const __grid_constant__ CUtensorMap tmWq,
        const __grid_constant__ CUtensorMap tmWk, const __grid_constant__ CUtensorMap tmWv,
        const __grid_constant__ CUtensorMap tmWo, const __grid_constant__ CUtensorMap tmWg,
        const __grid_constant__ CUtensorMap tmWu, const __grid_constant__ CUtensorMap tmWm,
        const __grid_constant__ Sched sched,
        const __nv_bfloat16* __restrict__ xin,
        const __nv_bfloat16* __restrict__ cvec, const __nv_bfloat16* __restrict__ w_o,
        const __nv_bfloat16* __restrict__ w_r, const __nv_bfloat16* __restrict__ w_gate, const __nv_bfloat16* __restrict__ w_up,
        const __nv_bfloat16* __restrict__ w_down, __nv_bfloat16* __restrict__ out) {
  extern __shared__ __align__(1024) uint8_t smem_raw[];
  const uint32_t base = smem_u32(smem_raw), bars = base + SM_BAR;
  const int warp = __shfl_sync(0xffffffff, threadIdx.x >> 5, 0), wg = warp >> 2;
  const int rank = cluster_ctarank(), p = blockIdx.x >> 1;
  const int mt = (p & 7) * 2 + rank;
  const bool spare = blockIdx.x >= NCTA;
  #pragma unroll
  for (int i = 0; i < PERT; i++) { uint32_t d; asm volatile("mov.u32 %0, %%laneid;" : "=r"(d)); }
  {
    const int h0 = KHEAD0 + (p >> 3);
    if (warp == 11) { prefetch_tmap(&tmC); prefetch_tmap(&tmWk); }
    #pragma unroll 1
    for (int t = warp == 8 ? 0 : warp < 8 ? warp + 1 : warp == 11 ? 64 : warp; t < B_PUB / 8; t += (warp == 8 ? 64 : 10))
      w_mbar_init(bars + 8 * t, t < B_WE / 8 ? 1 : t < B_RE / 8 ? 2 : 4);
    fence_mbar_init();
    cluster_arrive();
    if (warp == 9) prefetch_tmap(&tmWv);
    if (wg == 2) bar_arrive(1, 256);
    if (warp == 8 && !spare) {
      #pragma unroll 1
      for (int kb = 0; kb < 8; kb++) {
        w_expect_tx(bars + B_AF + 8 * kb, 16384);
        tma_load_2d(base + k_addrA(kb), &tmC, bars + B_AF + 8 * kb, kb * 64, mt * 128);
        if (kb == 0) cluster_wait();
        if (kb < 6) {
          w_expect_tx(bars + B_WF + 8 * kb, 16384);
          tma_load_2d_mc(base + k_addrW(kb) + rank * 8192, &tmWk, bars + B_WF + 8 * kb, h0 * 128 + rank * 64, kb * 64);
        }
      }
    }
  }
  const Sched::Pair& sp = sched.pair[p];
  const int nitems = sp.nitems, nsteps = sp.nsteps;
  auto oent = [&](int k) -> uint32_t { return sp.oent[k]; };
  const int ot = sp.otask, m = (ot & 7) * 2 + rank, grp = m * 8 + (ot >> 3);

  if (wg == 0) {
    asm volatile("setmaxnreg.dec.sync.aligned.u32 24;");
    const int lane = threadIdx.x & 31;
    #pragma unroll 1
    for (int t = B_PUB / 8 + warp; t < 80; t += 4) w_mbar_init(bars + 8 * t, t < B_RDY / 8 ? 4 : 1);
    bar_sync(6, 128);
    bar_arrive(7, 256); bar_arrive(8, 256);
    cluster_wait();
    const unsigned int tag = ld_relaxed(&g_epoch) + 1;
    if (warp == 0) {
      if (!spare) {
        int s = 0, ph = 0;
        tma_prefetch_2d(&tmWv, sp.khead[0] * 128 + rank * 64, (p & 7) * 64);
        #pragma unroll 1
        for (int g = 6; g < 64; g++) {
          const int u = g >> 3, kb = g & 7;
          if (kb == 0 && u < 7) tma_prefetch_2d((u & 1) ? &tmWk : &tmWv, sp.khead[(u + 1) >> 1] * 128 + rank * 64, (p & 7) * 64);
          mbar_wait(bars + B_WE + 8 * s, ph);
          w_expect_tx(bars + B_WF + 8 * s, 16384);
          tma_load_2d_mc(base + k_addrW(s) + rank * 8192, (u & 1) ? &tmWv : &tmWk, bars + B_WF + 8 * s, sp.khead[u >> 1] * 128 + rank * 64, kb * 64);
          if (++s == 6) { s = 0; ph ^= 1; }
        }
      }
      int s = 0, ph = 0;
      auto next_entry = [&](int bytes) {
        mbar_wait(bars + B_RE + 8 * s, ph);
        w_expect_tx(bars + B_RF + 8 * s, bytes);
      };
      auto advance = [&]() { if (++s == 6) { s = 0; ph ^= 1; } };
      if (spare) {
        #pragma unroll 1
        for (int g = 0; g < 24; g++) {
          if (g == 8) mbar_wait(bars + R_MOD, 0);
          next_entry(32768);
          for (int k = 0; k < 2; k++) tma_load_3d(base + s * 32768 + k * 16384, &tmWm, bars + B_RF + 8 * s, 0, (g & 7) * 64, (g >> 3) * 16 + (blockIdx.x - NCTA) * 4 + k * 2);
          advance();
        }
      }
      mbar_wait(bars + R_H1, 0);
      fence_async_global();
      int vrow = -1;
      #pragma unroll 1
      for (int i = 0; i <= nitems; i++) {
        const int item = sp.item[i & (MAX_ITEMS - 1)], h = item >> 3, j = item & 7;
        if (i < nitems) {
          const int row0 = j * 256 + ((i & 1) ? rank : 3 - rank) * 64, row1 = j * 256 + ((i & 1) ? 3 - rank : rank) * 64;
          #pragma unroll 1
          for (int kb = 0; kb < 8; kb++) {
            next_entry(32768);
            tma_load_2d_mc(base + s * 32768 + 16384 + rank * 8192, &tmWq, bars + B_RF + 8 * s, h * 128 + rank * 64, kb * 64);
            bulk_load(base + s * 32768, sched.h1 + row0 * DM + kb * 4096, 8192, bars + B_RF + 8 * s);
            bulk_load(base + s * 32768 + 8192, sched.h1 + row1 * DM + kb * 4096, 8192, bars + B_RF + 8 * s);
            advance();
          }
          mbar_wait(bars + R_ITEM + 8 * i, 0);
          fence_async_global();
        }
        #pragma unroll 1
        for (int n = i < nitems ? 4 * j + 3 : 0; n >= 0; n--) {
          const int krow = (h * 2 + rank) * SEQ + (n >> 1) * 128 + ((sp.lastuse[i & (MAX_ITEMS - 1)] >> (n >> 1)) & 1);
          const int row = (n & 1) ? krow : vrow;
          if (i + 1 == nitems && n == min(4 * j + 3, 2 * PF_AT + 1)) w_arrive(bars + R_NEAR);
          next_entry(row >= 0 ? 32768 : 0);
          if (row >= 0) bulk_load_mc(base + s * 32768 + rank * 16384, sched.kvc + (size_t)(row & ~1) * 64, bars + B_RF + 8 * s, row & 1);
          advance();
          if (!(n & 1)) vrow = krow + 64 * SEQ;
        }
      }
      if (!spare) {
      const int oc = ((ot >> 3) & 1) * 4 + rank * 2;
      auto o_next = [&](int k, int bytes) {
        const uint32_t v = oent(k); s = v & 7;
        mbar_wait(bars + B_RE + 8 * s, v >> 3);
        w_expect_tx(bars + B_RF + 8 * s, bytes);
      };
      #pragma unroll 1
      for (int i = 0; i < nsteps; i++) {
        const int c0 = sp.ochunk[i][0], c1 = sp.ochunk[i][1];
        const int pf = PF_MOE > 0 ? i - PF_MOE : i - nsteps - PF_MOE;
        if (pf >= 0 && pf < 3)
          bulk_prefetch((pf == 0 ? w_gate : pf == 1 ? w_up : w_down) + (size_t)blockIdx.x * (DM * FF / NCTA), DM * FF / NCTA * 2);
        if (c0 < 64) { o_next(3 * i, 32768); tma_load_3d_mc(base + s * 32768 + rank * 16384, &tmWo, bars + B_RF + 8 * s, 0, c0 * 64, oc); }
        mbar_wait(bars + R_CTX + 8 * i, 0);
        fence_async_global();
        o_next(3 * i + 1, c0 < 64 ? 32768 : 16384);
        if (c0 < 64) bulk_load(base + s * 32768, sched.kvc + (size_t)((128 + c0) * SEQ + m * 128) * 64, 16384, bars + B_RF + 8 * s);
        bulk_load(base + s * 32768 + 16384, sched.kvc + (size_t)((128 + c1) * SEQ + m * 128) * 64, 16384, bars + B_RF + 8 * s);
        o_next(3 * i + 2, 32768);
        tma_load_3d_mc(base + s * 32768 + rank * 16384, &tmWo, bars + B_RF + 8 * s, 0, c1 * 64, oc);
      }
      const int f0 = (blockIdx.x < FF / 16 ? blockIdx.x : 0) * 16;
      o_next(3 * nsteps, 32768);
      bulk_load(base + s * 32768, w_down + (size_t)f0 * DM, 16384, bars + B_RF + 8 * s);
      bulk_load(base + s * 32768 + 16384, xin + (size_t)grp * 16 * DM, 16384, bars + B_RF + 8 * s);
      o_next(3 * nsteps + 1, 32768);
      #pragma unroll 1
      for (int k = 0; k < 4; k++) tma_load_2d(base + s * 32768 + k * 8192, (k & 2) ? &tmWu : &tmWg, bars + B_RF + 8 * s, f0, (k & 1) * 256);
      #pragma unroll 1
      for (int k = 0; k < 4; k++) w_expect_tx(bars + R_PART + 8 * k, 16384);
      mbar_wait(bars + B_PUB + 8 * (5 + nitems), 0);
      mbar_wait(bars + B_PUB + 8 * (NPUB + 5 + nitems), 0);
      uint32_t todo = 0xff;
      #pragma unroll 1
      for (int n = 0; n < WAIT_LIM && todo; n++) {
        uint32_t now = __ballot_sync(0xffffffff, ld_acquire(&g_cnt[C_PART + (m * 2 + (ot >> 5)) * 32 + (lane & 7)]) == tag) & todo;
        todo &= ~now;
        if (now) fence_async_global();
        #pragma unroll 1
        for (; now; now &= now - 1) {
          const int q = __ffs(now) - 1;
          bulk_load(base + (oent(3 * nsteps - 3 + (q >> 2)) & 7) * 32768 + (q & 3) * 8192, sched.part + (grp * 8 + q) * 4096, 8192, bars + R_PART + 8 * (q >> 1));
        }
      }
      DBGP(11);
      }
    } else if (warp < 3) {
      const int w = warp - 1, n1 = w * NPUB + (spare ? 3 : 6) + nitems;
      #pragma unroll 1
      for (int n = w * NPUB; n < n1; n++) {
        #pragma unroll 1
        for (int k = 0; k < 8 * WAIT_LIM; k++) { if (mbar_try(bars + B_PUB + 8 * n, 0)) break; }
        const uint32_t idx = lds_u32(base + SM_MAIL + 4 * n);
        fence_async_global();
        if (lane == 0 && idx < (unsigned)C_END) red_release(idx);
        __syncwarp();
      }
    } else {
      *reinterpret_cast<volatile uint32_t*>(smem_raw + SM_KEY + 48) = tag;
      if (!spare) { mbar_wait(bars + B_AF + 8 * X_AT, 0); bulk_prefetch(xin + (size_t)blockIdx.x * 16 * DM, 16 * DM * 2); }
      #pragma unroll 1
      for (int n = 0; n < 8 + nsteps; n++) {
        if (n == 2 + nitems) n = 7;
        int idx = n == 0 ? C_MOD : n == 1 ? C_H1 : C_MOD2, cnt = n == 0 ? 8 : n == 1 ? 256 : 16;
        if (n >= 1 && n <= nitems) { const int item = sp.item[n - 1]; tma_prefetch_2d(&tmWq, (item >> 3) * 128 + rank * 64, (item & 7) * 64); }
        if (n >= 2 && n < 7) { idx = C_KV + (sp.item[n - 2] >> 3); cnt = 32; }
        if (n >= 8) { const int c0 = sp.ochunk[n - 8][0], c1 = sp.ochunk[n - 8][1]; idx = C_CTX + (((lane & 1) && c0 < 64 ? c0 : c1) >> 1) * 8 + (ot & 7); cnt = 4; }
        wait_count_lazy(idx, cnt * tag);
        w_arrive(bars + B_RDY + 8 * n);
        if (n == 0) DBGP(12);
        if (n == 8 + PF_N - 1) {
          #pragma unroll 1
          for (int k = 0; k < 8 * WAIT_LIM; k++) { if (mbar_try(bars + R_NEAR, 0)) break; }
          bulk_prefetch(w_o + (size_t)blockIdx.x * (NH * DH * DM / NCTA), NH * DH * DM / NCTA * 2);
          #pragma unroll 1
          for (int k = 0; k < PF_N; k++) {
            const int cc = sp.ochunk[k][(ot >> 3) & 1];
            if (cc < 64) bulk_prefetch(sched.kvc + ((size_t)(128 + cc) * SEQ + m * 128) * 64, 16384);
          }
        }
      }
    }
    __syncwarp();
    cluster_arrive();
    if (!spare) {
      bar_sync(6, 128);
      asm volatile("setmaxnreg.inc.sync.aligned.u32 88;");
      const int pos = blockIdx.x * 4 + (lane & 1) * 2, col = (blockIdx.x >> 2) * 16 + (blockIdx.x & 3) * 2 + (lane & 1) * 8, src = threadIdx.x >> 1;
      uint32_t gbest = 0, hh = 0, gbf = 0;
      uint2 xx = make_uint2(0, 0);
      uint4 ya = make_uint4(0, 0, 0, 0), yb = make_uint4(0, tag, 0, tag);
      auto poll_y = [&]() {
        if (ya.y != tag || ya.w != tag) ya = ld_tagged2(&g_yll[src][pos]);
        if (yb.y != tag || yb.w != tag) yb = ld_tagged2(&g_yll[src + 64][pos]);
        return __all_sync(0xffffffff, ya.y == tag && ya.w == tag && yb.y == tag && yb.w == tag);
      };
      ya.y = tag - 1; if (src + 64 < FF / 16) yb.y = tag - 1;
      poll_y();
      if (warp == 3) {
        gbf = __ldcg(reinterpret_cast<const uint32_t*>(g_mod + 5 * DM + col));
        uint32_t have = 0;
        uint2 k[4];
        #pragma unroll
        for (int i = 0; i < 4; i++) k[i] = make_uint2(0, tag - 1);
        #pragma unroll 1
        for (int n = 0; n < WAIT_LIM; n++) {
          #pragma unroll
          for (int i = 0; i < 4; i++) if (k[i].y != tag) k[i] = ld_tagged(&g_keys[i * 32 + lane][0]);
          if (gbest != have) {
            const int g = ((0xffffu - gbest) >> 4) & 127;
            uint4 hv[4];
            #pragma unroll
            for (int i = 0; i < 4; i++) hv[i] = ld_tagged2(&g_row[g][0][i * 64 + lane * 2]);
            xx = ld_tagged(&g_row[g][1][(col >> 8) * 128 + ((col >> 2) & 1) * 64 + ((col >> 3) & 31) * 2 + ((col >> 1) & 1)]);
            bool ok = xx.y == tag;
            #pragma unroll
            for (int i = 0; i < 4; i++) { ok = ok && hv[i].y == tag && hv[i].w == tag; reinterpret_cast<uint2*>(smem_raw + SM_H2)[(i >> 1) * 64 + lane * 2 + (i & 1)] = make_uint2(hv[i].x, hv[i].z); }
            if (lane == 0) *reinterpret_cast<uint32_t*>(smem_raw + SM_KEY + 32) = gbest;
            have = __all_sync(0xffffffff, ok) ? gbest : 0;
          }
          bool all = true;
          #pragma unroll
          for (int i = 0; i < 4; i++) { all = all && k[i].y == tag; gbest = max(gbest, k[i].y == tag ? k[i].x : 0u); }
          gbest = __reduce_max_sync(0xffffffff, gbest);
          if (__all_sync(0xffffffff, all) && gbest == have) break;
        }
        w_arrive(bars + R_KEY);
        if (blockIdx.x == 0 && lane == 0) g_epoch = tag;
        hh = lds_u32(base + SM_H2 + col * 2);
        DBGP(13);
      }
      const uint32_t sb16 = gbest & 0xffff0000u;
      const float rsel = __uint_as_float((sb16 & 0x80000000u) ? (sb16 & 0x7fffffffu) : (~sb16 & 0xffff0000u));
      const float rs = rbf(__fdividef(1.f, 1.f + __expf(-rsel)));
      bar_sync(9, 384);
      #pragma unroll 1
      for (int n = 0; n < WAIT_LIM; n++) { if (poll_y()) break; }
      float y0 = __uint_as_float(ya.x) + __uint_as_float(yb.x), y1 = __uint_as_float(ya.z) + __uint_as_float(yb.z);
      #pragma unroll
      for (int o = 2; o < 32; o <<= 1) { y0 += __shfl_xor_sync(0xffffffff, y0, o); y1 += __shfl_xor_sync(0xffffffff, y1, o); }
      float2* s_y = reinterpret_cast<float2*>(smem_raw + SM_KEY + 64);
      if (lane < 2) s_y[warp * 2 + lane] = make_float2(y0, y1);
      bar_sync(6, 128);
      if (warp == 3 && lane < 2) {
        y0 = 0.f; y1 = 0.f;
        #pragma unroll
        for (int i = 0; i < 4; i++) { y0 += reinterpret_cast<const float*>(s_y)[i * 4 + lane]; y1 += reinterpret_cast<const float*>(s_y)[i * 4 + 2 + lane]; }
        const float o0 = bf_lo(xx.x) + rbf(bf_lo(gbf) * rbf(bf_lo(hh) + rbf(rbf(y0) * rs)));
        const float o1 = bf_hi(xx.x) + rbf(bf_hi(gbf) * rbf(bf_hi(hh) + rbf(rbf(y1) * rs)));
        *reinterpret_cast<uint32_t*>(out + (size_t)((0xffffu - gbest) & (SEQ - 1)) * DM + col) = pack_bf16(o0, o1);
      }
      DBGP(14);
    }
    __syncwarp();
    cluster_wait();
  } else {
    asm volatile("setmaxnreg.inc.sync.aligned.u32 240;");
    Ctx x;
    x.w = wg - 1; x.base = base; x.bars = bars; x.nev = 0; x.sched = &sched;
    const int w = x.w, warp4 = warp & 3;
    x.rel = mapa(bars, (warp4 & 1) ^ 1);
    x.rel1 = (threadIdx.x & 127) == 32 || (threadIdx.x & 127) == 64;
    if (warp != 8 || spare) cluster_wait();
    if (w == 1 || spare) bar_sync(7 + w, 256);
    DBG(1);
    uint32_t PA[32], PB[32];
    int vtile = -1;
    if (spare) {
      mod_cta(x, cvec);
    } else {
      const int lane = wg_tid() & 31;
      Row xn[2];
      float acc0[64], acc1[64];
      int s = 2 * w, ph = w;
      #pragma unroll 1
      for (int u = w; u < 8; u += 2) {
        bar_sync(1 + w, 256);
        DBG(4 + (u >> 1) * 3);
        int ps = 0;
        #pragma unroll 1
        for (int kb = 0; kb < 8; kb++) {
          if (u < 2) mbar_wait(bars + B_AF + 8 * kb, 0);
          mbar_wait(bars + B_WF + 8 * s, ph);
          const uint32_t da = desc_lo(base + k_addrA(kb), 16), dw = desc_lo(base + k_addrW(s), 8192);
          wgmma_fence();
          kblock_n128<0>(acc0, da, dw, kb != 0);
          kblock_n128<512>(acc1, da, dw, kb != 0);
          wgmma_commit();
          if (kb == 7) bar_arrive(1 + (w ^ 1), 256);
          if (kb > 0) {
            wgmma_wait<1>();
            mbar_arrive_remote_if(x.rel + B_WE + 8 * ps, x.rel1);
            if (u == 7 && !(kb & 1)) {
              ring_release(x, kb == 2 ? 0 : kb - 3, false);
              if (kb > 2) ring_release(x, kb - 2, false);
            }
          }
          ps = s;
          if (++s == 6) { s = 0; ph ^= 1; }
        }
        Row t[2];
        const int lrow = blockIdx.x * 16 + w * 8 + warp4 * 2;
        if (u == w) { t[0] = ldg_row(xin + (size_t)lrow * DM, lane); t[1] = ldg_row(xin + (size_t)(lrow + 1) * DM, lane); }
        if (u == LN_AT || u == LN_AT + 1) {
          mbar_wait(bars + R_MOD, 0);
          t[0] = ldca_row(g_mod, lane); t[1] = ldca_row(g_mod + DM, lane);
        }
        wgmma_wait<0>();
        fence_regs(acc0); fence_regs(acc1);
        DBG(5 + (u >> 1) * 3);
        mbar_arrive_remote_if(x.rel + B_WE + 8 * ps, x.rel1);
        if (u == 6) { for (int k = 0; k < 5; k++) ring_release(x, k, false); }
        if (u >= 6) ring_release(x, 5, false);
        if (V_AT >= 0 && u == 7) {
          pack_tile(acc0, PA, 1.f, 1.f); pack_tile(acc1, PB, 1.f, 1.f);
          vtile = sp.khead[3] * 16 + mt;
          break;
        }
        s += 2; ph ^= 1; if (s >= 6) { s -= 6; ph ^= 1; }
        if (u == 0) bar_sync(7, 256);
        if (u == w) {
          float st[4] = {0.f, 0.f, 0.f, 0.f};
          #pragma unroll
          for (int i = 0; i < 32; i++) { const float v = row_at(t[i >> 4], i & 15); st[(i >> 4) * 2] += v; st[(i >> 4) * 2 + 1] = fmaf(v, v, st[(i >> 4) * 2 + 1]); }
          warp_sums(st);
          #pragma unroll
          for (int r = 0; r < 2; r++) { ln_stats(st[2*r], st[2*r+1]); xn[r] = ln_apply(t[r], st[2*r], st[2*r+1] * QSCALE); }
        }
        if ((u == LN_AT || u == LN_AT + 1)) {
          #pragma unroll
          for (int r = 0; r < 2; r++) {
            const Row hr = fma_row(xn[r], one_plus(t[1]), t[0]);
            __nv_bfloat16* hp = sched.h1 + (lrow & ~63) * DM + (lane >> 3) * 4096 + ((lrow + r) & 63) * 64 + (((lane ^ (lrow + r)) & 7) << 3);
            stg_v4(hp, hr.v[0], hr.v[1], hr.v[2], hr.v[3]); stg_v4(hp + 4 * 4096, hr.v[4], hr.v[5], hr.v[6], hr.v[7]);
          }
        }
        const int tile = sp.khead[u >> 1] * 16 + mt;
        __nv_bfloat16* dst = kv_tile(x, tile);
        uint32_t D[32];
        pack_tile(acc0, D, 1.f, 1.f); store_tile(dst + 2048, D);
        pack_tile(acc1, D, 1.f, 1.f); store_tile(dst, D);
        if (u == LN_AT || u == LN_AT + 1) publish(x, C_H1);
        publish(x, C_KV + (tile >> 4));
        DBG(6 + (u >> 1) * 3);
      }
    }
    x.tr = base + SM_RED + w * 1024;
    const int last = attention(x, sp.item, nitems, rank, PA, PB, vtile);
    DBG(100);
    const int lane = wg_tid() & 31, cw = w * 4 + warp4, ct = cw * 32 + lane;
    const int row0 = grp * 16 + cw * 2;
    const bool moe_cta = blockIdx.x < FF / 16;
    if (spare) { store_ctx(x, last, PB); __syncwarp(); cluster_arrive(); cluster_wait(); return; }
    const int kl = 3 * nsteps - 3;
    {
      float accA[64], accB[64];
      const int t0 = oent(0) == oent(1);
      uint32_t pa = 0, pb = 0;
      #pragma unroll 1
      for (int t = t0; t < 2 * nsteps - 2; t++) {
        const uint32_t eb = oent(3 * (t >> 1) + 2 * (t & 1)), ea = oent(3 * (t >> 1) + 1);
        o_wait_full(bars, eb);
        o_wait_full(bars, ea);
        const uint32_t da = desc_lo(base + w * 4096, 16) + (ea & 7) * 2048 + (t & 1) * 1024, db = desc_lo(base, 8192) + (eb & 7) * 2048;
        wgmma_fence();
        kblock_n128<0, 0, SW64>(accA, da, db, t != t0); kblock_n128<0, 1024, SW64>(accB, da, db, t != t0);
        wgmma_commit();
        if (t == CTX_T) store_ctx(x, last, PB);
        if (t > t0) { wgmma_wait<1>(); slot_release(x, pb, false); if (!(t & 1)) slot_release(x, pa, false); }
        pa = ea & 7; pb = eb & 7;
      }
      const uint32_t e0 = oent(kl), ea = oent(kl + 1), eb = oent(kl + 2);
      const uint32_t da = desc_lo(base + w * 4096, 16) + (ea & 7) * 2048;
      const uint32_t db0 = desc_lo(base, 8192) + (e0 & 7) * 2048, db1 = desc_lo(base, 8192) + (eb & 7) * 2048;
      o_wait_full(bars, e0);
      o_wait_full(bars, ea);
      o_wait_full(bars, eb);
      wgmma_fence();
      kblock_n128<0, 0, SW64>(accA, da, db0, 1); kblock_n128<1024, 0, SW64>(accA, da, db1, 1);
      wgmma_commit();
      kblock_n128<0, 1024, SW64>(accB, da, db0, 1); kblock_n128<1024, 1024, SW64>(accB, da, db1, 1);
      wgmma_commit();
      __syncwarp();
      cluster_arrive();
      __nv_bfloat16* dst = sched.part + ((m * 8 + cw) * 8 + (ot >> 3)) * 4096;
      auto send = [&](const float (&acc)[64], int h) {
        uint32_t D[32];
        pack_tile(acc, D, 1.f, 1.f);
        #pragma unroll
        for (int i = 0; i < 8; i++) stg_v4(dst + (h * 8 + i) * 256 + ((lane ^ (h * 4 + (i >> 1))) << 3), D[4*i], D[4*i+1], D[4*i+2], D[4*i+3]);
      };
      wgmma_wait<1>();
      fence_regs(accA);
      DBG(120);
      send(accA, 0);
      o_wait_full(bars, eb);
      wgmma_wait<0>();
      fence_regs(accB);
      DBG(101);
      send(accB, 1);
      publish(x, C_PART + (m * 2 + w) * 32 + (ot >> 3));
      DBG(121);
      DBG(102);
    }
    asm volatile("setmaxnreg.dec.sync.aligned.u32 208;");
    const Row ga = ldca_row(g_mod + 2 * DM, lane), sb = ldca_row(g_mod + 3 * DM, lane), cb = ldca_row(g_mod + 4 * DM, lane), gb = ldca_row(g_mod + 5 * DM, lane);
    const Row wr = ldca_row(w_r, lane);
    const uint32_t sD = base + (oent(kl + 3) & 7) * 32768, sW = base + (oent(kl + 4) & 7) * 32768;
    o_wait_full(bars, oent(kl + 3)); o_wait_full(bars, oent(kl + 4));
    Row x1[2];
    #pragma unroll
    for (int r = 0; r < 2; r++) x1[r] = lds_row(sD + 16384 + (cw * 2 + r) * 1024, lane);
    uint4 wgv[4], wuv[4], wdv[4];
    #pragma unroll
    for (int r = 0; r < 4; r++) {
      const uint32_t k = (lane & 7) + ((lane >> 4) << 3), h = (lane & 8) * 2;
      wgv[r] = ldsm_x4_t(sW + (cw * 64 + r * 16 + k) * 32 + h);
      wuv[r] = ldsm_x4_t(sW + 16384 + (cw * 64 + r * 16 + k) * 32 + h);
      wdv[r] = ldsm_x4_t(sD + k * 1024 + (cw * 64 + r * 16) * 2 + h);
    }
    const Row cb1 = one_plus(cb);
    const unsigned int tag = lds_u32(base + SM_KEY + 48);
    DBG(103);
    float u[16], ub[2] = {0.f, 0.f};
    #pragma unroll
    for (int i = 0; i < 16; i++) { u[i] = row_at(cb1, i) * row_at(wr, i); ub[0] += u[i]; ub[1] = fmaf(row_at(sb, i), row_at(wr, i), ub[1]); }
    warp_sums(ub);
    float st[6] = {0.f, 0.f, 0.f, 0.f, 0.f, 0.f};
    uint32_t key[2];
    {
      const uint32_t po = base + ((lane & 7) * 2 + (cw >> 2)) * 512 + (cw & 3) * 128;
      Row av[2][2];
      #pragma unroll
      for (int k = 0; k < 4; k++) {
        mbar_wait(bars + R_PART + 8 * k, 1);
        const uint32_t pa = po + (oent(kl + (k >> 1)) & 7) * 32768 + (k & 1) * 16384;
        #pragma unroll
        for (int r = 0; r < 2; r++) {
          const uint32_t sw = ((r * 4 + (lane >> 3)) ^ (lane & 7)) << 4;
          const uint4 lo = ldsm_x4(pa + sw), hi = ldsm_x4(pa + 8192 + sw);
          const Row v{{lo.x, lo.y, lo.z, lo.w, hi.x, hi.y, hi.z, hi.w}};
          av[r][k >> 1] = (k & 1) ? add_row(av[r][k >> 1], v) : v;
        }
      }
      DBG(104);
      #pragma unroll
      for (int r = 0; r < 2; r++) {
        x1[r] = fma_row(ga, add_row(av[r][0], av[r][1]), x1[r]);
        #pragma unroll
        for (int i = 0; i < 16; i++) { const float v = row_at(x1[r], i); st[3*r] += v; st[3*r+1] = fmaf(v, v, st[3*r+1]); st[3*r+2] = fmaf(v, u[i], st[3*r+2]); }
      }
      warp_sums(st);
      #pragma unroll
      for (int r = 0; r < 2; r++) {
        ln_stats(st[3*r], st[3*r+1]);
        const uint32_t rb = pack_bf16(0.f, fmaf(st[3*r+1], fmaf(-st[3*r], ub[0], st[3*r+2]), ub[1]));
        key[r] = (((rb & 0x80000000u) ? ~rb : (rb | 0x80000000u)) & 0xffff0000u) | (0xffffu - (uint32_t)(row0 + r));
      }
    }
    DBG(105);
    float* s_red = reinterpret_cast<float*>(smem_raw + SM_RED);
    uint32_t* s_key = reinterpret_cast<uint32_t*>(smem_raw + SM_KEY);
    const int rb = key[1] > key[0];
    const uint32_t wbest = rb ? key[1] : key[0];
    if (lane == 0) s_key[cw] = wbest;
    bar_sync(5, 256);
    const uint32_t cbest = __reduce_max_sync(0xffffffff, s_key[lane & 7]);
    if (wbest == cbest && lane == 0) st_tagged(&g_keys[grp][0], cbest, tag);
    Row xb, xo;
    #pragma unroll
    for (int i = 0; i < 8; i++) { xb.v[i] = rb ? x1[1].v[i] : x1[0].v[i]; xo.v[i] = rb ? x1[0].v[i] : x1[1].v[i]; }
    const Row hb = fma_row(ln_apply(xb, rb ? st[3] : st[0], rb ? st[4] : st[1]), cb1, sb);
    if (wbest == cbest) {
      #pragma unroll
      for (int i = 0; i < 4; i++) st_tagged2(&g_row[grp][0][i * 64 + lane * 2], hb.v[2*i], hb.v[2*i+1], tag);
      #pragma unroll
      for (int i = 0; i < 4; i++) st_tagged2(&g_row[grp][1][i * 64 + lane * 2], xb.v[2*i], xb.v[2*i+1], tag);
    }
    DBG(106);
    const Row ob = fma_row(gb, hb, xb);
    if (wbest != cbest) store_row(out + (size_t)(row0 + rb) * DM, lane, ob);
    store_row(out + (size_t)(row0 + 1 - rb) * DM, lane, fma_row(gb, fma_row(ln_apply(xo, rb ? st[0] : st[3], rb ? st[1] : st[4]), cb1, sb), xo));
    mbar_wait(bars + R_KEY, 1);
    DBG(107);
    if (moe_cta) {
      float cg[4] = {0, 0, 0, 0}, cu[4] = {0, 0, 0, 0};
      #pragma unroll
      for (int r = 0; r < 4; r++) {
        const uint32_t b0 = lds_u32(base + SM_H2 + (cw * 64 + r * 16) * 2 + (lane & 3) * 4), b1 = lds_u32(base + SM_H2 + (cw * 64 + r * 16) * 2 + 16 + (lane & 3) * 4);
        mma16816(cg, wgv[r], b0, b1); mma16816(cu, wuv[r], b0, b1);
      }
      s_red[cw * 32 + (lane & 3) * 8 + (lane >> 2)] = (lane & 2) ? ((lane & 1) ? cu[2] : cu[0]) : ((lane & 1) ? cg[2] : cg[0]);
      bar_sync(5, 256);
      float g = 0.f;
      #pragma unroll
      for (int i = 0; i < 8; i++) g += s_red[i * 32 + lane];
      g = rbf(g);
      const float act = rbf(__fdividef(g, 1.f + __expf(-g))) * __shfl_down_sync(0xffffffff, g, 16);
      const uint32_t a2 = pack_bf16(act, __shfl_down_sync(0xffffffff, act, 1));
      const uint32_t b0 = __shfl_sync(0xffffffff, a2, (lane & 3) * 2), b1 = __shfl_sync(0xffffffff, a2, (lane & 3) * 2 + 8);
      float y0 = 0.f, y1 = 0.f;
      #pragma unroll
      for (int r = 0; r < 4; r++) {
        float c[4] = {0, 0, 0, 0};
        mma16816(c, wdv[r], b0, b1);
        if ((lane & 3) == r) { y0 = c[0]; y1 = c[2]; }
      }
      st_tagged2(&g_yll[blockIdx.x][cw * 64 + (lane & 3) * 16 + (lane >> 2) * 2], __float_as_uint(y0), __float_as_uint(y1), tag);
    }
    bar_arrive(9, 384);
    DBG(108);
    if (wbest == cbest && wbest != s_key[8]) store_row(out + (size_t)(row0 + rb) * DM, lane, ob);
    DBG(109);
    __syncwarp();
    cluster_wait();
  }
}

typedef CUresult (*EncodeFn)(CUtensorMap*, CUtensorMapDataType, cuuint32_t, void*, const cuuint64_t*, const cuuint64_t*, const cuuint32_t*,
                             const cuuint32_t*, CUtensorMapInterleave, CUtensorMapSwizzle, CUtensorMapL2promotion, CUtensorMapFloatOOBfill);

struct HostState {
  bool ready = false;
  EncodeFn encode = nullptr;
  CUtensorMap tmC, tmWq, tmWk, tmWv, tmWo, tmWg, tmWu, tmWm;
  Sched sched;
};

void make_map(EncodeFn enc, CUtensorMap* m, const void* ptr, int rank, const cuuint64_t* dims, const cuuint64_t* strides, const cuuint32_t* box, bool swizzle = true) {
  const cuuint32_t es[3] = {1, 1, 1};
  enc(m, CU_TENSOR_MAP_DATA_TYPE_BFLOAT16, rank, const_cast<void*>(ptr), dims, strides, box, es, CU_TENSOR_MAP_INTERLEAVE_NONE,
      swizzle ? CU_TENSOR_MAP_SWIZZLE_128B : CU_TENSOR_MAP_SWIZZLE_NONE, swizzle ? CU_TENSOR_MAP_L2_PROMOTION_L2_128B : CU_TENSOR_MAP_L2_PROMOTION_NONE, CU_TENSOR_MAP_FLOAT_OOB_FILL_NONE);
}
void make_2d(EncodeFn enc, CUtensorMap* m, const void* ptr, int rows, int cols, int box_rows) {
  const cuuint64_t dims[2] = {(cuuint64_t)cols, (cuuint64_t)rows}, strides[1] = {(cuuint64_t)cols * 2};
  const cuuint32_t box[2] = {64, (cuuint32_t)box_rows};
  make_map(enc, m, ptr, 2, dims, strides, box);
}
void make_3d(EncodeFn enc, CUtensorMap* m, const void* ptr, int rows, int chunks, size_t row_stride, size_t chunk_stride) {
  const cuuint64_t dims[3] = {64, (cuuint64_t)rows, (cuuint64_t)chunks}, strides[2] = {row_stride, chunk_stride};
  const cuuint32_t box[3] = {64, 64, 2};
  make_map(enc, m, ptr, 3, dims, strides, box);
}

void make_ffn(EncodeFn enc, CUtensorMap* m, const void* ptr) {
  const cuuint64_t dims[2] = {(cuuint64_t)FF, (cuuint64_t)DM}, strides[1] = {(cuuint64_t)FF * 2};
  const cuuint32_t box[2] = {16, 256};
  make_map(enc, m, ptr, 2, dims, strides, box, false);
}

#define SR 0x213312
#define SEED 12345
#define LU_MARGIN 0
#define SPARE_N 3
void build_sched(Sched& s) {
  memset(&s, 0, sizeof(s));
  const int NP = NCTA / 2, korder[4] = {(KORDER >> 12) & 3, (KORDER >> 8) & 3, (KORDER >> 4) & 3, KORDER & 3};
  const int sround[4][2][3] = {{}, {{1}, {2}}, {{1, 2}, {1, 2}}, {{(SR >> 20) & 3, (SR >> 16) & 3, (SR >> 12) & 3}, {(SR >> 8) & 3, (SR >> 4) & 3, SR & 3}}};
  int jv[4][NP], used[4][8] = {};
  for (int r = 0; r < 4; r++) for (int p = 0; p < NP; p++) jv[r][p] = (r & 2) ? 7 - ((p + 4 * (r & 1)) & 7) : (p + 4 * (r & 1)) & 7;
  for (int q = 0; q < 2; q++) {
    s.pair[NP + q].nitems = SPARE_N;
    for (int i = 0; i < SPARE_N; i++) {
      const int r = sround[SPARE_N][q][i];
      s.pair[NP + q].item[i] = (uint8_t)((r * 8 + used[r][6]++) * 8 + 6);
      for (int p = 0; p < NP; p++) if (jv[r][p] == 6) { jv[r][p] = -2; break; }
    }
  }
  auto cost = [&](int p) {
    int u = 8 - ((p >> 4) < SPARE_N ? 21 : 22), z = 0, none = 0;
    for (int r = 0; r < 4; r++) { u += jv[r][p]; z += jv[r][p] == 0; none += jv[r][p] < 0; }
    return 4 * u * u + (z > 1) + 4 * (none > 1);
  };
  uint32_t rng = SEED;
  for (int it = 0; it < 2000000; it++) {
    if ((it & 255) == 0) { int t = 0; for (int p = 0; p < NP; p++) t += cost(p); if (t == 0) break; }
    rng = rng * 1664525u + 1013904223u;
    const int r = (rng >> 8) & 3, a = (rng >> 12) & 63, b = (rng >> 20) & 63, before = cost(a) + cost(b);
    int t = jv[r][a]; jv[r][a] = jv[r][b]; jv[r][b] = t;
    if (cost(a) + cost(b) > before) { jv[r][b] = jv[r][a]; jv[r][a] = t; }
  }
  int fin[256], done[256];
  for (int p = 0; p < NP + 2; p++) {
    Sched::Pair& q = s.pair[p];
    if (p < NP) {
      for (int k = 0; k < 4; k++) q.khead[k] = (uint8_t)(korder[k] * 8 + (p >> 3));
      for (int r = 0; r < 4; r++) {
        if (jv[r][p] < 0) continue;
        q.item[q.nitems++] = (uint8_t)((r * 8 + used[r][jv[r][p]]++) * 8 + jv[r][p]);
      }
    }
    int t = p < NP ? 0 : -3, e = 1;
    for (int i = 0; i < q.nitems; i++) { t += (q.item[i] & 7) + 2; fin[q.item[i]] = t; done[q.item[i]] = t + (i + 1 < q.nitems ? 2 : 0); e += 8 + 4 * ((q.item[i] & 7) + 1); }
    for (int k = 0; k < 3 * MAX_STEPS + 6; k++) {
      const int n = k > 0 ? k - (SPARE_N & 1) : 0, r = n % 7, f = (e + (r < 4 ? r : r - 1)) % 12;
      q.oent[k] = (uint8_t)((r == 4 ? 6 : f >= 6 ? f + 2 : f) ^ (((n / 7) & 1) << 3));
    }
  }
  for (int p = 0; p < NP + 2; p++)
    for (int i = 0; i < s.pair[p].nitems; i++) {
      const int it = s.pair[p].item[i];
      for (int n = 0; n < 2 * (it & 7) + 2; n++) {
        bool last = true;
        for (int j = n >> 1; j < 8; j++) { const int o = (it & ~7) + j; if (o != it && fin[o] + LU_MARGIN > fin[it]) last = false; }
        if (last) s.pair[p].lastuse[i] |= (uint16_t)(1 << n);
      }
    }
  for (int j = 0; j < 8; j++) {
    int order[NH], left[4];
    for (int h = 0; h < NH; h++) { int k = h; for (; k > 0 && done[order[k - 1] * 8 + j] < done[h * 8 + j]; k--) order[k] = order[k - 1]; order[k] = h; }
    for (int kq = 0; kq < 4; kq++) {
      left[kq] = SPARE_N == 0 ? 16 : kq < SPARE_N ? 20 - SPARE_N : 16 - SPARE_N;
      for (int nh = 0; nh < 2; nh++) { Sched::Pair& q = s.pair[kq * 16 + nh * 8 + j]; q.otask = (uint8_t)(kq * 16 + nh * 8 + j); q.nsteps = (uint8_t)((left[kq] + 1) / 2); q.ochunk[0][0] = 255; }
    }
    for (int n = 0, kq = 0, run = 0; n < 64; ) {
      if (left[kq] > 0 && run < 2) {
        const int pos = --left[kq] + (SPARE_N & 1);
        for (int nh = 0; nh < 2; nh++) s.pair[kq * 16 + nh * 8 + j].ochunk[pos >> 1][pos & 1] = (uint8_t)(order[n >> 1] * 2 + 1 - (n & 1));
        n++; run++;
      } else { kq = (kq + 1) & 3; run = 0; }
    }
  }
}

}

extern "C" void kernel_launch(void* const* d_in, const int* in_sizes, int n_in, void* d_out, int out_size) {
  (void)in_sizes; (void)n_in; (void)out_size;
  const __nv_bfloat16* x     = (const __nv_bfloat16*)d_in[0];
  const __nv_bfloat16* ckv   = (const __nv_bfloat16*)d_in[1];
  const __nv_bfloat16* w_q   = (const __nv_bfloat16*)d_in[2];
  const __nv_bfloat16* w_uk  = (const __nv_bfloat16*)d_in[3];
  const __nv_bfloat16* w_uv  = (const __nv_bfloat16*)d_in[4];
  const __nv_bfloat16* w_o   = (const __nv_bfloat16*)d_in[5];
  const __nv_bfloat16* w_r   = (const __nv_bfloat16*)d_in[7];
  const __nv_bfloat16* w_g   = (const __nv_bfloat16*)d_in[8];
  const __nv_bfloat16* w_u   = (const __nv_bfloat16*)d_in[9];
  const __nv_bfloat16* w_d   = (const __nv_bfloat16*)d_in[10];
  const __nv_bfloat16* cvec  = (const __nv_bfloat16*)d_in[11];
  const __nv_bfloat16* w_mod = (const __nv_bfloat16*)d_in[12];
  __nv_bfloat16* out = (__nv_bfloat16*)d_out;

  static HostState st;
  if (!st.ready) {
    void* fn = nullptr; cudaDriverEntryPointQueryResult qr;
    cudaGetDriverEntryPoint("cuTensorMapEncodeTiled", &fn, cudaEnableDefault, &qr);
    st.encode = (EncodeFn)fn;
    cudaFuncSetAttribute(k_fused, cudaFuncAttributeMaxDynamicSharedMemorySize, SMEM);
    build_sched(st.sched);
    void *p_kvc, *p_h1, *p_part;
    cudaGetSymbolAddress(&p_kvc, g_kvc); cudaGetSymbolAddress(&p_h1, g_h1); cudaGetSymbolAddress(&p_part, g_part);
    st.sched.kvc = (__nv_bfloat16*)p_kvc; st.sched.h1 = (__nv_bfloat16*)p_h1; st.sched.part = (__nv_bfloat16*)p_part;
    st.ready = true;
  }
  make_2d(st.encode, &st.tmC, ckv, SEQ, DM, 128);
  make_2d(st.encode, &st.tmWq, w_q, DM, NH * DH, 64);
  make_2d(st.encode, &st.tmWk, w_uk, DM, NH * DH, 64);
  make_2d(st.encode, &st.tmWv, w_uv, DM, NH * DH, 64);
  make_3d(st.encode, &st.tmWo, w_o, NH * DH, DM / 64, (size_t)DM * 2, 128);
  make_3d(st.encode, &st.tmWm, w_mod, DM, 6 * DM / 64, (size_t)6 * DM * 2, 128);
  make_ffn(st.encode, &st.tmWg, w_g);
  make_ffn(st.encode, &st.tmWu, w_u);

  k_fused<<<NGRID, 384, SMEM, cudaStreamPerThread>>>(st.tmC, st.tmWq, st.tmWk, st.tmWv, st.tmWo, st.tmWg, st.tmWu, st.tmWm, st.sched,
                                                     x, cvec, w_o, w_r, w_g, w_u, w_d, out);
}
```

```cpp
#include <cuda_runtime.h>
#include <cuda_bf16.h>
#include <cuda.h>
#include <stdint.h>
#include <string.h>
#include <math.h>

namespace {

constexpr int SEQ = 2048, DM = 512, NH = 32, DH = 128, FF = 1792;
constexpr int NCTA = 128, NGRID = 132;

__device__ __align__(128) __nv_bfloat16 g_kvc[192 * SEQ * 64];
__device__ __align__(128) __nv_bfloat16 g_h1[SEQ * DM];
__device__ __align__(128) __nv_bfloat16 g_part[128 * 8 * 4096];
__device__ __align__(16) __nv_bfloat16 g_mod[6 * DM];
constexpr int C_MOD = 0, C_MOD2 = 16, C_H1 = 32, C_KV = 64, C_CTX = 128, C_PART = 384, C_END = C_PART + 32 * 32;
__device__ __align__(128) unsigned int g_cnt[C_END];
__device__ unsigned int g_epoch;
__device__ __align__(128) uint2 g_keys[128][4];
__device__ __align__(16) uint2 g_row[128][2][DM / 2];
__device__ __align__(16) uint2 g_yll[FF / 16][DM];

#define DBG(i)
#define DBGP(i)

__device__ __forceinline__ uint32_t smem_u32(const void* p) { return (uint32_t)__cvta_generic_to_shared(p); }
__device__ __forceinline__ int wg_tid() { int t; asm volatile("mov.u32 %0, %%tid.x;" : "=r"(t)); return t & 127; }
__device__ __forceinline__ uint32_t clk32() { uint32_t c; asm volatile("mov.u32 %0, %%clock;" : "=r"(c)); return c; }
__device__ __forceinline__ void mbar_arrive(uint32_t bar) { asm volatile("mbarrier.arrive.shared::cta.b64 _, [%0];" :: "r"(bar) : "memory"); }
__device__ __forceinline__ uint32_t mapa(uint32_t addr, uint32_t cta) { uint32_t r; asm("mapa.shared::cluster.u32 %0, %1, %2;" : "=r"(r) : "r"(addr), "r"(cta)); return r; }
__device__ __forceinline__ void mbar_arrive_remote_if(uint32_t cluster_addr, bool pred) {
  asm volatile("{\n.reg .pred p;\nsetp.ne.u32 p, %1, 0;\n@p mbarrier.arrive.shared::cluster.b64 _, [%0];\n}" :: "r"(cluster_addr), "r"((uint32_t)pred) : "memory");
}
__device__ __forceinline__ bool mbar_try(uint32_t bar, uint32_t parity) {
  uint32_t done;
  asm volatile("{\n.reg .pred p;\nmbarrier.try_wait.parity.shared::cta.b64 p, [%1], %2;\nselp.u32 %0, 1, 0, p;\n}" : "=r"(done) : "r"(bar), "r"(parity) : "memory");
  return done;
}
__device__ __forceinline__ bool mbar_test2(uint32_t bar, uint32_t parity) {
  uint32_t done;
  asm volatile("{\n.reg .pred p, q;\nmbarrier.test_wait.parity.shared::cta.b64 p, [%1], %2;\nmbarrier.test_wait.parity.shared::cta.b64 q, [%1 + 8], %2;\n"
               "and.pred p, p, q;\nselp.u32 %0, 1, 0, p;\n}" : "=r"(done) : "r"(bar), "r"(parity) : "memory");
  return done;
}
#define WAIT_LIM (1 << 14)
__device__ __forceinline__ void mbar_wait(uint32_t bar, uint32_t parity) {
  #pragma unroll 1
  for (int n = 0; n < WAIT_LIM; n++) { if (mbar_try(bar, parity)) break; }
}
__device__ __forceinline__ unsigned int ld_acquire(const unsigned int* p) {
  unsigned int v; asm volatile("ld.acquire.gpu.global.u32 %0, [%1];" : "=r"(v) : "l"(p) : "memory"); return v;
}
__device__ __forceinline__ unsigned int ld_relaxed(const unsigned int* p) {
  unsigned int v; asm volatile("ld.relaxed.gpu.global.u32 %0, [%1];" : "=r"(v) : "l"(p) : "memory"); return v;
}
__device__ __forceinline__ void wait_count_lazy(int idx, unsigned int target) {
  #pragma unroll 1
  for (int n = 0; n < WAIT_LIM; n++) { if (__all_sync(0xffffffff, (int)(ld_relaxed(&g_cnt[idx]) - target) >= 0)) break; __nanosleep(100); }
  ld_acquire(&g_cnt[idx]);
}
__device__ __forceinline__ uint4 ld_tagged2(const void* p) {
  uint4 v;
  asm volatile("{\n.reg .b64 a, b;\nld.relaxed.gpu.global.v2.u64 {a, b}, [%4];\nmov.b64 {%0, %1}, a;\nmov.b64 {%2, %3}, b;\n}"
    : "=r"(v.x), "=r"(v.y), "=r"(v.z), "=r"(v.w) : "l"(p) : "memory");
  return v;
}
__device__ __forceinline__ uint2 ld_tagged(const void* p) {
  uint2 v; asm volatile("{\n.reg .b64 a;\nld.relaxed.gpu.global.u64 a, [%2];\nmov.b64 {%0, %1}, a;\n}" : "=r"(v.x), "=r"(v.y) : "l"(p) : "memory"); return v;
}
__device__ __forceinline__ void st_tagged2(void* p, uint32_t a, uint32_t b, uint32_t tag) {
  asm volatile("{\n.reg .b64 a, b;\nmov.b64 a, {%1, %3};\nmov.b64 b, {%2, %3};\nst.relaxed.gpu.global.v2.u64 [%0], {a, b};\n}" :: "l"(p), "r"(a), "r"(b), "r"(tag) : "memory");
}
__device__ __forceinline__ void st_tagged(void* p, uint32_t a, uint32_t tag) {
  asm volatile("{\n.reg .b64 a;\nmov.b64 a, {%1, %2};\nst.relaxed.gpu.global.u64 [%0], a;\n}" :: "l"(p), "r"(a), "r"(tag) : "memory");
}
__device__ __forceinline__ void stg_v4(void* p, uint32_t a, uint32_t b, uint32_t c, uint32_t d) {
  asm volatile("st.global.v4.u32 [%0], {%1, %2, %3, %4};" :: "l"(p), "r"(a), "r"(b), "r"(c), "r"(d) : "memory");
}
__device__ __forceinline__ uint4 lds_v4(uint32_t addr) {
  uint4 v; asm volatile("ld.shared.v4.u32 {%0, %1, %2, %3}, [%4];" : "=r"(v.x), "=r"(v.y), "=r"(v.z), "=r"(v.w) : "r"(addr) : "memory"); return v;
}
__device__ __forceinline__ uint32_t lds_u32(uint32_t addr) { uint32_t v; asm volatile("ld.shared.u32 %0, [%1];" : "=r"(v) : "r"(addr) : "memory"); return v; }
__device__ __forceinline__ void sts_v4(uint32_t addr, uint32_t a, uint32_t b, uint32_t c, uint32_t d) {
  asm volatile("st.shared.v4.u32 [%0], {%1, %2, %3, %4};" :: "r"(addr), "r"(a), "r"(b), "r"(c), "r"(d) : "memory");
}
#define ELECT "{\n.reg .pred p;\nelect.sync _|p, 0xffffffff;\n@p "
__device__ __forceinline__ void w_mbar_init(uint32_t bar, uint32_t cnt) { asm volatile(ELECT "mbarrier.init.shared::cta.b64 [%0], %1;\n}" :: "r"(bar), "r"(cnt) : "memory"); }
__device__ __forceinline__ void w_expect_tx(uint32_t bar, uint32_t bytes) { asm volatile(ELECT "mbarrier.arrive.expect_tx.shared::cta.b64 _, [%0], %1;\n}" :: "r"(bar), "r"(bytes) : "memory"); }
__device__ __forceinline__ void w_arrive(uint32_t bar) { asm volatile(ELECT "mbarrier.arrive.shared::cta.b64 _, [%0];\n}" :: "r"(bar) : "memory"); }
__device__ __forceinline__ void tma_load_2d(uint32_t dst, const CUtensorMap* tm, uint32_t bar, int c0, int c1) {
  asm volatile(ELECT "cp.async.bulk.tensor.2d.shared::cluster.global.mbarrier::complete_tx::bytes [%0], [%1, {%3, %4}], [%2];\n}"
    :: "r"(dst), "l"(tm), "r"(bar), "r"(c0), "r"(c1) : "memory");
}
__device__ __forceinline__ void tma_load_2d_mc(uint32_t dst, const CUtensorMap* tm, uint32_t bar, int c0, int c1) {
  asm volatile(ELECT "cp.async.bulk.tensor.2d.shared::cluster.global.mbarrier::complete_tx::bytes.multicast::cluster [%0], [%1, {%3, %4}], [%2], %5;\n}"
    :: "r"(dst), "l"(tm), "r"(bar), "r"(c0), "r"(c1), "h"((uint16_t)3) : "memory");
}
__device__ __forceinline__ void tma_load_3d(uint32_t dst, const CUtensorMap* tm, uint32_t bar, int c0, int c1, int c2) {
  asm volatile(ELECT "cp.async.bulk.tensor.3d.shared::cluster.global.mbarrier::complete_tx::bytes [%0], [%1, {%3, %4, %5}], [%2];\n}"
    :: "r"(dst), "l"(tm), "r"(bar), "r"(c0), "r"(c1), "r"(c2) : "memory");
}
__device__ __forceinline__ void tma_load_3d_mc(uint32_t dst, const CUtensorMap* tm, uint32_t bar, int c0, int c1, int c2) {
  asm volatile(ELECT "cp.async.bulk.tensor.3d.shared::cluster.global.mbarrier::complete_tx::bytes.multicast::cluster [%0], [%1, {%3, %4, %5}], [%2], %6;\n}"
    :: "r"(dst), "l"(tm), "r"(bar), "r"(c0), "r"(c1), "r"(c2), "h"((uint16_t)3) : "memory");
}
__device__ __forceinline__ void bulk_load_mc(uint32_t dst, const void* src, uint32_t bar, bool ef) {
  if (ef) {
    uint64_t pol; asm("createpolicy.fractional.L2::evict_first.b64 %0, 1.0;" : "=l"(pol));
    asm volatile(ELECT "cp.async.bulk.shared::cluster.global.mbarrier::complete_tx::bytes.multicast::cluster.L2::cache_hint [%0], [%1], 16384, [%2], %3, %4;\n}"
      :: "r"(dst), "l"(src), "r"(bar), "h"((uint16_t)3), "l"(pol) : "memory");
  } else
    asm volatile(ELECT "cp.async.bulk.shared::cluster.global.mbarrier::complete_tx::bytes.multicast::cluster [%0], [%1], 16384, [%2], %3;\n}"
      :: "r"(dst), "l"(src), "r"(bar), "h"((uint16_t)3) : "memory");
}
__device__ __forceinline__ void bulk_load(uint32_t dst, const void* src, uint32_t bytes, uint32_t bar) {
  asm volatile(ELECT "cp.async.bulk.shared::cluster.global.mbarrier::complete_tx::bytes [%0], [%1], %2, [%3];\n}" :: "r"(dst), "l"(src), "r"(bytes), "r"(bar) : "memory");
}
__device__ __forceinline__ void tma_prefetch_2d(const CUtensorMap* tm, int c0, int c1) {
  asm volatile(ELECT "cp.async.bulk.prefetch.tensor.2d.L2.global [%0, {%1, %2}];\n}" :: "l"(tm), "r"(c0), "r"(c1) : "memory");
}
__device__ __forceinline__ void bulk_prefetch(const void* p, uint32_t bytes) {
  asm volatile(ELECT "cp.async.bulk.prefetch.L2.global [%0], %1;\n}" :: "l"(p), "r"(bytes) : "memory");
}
__device__ __forceinline__ void red_release(int idx) { asm volatile("red.release.gpu.global.add.u32 [%0], 1;" :: "l"(&g_cnt[idx]) : "memory"); }
__device__ __forceinline__ void prefetch_tmap(const CUtensorMap* tm) { asm volatile("prefetch.tensormap [%0];" :: "l"(tm) : "memory"); }
__device__ __forceinline__ void bar_sync(int id, int n) { asm volatile("bar.sync %0, %1;" :: "r"(id), "r"(n) : "memory"); }
__device__ __forceinline__ void bar_arrive(int id, int n) { asm volatile("bar.arrive %0, %1;" :: "r"(id), "r"(n) : "memory"); }
__device__ __forceinline__ void fence_async_smem() { asm volatile("fence.proxy.async.shared::cta;" ::: "memory"); }
__device__ __forceinline__ void fence_async_global() { asm volatile("fence.proxy.async.global;" ::: "memory"); }
__device__ __forceinline__ void fence_mbar_init() { asm volatile("fence.mbarrier_init.release.cluster;" ::: "memory"); }
__device__ __forceinline__ void cluster_arrive() { asm volatile("barrier.cluster.arrive.relaxed.aligned;" ::: "memory"); }
__device__ __forceinline__ void cluster_wait() { asm volatile("barrier.cluster.wait.aligned;" ::: "memory"); }
__device__ __forceinline__ uint32_t cluster_ctarank() { uint32_t r; asm volatile("mov.u32 %0, %%cluster_ctarank;" : "=r"(r)); return r; }
__device__ __forceinline__ void wgmma_fence() { asm volatile("wgmma.fence.sync.aligned;" ::: "memory"); }
__device__ __forceinline__ void wgmma_commit() { asm volatile("wgmma.commit_group.sync.aligned;" ::: "memory"); }
template<int N> __device__ __forceinline__ void wgmma_wait() { asm volatile("wgmma.wait_group.sync.aligned %0;" :: "n"(N) : "memory"); }
__device__ __forceinline__ float ex2(float x) { float y; asm("ex2.approx.ftz.f32 %0, %1;" : "=f"(y) : "f"(x)); return y; }
__device__ __forceinline__ float rcp_fast(float x) { float y; asm("rcp.approx.ftz.f32 %0, %1;" : "=f"(y) : "f"(x)); return y; }
__device__ __forceinline__ uint32_t pack_bf16(float lo, float hi) { uint32_t r; asm("cvt.rn.bf16x2.f32 %0, %1, %2;" : "=r"(r) : "f"(hi), "f"(lo)); return r; }
__device__ __forceinline__ float rbf(float x) { return __uint_as_float(pack_bf16(0.f, x)); }
__device__ __forceinline__ float bf_lo(uint32_t v) { return __uint_as_float(v << 16); }
__device__ __forceinline__ float bf_hi(uint32_t v) { return __uint_as_float(v & 0xffff0000u); }
__device__ __forceinline__ uint32_t add2(uint32_t a, uint32_t b) { uint32_t r; asm("add.rn.bf16x2 %0, %1, %2;" : "=r"(r) : "r"(a), "r"(b)); return r; }
__device__ __forceinline__ uint32_t fma2(uint32_t a, uint32_t b, uint32_t c) { uint32_t r; asm("fma.rn.bf16x2 %0, %1, %2, %3;" : "=r"(r) : "r"(a), "r"(b), "r"(c)); return r; }
__device__ __forceinline__ uint4 ldsm_x4_t(uint32_t addr) {
  uint4 v; asm volatile("ldmatrix.sync.aligned.m8n8.x4.trans.shared.b16 {%0, %1, %2, %3}, [%4];" : "=r"(v.x), "=r"(v.y), "=r"(v.z), "=r"(v.w) : "r"(addr) : "memory"); return v;
}
__device__ __forceinline__ uint4 ldsm_x4(uint32_t addr) {
  uint4 v; asm volatile("ldmatrix.sync.aligned.m8n8.x4.shared.b16 {%0, %1, %2, %3}, [%4];" : "=r"(v.x), "=r"(v.y), "=r"(v.z), "=r"(v.w) : "r"(addr) : "memory"); return v;
}
__device__ __forceinline__ void mma16816(float (&c)[4], const uint4& a, uint32_t b0, uint32_t b1) {
  asm("mma.sync.aligned.m16n8k16.row.col.f32.bf16.bf16.f32 {%0, %1, %2, %3}, {%4, %5, %6, %7}, {%8, %9}, {%0, %1, %2, %3};"
    : "+f"(c[0]), "+f"(c[1]), "+f"(c[2]), "+f"(c[3]) : "r"(a.x), "r"(a.y), "r"(a.z), "r"(a.w), "r"(b0), "r"(b1));
}
template<int N> __device__ __forceinline__ void fence_regs(float (&a)[N]) {
  #pragma unroll
  for (int i = 0; i < N; i++) asm volatile("" : "+f"(a[i]) :: "memory");
}
template<int N> __device__ __forceinline__ void fence_regs_u(uint32_t (&a)[N]) {
  #pragma unroll
  for (int i = 0; i < N; i++) asm volatile("" : "+r"(a[i]) :: "memory");
}
constexpr uint32_t SW128 = 0x40000040u, SW64 = 0x80000020u;
__device__ __forceinline__ uint32_t desc_lo(uint32_t addr, uint32_t lbo) { return ((addr & 0x3FFFF) >> 4) | ((lbo >> 4) << 16); }

template<int TB, int OA, int OB, uint32_t HA, uint32_t HB> __device__ __forceinline__ void wgmma_ss_n128(float (&d)[64], uint32_t da, uint32_t db, int sd) {
  asm volatile("{\n.reg .pred p;\n.reg .b32 ta, tb;\n.reg .b64 da, db;\nsetp.ne.b32 p, %66, 0;\nadd.u32 ta, %64, %68;\nadd.u32 tb, %65, %69;\nmov.b64 da, {ta, %70};\nmov.b64 db, {tb, %71};\n"
    "wgmma.mma_async.sync.aligned.m64n128k16.f32.bf16.bf16 "
    "{%0, %1, %2, %3, %4, %5, %6, %7, %8, %9, %10, %11, %12, %13, %14, %15, %16, %17, %18, %19, %20, %21, %22, %23, %24, %25, %26, %27, %28, %29, %30, %31, %32, %33, %34, %35, %36, %37, %38, %39, %40, %41, %42, %43, %44, %45, %46, %47, %48, %49, %50, %51, %52, %53, %54, %55, %56, %57, %58, %59, %60, %61, %62, %63}, da, db, p, 1, 1, 0, %67;\n}\n"
    : "+f"(d[0]), "+f"(d[1]), "+f"(d[2]), "+f"(d[3]), "+f"(d[4]), "+f"(d[5]), "+f"(d[6]), "+f"(d[7]), "+f"(d[8]), "+f"(d[9]), "+f"(d[10]), "+f"(d[11]), "+f"(d[12]), "+f"(d[13]), "+f"(d[14]), "+f"(d[15]), "+f"(d[16]), "+f"(d[17]), "+f"(d[18]), "+f"(d[19]), "+f"(d[20]), "+f"(d[21]), "+f"(d[22]), "+f"(d[23]), "+f"(d[24]), "+f"(d[25]), "+f"(d[26]), "+f"(d[27]), "+f"(d[28]), "+f"(d[29]), "+f"(d[30]), "+f"(d[31]), "+f"(d[32]), "+f"(d[33]), "+f"(d[34]), "+f"(d[35]), "+f"(d[36]), "+f"(d[37]), "+f"(d[38]), "+f"(d[39]), "+f"(d[40]), "+f"(d[41]), "+f"(d[42]), "+f"(d[43]), "+f"(d[44]), "+f"(d[45]), "+f"(d[46]), "+f"(d[47]), "+f"(d[48]), "+f"(d[49]), "+f"(d[50]), "+f"(d[51]), "+f"(d[52]), "+f"(d[53]), "+f"(d[54]), "+f"(d[55]), "+f"(d[56]), "+f"(d[57]), "+f"(d[58]), "+f"(d[59]), "+f"(d[60]), "+f"(d[61]), "+f"(d[62]), "+f"(d[63])
    : "r"(da), "r"(db), "r"(sd), "n"(TB), "n"(OA), "n"(OB), "n"(HA), "n"(HB));
}
template<int TB, int OB, uint32_t HB> __device__ __forceinline__ void wgmma_rs_n128(float (&d)[64], uint32_t a0, uint32_t a1, uint32_t a2, uint32_t a3, uint32_t db, int sd) {
  asm volatile("{\n.reg .pred p;\n.reg .b32 tb;\n.reg .b64 db;\nsetp.ne.b32 p, %69, 0;\nadd.u32 tb, %68, %71;\nmov.b64 db, {tb, %72};\n"
    "wgmma.mma_async.sync.aligned.m64n128k16.f32.bf16.bf16 "
    "{%0, %1, %2, %3, %4, %5, %6, %7, %8, %9, %10, %11, %12, %13, %14, %15, %16, %17, %18, %19, %20, %21, %22, %23, %24, %25, %26, %27, %28, %29, %30, %31, %32, %33, %34, %35, %36, %37, %38, %39, %40, %41, %42, %43, %44, %45, %46, %47, %48, %49, %50, %51, %52, %53, %54, %55, %56, %57, %58, %59, %60, %61, %62, %63}, {%64,%65,%66,%67}, db, p, 1, 1, %70;\n}\n"
    : "+f"(d[0]), "+f"(d[1]), "+f"(d[2]), "+f"(d[3]), "+f"(d[4]), "+f"(d[5]), "+f"(d[6]), "+f"(d[7]), "+f"(d[8]), "+f"(d[9]), "+f"(d[10]), "+f"(d[11]), "+f"(d[12]), "+f"(d[13]), "+f"(d[14]), "+f"(d[15]), "+f"(d[16]), "+f"(d[17]), "+f"(d[18]), "+f"(d[19]), "+f"(d[20]), "+f"(d[21]), "+f"(d[22]), "+f"(d[23]), "+f"(d[24]), "+f"(d[25]), "+f"(d[26]), "+f"(d[27]), "+f"(d[28]), "+f"(d[29]), "+f"(d[30]), "+f"(d[31]), "+f"(d[32]), "+f"(d[33]), "+f"(d[34]), "+f"(d[35]), "+f"(d[36]), "+f"(d[37]), "+f"(d[38]), "+f"(d[39]), "+f"(d[40]), "+f"(d[41]), "+f"(d[42]), "+f"(d[43]), "+f"(d[44]), "+f"(d[45]), "+f"(d[46]), "+f"(d[47]), "+f"(d[48]), "+f"(d[49]), "+f"(d[50]), "+f"(d[51]), "+f"(d[52]), "+f"(d[53]), "+f"(d[54]), "+f"(d[55]), "+f"(d[56]), "+f"(d[57]), "+f"(d[58]), "+f"(d[59]), "+f"(d[60]), "+f"(d[61]), "+f"(d[62]), "+f"(d[63])
    : "r"(a0), "r"(a1), "r"(a2), "r"(a3), "r"(db), "r"(sd), "n"(TB), "n"(OB), "n"(HB));
}
template<int TB, int OA, int OB, uint32_t HA, uint32_t HB> __device__ __forceinline__ void wgmma_ss_n64(float (&d)[32], uint32_t da, uint32_t db, int sd) {
  asm volatile("{\n.reg .pred p;\n.reg .b32 ta, tb;\n.reg .b64 da, db;\nsetp.ne.b32 p, %34, 0;\nadd.u32 ta, %32, %36;\nadd.u32 tb, %33, %37;\nmov.b64 da, {ta, %38};\nmov.b64 db, {tb, %39};\n"
    "wgmma.mma_async.sync.aligned.m64n64k16.f32.bf16.bf16 "
    "{%0, %1, %2, %3, %4, %5, %6, %7, %8, %9, %10, %11, %12, %13, %14, %15, %16, %17, %18, %19, %20, %21, %22, %23, %24, %25, %26, %27, %28, %29, %30, %31}, da, db, p, 1, 1, 0, %35;\n}\n"
    : "+f"(d[0]), "+f"(d[1]), "+f"(d[2]), "+f"(d[3]), "+f"(d[4]), "+f"(d[5]), "+f"(d[6]), "+f"(d[7]), "+f"(d[8]), "+f"(d[9]), "+f"(d[10]), "+f"(d[11]), "+f"(d[12]), "+f"(d[13]), "+f"(d[14]), "+f"(d[15]), "+f"(d[16]), "+f"(d[17]), "+f"(d[18]), "+f"(d[19]), "+f"(d[20]), "+f"(d[21]), "+f"(d[22]), "+f"(d[23]), "+f"(d[24]), "+f"(d[25]), "+f"(d[26]), "+f"(d[27]), "+f"(d[28]), "+f"(d[29]), "+f"(d[30]), "+f"(d[31])
    : "r"(da), "r"(db), "r"(sd), "n"(TB), "n"(OA), "n"(OB), "n"(HA), "n"(HB));
}
template<int TB, int OA, int OB, uint32_t HA, uint32_t HB> __device__ __forceinline__ void wgmma_ss_n128_new(float (&d)[64], uint32_t da, uint32_t db) {
  asm volatile("{\n.reg .pred p;\n.reg .b32 ta, tb;\n.reg .b64 da, db;\nsetp.ne.b32 p, %66, 0;\nadd.u32 ta, %64, %68;\nadd.u32 tb, %65, %69;\nmov.b64 da, {ta, %70};\nmov.b64 db, {tb, %71};\n"
    "wgmma.mma_async.sync.aligned.m64n128k16.f32.bf16.bf16 "
    "{%0, %1, %2, %3, %4, %5, %6, %7, %8, %9, %10, %11, %12, %13, %14, %15, %16, %17, %18, %19, %20, %21, %22, %23, %24, %25, %26, %27, %28, %29, %30, %31, %32, %33, %34, %35, %36, %37, %38, %39, %40, %41, %42, %43, %44, %45, %46, %47, %48, %49, %50, %51, %52, %53, %54, %55, %56, %57, %58, %59, %60, %61, %62, %63}, da, db, p, 1, 1, 0, %67;\n}\n"
    : "=f"(d[0]), "=f"(d[1]), "=f"(d[2]), "=f"(d[3]), "=f"(d[4]), "=f"(d[5]), "=f"(d[6]), "=f"(d[7]), "=f"(d[8]), "=f"(d[9]), "=f"(d[10]), "=f"(d[11]), "=f"(d[12]), "=f"(d[13]), "=f"(d[14]), "=f"(d[15]), "=f"(d[16]), "=f"(d[17]), "=f"(d[18]), "=f"(d[19]), "=f"(d[20]), "=f"(d[21]), "=f"(d[22]), "=f"(d[23]), "=f"(d[24]), "=f"(d[25]), "=f"(d[26]), "=f"(d[27]), "=f"(d[28]), "=f"(d[29]), "=f"(d[30]), "=f"(d[31]), "=f"(d[32]), "=f"(d[33]), "=f"(d[34]), "=f"(d[35]), "=f"(d[36]), "=f"(d[37]), "=f"(d[38]), "=f"(d[39]), "=f"(d[40]), "=f"(d[41]), "=f"(d[42]), "=f"(d[43]), "=f"(d[44]), "=f"(d[45]), "=f"(d[46]), "=f"(d[47]), "=f"(d[48]), "=f"(d[49]), "=f"(d[50]), "=f"(d[51]), "=f"(d[52]), "=f"(d[53]), "=f"(d[54]), "=f"(d[55]), "=f"(d[56]), "=f"(d[57]), "=f"(d[58]), "=f"(d[59]), "=f"(d[60]), "=f"(d[61]), "=f"(d[62]), "=f"(d[63])
    : "r"(da), "r"(db), "n"(0), "n"(TB), "n"(OA), "n"(OB), "n"(HA), "n"(HB));
}
template<int TB, int OA, int OB, uint32_t HA, uint32_t HB> __device__ __forceinline__ void wgmma_ss_n64_new(float (&d)[32], uint32_t da, uint32_t db) {
  asm volatile("{\n.reg .pred p;\n.reg .b32 ta, tb;\n.reg .b64 da, db;\nsetp.ne.b32 p, %34, 0;\nadd.u32 ta, %32, %36;\nadd.u32 tb, %33, %37;\nmov.b64 da, {ta, %38};\nmov.b64 db, {tb, %39};\n"
    "wgmma.mma_async.sync.aligned.m64n64k16.f32.bf16.bf16 "
    "{%0, %1, %2, %3, %4, %5, %6, %7, %8, %9, %10, %11, %12, %13, %14, %15, %16, %17, %18, %19, %20, %21, %22, %23, %24, %25, %26, %27, %28, %29, %30, %31}, da, db, p, 1, 1, 0, %35;\n}\n"
    : "=f"(d[0]), "=f"(d[1]), "=f"(d[2]), "=f"(d[3]), "=f"(d[4]), "=f"(d[5]), "=f"(d[6]), "=f"(d[7]), "=f"(d[8]), "=f"(d[9]), "=f"(d[10]), "=f"(d[11]), "=f"(d[12]), "=f"(d[13]), "=f"(d[14]), "=f"(d[15]), "=f"(d[16]), "=f"(d[17]), "=f"(d[18]), "=f"(d[19]), "=f"(d[20]), "=f"(d[21]), "=f"(d[22]), "=f"(d[23]), "=f"(d[24]), "=f"(d[25]), "=f"(d[26]), "=f"(d[27]), "=f"(d[28]), "=f"(d[29]), "=f"(d[30]), "=f"(d[31])
    : "r"(da), "r"(db), "n"(0), "n"(TB), "n"(OA), "n"(OB), "n"(HA), "n"(HB));
}
template<int OA, int OB = 0, uint32_t HA = SW128> __device__ __forceinline__ void kblock_n128(float (&d)[64], uint32_t da, uint32_t db, int sd) {
  constexpr int H = HA == SW128 ? 4 : 512;
  wgmma_ss_n128<1, OA, OB, HA, SW128>(d, da, db, sd); wgmma_ss_n128<1, OA + 2, OB + 128, HA, SW128>(d, da, db, 1);
  wgmma_ss_n128<1, OA + H, OB + 256, HA, SW128>(d, da, db, 1); wgmma_ss_n128<1, OA + H + 2, OB + 384, HA, SW128>(d, da, db, 1);
}

__device__ __forceinline__ float quad_sum(float v) {
  v += __shfl_xor_sync(0xffffffff, v, 1);
  v += __shfl_xor_sync(0xffffffff, v, 2);
  return v;
}
struct Row { uint32_t v[8]; };
template<class F> __device__ __forceinline__ Row load_row(const __nv_bfloat16* p, int lane, F ld) {
  const uint4 a = ld(reinterpret_cast<const uint4*>(p) + lane), b = ld(reinterpret_cast<const uint4*>(p) + 32 + lane);
  return Row{{a.x, a.y, a.z, a.w, b.x, b.y, b.z, b.w}};
}
__device__ __forceinline__ Row ldg_row(const __nv_bfloat16* p, int lane) { return load_row(p, lane, [](const uint4* q) { return __ldg(q); }); }
__device__ __forceinline__ Row ldca_row(const __nv_bfloat16* p, int lane) { return load_row(p, lane, [](const uint4* q) { return __ldca(q); }); }
__device__ __forceinline__ Row lds_row(uint32_t addr, int lane) {
  const uint4 a = lds_v4(addr + lane * 16), b = lds_v4(addr + 512 + lane * 16);
  return Row{{a.x, a.y, a.z, a.w, b.x, b.y, b.z, b.w}};
}
__device__ __forceinline__ void store_row(__nv_bfloat16* p, int lane, const Row& r) {
  stg_v4(p + lane * 8, r.v[0], r.v[1], r.v[2], r.v[3]); stg_v4(p + 256 + lane * 8, r.v[4], r.v[5], r.v[6], r.v[7]);
}
__device__ __forceinline__ Row fma_row(const Row& a, const Row& b, const Row& c) {
  Row r;
  #pragma unroll
  for (int i = 0; i < 8; i++) r.v[i] = fma2(a.v[i], b.v[i], c.v[i]);
  return r;
}
__device__ __forceinline__ Row add_row(const Row& a, const Row& b) {
  Row r;
  #pragma unroll
  for (int i = 0; i < 8; i++) r.v[i] = add2(a.v[i], b.v[i]);
  return r;
}
__device__ __forceinline__ Row one_plus(const Row& a) {
  Row r;
  #pragma unroll
  for (int i = 0; i < 8; i++) r.v[i] = add2(a.v[i], 0x3f803f80u);
  return r;
}
__device__ __forceinline__ float row_at(const Row& x, int i) { return (i & 1) ? bf_hi(x.v[i >> 1]) : bf_lo(x.v[i >> 1]); }
template<int N> __device__ __forceinline__ void warp_sums(float (&s)[N]) {
  #pragma unroll
  for (int o = 16; o > 0; o >>= 1) {
    #pragma unroll
    for (int k = 0; k < N; k++) s[k] += __shfl_xor_sync(0xffffffff, s[k], o);
  }
}
__device__ __forceinline__ void ln_stats(float& s1, float& s2) {
  s1 *= 1.f / DM;
  asm("rsqrt.approx.ftz.f32 %0, %1;" : "=f"(s2) : "f"(fmaxf(fmaf(-s1, s1, s2 * (1.f / DM)), 0.f) + 1e-5f));
}
__device__ __forceinline__ Row ln_apply(const Row& x, float mean, float f) {
  Row n;
  const float o = -mean * f;
  #pragma unroll
  for (int i = 0; i < 8; i++) n.v[i] = pack_bf16(fmaf(bf_lo(x.v[i]), f, o), fmaf(bf_hi(x.v[i]), f, o));
  return n;
}

constexpr int SM_Q = 6 * 32768, SM_BAR = 7 * 32768, SM_MAIL = SM_BAR + 640, SM_RED = SM_MAIL + 128, SM_H2 = SM_RED + 1024, SM_KEY = SM_H2 + 1024, SMEM = SM_KEY + 128;
constexpr int B_AF = 0, B_WF = 64, B_RF = 112, B_WE = 168, B_RE = 216, B_PUB = 272, B_RDY = 496;
constexpr int R_MOD = B_RDY, R_H1 = B_RDY + 8, R_ITEM = B_RDY + 16, R_NEAR = B_RDY + 48, R_CTX = B_RDY + 64;
constexpr int R_KEY = B_AF + 8, R_PART = B_AF + 32;
constexpr int NPUB = 14;
__device__ __forceinline__ uint32_t k_addrA(int kb) { return ((0x6310u >> ((kb >> 1) * 4)) & 15u) * 32768u + (kb & 1) * 16384u; }
__device__ __forceinline__ uint32_t k_addrW(int s) { return ((0x254u >> ((s >> 1) * 4)) & 15u) * 32768u + (s & 1) * 16384u; }

#define KORDER 0x3201
constexpr int KHEAD0 = ((KORDER >> 12) & 3) * 8;
constexpr int MAX_ITEMS = 4;
constexpr int MAX_STEPS = 10;
struct Sched {
  __nv_bfloat16 *kvc, *h1, *part;
  struct Pair {
    uint8_t oent[3 * MAX_STEPS + 6];
    uint16_t lastuse[MAX_ITEMS];
    uint8_t khead[4];
    uint8_t nitems, item[MAX_ITEMS];
    uint8_t otask, nsteps;
    uint8_t ochunk[MAX_STEPS][2];
  } pair[NGRID / 2];
};

__device__ __forceinline__ int ring_add(int e, int n) { e += n; return e >= 12 ? e - 12 : e; }
__device__ __forceinline__ int ring_slot(int e) { return e >= 6 ? e - 6 : e; }
__device__ __forceinline__ void ring_wait_full(uint32_t bars, int e) { mbar_wait(bars + B_RF + 8 * ring_slot(e), e >= 6); }

__device__ __forceinline__ void o_wait_full(uint32_t bars, uint32_t v) { mbar_wait(bars + B_RF + 8 * (v & 7), v >> 3); }

struct Ctx {
  uint32_t base, bars;
  uint32_t rel;
  bool rel1;
  int w, nev;
  const Sched* sched;
  uint32_t tr;
};
#define TR(id)
__device__ __forceinline__ void slot_release(const Ctx& x, int s, bool twice) {
  mbar_arrive_remote_if(x.rel + B_RE + 8 * s, twice ? (wg_tid() & 31) == 0 : x.rel1);
}
__device__ __forceinline__ void ring_release(const Ctx& x, int e, bool twice) { slot_release(x, ring_slot(e), twice); }
__device__ __forceinline__ void publish(Ctx& x, int idx) {
  const uint32_t n = x.w * NPUB + x.nev;
  const int t = wg_tid();
  if (t == 0) asm volatile("st.shared.u32 [%0], %1;" :: "r"(x.base + SM_MAIL + 4 * n), "r"(idx) : "memory");
  __syncwarp();
  if ((t & 31) == 0) mbar_arrive(x.bars + B_PUB + 8 * n);
  x.nev++;
}

template<int KK = 0> __device__ __forceinline__ void issue_qk(float (&S)[64], uint32_t dq, uint32_t dk) {
  constexpr int off = (KK >> 1) * 512 + (KK & 1) * 2;
  if constexpr (KK == 0) wgmma_ss_n128_new<0, 0, 0, SW64, SW64>(S, dq, dk); else wgmma_ss_n128<0, off, off, SW64, SW64>(S, dq, dk, 1);
  if constexpr (KK < 7) issue_qk<KK + 1>(S, dq, dk);
}
template<int KK = 0> __device__ __forceinline__ void issue_qk_half(float (&S)[32], uint32_t dq, uint32_t dk) {
  constexpr int off = (KK >> 1) * 512 + (KK & 1) * 2;
  if constexpr (KK == 0) wgmma_ss_n64_new<0, 0, 256, SW64, SW64>(S, dq, dk); else wgmma_ss_n64<0, off, off + 256, SW64, SW64>(S, dq, dk, 1);
  if constexpr (KK < 7) issue_qk_half<KK + 1>(S, dq, dk);
}
template<int NK, int KK = 0>
__device__ __forceinline__ void issue_pv(float (&O)[64], uint32_t (&P)[32], uint32_t dv, int accumulate) {
  wgmma_rs_n128<1, (KK + 8 - NK) * 64, SW64>(O, P[4*KK], P[4*KK+1], P[4*KK+2], P[4*KK+3], dv, accumulate);
  if constexpr (KK + 1 < NK) issue_pv<NK, KK + 1>(O, P, dv, 1);
}
template<int K0, int K1>
__device__ __forceinline__ void exp_pack(const float (&S)[64], uint32_t (&D)[32], float& s0, float& s1) {
  #pragma unroll
  for (int k = K0; k < K1; k++) {
    const float e0 = ex2(S[2*k]), e1 = ex2(S[2*k+1]);
    D[k] = pack_bf16(e0, e1);
    if (k & 1) s1 += e0 + e1; else s0 += e0 + e1;
  }
}
__device__ __forceinline__ int diag_limit() { const int t = wg_tid(); return 16 * (t >> 5) + ((t & 31) >> 2) - 2 * (t & 3); }
__device__ __forceinline__ void exp_pack_diag(const float (&S)[64], uint32_t (&D)[32], int t, float& s0, float& s1) {
  #pragma unroll
  for (int k = 0; k < 16; k++) {
    const int c = 8 * (k >> 1) - 8 * (k & 1);
    const float e0 = ex2((c <= t) ? S[2*k] : -INFINITY), e1 = ex2((c + 1 <= t) ? S[2*k+1] : -INFINITY);
    D[k] = pack_bf16(e0, e1);
    if (k & 1) s1 += e0 + e1; else s0 += e0 + e1;
  }
}
constexpr float SUM_HI = 1.8446744073709552e19f;
constexpr float SUM_LO = 5.421010862427522e-20f;

__device__ __forceinline__ void classic_tile(const float (&S)[64], uint32_t (&P)[32], bool fresh, bool half, bool was_classic, volatile float* mc,
                                             float& l0, float& l1, float& s0, float& s1, float& sc0, float& sc1) {
  const int tmask = diag_limit();
  float4 t[16];
  #pragma unroll
  for (int j = 0; j < 16; j++) t[j] = make_float4(S[4*j], S[4*j+1], S[4*j+2], S[4*j+3]);
  float mx0 = -INFINITY, mx1 = -INFINITY;
  #pragma unroll 1
  for (int j = 0; j < 16; j++) {
    float4 v = t[j];
    const int lim = !fresh ? 1000 : j < 8 ? tmask - 8 * j : half ? -1000 : 1000;
    v.x = 0 <= lim ? v.x : -INFINITY; v.y = 1 <= lim ? v.y : -INFINITY; v.z = -8 <= lim ? v.z : -INFINITY; v.w = -7 <= lim ? v.w : -INFINITY;
    t[j] = v;
    mx0 = fmaxf(mx0, fmaxf(v.x, v.y)); mx1 = fmaxf(mx1, fmaxf(v.z, v.w));
  }
  mx0 = fmaxf(mx0, __shfl_xor_sync(0xffffffff, mx0, 1));
  mx1 = fmaxf(mx1, __shfl_xor_sync(0xffffffff, mx1, 1));
  mx0 = fmaxf(mx0, __shfl_xor_sync(0xffffffff, mx0, 2));
  mx1 = fmaxf(mx1, __shfl_xor_sync(0xffffffff, mx1, 2));
  const float mc0 = was_classic ? mc[0] : 0.f, mc1 = was_classic ? mc[1] : 0.f;
  const float n0 = fresh ? -mx0 : fminf(mc0, -mx0), n1 = fresh ? -mx1 : fminf(mc1, -mx1);
  sc0 = ex2(n0 - mc0); sc1 = ex2(n1 - mc1);
  mc[0] = n0; mc[1] = n1;
  s0 = 0.f; s1 = 0.f;
  #pragma unroll 1
  for (int j = 0; j < 16; j++) {
    const float4 v = t[j];
    const float e0 = ex2(v.x + n0), e1 = ex2(v.y + n0), e2 = ex2(v.z + n1), e3 = ex2(v.w + n1);
    s0 += e0 + e1; s1 += e2 + e3;
    reinterpret_cast<uint2*>(t)[j] = make_uint2(pack_bf16(e0, e1), pack_bf16(e2, e3));
  }
  #pragma unroll
  for (int j = 0; j < 8; j++) { P[4*j] = __float_as_uint(t[j].x); P[4*j+1] = __float_as_uint(t[j].y); P[4*j+2] = __float_as_uint(t[j].z); P[4*j+3] = __float_as_uint(t[j].w); }
  if (!fresh) { l0 *= sc0; l1 *= sc1; }
}
__device__ __forceinline__ void pack_tile(const float (&A)[64], uint32_t (&D)[32], float f0, float f1) {
  #pragma unroll
  for (int j = 0; j < 16; j++) {
    D[8 * (j >> 2) + (j & 3)] = pack_bf16(A[4*j] * f0, A[4*j+1] * f0);
    D[8 * (j >> 2) + 4 + (j & 3)] = pack_bf16(A[4*j+2] * f1, A[4*j+3] * f1);
  }
}
__device__ __forceinline__ int piece0(int t) { return ((t >> 5) * 16 + ((t & 31) >> 2)) * 32 + (((t ^ (t >> 3)) & 3) << 3); }
__device__ __forceinline__ void store_tile(__nv_bfloat16* p, const uint32_t (&D)[32]) {
  #pragma unroll
  for (int i = 0; i < 8; i++) stg_v4(p + (i >> 2) * (SEQ * 64) + ((i >> 1) & 1) * 4096 + (i & 1) * 256, D[4*i], D[4*i+1], D[4*i+2], D[4*i+3]);
}

enum : int { PV_ACC = 0, PV_ZERO = 1, PV_HALF = 2, PV_NONE = 3 };
struct Att {
  float l0, l1, i0, i1;
  bool classic;
  volatile float* mc;
};
__device__ __forceinline__ void store_ctx(Ctx& x, int code, const uint32_t (&D)[32]) {
  store_tile(x.sched->kvc + ((size_t)(128 + (code >> 5) * 2) * SEQ + ((code >> 1) & 15) * 128) * 64 + (code & 1) * 2048 + piece0(wg_tid()), D);
  publish(x, C_CTX + (code >> 2));
}
__device__ __forceinline__ __nv_bfloat16* kv_tile(const Ctx& x, int code) {
  return x.sched->kvc + ((size_t)(x.w * 64 + (code >> 4) * 2) * SEQ + (code & 15) * 128) * 64 + piece0(wg_tid());
}
#define V_AT 3
#define V_AT2 7
#define MERGE1 1
#define NO_CLASSIC 0
__device__ __forceinline__ void q_proj(Ctx& x, int& e, bool isY, const uint32_t (&PA)[32], const uint32_t (&PB)[32], int vtile, bool first, bool dbg = false) {
  float S[64];
  if (isY) bar_sync(1 + x.w, 256);
  if (dbg) DBG(80);
  TR(1);
  #pragma unroll 1
  for (int kb = 0; kb < 8; kb++) {
    if (kb > 0 || first) ring_wait_full(x.bars, e);
    if (dbg) DBG(81 + kb);
    TR(2);
    const uint32_t da = desc_lo(x.base + x.w * 8192, 16) + ring_slot(e) * 2048, dw = desc_lo(x.base + 16384, 8192) + ring_slot(e) * 2048;
    wgmma_fence();
    kblock_n128<0>(S, da, dw, kb != 0);
    wgmma_commit();
    if (kb == 7 && !isY) bar_arrive(1 + (x.w ^ 1), 256);
    if (kb > 0) { wgmma_wait<1>(); ring_release(x, ring_add(e, 11), false); }
    if (kb == V_AT && vtile >= 0) store_tile(kv_tile(x, vtile) + 2048, PA);
    if (kb == V_AT2 && vtile >= 0) { store_tile(kv_tile(x, vtile), PB); publish(x, C_KV + (vtile >> 4)); }
    e = ring_add(e, 1);
  }
  wgmma_wait<0>();
  fence_regs(S);
  if (dbg) DBG(89);
  TR(3);
  ring_release(x, ring_add(e, 11), false);
  const uint32_t qa = x.base + SM_Q + x.w * 4096 + piece0(wg_tid()) * 2;
  #pragma unroll
  for (int i = 0; i < 8; i++) {
    const int j = 4 * (i >> 1), o = 2 * (i & 1);
    sts_v4(qa + (i >> 1) * 8192 + (i & 1) * 512,
           pack_bf16(S[4*j+o], S[4*j+o+1]), pack_bf16(S[4*j+4+o], S[4*j+5+o]), pack_bf16(S[4*j+8+o], S[4*j+9+o]), pack_bf16(S[4*j+12+o], S[4*j+13+o]));
  }
  fence_async_smem();
  if (dbg) DBG(90);
  TR(4);
  ring_wait_full(x.bars, ring_add(e, isY ? 0 : 2));
  ring_wait_full(x.bars, e + 1);
}

template<int KIND>
__device__ __forceinline__ void slot(Ctx& x, Att& a, int& e, float (&O)[64], uint32_t (&Pn)[32], uint32_t (&Po)[32],
                                     bool more, bool isY, bool half, int pv, int pend) {
  float S[64];
  const int w = x.w;
  const bool skip = KIND == 0 && !isY;
  const int en = ring_add(e, skip ? 4 : 2), sn = ring_slot(en), sv = ring_slot(e) + 1, sk = skip ? ring_slot(ring_add(e, 2)) : sv - 1;
  const uint32_t dq = desc_lo(x.base + SM_Q + w * 4096, 16), dk = desc_lo(x.base, 16) + sk * 2048, dv = desc_lo(x.base, 8192) + sv * 2048;
  bar_sync(1 + w, 256);
  TR(5 + KIND);
  if (KIND == 2) {
    wgmma_fence();
    issue_qk(S, dq, dk); wgmma_commit();
    issue_pv<8>(O, Po, dv, 1); wgmma_commit();
    bar_arrive(1 + (w ^ 1), 256);
    wgmma_wait<1>();
  } else if (KIND == 0 && half) {
    float T[32];
    wgmma_fence(); issue_qk_half(T, dq, dk); wgmma_commit();
    a.i0 = rcp_fast(quad_sum(a.l0)); a.i1 = rcp_fast(quad_sum(a.l1));
    if (pv == PV_NONE) { wgmma_fence(); wgmma_commit(); }
    else               { wgmma_fence(); issue_pv<8>(O, Po, dv, pv == PV_ACC); wgmma_commit(); }
    bar_arrive(1 + (w ^ 1), 256);
    wgmma_wait<1>();
    fence_regs(T);
    #pragma unroll
    for (int i = 0; i < 32; i++) { S[i] = T[i]; asm volatile("" : "=f"(S[32 + i])); }
  } else {
    wgmma_fence(); issue_qk(S, dq, dk); wgmma_commit();
    if (KIND == 1 && pend >= 0) { bar_arrive(1 + (w ^ 1), 256); pack_tile(O, Pn, a.i0, a.i1); store_ctx(x, pend, Pn); TR(8); }
    if (KIND == 0) { a.i0 = rcp_fast(quad_sum(a.l0)); a.i1 = rcp_fast(quad_sum(a.l1)); }
    if (KIND == 0 && pv == PV_NONE) { wgmma_fence(); wgmma_commit(); }
    else if (pv == PV_HALF)         { wgmma_fence(); issue_pv<4>(O, Po, dv, 0); wgmma_commit(); }
    else                            { wgmma_fence(); issue_pv<8>(O, Po, dv, pv == PV_ACC); wgmma_commit(); }
    if (KIND == 0 || pend < 0) bar_arrive(1 + (w ^ 1), 256);
    wgmma_wait<1>();
  }
  fence_regs(S);
  fence_regs_u(Pn);
  TR(9);
  slot_release(x, sk, KIND == 0 && isY);
  const bool landed = KIND != 0 && mbar_test2(x.bars + B_RF + 8 * sn, en >= 6);
  float s0 = 0.f, s1 = 0.f;
  const bool was_classic = KIND != 0 && a.classic;
  if (KIND == 0) {
    a.l0 = 0.f; a.l1 = 0.f;
    if (!half) exp_pack<16, 32>(S, Pn, s0, s1);
    else {
      #pragma unroll
      for (int i = 16; i < 32; i++) asm volatile("" : "=r"(Pn[i]));
    }
    exp_pack_diag(S, Pn, diag_limit(), s0, s1);
    uint32_t b0 = __ballot_sync(0xffffffff, s0 >= SUM_LO), b1 = __ballot_sync(0xffffffff, s1 >= SUM_LO);
    b0 |= b0 >> 1; b0 |= b0 >> 2; b1 |= b1 >> 1; b1 |= b1 >> 2;
    a.classic = __any_sync(0xffffffff, !(s0 <= SUM_HI && s1 <= SUM_HI)) || (b0 & b1 & 0x11111111u) != 0x11111111u;
  } else {
    exp_pack<0, 32>(S, Pn, s0, s1);
    a.classic = __any_sync(0xffffffff, a.classic || !(s0 <= SUM_HI && s1 <= SUM_HI));
  }
  fence_regs_u(Pn);
  TR(10);
  if (!landed) {
    mbar_wait(x.bars + B_RF + 8 * sn, en >= 6);
    if (more) mbar_wait(x.bars + B_RF + 8 * sn + 8, en >= 6);
  }
  wgmma_wait<0>();
  fence_regs(O);
  fence_regs_u(Po);
  TR(11);
  slot_release(x, sv, KIND == 1 && isY && pv != PV_ACC);
  if (!NO_CLASSIC && __builtin_expect(a.classic, 0)) {
    float sc0, sc1;
    classic_tile(S, Pn, KIND == 0, half, was_classic, a.mc, a.l0, a.l1, s0, s1, sc0, sc1);
    if (KIND != 0) {
      #pragma unroll
      for (int j = 0; j < 16; j++) { O[4*j] *= sc0; O[4*j+1] *= sc0; O[4*j+2] *= sc1; O[4*j+3] *= sc1; }
    }
  }
  a.l0 += s0; a.l1 += s1;
  e = en;
}

__device__ __forceinline__ int attention(Ctx& x, const uint8_t* items, int nitems, int rank, uint32_t (&PA)[32], uint32_t (&PB)[32], int vtile) {
  int e = 0;
  float O[64];
  Att a;
  volatile float mc[2];
  a.l0 = 1.f; a.l1 = 1.f; a.i0 = 0.f; a.i1 = 0.f; a.classic = false; a.mc = mc;
  int pv = PV_NONE, cur = -1;
#define DBGS()
  #pragma unroll 1
  for (int it = 0; ; it++) {
    const bool isY = (it & 1) == x.w;
    int pend = cur;
    if (it < nitems) {
      const int item = items[it];
      const bool half = isY == (rank != 0);
      cur = item * 4 + (isY ? 3 - rank : rank);
      int rem = 2 * (item & 7) + (isY ? 1 : 0);
      DBG(16 + it);
      q_proj(x, e, isY, PA, PB, vtile, it == 0);
      vtile = -1;
      DBGS();
      slot<0>(x, a, e, O, PA, PB, rem > 0, isY, half, pv, -1);
      pv = half ? PV_HALF : PV_ZERO;
      #pragma unroll 1
      while (rem > 0) {
        DBGS();
        slot<1>(x, a, e, O, PB, PA, rem > 1, isY, false, pv, pend);
        pv = PV_ACC; pend = -1;
        if (rem == 1) break;
        rem -= 2;
        DBGS();
        slot<2>(x, a, e, O, PA, PB, rem > 0, false, false, 0, -1);
      }
      if (isY) continue;
    } else {
      DBGS();
      slot_release(x, 6, false);
      const uint32_t dv = desc_lo(x.base, 8192) + ring_slot(e) * 2048;
      bar_sync(1 + x.w, 256);
      if (pv == PV_HALF) { wgmma_fence(); issue_pv<4>(O, PB, dv, 0); wgmma_commit(); }
      else { wgmma_fence(); issue_pv<8>(O, PB, dv, pv == PV_ACC); wgmma_commit(); }
      if (isY) bar_arrive(1 + (x.w ^ 1), 256);
      a.i0 = rcp_fast(quad_sum(a.l0)); a.i1 = rcp_fast(quad_sum(a.l1));
      ring_wait_full(x.bars, e);
      wgmma_wait<0>();
      fence_regs(O);
      fence_regs_u(PB);
      ring_release(x, e, false);
    }
    if (pend >= 0) {
      pack_tile(O, PB, a.i0, a.i1);
      if (it == nitems) return pend;
      store_ctx(x, pend, PB);
    }
    #pragma unroll
    for (int i = 0; i < 32; i++) asm volatile("mov.b32 %0, %1;" : "=r"(PB[i]) : "r"(PA[i]));
  }
}

#define LN_AT 2
#define X_AT 6
#define PERT 1
#define CTX_T 3
#define PF_AT 5
#define PF_N 4
#define PF_MOE -3
constexpr float QSCALE = 0.08838834764831845f * 1.4426950408889634f;
__device__ __forceinline__ void mod_cta(Ctx& x, const __nv_bfloat16* cvec) {
  const int t = wg_tid(), ct = x.w * 128 + t;
  #pragma unroll 1
  for (int k = 0; k < 6; k++) slot_release(x, k, false);
  const uint32_t cv = __ldg(reinterpret_cast<const uint32_t*>(cvec) + ct);
  asm volatile("st.shared.u32 [%0], %1;" :: "r"(x.base + SM_H2 + ct * 4),
               "r"(pack_bf16(__fdividef(bf_lo(cv), 1.f + __expf(-bf_lo(cv))), __fdividef(bf_hi(cv), 1.f + __expf(-bf_hi(cv))))) : "memory");
  bar_sync(5, 256);
  float acc[64];
  int e = 0;
  #pragma unroll 1
  for (int g = 0; g < 24; g++) {
    uint32_t a[8];
    #pragma unroll
    for (int i = 0; i < 8; i++) a[i] = lds_u32(x.base + SM_H2 + (g & 7) * 128 + i * 16 + (t & 3) * 4);
    ring_wait_full(x.bars, e);
    const uint32_t db = desc_lo(x.base + x.w * 16384, 8192) + ring_slot(e) * 2048;
    wgmma_fence();
    wgmma_rs_n128<1, 0, SW128>(acc, a[0], a[0], a[1], a[1], db, g & 7);
    wgmma_rs_n128<1, 128, SW128>(acc, a[2], a[2], a[3], a[3], db, 1);
    wgmma_rs_n128<1, 256, SW128>(acc, a[4], a[4], a[5], a[5], db, 1);
    wgmma_rs_n128<1, 384, SW128>(acc, a[6], a[6], a[7], a[7], db, 1);
    wgmma_commit();
    wgmma_wait<0>();
    fence_regs(acc);
    ring_release(x, e, false);
    e = ring_add(e, 1);
    if ((g & 7) == 7) {
      if (t < 4) {
        const float sc = (g == 7 && blockIdx.x < NCTA + 2) ? QSCALE : 1.f;
        uint32_t* dst = reinterpret_cast<uint32_t*>(g_mod + (g >> 3) * 1024 + (blockIdx.x - NCTA) * 256 + x.w * 128) + t;
        #pragma unroll
        for (int j = 0; j < 16; j++) dst[4 * j] = pack_bf16(rbf(acc[4*j]) * sc, rbf(acc[4*j+1]) * sc);
      }
      publish(x, g == 7 ? C_MOD : C_MOD2);
      DBG(1 + (g >> 3));
    }
  }
}

__global__ void __cluster_dims__(2, 1, 1) __launch_bounds__(384, 1)
k_fused(const __grid_constant__ CUtensorMap tmC, const __grid_constant__ CUtensorMap tmWq,
        const __grid_constant__ CUtensorMap tmWk, const __grid_constant__ CUtensorMap tmWv,
        const __grid_constant__ CUtensorMap tmWo, const __grid_constant__ CUtensorMap tmWg,
        const __grid_constant__ CUtensorMap tmWu, const __grid_constant__ CUtensorMap tmWm,
        const __grid_constant__ Sched sched,
        const __nv_bfloat16* __restrict__ xin,
        const __nv_bfloat16* __restrict__ cvec, const __nv_bfloat16* __restrict__ w_o,
        const __nv_bfloat16* __restrict__ w_r, const __nv_bfloat16* __restrict__ w_gate, const __nv_bfloat16* __restrict__ w_up,
        const __nv_bfloat16* __restrict__ w_down, __nv_bfloat16* __restrict__ out) {
  extern __shared__ __align__(1024) uint8_t smem_raw[];
  const uint32_t base = smem_u32(smem_raw), bars = base + SM_BAR;
  const int warp = __shfl_sync(0xffffffff, threadIdx.x >> 5, 0), wg = warp >> 2;
  const int rank = cluster_ctarank(), p = blockIdx.x >> 1;
  const int mt = (p & 7) * 2 + rank;
  const bool spare = blockIdx.x >= NCTA;
  #pragma unroll
  for (int i = 0; i < PERT; i++) { uint32_t d; asm volatile("mov.u32 %0, %%laneid;" : "=r"(d)); }
  {
    const int h0 = KHEAD0 + (p >> 3);
    if (warp == 11) { prefetch_tmap(&tmC); prefetch_tmap(&tmWk); }
    #pragma unroll 1
    for (int t = warp == 8 ? 0 : warp < 8 ? warp + 1 : warp == 11 ? 64 : warp; t < B_PUB / 8; t += (warp == 8 ? 64 : 10))
      w_mbar_init(bars + 8 * t, t < B_WE / 8 ? 1 : t < B_RE / 8 ? 2 : 4);
    fence_mbar_init();
    cluster_arrive();
    if (warp == 9) prefetch_tmap(&tmWv);
    if (wg == 2) bar_arrive(1, 256);
    if (warp == 8 && !spare) {
      #pragma unroll 1
      for (int kb = 0; kb < 8; kb++) {
        w_expect_tx(bars + B_AF + 8 * kb, 16384);
        tma_load_2d(base + k_addrA(kb), &tmC, bars + B_AF + 8 * kb, kb * 64, mt * 128);
        if (kb == 0) cluster_wait();
        if (kb < 6) {
          w_expect_tx(bars + B_WF + 8 * kb, 16384);
          tma_load_2d_mc(base + k_addrW(kb) + rank * 8192, &tmWk, bars + B_WF + 8 * kb, h0 * 128 + rank * 64, kb * 64);
        }
      }
    }
  }
  const Sched::Pair& sp = sched.pair[p];
  const int nitems = sp.nitems, nsteps = sp.nsteps;
  auto oent = [&](int k) -> uint32_t { return sp.oent[k]; };
  const int ot = sp.otask, m = (ot & 7) * 2 + rank, grp = m * 8 + (ot >> 3);

  if (wg == 0) {
    asm volatile("setmaxnreg.dec.sync.aligned.u32 24;");
    const int lane = threadIdx.x & 31;
    #pragma unroll 1
    for (int t = B_PUB / 8 + warp; t < 80; t += 4) w_mbar_init(bars + 8 * t, t < B_RDY / 8 ? 4 : 1);
    bar_sync(6, 128);
    bar_arrive(7, 256); bar_arrive(8, 256);
    cluster_wait();
    const unsigned int tag = ld_relaxed(&g_epoch) + 1;
    if (warp == 0) {
      if (!spare) {
        int s = 0, ph = 0;
        tma_prefetch_2d(&tmWv, sp.khead[0] * 128 + rank * 64, (p & 7) * 64);
        #pragma unroll 1
        for (int g = 6; g < 64; g++) {
          const int u = g >> 3, kb = g & 7;
          if (kb == 0 && u < 7) tma_prefetch_2d((u & 1) ? &tmWk : &tmWv, sp.khead[(u + 1) >> 1] * 128 + rank * 64, (p & 7) * 64);
          mbar_wait(bars + B_WE + 8 * s, ph);
          w_expect_tx(bars + B_WF + 8 * s, 16384);
          tma_load_2d_mc(base + k_addrW(s) + rank * 8192, (u & 1) ? &tmWv : &tmWk, bars + B_WF + 8 * s, sp.khead[u >> 1] * 128 + rank * 64, kb * 64);
          if (++s == 6) { s = 0; ph ^= 1; }
        }
      }
      int s = 0, ph = 0;
      auto next_entry = [&](int bytes) {
        mbar_wait(bars + B_RE + 8 * s, ph);
        w_expect_tx(bars + B_RF + 8 * s, bytes);
      };
      auto advance = [&]() { if (++s == 6) { s = 0; ph ^= 1; } };
      if (spare) {
        #pragma unroll 1
        for (int g = 0; g < 24; g++) {
          if (g == 8) mbar_wait(bars + R_MOD, 0);
          next_entry(32768);
          for (int k = 0; k < 2; k++) tma_load_3d(base + s * 32768 + k * 16384, &tmWm, bars + B_RF + 8 * s, 0, (g & 7) * 64, (g >> 3) * 16 + (blockIdx.x - NCTA) * 4 + k * 2);
          advance();
        }
      }
      mbar_wait(bars + R_H1, 0);
      fence_async_global();
      int vrow = -1;
      #pragma unroll 1
      for (int i = 0; i <= nitems; i++) {
        const int item = sp.item[i & (MAX_ITEMS - 1)], h = item >> 3, j = item & 7;
        if (i < nitems) {
          const int row0 = j * 256 + ((i & 1) ? rank : 3 - rank) * 64, row1 = j * 256 + ((i & 1) ? 3 - rank : rank) * 64;
          #pragma unroll 1
          for (int kb = 0; kb < 8; kb++) {
            next_entry(32768);
            tma_load_2d_mc(base + s * 32768 + 16384 + rank * 8192, &tmWq, bars + B_RF + 8 * s, h * 128 + rank * 64, kb * 64);
            bulk_load(base + s * 32768, sched.h1 + row0 * DM + kb * 4096, 8192, bars + B_RF + 8 * s);
            bulk_load(base + s * 32768 + 8192, sched.h1 + row1 * DM + kb * 4096, 8192, bars + B_RF + 8 * s);
            advance();
          }
          mbar_wait(bars + R_ITEM + 8 * i, 0);
          fence_async_global();
        }
        #pragma unroll 1
        for (int n = i < nitems ? 4 * j + 3 : 0; n >= 0; n--) {
          const int krow = (h * 2 + rank) * SEQ + (n >> 1) * 128 + ((sp.lastuse[i & (MAX_ITEMS - 1)] >> (n >> 1)) & 1);
          const int row = (n & 1) ? krow : vrow;
          if (i + 1 == nitems && n == min(4 * j + 3, 2 * PF_AT + 1)) w_arrive(bars + R_NEAR);
          next_entry(row >= 0 ? 32768 : 0);
          if (row >= 0) bulk_load_mc(base + s * 32768 + rank * 16384, sched.kvc + (size_t)(row & ~1) * 64, bars + B_RF + 8 * s, row & 1);
          advance();
          if (!(n & 1)) vrow = krow + 64 * SEQ;
        }
      }
      if (!spare) {
      const int oc = ((ot >> 3) & 1) * 4 + rank * 2;
      auto o_next = [&](int k, int bytes) {
        const uint32_t v = oent(k); s = v & 7;
        mbar_wait(bars + B_RE + 8 * s, v >> 3);
        w_expect_tx(bars + B_RF + 8 * s, bytes);
      };
      #pragma unroll 1
      for (int i = 0; i < nsteps; i++) {
        const int c0 = sp.ochunk[i][0], c1 = sp.ochunk[i][1];
        const int pf = PF_MOE > 0 ? i - PF_MOE : i - nsteps - PF_MOE;
        if (pf >= 0 && pf < 3)
          bulk_prefetch((pf == 0 ? w_gate : pf == 1 ? w_up : w_down) + (size_t)blockIdx.x * (DM * FF / NCTA), DM * FF / NCTA * 2);
        if (c0 < 64) { o_next(3 * i, 32768); tma_load_3d_mc(base + s * 32768 + rank * 16384, &tmWo, bars + B_RF + 8 * s, 0, c0 * 64, oc); }
        mbar_wait(bars + R_CTX + 8 * i, 0);
        fence_async_global();
        o_next(3 * i + 1, c0 < 64 ? 32768 : 16384);
        if (c0 < 64) bulk_load(base + s * 32768, sched.kvc + (size_t)((128 + c0) * SEQ + m * 128) * 64, 16384, bars + B_RF + 8 * s);
        bulk_load(base + s * 32768 + 16384, sched.kvc + (size_t)((128 + c1) * SEQ + m * 128) * 64, 16384, bars + B_RF + 8 * s);
        o_next(3 * i + 2, 32768);
        tma_load_3d_mc(base + s * 32768 + rank * 16384, &tmWo, bars + B_RF + 8 * s, 0, c1 * 64, oc);
      }
      const int f0 = (blockIdx.x < FF / 16 ? blockIdx.x : 0) * 16;
      o_next(3 * nsteps, 32768);
      bulk_load(base + s * 32768, w_down + (size_t)f0 * DM, 16384, bars + B_RF + 8 * s);
      bulk_load(base + s * 32768 + 16384, xin + (size_t)grp * 16 * DM, 16384, bars + B_RF + 8 * s);
      o_next(3 * nsteps + 1, 32768);
      #pragma unroll 1
      for (int k = 0; k < 4; k++) tma_load_2d(base + s * 32768 + k * 8192, (k & 2) ? &tmWu : &tmWg, bars + B_RF + 8 * s, f0, (k & 1) * 256);
      #pragma unroll 1
      for (int k = 0; k < 4; k++) w_expect_tx(bars + R_PART + 8 * k, 16384);
      mbar_wait(bars + B_PUB + 8 * (5 + nitems), 0);
      mbar_wait(bars + B_PUB + 8 * (NPUB + 5 + nitems), 0);
      uint32_t todo = 0xff;
      #pragma unroll 1
      for (int n = 0; n < WAIT_LIM && todo; n++) {
        uint32_t now = __ballot_sync(0xffffffff, ld_acquire(&g_cnt[C_PART + (m * 2 + (ot >> 5)) * 32 + (lane & 7)]) == tag) & todo;
        todo &= ~now;
        if (now) fence_async_global();
        #pragma unroll 1
        for (; now; now &= now - 1) {
          const int q = __ffs(now) - 1;
          bulk_load(base + (oent(3 * nsteps - 3 + (q >> 2)) & 7) * 32768 + (q & 3) * 8192, sched.part + (grp * 8 + q) * 4096, 8192, bars + R_PART + 8 * (q >> 1));
        }
      }
      DBGP(11);
      }
    } else if (warp < 3) {
      const int w = warp - 1, n1 = w * NPUB + (spare ? 3 : 6) + nitems;
      #pragma unroll 1
      for (int n = w * NPUB; n < n1; n++) {
        #pragma unroll 1
        for (int k = 0; k < 8 * WAIT_LIM; k++) { if (mbar_try(bars + B_PUB + 8 * n, 0)) break; }
        const uint32_t idx = lds_u32(base + SM_MAIL + 4 * n);
        fence_async_global();
        if (lane == 0 && idx < (unsigned)C_END) red_release(idx);
        __syncwarp();
      }
    } else {
      *reinterpret_cast<volatile uint32_t*>(smem_raw + SM_KEY + 48) = tag;
      if (!spare) { mbar_wait(bars + B_AF + 8 * X_AT, 0); bulk_prefetch(xin + (size_t)blockIdx.x * 16 * DM, 16 * DM * 2); }
      #pragma unroll 1
      for (int n = 0; n < 8 + nsteps; n++) {
        if (n == 2 + nitems) n = 7;
        int idx = n == 0 ? C_MOD : n == 1 ? C_H1 : C_MOD2, cnt = n == 0 ? 8 : n == 1 ? 256 : 16;
        if (n >= 1 && n <= nitems) { const int item = sp.item[n - 1]; tma_prefetch_2d(&tmWq, (item >> 3) * 128 + rank * 64, (item & 7) * 64); }
        if (n >= 2 && n < 7) { idx = C_KV + (sp.item[n - 2] >> 3); cnt = 32; }
        if (n >= 8) { const int c0 = sp.ochunk[n - 8][0], c1 = sp.ochunk[n - 8][1]; idx = C_CTX + (((lane & 1) && c0 < 64 ? c0 : c1) >> 1) * 8 + (ot & 7); cnt = 4; }
        wait_count_lazy(idx, cnt * tag);
        w_arrive(bars + B_RDY + 8 * n);
        if (n == 0) DBGP(12);
        if (n == 8 + PF_N - 1) {
          #pragma unroll 1
          for (int k = 0; k < 8 * WAIT_LIM; k++) { if (mbar_try(bars + R_NEAR, 0)) break; }
          bulk_prefetch(w_o + (size_t)blockIdx.x * (NH * DH * DM / NCTA), NH * DH * DM / NCTA * 2);
          #pragma unroll 1
          for (int k = 0; k < PF_N; k++) {
            const int cc = sp.ochunk[k][(ot >> 3) & 1];
            if (cc < 64) bulk_prefetch(sched.kvc + ((size_t)(128 + cc) * SEQ + m * 128) * 64, 16384);
          }
        }
      }
    }
    __syncwarp();
    cluster_arrive();
    if (!spare) {
      bar_sync(6, 128);
      asm volatile("setmaxnreg.inc.sync.aligned.u32 88;");
      const int pos = blockIdx.x * 4 + (lane & 1) * 2, col = (blockIdx.x >> 2) * 16 + (blockIdx.x & 3) * 2 + (lane & 1) * 8, src = threadIdx.x >> 1;
      uint32_t gbest = 0, hh = 0, gbf = 0;
      uint2 xx = make_uint2(0, 0);
      uint4 ya = make_uint4(0, 0, 0, 0), yb = make_uint4(0, tag, 0, tag);
      auto poll_y = [&]() {
        if (ya.y != tag || ya.w != tag) ya = ld_tagged2(&g_yll[src][pos]);
        if (yb.y != tag || yb.w != tag) yb = ld_tagged2(&g_yll[src + 64][pos]);
        return __all_sync(0xffffffff, ya.y == tag && ya.w == tag && yb.y == tag && yb.w == tag);
      };
      ya.y = tag - 1; if (src + 64 < FF / 16) yb.y = tag - 1;
      poll_y();
      if (warp == 3) {
        gbf = __ldcg(reinterpret_cast<const uint32_t*>(g_mod + 5 * DM + col));
        uint32_t have = 0;
        uint2 k[4];
        #pragma unroll
        for (int i = 0; i < 4; i++) k[i] = make_uint2(0, tag - 1);
        #pragma unroll 1
        for (int n = 0; n < WAIT_LIM; n++) {
          #pragma unroll
          for (int i = 0; i < 4; i++) if (k[i].y != tag) k[i] = ld_tagged(&g_keys[i * 32 + lane][0]);
          if (gbest != have) {
            const int g = ((0xffffu - gbest) >> 4) & 127;
            uint4 hv[4];
            #pragma unroll
            for (int i = 0; i < 4; i++) hv[i] = ld_tagged2(&g_row[g][0][i * 64 + lane * 2]);
            xx = ld_tagged(&g_row[g][1][(col >> 8) * 128 + ((col >> 2) & 1) * 64 + ((col >> 3) & 31) * 2 + ((col >> 1) & 1)]);
            bool ok = xx.y == tag;
            #pragma unroll
            for (int i = 0; i < 4; i++) { ok = ok && hv[i].y == tag && hv[i].w == tag; reinterpret_cast<uint2*>(smem_raw + SM_H2)[(i >> 1) * 64 + lane * 2 + (i & 1)] = make_uint2(hv[i].x, hv[i].z); }
            if (lane == 0) *reinterpret_cast<uint32_t*>(smem_raw + SM_KEY + 32) = gbest;
            have = __all_sync(0xffffffff, ok) ? gbest : 0;
          }
          bool all = true;
          #pragma unroll
          for (int i = 0; i < 4; i++) { all = all && k[i].y == tag; gbest = max(gbest, k[i].y == tag ? k[i].x : 0u); }
          gbest = __reduce_max_sync(0xffffffff, gbest);
          if (__all_sync(0xffffffff, all) && gbest == have) break;
        }
        w_arrive(bars + R_KEY);
        if (blockIdx.x == 0 && lane == 0) g_epoch = tag;
        hh = lds_u32(base + SM_H2 + col * 2);
        DBGP(13);
      }
      const uint32_t sb16 = gbest & 0xffff0000u;
      const float rsel = __uint_as_float((sb16 & 0x80000000u) ? (sb16 & 0x7fffffffu) : (~sb16 & 0xffff0000u));
      const float rs = rbf(__fdividef(1.f, 1.f + __expf(-rsel)));
      bar_sync(9, 384);
      #pragma unroll 1
      for (int n = 0; n < WAIT_LIM; n++) { if (poll_y()) break; }
      float y0 = __uint_as_float(ya.x) + __uint_as_float(yb.x), y1 = __uint_as_float(ya.z) + __uint_as_float(yb.z);
      #pragma unroll
      for (int o = 2; o < 32; o <<= 1) { y0 += __shfl_xor_sync(0xffffffff, y0, o); y1 += __shfl_xor_sync(0xffffffff, y1, o); }
      float2* s_y = reinterpret_cast<float2*>(smem_raw + SM_KEY + 64);
      if (lane < 2) s_y[warp * 2 + lane] = make_float2(y0, y1);
      bar_sync(6, 128);
      if (warp == 3 && lane < 2) {
        y0 = 0.f; y1 = 0.f;
        #pragma unroll
        for (int i = 0; i < 4; i++) { y0 += reinterpret_cast<const float*>(s_y)[i * 4 + lane]; y1 += reinterpret_cast<const float*>(s_y)[i * 4 + 2 + lane]; }
        const float o0 = bf_lo(xx.x) + rbf(bf_lo(gbf) * rbf(bf_lo(hh) + rbf(rbf(y0) * rs)));
        const float o1 = bf_hi(xx.x) + rbf(bf_hi(gbf) * rbf(bf_hi(hh) + rbf(rbf(y1) * rs)));
        *reinterpret_cast<uint32_t*>(out + (size_t)((0xffffu - gbest) & (SEQ - 1)) * DM + col) = pack_bf16(o0, o1);
      }
      DBGP(14);
    }
    __syncwarp();
    cluster_wait();
  } else {
    asm volatile("setmaxnreg.inc.sync.aligned.u32 240;");
    Ctx x;
    x.w = wg - 1; x.base = base; x.bars = bars; x.nev = 0; x.sched = &sched;
    const int w = x.w, warp4 = warp & 3;
    x.rel = mapa(bars, (warp4 & 1) ^ 1);
    x.rel1 = (threadIdx.x & 127) == 32 || (threadIdx.x & 127) == 64;
    if (warp != 8 || spare) cluster_wait();
    if (w == 1 || spare) bar_sync(7 + w, 256);
    DBG(1);
    uint32_t PA[32], PB[32];
    int vtile = -1;
    if (spare) {
      mod_cta(x, cvec);
    } else {
      const int lane = wg_tid() & 31;
      Row xn[2];
      float acc0[64], acc1[64];
      int s = 2 * w, ph = w;
      #pragma unroll 1
      for (int u = w; u < 8; u += 2) {
        bar_sync(1 + w, 256);
        DBG(4 + (u >> 1) * 3);
        int ps = 0;
        #pragma unroll 1
        for (int kb = 0; kb < 8; kb++) {
          if (u < 2) mbar_wait(bars + B_AF + 8 * kb, 0);
          mbar_wait(bars + B_WF + 8 * s, ph);
          const uint32_t da = desc_lo(base + k_addrA(kb), 16), dw = desc_lo(base + k_addrW(s), 8192);
          wgmma_fence();
          kblock_n128<0>(acc0, da, dw, kb != 0);
          kblock_n128<512>(acc1, da, dw, kb != 0);
          wgmma_commit();
          if (kb == 7) bar_arrive(1 + (w ^ 1), 256);
          if (kb > 0) {
            wgmma_wait<1>();
            mbar_arrive_remote_if(x.rel + B_WE + 8 * ps, x.rel1);
            if (u == 7 && !(kb & 1)) {
              ring_release(x, kb == 2 ? 0 : kb - 3, false);
              if (kb > 2) ring_release(x, kb - 2, false);
            }
          }
          ps = s;
          if (++s == 6) { s = 0; ph ^= 1; }
        }
        Row t[2];
        const int lrow = blockIdx.x * 16 + w * 8 + warp4 * 2;
        if (u == w) { t[0] = ldg_row(xin + (size_t)lrow * DM, lane); t[1] = ldg_row(xin + (size_t)(lrow + 1) * DM, lane); }
        if (u == LN_AT || u == LN_AT + 1) {
          mbar_wait(bars + R_MOD, 0);
          t[0] = ldca_row(g_mod, lane); t[1] = ldca_row(g_mod + DM, lane);
        }
        wgmma_wait<0>();
        fence_regs(acc0); fence_regs(acc1);
        DBG(5 + (u >> 1) * 3);
        mbar_arrive_remote_if(x.rel + B_WE + 8 * ps, x.rel1);
        if (u == 6) { for (int k = 0; k < 5; k++) ring_release(x, k, false); }
        if (u >= 6) ring_release(x, 5, false);
        if (V_AT >= 0 && u == 7) {
          pack_tile(acc0, PA, 1.f, 1.f); pack_tile(acc1, PB, 1.f, 1.f);
          vtile = sp.khead[3] * 16 + mt;
          break;
        }
        s += 2; ph ^= 1; if (s >= 6) { s -= 6; ph ^= 1; }
        if (u == 0) bar_sync(7, 256);
        if (u == w) {
          float st[4] = {0.f, 0.f, 0.f, 0.f};
          #pragma unroll
          for (int i = 0; i < 32; i++) { const float v = row_at(t[i >> 4], i & 15); st[(i >> 4) * 2] += v; st[(i >> 4) * 2 + 1] = fmaf(v, v, st[(i >> 4) * 2 + 1]); }
          warp_sums(st);
          #pragma unroll
          for (int r = 0; r < 2; r++) { ln_stats(st[2*r], st[2*r+1]); xn[r] = ln_apply(t[r], st[2*r], st[2*r+1] * QSCALE); }
        }
        if ((u == LN_AT || u == LN_AT + 1)) {
          #pragma unroll
          for (int r = 0; r < 2; r++) {
            const Row hr = fma_row(xn[r], one_plus(t[1]), t[0]);
            __nv_bfloat16* hp = sched.h1 + (lrow & ~63) * DM + (lane >> 3) * 4096 + ((lrow + r) & 63) * 64 + (((lane ^ (lrow + r)) & 7) << 3);
            stg_v4(hp, hr.v[0], hr.v[1], hr.v[2], hr.v[3]); stg_v4(hp + 4 * 4096, hr.v[4], hr.v[5], hr.v[6], hr.v[7]);
          }
        }
        const int tile = sp.khead[u >> 1] * 16 + mt;
        __nv_bfloat16* dst = kv_tile(x, tile);
        uint32_t D[32];
        pack_tile(acc0, D, 1.f, 1.f); store_tile(dst + 2048, D);
        pack_tile(acc1, D, 1.f, 1.f); store_tile(dst, D);
        if (u == LN_AT || u == LN_AT + 1) publish(x, C_H1);
        publish(x, C_KV + (tile >> 4));
        DBG(6 + (u >> 1) * 3);
      }
    }
    x.tr = base + SM_RED + w * 1024;
    const int last = attention(x, sp.item, nitems, rank, PA, PB, vtile);
    DBG(100);
    const int lane = wg_tid() & 31, cw = w * 4 + warp4, ct = cw * 32 + lane;
    const int row0 = grp * 16 + cw * 2;
    const bool moe_cta = blockIdx.x < FF / 16;
    if (spare) { store_ctx(x, last, PB); __syncwarp(); cluster_arrive(); cluster_wait(); return; }
    const int kl = 3 * nsteps - 3;
    Row ga, sb, cb, gb, wr;
    {
      float accA[64], accB[64];
      const int t0 = oent(0) == oent(1);
      uint32_t pa = 0, pb = 0;
      #pragma unroll 1
      for (int t = t0; t < 2 * nsteps - 2; t++) {
        const uint32_t eb = oent(3 * (t >> 1) + 2 * (t & 1)), ea = oent(3 * (t >> 1) + 1);
        o_wait_full(bars, eb);
        o_wait_full(bars, ea);
        const uint32_t da = desc_lo(base + w * 4096, 16) + (ea & 7) * 2048 + (t & 1) * 1024, db = desc_lo(base, 8192) + (eb & 7) * 2048;
        wgmma_fence();
        kblock_n128<0, 0, SW64>(accA, da, db, t != t0); kblock_n128<0, 1024, SW64>(accB, da, db, t != t0);
        wgmma_commit();
        if (t == CTX_T) store_ctx(x, last, PB);
        if (t > t0) { wgmma_wait<1>(); slot_release(x, pb, false); if (!(t & 1)) slot_release(x, pa, false); }
        pa = ea & 7; pb = eb & 7;
      }
      const uint32_t e0 = oent(kl), ea = oent(kl + 1), eb = oent(kl + 2);
      const uint32_t da = desc_lo(base + w * 4096, 16) + (ea & 7) * 2048;
      const uint32_t db0 = desc_lo(base, 8192) + (e0 & 7) * 2048, db1 = desc_lo(base, 8192) + (eb & 7) * 2048;
      ga = ldca_row(g_mod + 2 * DM, lane); sb = ldca_row(g_mod + 3 * DM, lane); cb = ldca_row(g_mod + 4 * DM, lane); gb = ldca_row(g_mod + 5 * DM, lane);
      wr = ldca_row(w_r, lane);
      o_wait_full(bars, e0);
      o_wait_full(bars, ea);
      o_wait_full(bars, eb);
      wgmma_fence();
      kblock_n128<0, 0, SW64>(accA, da, db0, 1); kblock_n128<1024, 0, SW64>(accA, da, db1, 1);
      wgmma_commit();
      kblock_n128<0, 1024, SW64>(accB, da, db0, 1); kblock_n128<1024, 1024, SW64>(accB, da, db1, 1);
      wgmma_commit();
      __syncwarp();
      cluster_arrive();
      __nv_bfloat16* dst = sched.part + ((m * 8 + cw) * 8 + (ot >> 3)) * 4096;
      auto send = [&](const float (&acc)[64], int h) {
        uint32_t D[32];
        pack_tile(acc, D, 1.f, 1.f);
        #pragma unroll
        for (int i = 0; i < 8; i++) stg_v4(dst + (h * 8 + i) * 256 + ((lane ^ (h * 4 + (i >> 1))) << 3), D[4*i], D[4*i+1], D[4*i+2], D[4*i+3]);
      };
      wgmma_wait<1>();
      fence_regs(accA);
      DBG(120);
      send(accA, 0);
      o_wait_full(bars, eb);
      wgmma_wait<0>();
      fence_regs(accB);
      DBG(101);
      send(accB, 1);
      publish(x, C_PART + (m * 2 + w) * 32 + (ot >> 3));
      DBG(121);
      DBG(102);
    }
    asm volatile("setmaxnreg.dec.sync.aligned.u32 208;");
    const uint32_t sD = base + (oent(kl + 3) & 7) * 32768, sW = base + (oent(kl + 4) & 7) * 32768;
    o_wait_full(bars, oent(kl + 3)); o_wait_full(bars, oent(kl + 4));
    Row x1[2];
    #pragma unroll
    for (int r = 0; r < 2; r++) x1[r] = lds_row(sD + 16384 + (cw * 2 + r) * 1024, lane);
    uint4 wgv[4], wuv[4], wdv[4];
    #pragma unroll
    for (int r = 0; r < 4; r++) {
      const uint32_t k = (lane & 7) + ((lane >> 4) << 3), h = (lane & 8) * 2;
      wgv[r] = ldsm_x4_t(sW + (cw * 64 + r * 16 + k) * 32 + h);
      wuv[r] = ldsm_x4_t(sW + 16384 + (cw * 64 + r * 16 + k) * 32 + h);
      wdv[r] = ldsm_x4_t(sD + k * 1024 + (cw * 64 + r * 16) * 2 + h);
    }
    const Row cb1 = one_plus(cb);
    const unsigned int tag = lds_u32(base + SM_KEY + 48);
    DBG(103);
    float u[16], ub[2] = {0.f, 0.f};
    #pragma unroll
    for (int i = 0; i < 16; i++) { u[i] = row_at(cb1, i) * row_at(wr, i); ub[0] += u[i]; ub[1] = fmaf(row_at(sb, i), row_at(wr, i), ub[1]); }
    warp_sums(ub);
    float st[6] = {0.f, 0.f, 0.f, 0.f, 0.f, 0.f};
    uint32_t key[2];
    {
      const uint32_t po = base + ((lane & 7) * 2 + (cw >> 2)) * 512 + (cw & 3) * 128;
      Row av[2][2];
      #pragma unroll
      for (int k = 0; k < 4; k++) {
        mbar_wait(bars + R_PART + 8 * k, 1);
        const uint32_t pa = po + (oent(kl + (k >> 1)) & 7) * 32768 + (k & 1) * 16384;
        #pragma unroll
        for (int r = 0; r < 2; r++) {
          const uint32_t sw = ((r * 4 + (lane >> 3)) ^ (lane & 7)) << 4;
          const uint4 lo = ldsm_x4(pa + sw), hi = ldsm_x4(pa + 8192 + sw);
          const Row v{{lo.x, lo.y, lo.z, lo.w, hi.x, hi.y, hi.z, hi.w}};
          av[r][k >> 1] = (k & 1) ? add_row(av[r][k >> 1], v) : v;
        }
      }
      DBG(104);
      #pragma unroll
      for (int r = 0; r < 2; r++) {
        x1[r] = fma_row(ga, add_row(av[r][0], av[r][1]), x1[r]);
        #pragma unroll
        for (int i = 0; i < 16; i++) { const float v = row_at(x1[r], i); st[3*r] += v; st[3*r+1] = fmaf(v, v, st[3*r+1]); st[3*r+2] = fmaf(v, u[i], st[3*r+2]); }
      }
      warp_sums(st);
      #pragma unroll
      for (int r = 0; r < 2; r++) {
        ln_stats(st[3*r], st[3*r+1]);
        const uint32_t rb = pack_bf16(0.f, fmaf(st[3*r+1], fmaf(-st[3*r], ub[0], st[3*r+2]), ub[1]));
        key[r] = (((rb & 0x80000000u) ? ~rb : (rb | 0x80000000u)) & 0xffff0000u) | (0xffffu - (uint32_t)(row0 + r));
      }
    }
    DBG(105);
    float* s_red = reinterpret_cast<float*>(smem_raw + SM_RED);
    uint32_t* s_key = reinterpret_cast<uint32_t*>(smem_raw + SM_KEY);
    const int rb = key[1] > key[0];
    const uint32_t wbest = rb ? key[1] : key[0];
    if (lane == 0) s_key[cw] = wbest;
    bar_sync(5, 256);
    const uint32_t cbest = __reduce_max_sync(0xffffffff, s_key[lane & 7]);
    if (wbest == cbest && lane == 0) st_tagged(&g_keys[grp][0], cbest, tag);
    Row xb, xo;
    #pragma unroll
    for (int i = 0; i < 8; i++) { xb.v[i] = rb ? x1[1].v[i] : x1[0].v[i]; xo.v[i] = rb ? x1[0].v[i] : x1[1].v[i]; }
    const Row hb = fma_row(ln_apply(xb, rb ? st[3] : st[0], rb ? st[4] : st[1]), cb1, sb);
    if (wbest == cbest) {
      #pragma unroll
      for (int i = 0; i < 4; i++) st_tagged2(&g_row[grp][0][i * 64 + lane * 2], hb.v[2*i], hb.v[2*i+1], tag);
      #pragma unroll
      for (int i = 0; i < 4; i++) st_tagged2(&g_row[grp][1][i * 64 + lane * 2], xb.v[2*i], xb.v[2*i+1], tag);
    }
    DBG(106);
    const Row ob = fma_row(gb, hb, xb);
    if (wbest != cbest) store_row(out + (size_t)(row0 + rb) * DM, lane, ob);
    store_row(out + (size_t)(row0 + 1 - rb) * DM, lane, fma_row(gb, fma_row(ln_apply(xo, rb ? st[0] : st[3], rb ? st[1] : st[4]), cb1, sb), xo));
    mbar_wait(bars + R_KEY, 1);
    DBG(107);
    if (moe_cta) {
      float cg[4] = {0, 0, 0, 0}, cu[4] = {0, 0, 0, 0};
      #pragma unroll
      for (int r = 0; r < 4; r++) {
        const uint32_t b0 = lds_u32(base + SM_H2 + (cw * 64 + r * 16) * 2 + (lane & 3) * 4), b1 = lds_u32(base + SM_H2 + (cw * 64 + r * 16) * 2 + 16 + (lane & 3) * 4);
        mma16816(cg, wgv[r], b0, b1); mma16816(cu, wuv[r], b0, b1);
      }
      s_red[cw * 32 + (lane & 3) * 8 + (lane >> 2)] = (lane & 2) ? ((lane & 1) ? cu[2] : cu[0]) : ((lane & 1) ? cg[2] : cg[0]);
      bar_sync(5, 256);
      float g = 0.f;
      #pragma unroll
      for (int i = 0; i < 8; i++) g += s_red[i * 32 + lane];
      g = rbf(g);
      const float act = rbf(__fdividef(g, 1.f + __expf(-g))) * __shfl_down_sync(0xffffffff, g, 16);
      const uint32_t a2 = pack_bf16(act, __shfl_down_sync(0xffffffff, act, 1));
      const uint32_t b0 = __shfl_sync(0xffffffff, a2, (lane & 3) * 2), b1 = __shfl_sync(0xffffffff, a2, (lane & 3) * 2 + 8);
      float y0 = 0.f, y1 = 0.f;
      #pragma unroll
      for (int r = 0; r < 4; r++) {
        float c[4] = {0, 0, 0, 0};
        mma16816(c, wdv[r], b0, b1);
        if ((lane & 3) == r) { y0 = c[0]; y1 = c[2]; }
      }
      st_tagged2(&g_yll[blockIdx.x][cw * 64 + (lane & 3) * 16 + (lane >> 2) * 2], __float_as_uint(y0), __float_as_uint(y1), tag);
    }
    bar_arrive(9, 384);
    DBG(108);
    if (wbest == cbest && wbest != s_key[8]) store_row(out + (size_t)(row0 + rb) * DM, lane, ob);
    DBG(109);
    __syncwarp();
    cluster_wait();
  }
}

typedef CUresult (*EncodeFn)(CUtensorMap*, CUtensorMapDataType, cuuint32_t, void*, const cuuint64_t*, const cuuint64_t*, const cuuint32_t*,
                             const cuuint32_t*, CUtensorMapInterleave, CUtensorMapSwizzle, CUtensorMapL2promotion, CUtensorMapFloatOOBfill);

struct HostState {
  bool ready = false;
  EncodeFn encode = nullptr;
  CUtensorMap tmC, tmWq, tmWk, tmWv, tmWo, tmWg, tmWu, tmWm;
  Sched sched;
};

void make_map(EncodeFn enc, CUtensorMap* m, const void* ptr, int rank, const cuuint64_t* dims, const cuuint64_t* strides, const cuuint32_t* box, bool swizzle = true) {
  const cuuint32_t es[3] = {1, 1, 1};
  enc(m, CU_TENSOR_MAP_DATA_TYPE_BFLOAT16, rank, const_cast<void*>(ptr), dims, strides, box, es, CU_TENSOR_MAP_INTERLEAVE_NONE,
      swizzle ? CU_TENSOR_MAP_SWIZZLE_128B : CU_TENSOR_MAP_SWIZZLE_NONE, swizzle ? CU_TENSOR_MAP_L2_PROMOTION_L2_128B : CU_TENSOR_MAP_L2_PROMOTION_NONE, CU_TENSOR_MAP_FLOAT_OOB_FILL_NONE);
}
void make_2d(EncodeFn enc, CUtensorMap* m, const void* ptr, int rows, int cols, int box_rows) {
  const cuuint64_t dims[2] = {(cuuint64_t)cols, (cuuint64_t)rows}, strides[1] = {(cuuint64_t)cols * 2};
  const cuuint32_t box[2] = {64, (cuuint32_t)box_rows};
  make_map(enc, m, ptr, 2, dims, strides, box);
}
void make_3d(EncodeFn enc, CUtensorMap* m, const void* ptr, int rows, int chunks, size_t row_stride, size_t chunk_stride) {
  const cuuint64_t dims[3] = {64, (cuuint64_t)rows, (cuuint64_t)chunks}, strides[2] = {row_stride, chunk_stride};
  const cuuint32_t box[3] = {64, 64, 2};
  make_map(enc, m, ptr, 3, dims, strides, box);
}

void make_ffn(EncodeFn enc, CUtensorMap* m, const void* ptr) {
  const cuuint64_t dims[2] = {(cuuint64_t)FF, (cuuint64_t)DM}, strides[1] = {(cuuint64_t)FF * 2};
  const cuuint32_t box[2] = {16, 256};
  make_map(enc, m, ptr, 2, dims, strides, box, false);
}

#define SR 0x213312
#define SEED 12345
#define LU_MARGIN 0
#define SPARE_N 3
void build_sched(Sched& s) {
  memset(&s, 0, sizeof(s));
  const int NP = NCTA / 2, korder[4] = {(KORDER >> 12) & 3, (KORDER >> 8) & 3, (KORDER >> 4) & 3, KORDER & 3};
  const int sround[4][2][3] = {{}, {{1}, {2}}, {{1, 2}, {1, 2}}, {{(SR >> 20) & 3, (SR >> 16) & 3, (SR >> 12) & 3}, {(SR >> 8) & 3, (SR >> 4) & 3, SR & 3}}};
  int jv[4][NP], used[4][8] = {};
  for (int r = 0; r < 4; r++) for (int p = 0; p < NP; p++) jv[r][p] = (r & 2) ? 7 - ((p + 4 * (r & 1)) & 7) : (p + 4 * (r & 1)) & 7;
  for (int q = 0; q < 2; q++) {
    s.pair[NP + q].nitems = SPARE_N;
    for (int i = 0; i < SPARE_N; i++) {
      const int r = sround[SPARE_N][q][i];
      s.pair[NP + q].item[i] = (uint8_t)((r * 8 + used[r][6]++) * 8 + 6);
      for (int p = 0; p < NP; p++) if (jv[r][p] == 6) { jv[r][p] = -2; break; }
    }
  }
  auto cost = [&](int p) {
    int u = 8 - ((p >> 4) < SPARE_N ? 21 : 22), z = 0, none = 0;
    for (int r = 0; r < 4; r++) { u += jv[r][p]; z += jv[r][p] == 0; none += jv[r][p] < 0; }
    return 4 * u * u + (z > 1) + 4 * (none > 1);
  };
  uint32_t rng = SEED;
  for (int it = 0; it < 2000000; it++) {
    if ((it & 255) == 0) { int t = 0; for (int p = 0; p < NP; p++) t += cost(p); if (t == 0) break; }
    rng = rng * 1664525u + 1013904223u;
    const int r = (rng >> 8) & 3, a = (rng >> 12) & 63, b = (rng >> 20) & 63, before = cost(a) + cost(b);
    int t = jv[r][a]; jv[r][a] = jv[r][b]; jv[r][b] = t;
    if (cost(a) + cost(b) > before) { jv[r][b] = jv[r][a]; jv[r][a] = t; }
  }
  int fin[256], done[256];
  for (int p = 0; p < NP + 2; p++) {
    Sched::Pair& q = s.pair[p];
    if (p < NP) {
      for (int k = 0; k < 4; k++) q.khead[k] = (uint8_t)(korder[k] * 8 + (p >> 3));
      for (int r = 0; r < 4; r++) {
        if (jv[r][p] < 0) continue;
        q.item[q.nitems++] = (uint8_t)((r * 8 + used[r][jv[r][p]]++) * 8 + jv[r][p]);
      }
    }
    int t = p < NP ? 0 : -3, e = 1;
    for (int i = 0; i < q.nitems; i++) { t += (q.item[i] & 7) + 2; fin[q.item[i]] = t; done[q.item[i]] = t + (i + 1 < q.nitems ? 2 : 0); e += 8 + 4 * ((q.item[i] & 7) + 1); }
    for (int k = 0; k < 3 * MAX_STEPS + 6; k++) {
      const int n = k > 0 ? k - (SPARE_N & 1) : 0, r = n % 7, f = (e + (r < 4 ? r : r - 1)) % 12;
      q.oent[k] = (uint8_t)((r == 4 ? 6 : f >= 6 ? f + 2 : f) ^ (((n / 7) & 1) << 3));
    }
  }
  for (int p = 0; p < NP + 2; p++)
    for (int i = 0; i < s.pair[p].nitems; i++) {
      const int it = s.pair[p].item[i];
      for (int n = 0; n < 2 * (it & 7) + 2; n++) {
        bool last = true;
        for (int j = n >> 1; j < 8; j++) { const int o = (it & ~7) + j; if (o != it && fin[o] + LU_MARGIN > fin[it]) last = false; }
        if (last) s.pair[p].lastuse[i] |= (uint16_t)(1 << n);
      }
    }
  for (int j = 0; j < 8; j++) {
    int order[NH], left[4];
    for (int h = 0; h < NH; h++) { int k = h; for (; k > 0 && done[order[k - 1] * 8 + j] < done[h * 8 + j]; k--) order[k] = order[k - 1]; order[k] = h; }
    for (int kq = 0; kq < 4; kq++) {
      left[kq] = SPARE_N == 0 ? 16 : kq < SPARE_N ? 20 - SPARE_N : 16 - SPARE_N;
      for (int nh = 0; nh < 2; nh++) { Sched::Pair& q = s.pair[kq * 16 + nh * 8 + j]; q.otask = (uint8_t)(kq * 16 + nh * 8 + j); q.nsteps = (uint8_t)((left[kq] + 1) / 2); q.ochunk[0][0] = 255; }
    }
    for (int n = 0, kq = 0, run = 0; n < 64; ) {
      if (left[kq] > 0 && run < 2) {
        const int pos = --left[kq] + (SPARE_N & 1);
        for (int nh = 0; nh < 2; nh++) s.pair[kq * 16 + nh * 8 + j].ochunk[pos >> 1][pos & 1] = (uint8_t)(order[n >> 1] * 2 + 1 - (n & 1));
        n++; run++;
      } else { kq = (kq + 1) & 3; run = 0; }
    }
  }
}

}

extern "C" void kernel_launch(void* const* d_in, const int* in_sizes, int n_in, void* d_out, int out_size) {
  (void)in_sizes; (void)n_in; (void)out_size;
  const __nv_bfloat16* x     = (const __nv_bfloat16*)d_in[0];
  const __nv_bfloat16* ckv   = (const __nv_bfloat16*)d_in[1];
  const __nv_bfloat16* w_q   = (const __nv_bfloat16*)d_in[2];
  const __nv_bfloat16* w_uk  = (const __nv_bfloat16*)d_in[3];
  const __nv_bfloat16* w_uv  = (const __nv_bfloat16*)d_in[4];
  const __nv_bfloat16* w_o   = (const __nv_bfloat16*)d_in[5];
  const __nv_bfloat16* w_r   = (const __nv_bfloat16*)d_in[7];
  const __nv_bfloat16* w_g   = (const __nv_bfloat16*)d_in[8];
  const __nv_bfloat16* w_u   = (const __nv_bfloat16*)d_in[9];
  const __nv_bfloat16* w_d   = (const __nv_bfloat16*)d_in[10];
  const __nv_bfloat16* cvec  = (const __nv_bfloat16*)d_in[11];
  const __nv_bfloat16* w_mod = (const __nv_bfloat16*)d_in[12];
  __nv_bfloat16* out = (__nv_bfloat16*)d_out;

  static HostState st;
  if (!st.ready) {
    void* fn = nullptr; cudaDriverEntryPointQueryResult qr;
    cudaGetDriverEntryPoint("cuTensorMapEncodeTiled", &fn, cudaEnableDefault, &qr);
    st.encode = (EncodeFn)fn;
    cudaFuncSetAttribute(k_fused, cudaFuncAttributeMaxDynamicSharedMemorySize, SMEM);
    build_sched(st.sched);
    void *p_kvc, *p_h1, *p_part;
    cudaGetSymbolAddress(&p_kvc, g_kvc); cudaGetSymbolAddress(&p_h1, g_h1); cudaGetSymbolAddress(&p_part, g_part);
    st.sched.kvc = (__nv_bfloat16*)p_kvc; st.sched.h1 = (__nv_bfloat16*)p_h1; st.sched.part = (__nv_bfloat16*)p_part;
    st.ready = true;
  }
  make_2d(st.encode, &st.tmC, ckv, SEQ, DM, 128);
  make_2d(st.encode, &st.tmWq, w_q, DM, NH * DH, 64);
  make_2d(st.encode, &st.tmWk, w_uk, DM, NH * DH, 64);
  make_2d(st.encode, &st.tmWv, w_uv, DM, NH * DH, 64);
  make_3d(st.encode, &st.tmWo, w_o, NH * DH, DM / 64, (size_t)DM * 2, 128);
  make_3d(st.encode, &st.tmWm, w_mod, DM, 6 * DM / 64, (size_t)6 * DM * 2, 128);
  make_ffn(st.encode, &st.tmWg, w_g);
  make_ffn(st.encode, &st.tmWu, w_u);

  k_fused<<<NGRID, 384, SMEM, cudaStreamPerThread>>>(st.tmC, st.tmWq, st.tmWk, st.tmWv, st.tmWo, st.tmWg, st.tmWu, st.tmWm, st.sched,
                                                     x, cvec, w_o, w_r, w_g, w_u, w_d, out);
}
```

```cpp
#include <cuda_runtime.h>
#include <cuda_bf16.h>
#include <cuda.h>
#include <stdint.h>
#include <string.h>
#include <math.h>

namespace {

constexpr int SEQ = 2048, DM = 512, NH = 32, DH = 128, FF = 1792;
constexpr int NCTA = 128, NGRID = 132;

__device__ __align__(128) __nv_bfloat16 g_kvc[192 * SEQ * 64];
__device__ __align__(128) __nv_bfloat16 g_h1[SEQ * DM];
__device__ __align__(128) __nv_bfloat16 g_part[128 * 8 * 4096];
__device__ __align__(16) __nv_bfloat16 g_mod[6 * DM];
constexpr int C_MOD = 0, C_MOD2 = 16, C_H1 = 32, C_KV = 64, C_CTX = 128, C_PART = 384, C_END = C_PART + 32 * 32;
__device__ __align__(128) unsigned int g_cnt[C_END];
__device__ unsigned int g_epoch;
__device__ __align__(128) uint2 g_keys[128][4];
__device__ __align__(16) uint2 g_row[128][2][DM / 2];
__device__ __align__(16) uint2 g_yll[FF / 16][DM];

#define DBG(i)
#define DBGP(i)

__device__ __forceinline__ uint32_t smem_u32(const void* p) { return (uint32_t)__cvta_generic_to_shared(p); }
__device__ __forceinline__ int wg_tid() { int t; asm volatile("mov.u32 %0, %%tid.x;" : "=r"(t)); return t & 127; }
__device__ __forceinline__ uint32_t clk32() { uint32_t c; asm volatile("mov.u32 %0, %%clock;" : "=r"(c)); return c; }
__device__ __forceinline__ void mbar_arrive(uint32_t bar) { asm volatile("mbarrier.arrive.shared::cta.b64 _, [%0];" :: "r"(bar) : "memory"); }
__device__ __forceinline__ uint32_t mapa(uint32_t addr, uint32_t cta) { uint32_t r; asm("mapa.shared::cluster.u32 %0, %1, %2;" : "=r"(r) : "r"(addr), "r"(cta)); return r; }
__device__ __forceinline__ void mbar_arrive_remote_if(uint32_t cluster_addr, bool pred) {
  asm volatile("{\n.reg .pred p;\nsetp.ne.u32 p, %1, 0;\n@p mbarrier.arrive.shared::cluster.b64 _, [%0];\n}" :: "r"(cluster_addr), "r"((uint32_t)pred) : "memory");
}
__device__ __forceinline__ bool mbar_try(uint32_t bar, uint32_t parity) {
  uint32_t done;
  asm volatile("{\n.reg .pred p;\nmbarrier.try_wait.parity.shared::cta.b64 p, [%1], %2;\nselp.u32 %0, 1, 0, p;\n}" : "=r"(done) : "r"(bar), "r"(parity) : "memory");
  return done;
}
__device__ __forceinline__ bool mbar_test2(uint32_t bar, uint32_t parity) {
  uint32_t done;
  asm volatile("{\n.reg .pred p, q;\nmbarrier.test_wait.parity.shared::cta.b64 p, [%1], %2;\nmbarrier.test_wait.parity.shared::cta.b64 q, [%1 + 8], %2;\n"
               "and.pred p, p, q;\nselp.u32 %0, 1, 0, p;\n}" : "=r"(done) : "r"(bar), "r"(parity) : "memory");
  return done;
}
#define WAIT_LIM (1 << 14)
__device__ __forceinline__ void mbar_wait(uint32_t bar, uint32_t parity) {
  #pragma unroll 1
  for (int n = 0; n < WAIT_LIM; n++) { if (mbar_try(bar, parity)) break; }
}
__device__ __forceinline__ unsigned int ld_acquire(const unsigned int* p) {
  unsigned int v; asm volatile("ld.acquire.gpu.global.u32 %0, [%1];" : "=r"(v) : "l"(p) : "memory"); return v;
}
__device__ __forceinline__ unsigned int ld_relaxed(const unsigned int* p) {
  unsigned int v; asm volatile("ld.relaxed.gpu.global.u32 %0, [%1];" : "=r"(v) : "l"(p) : "memory"); return v;
}
__device__ __forceinline__ void wait_count_lazy(int idx, unsigned int target) {
  #pragma unroll 1
  for (int n = 0; n < WAIT_LIM; n++) { if (__all_sync(0xffffffff, (int)(ld_relaxed(&g_cnt[idx]) - target) >= 0)) break; __nanosleep(100); }
  ld_acquire(&g_cnt[idx]);
}
__device__ __forceinline__ uint4 ld_tagged2(const void* p) {
  uint4 v;
  asm volatile("{\n.reg .b64 a, b;\nld.relaxed.gpu.global.v2.u64 {a, b}, [%4];\nmov.b64 {%0, %1}, a;\nmov.b64 {%2, %3}, b;\n}"
    : "=r"(v.x), "=r"(v.y), "=r"(v.z), "=r"(v.w) : "l"(p) : "memory");
  return v;
}
__device__ __forceinline__ uint2 ld_tagged(const void* p) {
  uint2 v; asm volatile("{\n.reg .b64 a;\nld.relaxed.gpu.global.u64 a, [%2];\nmov.b64 {%0, %1}, a;\n}" : "=r"(v.x), "=r"(v.y) : "l"(p) : "memory"); return v;
}
__device__ __forceinline__ void st_tagged2(void* p, uint32_t a, uint32_t b, uint32_t tag) {
  asm volatile("{\n.reg .b64 a, b;\nmov.b64 a, {%1, %3};\nmov.b64 b, {%2, %3};\nst.relaxed.gpu.global.v2.u64 [%0], {a, b};\n}" :: "l"(p), "r"(a), "r"(b), "r"(tag) : "memory");
}
__device__ __forceinline__ void st_tagged(void* p, uint32_t a, uint32_t tag) {
  asm volatile("{\n.reg .b64 a;\nmov.b64 a, {%1, %2};\nst.relaxed.gpu.global.u64 [%0], a;\n}" :: "l"(p), "r"(a), "r"(tag) : "memory");
}
__device__ __forceinline__ void stg_v4(void* p, uint32_t a, uint32_t b, uint32_t c, uint32_t d) {
  asm volatile("st.global.v4.u32 [%0], {%1, %2, %3, %4};" :: "l"(p), "r"(a), "r"(b), "r"(c), "r"(d) : "memory");
}
__device__ __forceinline__ uint4 lds_v4(uint32_t addr) {
  uint4 v; asm volatile("ld.shared.v4.u32 {%0, %1, %2, %3}, [%4];" : "=r"(v.x), "=r"(v.y), "=r"(v.z), "=r"(v.w) : "r"(addr) : "memory"); return v;
}
__device__ __forceinline__ uint32_t lds_u32(uint32_t addr) { uint32_t v; asm volatile("ld.shared.u32 %0, [%1];" : "=r"(v) : "r"(addr) : "memory"); return v; }
__device__ __forceinline__ void sts_v4(uint32_t addr, uint32_t a, uint32_t b, uint32_t c, uint32_t d) {
  asm volatile("st.shared.v4.u32 [%0], {%1, %2, %3, %4};" :: "r"(addr), "r"(a), "r"(b), "r"(c), "r"(d) : "memory");
}
#define ELECT "{\n.reg .pred p;\nelect.sync _|p, 0xffffffff;\n@p "
__device__ __forceinline__ void w_mbar_init(uint32_t bar, uint32_t cnt) { asm volatile(ELECT "mbarrier.init.shared::cta.b64 [%0], %1;\n}" :: "r"(bar), "r"(cnt) : "memory"); }
__device__ __forceinline__ void w_expect_tx(uint32_t bar, uint32_t bytes) { asm volatile(ELECT "mbarrier.arrive.expect_tx.shared::cta.b64 _, [%0], %1;\n}" :: "r"(bar), "r"(bytes) : "memory"); }
__device__ __forceinline__ void w_arrive(uint32_t bar) { asm volatile(ELECT "mbarrier.arrive.shared::cta.b64 _, [%0];\n}" :: "r"(bar) : "memory"); }
__device__ __forceinline__ void tma_load_2d(uint32_t dst, const CUtensorMap* tm, uint32_t bar, int c0, int c1) {
  asm volatile(ELECT "cp.async.bulk.tensor.2d.shared::cluster.global.mbarrier::complete_tx::bytes [%0], [%1, {%3, %4}], [%2];\n}"
    :: "r"(dst), "l"(tm), "r"(bar), "r"(c0), "r"(c1) : "memory");
}
__device__ __forceinline__ void tma_load_2d_mc(uint32_t dst, const CUtensorMap* tm, uint32_t bar, int c0, int c1) {
  asm volatile(ELECT "cp.async.bulk.tensor.2d.shared::cluster.global.mbarrier::complete_tx::bytes.multicast::cluster [%0], [%1, {%3, %4}], [%2], %5;\n}"
    :: "r"(dst), "l"(tm), "r"(bar), "r"(c0), "r"(c1), "h"((uint16_t)3) : "memory");
}
__device__ __forceinline__ void tma_load_3d(uint32_t dst, const CUtensorMap* tm, uint32_t bar, int c0, int c1, int c2) {
  asm volatile(ELECT "cp.async.bulk.tensor.3d.shared::cluster.global.mbarrier::complete_tx::bytes [%0], [%1, {%3, %4, %5}], [%2];\n}"
    :: "r"(dst), "l"(tm), "r"(bar), "r"(c0), "r"(c1), "r"(c2) : "memory");
}
__device__ __forceinline__ void tma_load_3d_mc(uint32_t dst, const CUtensorMap* tm, uint32_t bar, int c0, int c1, int c2) {
  asm volatile(ELECT "cp.async.bulk.tensor.3d.shared::cluster.global.mbarrier::complete_tx::bytes.multicast::cluster [%0], [%1, {%3, %4, %5}], [%2], %6;\n}"
    :: "r"(dst), "l"(tm), "r"(bar), "r"(c0), "r"(c1), "r"(c2), "h"((uint16_t)3) : "memory");
}
__device__ __forceinline__ void bulk_load_mc(uint32_t dst, const void* src, uint32_t bar, bool ef) {
  if (ef) {
    uint64_t pol; asm("createpolicy.fractional.L2::evict_first.b64 %0, 1.0;" : "=l"(pol));
    asm volatile(ELECT "cp.async.bulk.shared::cluster.global.mbarrier::complete_tx::bytes.multicast::cluster.L2::cache_hint [%0], [%1], 16384, [%2], %3, %4;\n}"
      :: "r"(dst), "l"(src), "r"(bar), "h"((uint16_t)3), "l"(pol) : "memory");
  } else
    asm volatile(ELECT "cp.async.bulk.shared::cluster.global.mbarrier::complete_tx::bytes.multicast::cluster [%0], [%1], 16384, [%2], %3;\n}"
      :: "r"(dst), "l"(src), "r"(bar), "h"((uint16_t)3) : "memory");
}
__device__ __forceinline__ void bulk_load(uint32_t dst, const void* src, uint32_t bytes, uint32_t bar) {
  asm volatile(ELECT "cp.async.bulk.shared::cluster.global.mbarrier::complete_tx::bytes [%0], [%1], %2, [%3];\n}" :: "r"(dst), "l"(src), "r"(bytes), "r"(bar) : "memory");
}
__device__ __forceinline__ void tma_prefetch_2d(const CUtensorMap* tm, int c0, int c1) {
  asm volatile(ELECT "cp.async.bulk.prefetch.tensor.2d.L2.global [%0, {%1, %2}];\n}" :: "l"(tm), "r"(c0), "r"(c1) : "memory");
}
__device__ __forceinline__ void bulk_prefetch(const void* p, uint32_t bytes) {
  asm volatile(ELECT "cp.async.bulk.prefetch.L2.global [%0], %1;\n}" :: "l"(p), "r"(bytes) : "memory");
}
__device__ __forceinline__ void red_release(int idx) { asm volatile("red.release.gpu.global.add.u32 [%0], 1;" :: "l"(&g_cnt[idx]) : "memory"); }
__device__ __forceinline__ void prefetch_tmap(const CUtensorMap* tm) { asm volatile("prefetch.tensormap [%0];" :: "l"(tm) : "memory"); }
__device__ __forceinline__ void bar_sync(int id, int n) { asm volatile("bar.sync %0, %1;" :: "r"(id), "r"(n) : "memory"); }
__device__ __forceinline__ void bar_arrive(int id, int n) { asm volatile("bar.arrive %0, %1;" :: "r"(id), "r"(n) : "memory"); }
__device__ __forceinline__ void fence_async_smem() { asm volatile("fence.proxy.async.shared::cta;" ::: "memory"); }
__device__ __forceinline__ void fence_async_global() { asm volatile("fence.proxy.async.global;" ::: "memory"); }
__device__ __forceinline__ void fence_mbar_init() { asm volatile("fence.mbarrier_init.release.cluster;" ::: "memory"); }
__device__ __forceinline__ void cluster_arrive() { asm volatile("barrier.cluster.arrive.relaxed.aligned;" ::: "memory"); }
__device__ __forceinline__ void cluster_wait() { asm volatile("barrier.cluster.wait.aligned;" ::: "memory"); }
__device__ __forceinline__ uint32_t cluster_ctarank() { uint32_t r; asm volatile("mov.u32 %0, %%cluster_ctarank;" : "=r"(r)); return r; }
__device__ __forceinline__ void wgmma_fence() { asm volatile("wgmma.fence.sync.aligned;" ::: "memory"); }
__device__ __forceinline__ void wgmma_commit() { asm volatile("wgmma.commit_group.sync.aligned;" ::: "memory"); }
template<int N> __device__ __forceinline__ void wgmma_wait() { asm volatile("wgmma.wait_group.sync.aligned %0;" :: "n"(N) : "memory"); }
__device__ __forceinline__ float ex2(float x) { float y; asm("ex2.approx.ftz.f32 %0, %1;" : "=f"(y) : "f"(x)); return y; }
__device__ __forceinline__ float rcp_fast(float x) { float y; asm("rcp.approx.ftz.f32 %0, %1;" : "=f"(y) : "f"(x)); return y; }
__device__ __forceinline__ uint32_t pack_bf16(float lo, float hi) { uint32_t r; asm("cvt.rn.bf16x2.f32 %0, %1, %2;" : "=r"(r) : "f"(hi), "f"(lo)); return r; }
__device__ __forceinline__ float rbf(float x) { return __uint_as_float(pack_bf16(0.f, x)); }
__device__ __forceinline__ float bf_lo(uint32_t v) { return __uint_as_float(v << 16); }
__device__ __forceinline__ float bf_hi(uint32_t v) { return __uint_as_float(v & 0xffff0000u); }
__device__ __forceinline__ uint32_t add2(uint32_t a, uint32_t b) { uint32_t r; asm("add.rn.bf16x2 %0, %1, %2;" : "=r"(r) : "r"(a), "r"(b)); return r; }
__device__ __forceinline__ uint32_t fma2(uint32_t a, uint32_t b, uint32_t c) { uint32_t r; asm("fma.rn.bf16x2 %0, %1, %2, %3;" : "=r"(r) : "r"(a), "r"(b), "r"(c)); return r; }
__device__ __forceinline__ uint4 ldsm_x4_t(uint32_t addr) {
  uint4 v; asm volatile("ldmatrix.sync.aligned.m8n8.x4.trans.shared.b16 {%0, %1, %2, %3}, [%4];" : "=r"(v.x), "=r"(v.y), "=r"(v.z), "=r"(v.w) : "r"(addr) : "memory"); return v;
}
__device__ __forceinline__ uint4 ldsm_x4(uint32_t addr) {
  uint4 v; asm volatile("ldmatrix.sync.aligned.m8n8.x4.shared.b16 {%0, %1, %2, %3}, [%4];" : "=r"(v.x), "=r"(v.y), "=r"(v.z), "=r"(v.w) : "r"(addr) : "memory"); return v;
}
__device__ __forceinline__ void mma16816(float (&c)[4], const uint4& a, uint32_t b0, uint32_t b1) {
  asm("mma.sync.aligned.m16n8k16.row.col.f32.bf16.bf16.f32 {%0, %1, %2, %3}, {%4, %5, %6, %7}, {%8, %9}, {%0, %1, %2, %3};"
    : "+f"(c[0]), "+f"(c[1]), "+f"(c[2]), "+f"(c[3]) : "r"(a.x), "r"(a.y), "r"(a.z), "r"(a.w), "r"(b0), "r"(b1));
}
template<int N> __device__ __forceinline__ void fence_regs(float (&a)[N]) {
  #pragma unroll
  for (int i = 0; i < N; i++) asm volatile("" : "+f"(a[i]) :: "memory");
}
template<int N> __device__ __forceinline__ void fence_regs_u(uint32_t (&a)[N]) {
  #pragma unroll
  for (int i = 0; i < N; i++) asm volatile("" : "+r"(a[i]) :: "memory");
}
constexpr uint32_t SW128 = 0x40000040u, SW64 = 0x80000020u;
__device__ __forceinline__ uint32_t desc_lo(uint32_t addr, uint32_t lbo) { return ((addr & 0x3FFFF) >> 4) | ((lbo >> 4) << 16); }

template<int TB, int OA, int OB, uint32_t HA, uint32_t HB> __device__ __forceinline__ void wgmma_ss_n128(float (&d)[64], uint32_t da, uint32_t db, int sd) {
  asm volatile("{\n.reg .pred p;\n.reg .b32 ta, tb;\n.reg .b64 da, db;\nsetp.ne.b32 p, %66, 0;\nadd.u32 ta, %64, %68;\nadd.u32 tb, %65, %69;\nmov.b64 da, {ta, %70};\nmov.b64 db, {tb, %71};\n"
    "wgmma.mma_async.sync.aligned.m64n128k16.f32.bf16.bf16 "
    "{%0, %1, %2, %3, %4, %5, %6, %7, %8, %9, %10, %11, %12, %13, %14, %15, %16, %17, %18, %19, %20, %21, %22, %23, %24, %25, %26, %27, %28, %29, %30, %31, %32, %33, %34, %35, %36, %37, %38, %39, %40, %41, %42, %43, %44, %45, %46, %47, %48, %49, %50, %51, %52, %53, %54, %55, %56, %57, %58, %59, %60, %61, %62, %63}, da, db, p, 1, 1, 0, %67;\n}\n"
    : "+f"(d[0]), "+f"(d[1]), "+f"(d[2]), "+f"(d[3]), "+f"(d[4]), "+f"(d[5]), "+f"(d[6]), "+f"(d[7]), "+f"(d[8]), "+f"(d[9]), "+f"(d[10]), "+f"(d[11]), "+f"(d[12]), "+f"(d[13]), "+f"(d[14]), "+f"(d[15]), "+f"(d[16]), "+f"(d[17]), "+f"(d[18]), "+f"(d[19]), "+f"(d[20]), "+f"(d[21]), "+f"(d[22]), "+f"(d[23]), "+f"(d[24]), "+f"(d[25]), "+f"(d[26]), "+f"(d[27]), "+f"(d[28]), "+f"(d[29]), "+f"(d[30]), "+f"(d[31]), "+f"(d[32]), "+f"(d[33]), "+f"(d[34]), "+f"(d[35]), "+f"(d[36]), "+f"(d[37]), "+f"(d[38]), "+f"(d[39]), "+f"(d[40]), "+f"(d[41]), "+f"(d[42]), "+f"(d[43]), "+f"(d[44]), "+f"(d[45]), "+f"(d[46]), "+f"(d[47]), "+f"(d[48]), "+f"(d[49]), "+f"(d[50]), "+f"(d[51]), "+f"(d[52]), "+f"(d[53]), "+f"(d[54]), "+f"(d[55]), "+f"(d[56]), "+f"(d[57]), "+f"(d[58]), "+f"(d[59]), "+f"(d[60]), "+f"(d[61]), "+f"(d[62]), "+f"(d[63])
    : "r"(da), "r"(db), "r"(sd), "n"(TB), "n"(OA), "n"(OB), "n"(HA), "n"(HB));
}
template<int TB, int OB, uint32_t HB> __device__ __forceinline__ void wgmma_rs_n128(float (&d)[64], uint32_t a0, uint32_t a1, uint32_t a2, uint32_t a3, uint32_t db, int sd) {
  asm volatile("{\n.reg .pred p;\n.reg .b32 tb;\n.reg .b64 db;\nsetp.ne.b32 p, %69, 0;\nadd.u32 tb, %68, %71;\nmov.b64 db, {tb, %72};\n"
    "wgmma.mma_async.sync.aligned.m64n128k16.f32.bf16.bf16 "
    "{%0, %1, %2, %3, %4, %5, %6, %7, %8, %9, %10, %11, %12, %13, %14, %15, %16, %17, %18, %19, %20, %21, %22, %23, %24, %25, %26, %27, %28, %29, %30, %31, %32, %33, %34, %35, %36, %37, %38, %39, %40, %41, %42, %43, %44, %45, %46, %47, %48, %49, %50, %51, %52, %53, %54, %55, %56, %57, %58, %59, %60, %61, %62, %63}, {%64,%65,%66,%67}, db, p, 1, 1, %70;\n}\n"
    : "+f"(d[0]), "+f"(d[1]), "+f"(d[2]), "+f"(d[3]), "+f"(d[4]), "+f"(d[5]), "+f"(d[6]), "+f"(d[7]), "+f"(d[8]), "+f"(d[9]), "+f"(d[10]), "+f"(d[11]), "+f"(d[12]), "+f"(d[13]), "+f"(d[14]), "+f"(d[15]), "+f"(d[16]), "+f"(d[17]), "+f"(d[18]), "+f"(d[19]), "+f"(d[20]), "+f"(d[21]), "+f"(d[22]), "+f"(d[23]), "+f"(d[24]), "+f"(d[25]), "+f"(d[26]), "+f"(d[27]), "+f"(d[28]), "+f"(d[29]), "+f"(d[30]), "+f"(d[31]), "+f"(d[32]), "+f"(d[33]), "+f"(d[34]), "+f"(d[35]), "+f"(d[36]), "+f"(d[37]), "+f"(d[38]), "+f"(d[39]), "+f"(d[40]), "+f"(d[41]), "+f"(d[42]), "+f"(d[43]), "+f"(d[44]), "+f"(d[45]), "+f"(d[46]), "+f"(d[47]), "+f"(d[48]), "+f"(d[49]), "+f"(d[50]), "+f"(d[51]), "+f"(d[52]), "+f"(d[53]), "+f"(d[54]), "+f"(d[55]), "+f"(d[56]), "+f"(d[57]), "+f"(d[58]), "+f"(d[59]), "+f"(d[60]), "+f"(d[61]), "+f"(d[62]), "+f"(d[63])
    : "r"(a0), "r"(a1), "r"(a2), "r"(a3), "r"(db), "r"(sd), "n"(TB), "n"(OB), "n"(HB));
}
template<int TB, int OA, int OB, uint32_t HA, uint32_t HB> __device__ __forceinline__ void wgmma_ss_n64(float (&d)[32], uint32_t da, uint32_t db, int sd) {
  asm volatile("{\n.reg .pred p;\n.reg .b32 ta, tb;\n.reg .b64 da, db;\nsetp.ne.b32 p, %34, 0;\nadd.u32 ta, %32, %36;\nadd.u32 tb, %33, %37;\nmov.b64 da, {ta, %38};\nmov.b64 db, {tb, %39};\n"
    "wgmma.mma_async.sync.aligned.m64n64k16.f32.bf16.bf16 "
    "{%0, %1, %2, %3, %4, %5, %6, %7, %8, %9, %10, %11, %12, %13, %14, %15, %16, %17, %18, %19, %20, %21, %22, %23, %24, %25, %26, %27, %28, %29, %30, %31}, da, db, p, 1, 1, 0, %35;\n}\n"
    : "+f"(d[0]), "+f"(d[1]), "+f"(d[2]), "+f"(d[3]), "+f"(d[4]), "+f"(d[5]), "+f"(d[6]), "+f"(d[7]), "+f"(d[8]), "+f"(d[9]), "+f"(d[10]), "+f"(d[11]), "+f"(d[12]), "+f"(d[13]), "+f"(d[14]), "+f"(d[15]), "+f"(d[16]), "+f"(d[17]), "+f"(d[18]), "+f"(d[19]), "+f"(d[20]), "+f"(d[21]), "+f"(d[22]), "+f"(d[23]), "+f"(d[24]), "+f"(d[25]), "+f"(d[26]), "+f"(d[27]), "+f"(d[28]), "+f"(d[29]), "+f"(d[30]), "+f"(d[31])
    : "r"(da), "r"(db), "r"(sd), "n"(TB), "n"(OA), "n"(OB), "n"(HA), "n"(HB));
}
template<int TB, int OA, int OB, uint32_t HA, uint32_t HB> __device__ __forceinline__ void wgmma_ss_n128_new(float (&d)[64], uint32_t da, uint32_t db) {
  asm volatile("{\n.reg .pred p;\n.reg .b32 ta, tb;\n.reg .b64 da, db;\nsetp.ne.b32 p, %66, 0;\nadd.u32 ta, %64, %68;\nadd.u32 tb, %65, %69;\nmov.b64 da, {ta, %70};\nmov.b64 db, {tb, %71};\n"
    "wgmma.mma_async.sync.aligned.m64n128k16.f32.bf16.bf16 "
    "{%0, %1, %2, %3, %4, %5, %6, %7, %8, %9, %10, %11, %12, %13, %14, %15, %16, %17, %18, %19, %20, %21, %22, %23, %24, %25, %26, %27, %28, %29, %30, %31, %32, %33, %34, %35, %36, %37, %38, %39, %40, %41, %42, %43, %44, %45, %46, %47, %48, %49, %50, %51, %52, %53, %54, %55, %56, %57, %58, %59, %60, %61, %62, %63}, da, db, p, 1, 1, 0, %67;\n}\n"
    : "=f"(d[0]), "=f"(d[1]), "=f"(d[2]), "=f"(d[3]), "=f"(d[4]), "=f"(d[5]), "=f"(d[6]), "=f"(d[7]), "=f"(d[8]), "=f"(d[9]), "=f"(d[10]), "=f"(d[11]), "=f"(d[12]), "=f"(d[13]), "=f"(d[14]), "=f"(d[15]), "=f"(d[16]), "=f"(d[17]), "=f"(d[18]), "=f"(d[19]), "=f"(d[20]), "=f"(d[21]), "=f"(d[22]), "=f"(d[23]), "=f"(d[24]), "=f"(d[25]), "=f"(d[26]), "=f"(d[27]), "=f"(d[28]), "=f"(d[29]), "=f"(d[30]), "=f"(d[31]), "=f"(d[32]), "=f"(d[33]), "=f"(d[34]), "=f"(d[35]), "=f"(d[36]), "=f"(d[37]), "=f"(d[38]), "=f"(d[39]), "=f"(d[40]), "=f"(d[41]), "=f"(d[42]), "=f"(d[43]), "=f"(d[44]), "=f"(d[45]), "=f"(d[46]), "=f"(d[47]), "=f"(d[48]), "=f"(d[49]), "=f"(d[50]), "=f"(d[51]), "=f"(d[52]), "=f"(d[53]), "=f"(d[54]), "=f"(d[55]), "=f"(d[56]), "=f"(d[57]), "=f"(d[58]), "=f"(d[59]), "=f"(d[60]), "=f"(d[61]), "=f"(d[62]), "=f"(d[63])
    : "r"(da), "r"(db), "n"(0), "n"(TB), "n"(OA), "n"(OB), "n"(HA), "n"(HB));
}
template<int TB, int OA, int OB, uint32_t HA, uint32_t HB> __device__ __forceinline__ void wgmma_ss_n64_new(float (&d)[32], uint32_t da, uint32_t db) {
  asm volatile("{\n.reg .pred p;\n.reg .b32 ta, tb;\n.reg .b64 da, db;\nsetp.ne.b32 p, %34, 0;\nadd.u32 ta, %32, %36;\nadd.u32 tb, %33, %37;\nmov.b64 da, {ta, %38};\nmov.b64 db, {tb, %39};\n"
    "wgmma.mma_async.sync.aligned.m64n64k16.f32.bf16.bf16 "
    "{%0, %1, %2, %3, %4, %5, %6, %7, %8, %9, %10, %11, %12, %13, %14, %15, %16, %17, %18, %19, %20, %21, %22, %23, %24, %25, %26, %27, %28, %29, %30, %31}, da, db, p, 1, 1, 0, %35;\n}\n"
    : "=f"(d[0]), "=f"(d[1]), "=f"(d[2]), "=f"(d[3]), "=f"(d[4]), "=f"(d[5]), "=f"(d[6]), "=f"(d[7]), "=f"(d[8]), "=f"(d[9]), "=f"(d[10]), "=f"(d[11]), "=f"(d[12]), "=f"(d[13]), "=f"(d[14]), "=f"(d[15]), "=f"(d[16]), "=f"(d[17]), "=f"(d[18]), "=f"(d[19]), "=f"(d[20]), "=f"(d[21]), "=f"(d[22]), "=f"(d[23]), "=f"(d[24]), "=f"(d[25]), "=f"(d[26]), "=f"(d[27]), "=f"(d[28]), "=f"(d[29]), "=f"(d[30]), "=f"(d[31])
    : "r"(da), "r"(db), "n"(0), "n"(TB), "n"(OA), "n"(OB), "n"(HA), "n"(HB));
}
template<int OA, int OB = 0, uint32_t HA = SW128> __device__ __forceinline__ void kblock_n128(float (&d)[64], uint32_t da, uint32_t db, int sd) {
  constexpr int H = HA == SW128 ? 4 : 512;
  wgmma_ss_n128<1, OA, OB, HA, SW128>(d, da, db, sd); wgmma_ss_n128<1, OA + 2, OB + 128, HA, SW128>(d, da, db, 1);
  wgmma_ss_n128<1, OA + H, OB + 256, HA, SW128>(d, da, db, 1); wgmma_ss_n128<1, OA + H + 2, OB + 384, HA, SW128>(d, da, db, 1);
}

__device__ __forceinline__ float quad_sum(float v) {
  v += __shfl_xor_sync(0xffffffff, v, 1);
  v += __shfl_xor_sync(0xffffffff, v, 2);
  return v;
}
struct Row { uint32_t v[8]; };
template<class F> __device__ __forceinline__ Row load_row(const __nv_bfloat16* p, int lane, F ld) {
  const uint4 a = ld(reinterpret_cast<const uint4*>(p) + lane), b = ld(reinterpret_cast<const uint4*>(p) + 32 + lane);
  return Row{{a.x, a.y, a.z, a.w, b.x, b.y, b.z, b.w}};
}
__device__ __forceinline__ Row ldg_row(const __nv_bfloat16* p, int lane) { return load_row(p, lane, [](const uint4* q) { return __ldg(q); }); }
__device__ __forceinline__ Row ldca_row(const __nv_bfloat16* p, int lane) { return load_row(p, lane, [](const uint4* q) { return __ldca(q); }); }
__device__ __forceinline__ Row lds_row(uint32_t addr, int lane) {
  const uint4 a = lds_v4(addr + lane * 16), b = lds_v4(addr + 512 + lane * 16);
  return Row{{a.x, a.y, a.z, a.w, b.x, b.y, b.z, b.w}};
}
__device__ __forceinline__ void store_row(__nv_bfloat16* p, int lane, const Row& r) {
  stg_v4(p + lane * 8, r.v[0], r.v[1], r.v[2], r.v[3]); stg_v4(p + 256 + lane * 8, r.v[4], r.v[5], r.v[6], r.v[7]);
}
__device__ __forceinline__ Row fma_row(const Row& a, const Row& b, const Row& c) {
  Row r;
  #pragma unroll
  for (int i = 0; i < 8; i++) r.v[i] = fma2(a.v[i], b.v[i], c.v[i]);
  return r;
}
__device__ __forceinline__ Row add_row(const Row& a, const Row& b) {
  Row r;
  #pragma unroll
  for (int i = 0; i < 8; i++) r.v[i] = add2(a.v[i], b.v[i]);
  return r;
}
__device__ __forceinline__ Row one_plus(const Row& a) {
  Row r;
  #pragma unroll
  for (int i = 0; i < 8; i++) r.v[i] = add2(a.v[i], 0x3f803f80u);
  return r;
}
__device__ __forceinline__ float row_at(const Row& x, int i) { return (i & 1) ? bf_hi(x.v[i >> 1]) : bf_lo(x.v[i >> 1]); }
template<int N> __device__ __forceinline__ void warp_sums(float (&s)[N]) {
  #pragma unroll
  for (int o = 16; o > 0; o >>= 1) {
    #pragma unroll
    for (int k = 0; k < N; k++) s[k] += __shfl_xor_sync(0xffffffff, s[k], o);
  }
}
__device__ __forceinline__ void ln_stats(float& s1, float& s2) {
  s1 *= 1.f / DM;
  asm("rsqrt.approx.ftz.f32 %0, %1;" : "=f"(s2) : "f"(fmaxf(fmaf(-s1, s1, s2 * (1.f / DM)), 0.f) + 1e-5f));
}
__device__ __forceinline__ Row ln_apply(const Row& x, float mean, float f) {
  Row n;
  const float o = -mean * f;
  #pragma unroll
  for (int i = 0; i < 8; i++) n.v[i] = pack_bf16(fmaf(bf_lo(x.v[i]), f, o), fmaf(bf_hi(x.v[i]), f, o));
  return n;
}

constexpr int SM_Q = 6 * 32768, SM_BAR = 7 * 32768, SM_MAIL = SM_BAR + 640, SM_RED = SM_MAIL + 128, SM_H2 = SM_RED + 1024, SM_KEY = SM_H2 + 1024, SMEM = SM_KEY + 128;
constexpr int B_AF = 0, B_WF = 64, B_RF = 112, B_WE = 168, B_RE = 216, B_PUB = 272, B_RDY = 496;
constexpr int R_MOD = B_RDY, R_H1 = B_RDY + 8, R_ITEM = B_RDY + 16, R_NEAR = B_RDY + 48, R_CTX = B_RDY + 64;
constexpr int R_KEY = B_AF + 8, R_PART = B_AF + 32;
constexpr int NPUB = 14;
__device__ __forceinline__ uint32_t k_addrA(int kb) { return ((0x6310u >> ((kb >> 1) * 4)) & 15u) * 32768u + (kb & 1) * 16384u; }
__device__ __forceinline__ uint32_t k_addrW(int s) { return ((0x254u >> ((s >> 1) * 4)) & 15u) * 32768u + (s & 1) * 16384u; }

#define KORDER 0x3201
constexpr int KHEAD0 = ((KORDER >> 12) & 3) * 8;
constexpr int MAX_ITEMS = 4;
constexpr int MAX_STEPS = 10;
struct Sched {
  __nv_bfloat16 *kvc, *h1, *part;
  struct Pair {
    uint8_t oent[3 * MAX_STEPS + 6];
    uint16_t lastuse[MAX_ITEMS];
    uint8_t khead[4];
    uint8_t nitems, item[MAX_ITEMS];
    uint8_t otask, nsteps;
    uint8_t ochunk[MAX_STEPS][2];
  } pair[NGRID / 2];
};

__device__ __forceinline__ int ring_add(int e, int n) { e += n; return e >= 12 ? e - 12 : e; }
__device__ __forceinline__ int ring_slot(int e) { return e >= 6 ? e - 6 : e; }
__device__ __forceinline__ void ring_wait_full(uint32_t bars, int e) { mbar_wait(bars + B_RF + 8 * ring_slot(e), e >= 6); }

__device__ __forceinline__ void o_wait_full(uint32_t bars, uint32_t v) { mbar_wait(bars + B_RF + 8 * (v & 7), v >> 3); }

struct Ctx {
  uint32_t base, bars;
  uint32_t rel;
  bool rel1;
  int w, nev;
  const Sched* sched;
  uint32_t tr;
};
#define TR(id)
__device__ __forceinline__ void slot_release(const Ctx& x, int s, bool twice) {
  mbar_arrive_remote_if(x.rel + B_RE + 8 * s, twice ? (wg_tid() & 31) == 0 : x.rel1);
}
__device__ __forceinline__ void ring_release(const Ctx& x, int e, bool twice) { slot_release(x, ring_slot(e), twice); }
__device__ __forceinline__ void publish(Ctx& x, int idx) {
  const uint32_t n = x.w * NPUB + x.nev;
  const int t = wg_tid();
  if (t == 0) asm volatile("st.shared.u32 [%0], %1;" :: "r"(x.base + SM_MAIL + 4 * n), "r"(idx) : "memory");
  __syncwarp();
  if ((t & 31) == 0) mbar_arrive(x.bars + B_PUB + 8 * n);
  x.nev++;
}

template<int KK = 0> __device__ __forceinline__ void issue_qk(float (&S)[64], uint32_t dq, uint32_t dk) {
  constexpr int off = (KK >> 1) * 512 + (KK & 1) * 2;
  if constexpr (KK == 0) wgmma_ss_n128_new<0, 0, 0, SW64, SW64>(S, dq, dk); else wgmma_ss_n128<0, off, off, SW64, SW64>(S, dq, dk, 1);
  if constexpr (KK < 7) issue_qk<KK + 1>(S, dq, dk);
}
template<int KK = 0> __device__ __forceinline__ void issue_qk_half(float (&S)[32], uint32_t dq, uint32_t dk) {
  constexpr int off = (KK >> 1) * 512 + (KK & 1) * 2;
  if constexpr (KK == 0) wgmma_ss_n64_new<0, 0, 256, SW64, SW64>(S, dq, dk); else wgmma_ss_n64<0, off, off + 256, SW64, SW64>(S, dq, dk, 1);
  if constexpr (KK < 7) issue_qk_half<KK + 1>(S, dq, dk);
}
template<int NK, int KK = 0>
__device__ __forceinline__ void issue_pv(float (&O)[64], uint32_t (&P)[32], uint32_t dv, int accumulate) {
  wgmma_rs_n128<1, (KK + 8 - NK) * 64, SW64>(O, P[4*KK], P[4*KK+1], P[4*KK+2], P[4*KK+3], dv, accumulate);
  if constexpr (KK + 1 < NK) issue_pv<NK, KK + 1>(O, P, dv, 1);
}
template<int K0, int K1>
__device__ __forceinline__ void exp_pack(const float (&S)[64], uint32_t (&D)[32], float& s0, float& s1) {
  #pragma unroll
  for (int k = K0; k < K1; k++) {
    const float e0 = ex2(S[2*k]), e1 = ex2(S[2*k+1]);
    D[k] = pack_bf16(e0, e1);
    if (k & 1) s1 += e0 + e1; else s0 += e0 + e1;
  }
}
__device__ __forceinline__ int diag_limit() { const int t = wg_tid(); return 16 * (t >> 5) + ((t & 31) >> 2) - 2 * (t & 3); }
__device__ __forceinline__ void exp_pack_diag(const float (&S)[64], uint32_t (&D)[32], int t, float& s0, float& s1) {
  #pragma unroll
  for (int k = 0; k < 16; k++) {
    const int c = 8 * (k >> 1) - 8 * (k & 1);
    const float e0 = ex2((c <= t) ? S[2*k] : -INFINITY), e1 = ex2((c + 1 <= t) ? S[2*k+1] : -INFINITY);
    D[k] = pack_bf16(e0, e1);
    if (k & 1) s1 += e0 + e1; else s0 += e0 + e1;
  }
}
constexpr float SUM_HI = 1.8446744073709552e19f;
constexpr float SUM_LO = 5.421010862427522e-20f;

__device__ __forceinline__ void classic_tile(const float (&S)[64], uint32_t (&P)[32], bool fresh, bool half, bool was_classic, volatile float* mc,
                                             float& l0, float& l1, float& s0, float& s1, float& sc0, float& sc1) {
  const int tmask = diag_limit();
  float4 t[16];
  #pragma unroll
  for (int j = 0; j < 16; j++) t[j] = make_float4(S[4*j], S[4*j+1], S[4*j+2], S[4*j+3]);
  float mx0 = -INFINITY, mx1 = -INFINITY;
  #pragma unroll 1
  for (int j = 0; j < 16; j++) {
    float4 v = t[j];
    const int lim = !fresh ? 1000 : j < 8 ? tmask - 8 * j : half ? -1000 : 1000;
    v.x = 0 <= lim ? v.x : -INFINITY; v.y = 1 <= lim ? v.y : -INFINITY; v.z = -8 <= lim ? v.z : -INFINITY; v.w = -7 <= lim ? v.w : -INFINITY;
    t[j] = v;
    mx0 = fmaxf(mx0, fmaxf(v.x, v.y)); mx1 = fmaxf(mx1, fmaxf(v.z, v.w));
  }
  mx0 = fmaxf(mx0, __shfl_xor_sync(0xffffffff, mx0, 1));
  mx1 = fmaxf(mx1, __shfl_xor_sync(0xffffffff, mx1, 1));
  mx0 = fmaxf(mx0, __shfl_xor_sync(0xffffffff, mx0, 2));
  mx1 = fmaxf(mx1, __shfl_xor_sync(0xffffffff, mx1, 2));
  const float mc0 = was_classic ? mc[0] : 0.f, mc1 = was_classic ? mc[1] : 0.f;
  const float n0 = fresh ? -mx0 : fminf(mc0, -mx0), n1 = fresh ? -mx1 : fminf(mc1, -mx1);
  sc0 = ex2(n0 - mc0); sc1 = ex2(n1 - mc1);
  mc[0] = n0; mc[1] = n1;
  s0 = 0.f; s1 = 0.f;
  #pragma unroll 1
  for (int j = 0; j < 16; j++) {
    const float4 v = t[j];
    const float e0 = ex2(v.x + n0), e1 = ex2(v.y + n0), e2 = ex2(v.z + n1), e3 = ex2(v.w + n1);
    s0 += e0 + e1; s1 += e2 + e3;
    reinterpret_cast<uint2*>(t)[j] = make_uint2(pack_bf16(e0, e1), pack_bf16(e2, e3));
  }
  #pragma unroll
  for (int j = 0; j < 8; j++) { P[4*j] = __float_as_uint(t[j].x); P[4*j+1] = __float_as_uint(t[j].y); P[4*j+2] = __float_as_uint(t[j].z); P[4*j+3] = __float_as_uint(t[j].w); }
  if (!fresh) { l0 *= sc0; l1 *= sc1; }
}
__device__ __forceinline__ void pack_tile(const float (&A)[64], uint32_t (&D)[32], float f0, float f1) {
  #pragma unroll
  for (int j = 0; j < 16; j++) {
    D[8 * (j >> 2) + (j & 3)] = pack_bf16(A[4*j] * f0, A[4*j+1] * f0);
    D[8 * (j >> 2) + 4 + (j & 3)] = pack_bf16(A[4*j+2] * f1, A[4*j+3] * f1);
  }
}
__device__ __forceinline__ int piece0(int t) { return ((t >> 5) * 16 + ((t & 31) >> 2)) * 32 + (((t ^ (t >> 3)) & 3) << 3); }
__device__ __forceinline__ void store_tile(__nv_bfloat16* p, const uint32_t (&D)[32]) {
  #pragma unroll
  for (int i = 0; i < 8; i++) stg_v4(p + (i >> 2) * (SEQ * 64) + ((i >> 1) & 1) * 4096 + (i & 1) * 256, D[4*i], D[4*i+1], D[4*i+2], D[4*i+3]);
}

enum : int { PV_ACC = 0, PV_ZERO = 1, PV_HALF = 2, PV_NONE = 3 };
struct Att {
  float l0, l1, i0, i1;
  bool classic;
  volatile float* mc;
};
__device__ __forceinline__ void store_ctx(Ctx& x, int code, const uint32_t (&D)[32]) {
  store_tile(x.sched->kvc + ((size_t)(128 + (code >> 5) * 2) * SEQ + ((code >> 1) & 15) * 128) * 64 + (code & 1) * 2048 + piece0(wg_tid()), D);
  publish(x, C_CTX + (code >> 2));
}
__device__ __forceinline__ __nv_bfloat16* kv_tile(const Ctx& x, int code) {
  return x.sched->kvc + ((size_t)(x.w * 64 + (code >> 4) * 2) * SEQ + (code & 15) * 128) * 64 + piece0(wg_tid());
}
#define NO_CLASSIC 0
__device__ __forceinline__ void q_proj(Ctx& x, Att& a, int& e, int& sk, int& sv, int& en, int& sn, bool isY,
                                       const uint32_t (&PA)[32], const uint32_t (&PB)[32], int vtile, bool first, bool dbg = false) {
  float S[64];
  int ek = 0, s = sk, ps = 0, ph = e >= 6, kb = 0;
  uint32_t qa = 0;
  sv = en = sn = 0;
  if (isY) bar_sync(1 + x.w, 256);
  if (dbg) DBG(80);
  TR(1);
  if (first) mbar_wait(x.bars + B_RF + 8 * s, ph);
  #pragma unroll 1
  while (true) {
    #pragma unroll 1
    do {
      if (dbg) DBG(81 + kb);
      TR(2);
      wgmma_fence();
      kblock_n128<0>(S, desc_lo(x.base + x.w * 8192, 16) + s * 2048, desc_lo(x.base + 16384, 8192) + s * 2048, kb != 0);
      wgmma_commit();
      if (kb == 7 && !isY) bar_arrive(1 + (x.w ^ 1), 256);
      wgmma_wait<1>();
      mbar_arrive_remote_if(x.rel + B_RE + 8 * ps, x.rel1 && kb > 0);
      ps = s;
      if (++s == 6) { s = 0; ph ^= 1; }
      if (++kb == 8) break;
      mbar_wait(x.bars + B_RF + 8 * s, ph);
    } while (kb != 4);
    asm volatile("" : "+r"(vtile));
    if (kb == 8) break;
    a.i0 = rcp_fast(quad_sum(a.l0)); a.i1 = rcp_fast(quad_sum(a.l1));
    e = ring_add(e, 8); ek = ring_add(e, isY ? 0 : 2); en = ring_add(e, isY ? 2 : 4);
    sk = ring_slot(ek); sv = ring_slot(e) + 1; sn = ring_slot(en);
    qa = x.base + SM_Q + x.w * 4096 + piece0(wg_tid()) * 2;
    if (vtile >= 0) store_tile(kv_tile(x, vtile) + 2048, PA);
  }
  if (vtile >= 0) { store_tile(kv_tile(x, vtile), PB); publish(x, C_KV + (vtile >> 4)); }
  wgmma_wait<0>();
  fence_regs(S);
  if (dbg) DBG(89);
  TR(3);
  slot_release(x, ps, false);
  const bool landed = isY && mbar_test2(x.bars + B_RF + 8 * sk, e >= 6);
  #pragma unroll
  for (int i = 0; i < 8; i++) {
    const int j = 4 * (i >> 1), o = 2 * (i & 1);
    sts_v4(qa + (i >> 1) * 8192 + (i & 1) * 512,
           pack_bf16(S[4*j+o], S[4*j+o+1]), pack_bf16(S[4*j+4+o], S[4*j+5+o]), pack_bf16(S[4*j+8+o], S[4*j+9+o]), pack_bf16(S[4*j+12+o], S[4*j+13+o]));
  }
  fence_async_smem();
  if (dbg) DBG(90);
  TR(4);
  if (!landed) { mbar_wait(x.bars + B_RF + 8 * sk, ek >= 6); mbar_wait(x.bars + B_RF + 8 * sv, e >= 6); }
}

template<int KIND>
__device__ __forceinline__ void slot(Ctx& x, Att& a, int& e, int& sk, int sv, int en, int sn, float (&O)[64], uint32_t (&Pn)[32], uint32_t (&Po)[32],
                                     bool more, bool isY, bool half, int pv, int pend) {
  float S[64];
  const int w = x.w;
  const uint32_t dq = desc_lo(x.base + SM_Q + w * 4096, 16), dk = desc_lo(x.base, 16) + sk * 2048, dv = desc_lo(x.base, 8192) + sv * 2048;
  bar_sync(1 + w, 256);
  TR(5 + KIND);
  if (KIND == 2) {
    wgmma_fence();
    issue_qk(S, dq, dk); wgmma_commit();
    issue_pv<8>(O, Po, dv, 1); wgmma_commit();
    bar_arrive(1 + (w ^ 1), 256);
    wgmma_wait<1>();
  } else if (KIND == 0 && half) {
    float T[32];
    wgmma_fence(); issue_qk_half(T, dq, dk); wgmma_commit();
    if (pv == PV_NONE) { wgmma_fence(); wgmma_commit(); }
    else               { wgmma_fence(); issue_pv<8>(O, Po, dv, pv == PV_ACC); wgmma_commit(); }
    bar_arrive(1 + (w ^ 1), 256);
    wgmma_wait<1>();
    fence_regs(T);
    #pragma unroll
    for (int i = 0; i < 32; i++) { S[i] = T[i]; asm volatile("" : "=f"(S[32 + i])); }
  } else {
    wgmma_fence(); issue_qk(S, dq, dk); wgmma_commit();
    if (KIND == 1 && pend >= 0) { bar_arrive(1 + (w ^ 1), 256); pack_tile(O, Pn, a.i0, a.i1); store_ctx(x, pend, Pn); TR(8); }
    if (KIND == 0 && pv == PV_NONE) { wgmma_fence(); wgmma_commit(); }
    else if (pv == PV_HALF)         { wgmma_fence(); issue_pv<4>(O, Po, dv, 0); wgmma_commit(); }
    else                            { wgmma_fence(); issue_pv<8>(O, Po, dv, pv == PV_ACC); wgmma_commit(); }
    if (KIND == 0 || pend < 0) bar_arrive(1 + (w ^ 1), 256);
    wgmma_wait<1>();
  }
  fence_regs(S);
  fence_regs_u(Pn);
  TR(9);
  slot_release(x, sk, KIND == 0 && isY);
  const bool landed = mbar_test2(x.bars + B_RF + 8 * sn, en >= 6);
  float s0 = 0.f, s1 = 0.f;
  const bool was_classic = KIND != 0 && a.classic;
  if (KIND == 0) {
    a.l0 = 0.f; a.l1 = 0.f;
    if (!half) exp_pack<16, 32>(S, Pn, s0, s1);
    else {
      #pragma unroll
      for (int i = 16; i < 32; i++) asm volatile("" : "=r"(Pn[i]));
    }
    exp_pack_diag(S, Pn, diag_limit(), s0, s1);
    uint32_t b0 = __ballot_sync(0xffffffff, s0 >= SUM_LO), b1 = __ballot_sync(0xffffffff, s1 >= SUM_LO);
    b0 |= b0 >> 1; b0 |= b0 >> 2; b1 |= b1 >> 1; b1 |= b1 >> 2;
    a.classic = __any_sync(0xffffffff, !(s0 <= SUM_HI && s1 <= SUM_HI)) || (b0 & b1 & 0x11111111u) != 0x11111111u;
  } else {
    exp_pack<0, 32>(S, Pn, s0, s1);
    a.classic = __any_sync(0xffffffff, a.classic || !(s0 <= SUM_HI && s1 <= SUM_HI));
  }
  fence_regs_u(Pn);
  TR(10);
  if (!landed) {
    mbar_wait(x.bars + B_RF + 8 * sn, en >= 6);
    if (more) mbar_wait(x.bars + B_RF + 8 * sn + 8, en >= 6);
  }
  wgmma_wait<0>();
  fence_regs(O);
  fence_regs_u(Po);
  TR(11);
  slot_release(x, sv, KIND == 1 && isY && pv != PV_ACC);
  if (!NO_CLASSIC && __builtin_expect(a.classic, 0)) {
    float sc0, sc1;
    classic_tile(S, Pn, KIND == 0, half, was_classic, a.mc, a.l0, a.l1, s0, s1, sc0, sc1);
    if (KIND != 0) {
      #pragma unroll
      for (int j = 0; j < 16; j++) { O[4*j] *= sc0; O[4*j+1] *= sc0; O[4*j+2] *= sc1; O[4*j+3] *= sc1; }
    }
  }
  a.l0 += s0; a.l1 += s1;
  e = en; sk = sn;
}

__device__ __forceinline__ int attention(Ctx& x, const uint8_t* items, int nitems, int rank, uint32_t (&PA)[32], uint32_t (&PB)[32], int vtile) {
  int e = 0, sk = 0;
  float O[64];
  Att a;
  volatile float mc[2];
  a.l0 = 1.f; a.l1 = 1.f; a.i0 = 0.f; a.i1 = 0.f; a.classic = false; a.mc = mc;
  int pv = PV_NONE, cur = -1;
#define DBGS()
  #pragma unroll 1
  for (int it = 0; ; it++) {
    const bool isY = (it & 1) == x.w;
    int pend = cur;
    if (it < nitems) {
      const bool half = isY == (rank != 0);
      int sv, en, sn;
      DBG(16 + it);
      q_proj(x, a, e, sk, sv, en, sn, isY, PA, PB, vtile, it == 0);
      vtile = -1;
      const int item = items[it];
      cur = item * 4 + (isY ? 3 - rank : rank);
      int rem = 2 * (item & 7) + (isY ? 1 : 0);
      DBGS();
      slot<0>(x, a, e, sk, sv, en, sn, O, PA, PB, rem > 0, isY, half, pv, -1);
      pv = half ? PV_HALF : PV_ZERO;
      #pragma unroll 1
      while (rem > 0) {
        DBGS();
        slot<1>(x, a, e, sk, sk + 1, ring_add(e, 2), sk == 4 ? 0 : sk + 2, O, PB, PA, rem > 1, isY, false, pv, pend);
        pv = PV_ACC; pend = -1;
        if (rem == 1) break;
        rem -= 2;
        DBGS();
        slot<2>(x, a, e, sk, sk + 1, ring_add(e, 2), sk == 4 ? 0 : sk + 2, O, PA, PB, rem > 0, false, false, 0, -1);
      }
      if (isY) continue;
    } else {
      DBGS();
      slot_release(x, 6, false);
      const uint32_t dv = desc_lo(x.base, 8192) + sk * 2048;
      bar_sync(1 + x.w, 256);
      if (pv == PV_HALF) { wgmma_fence(); issue_pv<4>(O, PB, dv, 0); wgmma_commit(); }
      else { wgmma_fence(); issue_pv<8>(O, PB, dv, pv == PV_ACC); wgmma_commit(); }
      if (isY) bar_arrive(1 + (x.w ^ 1), 256);
      a.i0 = rcp_fast(quad_sum(a.l0)); a.i1 = rcp_fast(quad_sum(a.l1));
      ring_wait_full(x.bars, e);
      wgmma_wait<0>();
      fence_regs(O);
      fence_regs_u(PB);
      slot_release(x, sk, false);
    }
    if (pend >= 0) {
      pack_tile(O, PB, a.i0, a.i1);
      if (it == nitems) return pend;
      store_ctx(x, pend, PB);
    }
    #pragma unroll
    for (int i = 0; i < 32; i++) asm volatile("mov.b32 %0, %1;" : "=r"(PB[i]) : "r"(PA[i]));
  }
}

#define LN_AT 2
#define X_AT 6
#define PERT 0
#define CTX_T 3
#define PF_AT 5
#define PF_N 4
#define PF_MOE -3
constexpr float QSCALE = 0.08838834764831845f * 1.4426950408889634f;
__device__ __forceinline__ void mod_cta(Ctx& x, const __nv_bfloat16* cvec) {
  const int t = wg_tid(), ct = x.w * 128 + t;
  #pragma unroll 1
  for (int k = 0; k < 6; k++) slot_release(x, k, false);
  const uint32_t cv = __ldg(reinterpret_cast<const uint32_t*>(cvec) + ct);
  asm volatile("st.shared.u32 [%0], %1;" :: "r"(x.base + SM_H2 + ct * 4),
               "r"(pack_bf16(__fdividef(bf_lo(cv), 1.f + __expf(-bf_lo(cv))), __fdividef(bf_hi(cv), 1.f + __expf(-bf_hi(cv))))) : "memory");
  bar_sync(5, 256);
  float acc[64];
  int e = 0;
  #pragma unroll 1
  for (int g = 0; g < 24; g++) {
    uint32_t a[8];
    #pragma unroll
    for (int i = 0; i < 8; i++) a[i] = lds_u32(x.base + SM_H2 + (g & 7) * 128 + i * 16 + (t & 3) * 4);
    ring_wait_full(x.bars, e);
    const uint32_t db = desc_lo(x.base + x.w * 16384, 8192) + ring_slot(e) * 2048;
    wgmma_fence();
    wgmma_rs_n128<1, 0, SW128>(acc, a[0], a[0], a[1], a[1], db, g & 7);
    wgmma_rs_n128<1, 128, SW128>(acc, a[2], a[2], a[3], a[3], db, 1);
    wgmma_rs_n128<1, 256, SW128>(acc, a[4], a[4], a[5], a[5], db, 1);
    wgmma_rs_n128<1, 384, SW128>(acc, a[6], a[6], a[7], a[7], db, 1);
    wgmma_commit();
    wgmma_wait<0>();
    fence_regs(acc);
    ring_release(x, e, false);
    e = ring_add(e, 1);
    if ((g & 7) == 7) {
      if (t < 4) {
        const float sc = (g == 7 && blockIdx.x < NCTA + 2) ? QSCALE : 1.f;
        uint32_t* dst = reinterpret_cast<uint32_t*>(g_mod + (g >> 3) * 1024 + (blockIdx.x - NCTA) * 256 + x.w * 128) + t;
        #pragma unroll
        for (int j = 0; j < 16; j++) dst[4 * j] = pack_bf16(rbf(acc[4*j]) * sc, rbf(acc[4*j+1]) * sc);
      }
      publish(x, g == 7 ? C_MOD : C_MOD2);
      DBG(1 + (g >> 3));
    }
  }
}

__global__ void __cluster_dims__(2, 1, 1) __launch_bounds__(384, 1)
k_fused(const __grid_constant__ CUtensorMap tmC, const __grid_constant__ CUtensorMap tmWq,
        const __grid_constant__ CUtensorMap tmWk, const __grid_constant__ CUtensorMap tmWv,
        const __grid_constant__ CUtensorMap tmWo, const __grid_constant__ CUtensorMap tmWg,
        const __grid_constant__ CUtensorMap tmWu, const __grid_constant__ CUtensorMap tmWm,
        const __grid_constant__ Sched sched,
        const __nv_bfloat16* __restrict__ xin,
        const __nv_bfloat16* __restrict__ cvec, const __nv_bfloat16* __restrict__ w_o,
        const __nv_bfloat16* __restrict__ w_r, const __nv_bfloat16* __restrict__ w_gate, const __nv_bfloat16* __restrict__ w_up,
        const __nv_bfloat16* __restrict__ w_down, __nv_bfloat16* __restrict__ out) {
  extern __shared__ __align__(1024) uint8_t smem_raw[];
  const uint32_t base = smem_u32(smem_raw), bars = base + SM_BAR;
  const int warp = __shfl_sync(0xffffffff, threadIdx.x >> 5, 0), wg = warp >> 2;
  const int rank = cluster_ctarank(), p = blockIdx.x >> 1;
  const int mt = (p & 7) * 2 + rank;
  const bool spare = blockIdx.x >= NCTA;
  #pragma unroll
  for (int i = 0; i < PERT; i++) { uint32_t d; asm volatile("mov.u32 %0, %%laneid;" : "=r"(d)); }
  {
    const int h0 = KHEAD0 + (p >> 3);
    if (warp == 11) { prefetch_tmap(&tmC); prefetch_tmap(&tmWk); }
    #pragma unroll 1
    for (int t = warp == 8 ? 0 : warp < 8 ? warp + 1 : warp == 11 ? 64 : warp; t < B_PUB / 8; t += (warp == 8 ? 64 : 10))
      w_mbar_init(bars + 8 * t, t < B_WE / 8 ? 1 : t < B_RE / 8 ? 2 : 4);
    fence_mbar_init();
    cluster_arrive();
    if (warp == 9) prefetch_tmap(&tmWv);
    if (wg == 2) bar_arrive(1, 256);
    if (warp == 8 && !spare) {
      #pragma unroll 1
      for (int kb = 0; kb < 8; kb++) {
        w_expect_tx(bars + B_AF + 8 * kb, 16384);
        tma_load_2d(base + k_addrA(kb), &tmC, bars + B_AF + 8 * kb, kb * 64, mt * 128);
        if (kb == 0) cluster_wait();
        if (kb < 6) {
          w_expect_tx(bars + B_WF + 8 * kb, 16384);
          tma_load_2d_mc(base + k_addrW(kb) + rank * 8192, &tmWk, bars + B_WF + 8 * kb, h0 * 128 + rank * 64, kb * 64);
        }
      }
    }
  }
  const Sched::Pair& sp = sched.pair[p];
  const int nitems = sp.nitems, nsteps = sp.nsteps;
  auto oent = [&](int k) -> uint32_t { return sp.oent[k]; };
  const int ot = sp.otask, m = (ot & 7) * 2 + rank, grp = m * 8 + (ot >> 3);

  if (wg == 0) {
    asm volatile("setmaxnreg.dec.sync.aligned.u32 24;");
    const int lane = threadIdx.x & 31;
    #pragma unroll 1
    for (int t = B_PUB / 8 + warp; t < 80; t += 4) w_mbar_init(bars + 8 * t, t < B_RDY / 8 ? 4 : 1);
    bar_sync(6, 128);
    bar_arrive(7, 256); bar_arrive(8, 256);
    cluster_wait();
    const unsigned int tag = ld_relaxed(&g_epoch) + 1;
    if (warp == 0) {
      if (!spare) {
        int s = 0, ph = 0;
        tma_prefetch_2d(&tmWv, sp.khead[0] * 128 + rank * 64, (p & 7) * 64);
        #pragma unroll 1
        for (int g = 6; g < 64; g++) {
          const int u = g >> 3, kb = g & 7;
          if (kb == 0 && u < 7) tma_prefetch_2d((u & 1) ? &tmWk : &tmWv, sp.khead[(u + 1) >> 1] * 128 + rank * 64, (p & 7) * 64);
          mbar_wait(bars + B_WE + 8 * s, ph);
          w_expect_tx(bars + B_WF + 8 * s, 16384);
          tma_load_2d_mc(base + k_addrW(s) + rank * 8192, (u & 1) ? &tmWv : &tmWk, bars + B_WF + 8 * s, sp.khead[u >> 1] * 128 + rank * 64, kb * 64);
          if (++s == 6) { s = 0; ph ^= 1; }
        }
      }
      int s = 0, ph = 0;
      auto next_entry = [&](int bytes) {
        mbar_wait(bars + B_RE + 8 * s, ph);
        w_expect_tx(bars + B_RF + 8 * s, bytes);
      };
      auto advance = [&]() { if (++s == 6) { s = 0; ph ^= 1; } };
      if (spare) {
        #pragma unroll 1
        for (int g = 0; g < 24; g++) {
          if (g == 8) mbar_wait(bars + R_MOD, 0);
          next_entry(32768);
          for (int k = 0; k < 2; k++) tma_load_3d(base + s * 32768 + k * 16384, &tmWm, bars + B_RF + 8 * s, 0, (g & 7) * 64, (g >> 3) * 16 + (blockIdx.x - NCTA) * 4 + k * 2);
          advance();
        }
      }
      mbar_wait(bars + R_H1, 0);
      fence_async_global();
      int vrow = -1;
      #pragma unroll 1
      for (int i = 0; i <= nitems; i++) {
        const int item = sp.item[i & (MAX_ITEMS - 1)], h = item >> 3, j = item & 7;
        if (i < nitems) {
          const int row0 = j * 256 + ((i & 1) ? rank : 3 - rank) * 64, row1 = j * 256 + ((i & 1) ? 3 - rank : rank) * 64;
          #pragma unroll 1
          for (int kb = 0; kb < 8; kb++) {
            next_entry(32768);
            tma_load_2d_mc(base + s * 32768 + 16384 + rank * 8192, &tmWq, bars + B_RF + 8 * s, h * 128 + rank * 64, kb * 64);
            bulk_load(base + s * 32768, sched.h1 + row0 * DM + kb * 4096, 8192, bars + B_RF + 8 * s);
            bulk_load(base + s * 32768 + 8192, sched.h1 + row1 * DM + kb * 4096, 8192, bars + B_RF + 8 * s);
            advance();
          }
          mbar_wait(bars + R_ITEM + 8 * i, 0);
          fence_async_global();
        }
        #pragma unroll 1
        for (int n = i < nitems ? 4 * j + 3 : 0; n >= 0; n--) {
          const int krow = (h * 2 + rank) * SEQ + (n >> 1) * 128 + ((sp.lastuse[i & (MAX_ITEMS - 1)] >> (n >> 1)) & 1);
          const int row = (n & 1) ? krow : vrow;
          if (i + 1 == nitems && n == min(4 * j + 3, 2 * PF_AT + 1)) w_arrive(bars + R_NEAR);
          next_entry(row >= 0 ? 32768 : 0);
          if (row >= 0) bulk_load_mc(base + s * 32768 + rank * 16384, sched.kvc + (size_t)(row & ~1) * 64, bars + B_RF + 8 * s, row & 1);
          advance();
          if (!(n & 1)) vrow = krow + 64 * SEQ;
        }
      }
      if (!spare) {
      const int oc = ((ot >> 3) & 1) * 4 + rank * 2;
      auto o_next = [&](int k, int bytes) {
        const uint32_t v = oent(k); s = v & 7;
        mbar_wait(bars + B_RE + 8 * s, v >> 3);
        w_expect_tx(bars + B_RF + 8 * s, bytes);
      };
      #pragma unroll 1
      for (int i = 0; i < nsteps; i++) {
        const int c0 = sp.ochunk[i][0], c1 = sp.ochunk[i][1];
        const int pf = PF_MOE > 0 ? i - PF_MOE : i - nsteps - PF_MOE;
        if (pf >= 0 && pf < 3)
          bulk_prefetch((pf == 0 ? w_gate : pf == 1 ? w_up : w_down) + (size_t)blockIdx.x * (DM * FF / NCTA), DM * FF / NCTA * 2);
        if (c0 < 64) { o_next(3 * i, 32768); tma_load_3d_mc(base + s * 32768 + rank * 16384, &tmWo, bars + B_RF + 8 * s, 0, c0 * 64, oc); }
        mbar_wait(bars + R_CTX + 8 * i, 0);
        fence_async_global();
        o_next(3 * i + 1, c0 < 64 ? 32768 : 16384);
        if (c0 < 64) bulk_load(base + s * 32768, sched.kvc + (size_t)((128 + c0) * SEQ + m * 128) * 64, 16384, bars + B_RF + 8 * s);
        bulk_load(base + s * 32768 + 16384, sched.kvc + (size_t)((128 + c1) * SEQ + m * 128) * 64, 16384, bars + B_RF + 8 * s);
        o_next(3 * i + 2, 32768);
        tma_load_3d_mc(base + s * 32768 + rank * 16384, &tmWo, bars + B_RF + 8 * s, 0, c1 * 64, oc);
      }
      const int f0 = (blockIdx.x < FF / 16 ? blockIdx.x : 0) * 16;
      o_next(3 * nsteps, 32768);
      bulk_load(base + s * 32768, w_down + (size_t)f0 * DM, 16384, bars + B_RF + 8 * s);
      bulk_load(base + s * 32768 + 16384, xin + (size_t)grp * 16 * DM, 16384, bars + B_RF + 8 * s);
      o_next(3 * nsteps + 1, 32768);
      #pragma unroll 1
      for (int k = 0; k < 4; k++) tma_load_2d(base + s * 32768 + k * 8192, (k & 2) ? &tmWu : &tmWg, bars + B_RF + 8 * s, f0, (k & 1) * 256);
      #pragma unroll 1
      for (int k = 0; k < 4; k++) w_expect_tx(bars + R_PART + 8 * k, 16384);
      mbar_wait(bars + B_PUB + 8 * (5 + nitems), 0);
      mbar_wait(bars + B_PUB + 8 * (NPUB + 5 + nitems), 0);
      uint32_t todo = 0xff;
      #pragma unroll 1
      for (int n = 0; n < WAIT_LIM && todo; n++) {
        uint32_t now = __ballot_sync(0xffffffff, ld_acquire(&g_cnt[C_PART + (m * 2 + (ot >> 5)) * 32 + (lane & 7)]) == tag) & todo;
        todo &= ~now;
        if (now) fence_async_global();
        #pragma unroll 1
        for (; now; now &= now - 1) {
          const int q = __ffs(now) - 1;
          bulk_load(base + (oent(3 * nsteps - 3 + (q >> 2)) & 7) * 32768 + (q & 3) * 8192, sched.part + (grp * 8 + q) * 4096, 8192, bars + R_PART + 8 * (q >> 1));
        }
      }
      DBGP(11);
      }
    } else if (warp < 3) {
      const int w = warp - 1, n1 = w * NPUB + (spare ? 3 : 6) + nitems;
      #pragma unroll 1
      for (int n = w * NPUB; n < n1; n++) {
        #pragma unroll 1
        for (int k = 0; k < 8 * WAIT_LIM; k++) { if (mbar_try(bars + B_PUB + 8 * n, 0)) break; }
        const uint32_t idx = lds_u32(base + SM_MAIL + 4 * n);
        fence_async_global();
        if (lane == 0 && idx < (unsigned)C_END) red_release(idx);
        __syncwarp();
      }
    } else {
      *reinterpret_cast<volatile uint32_t*>(smem_raw + SM_KEY + 48) = tag;
      if (!spare) { mbar_wait(bars + B_AF + 8 * X_AT, 0); bulk_prefetch(xin + (size_t)blockIdx.x * 16 * DM, 16 * DM * 2); }
      #pragma unroll 1
      for (int n = 0; n < 8 + nsteps; n++) {
        if (n == 2 + nitems) n = 7;
        int idx = n == 0 ? C_MOD : n == 1 ? C_H1 : C_MOD2, cnt = n == 0 ? 8 : n == 1 ? 256 : 16;
        if (n >= 1 && n <= nitems) { const int item = sp.item[n - 1]; tma_prefetch_2d(&tmWq, (item >> 3) * 128 + rank * 64, (item & 7) * 64); }
        if (n >= 2 && n < 7) { idx = C_KV + (sp.item[n - 2] >> 3); cnt = 32; }
        if (n >= 8) { const int c0 = sp.ochunk[n - 8][0], c1 = sp.ochunk[n - 8][1]; idx = C_CTX + (((lane & 1) && c0 < 64 ? c0 : c1) >> 1) * 8 + (ot & 7); cnt = 4; }
        wait_count_lazy(idx, cnt * tag);
        w_arrive(bars + B_RDY + 8 * n);
        if (n == 0) DBGP(12);
        if (n == 8 + PF_N - 1) {
          #pragma unroll 1
          for (int k = 0; k < 8 * WAIT_LIM; k++) { if (mbar_try(bars + R_NEAR, 0)) break; }
          bulk_prefetch(w_o + (size_t)blockIdx.x * (NH * DH * DM / NCTA), NH * DH * DM / NCTA * 2);
          #pragma unroll 1
          for (int k = 0; k < PF_N; k++) {
            const int cc = sp.ochunk[k][(ot >> 3) & 1];
            if (cc < 64) bulk_prefetch(sched.kvc + ((size_t)(128 + cc) * SEQ + m * 128) * 64, 16384);
          }
        }
      }
    }
    __syncwarp();
    cluster_arrive();
    if (!spare) {
      bar_sync(6, 128);
      asm volatile("setmaxnreg.inc.sync.aligned.u32 88;");
      const int pos = blockIdx.x * 4 + (lane & 1) * 2, col = (blockIdx.x >> 2) * 16 + (blockIdx.x & 3) * 2 + (lane & 1) * 8, src = threadIdx.x >> 1;
      uint32_t gbest = 0, hh = 0, gbf = 0;
      uint2 xx = make_uint2(0, 0);
      uint4 ya = make_uint4(0, 0, 0, 0), yb = make_uint4(0, tag, 0, tag);
      auto poll_y = [&]() {
        if (ya.y != tag || ya.w != tag) ya = ld_tagged2(&g_yll[src][pos]);
        if (yb.y != tag || yb.w != tag) yb = ld_tagged2(&g_yll[src + 64][pos]);
        return __all_sync(0xffffffff, ya.y == tag && ya.w == tag && yb.y == tag && yb.w == tag);
      };
      ya.y = tag - 1; if (src + 64 < FF / 16) yb.y = tag - 1;
      poll_y();
      if (warp == 3) {
        gbf = __ldcg(reinterpret_cast<const uint32_t*>(g_mod + 5 * DM + col));
        uint32_t have = 0;
        uint2 k[4];
        #pragma unroll
        for (int i = 0; i < 4; i++) k[i] = make_uint2(0, tag - 1);
        #pragma unroll 1
        for (int n = 0; n < WAIT_LIM; n++) {
          #pragma unroll
          for (int i = 0; i < 4; i++) if (k[i].y != tag) k[i] = ld_tagged(&g_keys[i * 32 + lane][0]);
          if (gbest != have) {
            const int g = ((0xffffu - gbest) >> 4) & 127;
            uint4 hv[4];
            #pragma unroll
            for (int i = 0; i < 4; i++) hv[i] = ld_tagged2(&g_row[g][0][i * 64 + lane * 2]);
            xx = ld_tagged(&g_row[g][1][(col >> 8) * 128 + ((col >> 2) & 1) * 64 + ((col >> 3) & 31) * 2 + ((col >> 1) & 1)]);
            bool ok = xx.y == tag;
            #pragma unroll
            for (int i = 0; i < 4; i++) { ok = ok && hv[i].y == tag && hv[i].w == tag; reinterpret_cast<uint2*>(smem_raw + SM_H2)[(i >> 1) * 64 + lane * 2 + (i & 1)] = make_uint2(hv[i].x, hv[i].z); }
            if (lane == 0) *reinterpret_cast<uint32_t*>(smem_raw + SM_KEY + 32) = gbest;
            have = __all_sync(0xffffffff, ok) ? gbest : 0;
          }
          bool all = true;
          #pragma unroll
          for (int i = 0; i < 4; i++) { all = all && k[i].y == tag; gbest = max(gbest, k[i].y == tag ? k[i].x : 0u); }
          gbest = __reduce_max_sync(0xffffffff, gbest);
          if (__all_sync(0xffffffff, all) && gbest == have) break;
        }
        w_arrive(bars + R_KEY);
        if (blockIdx.x == 0 && lane == 0) g_epoch = tag;
        hh = lds_u32(base + SM_H2 + col * 2);
        DBGP(13);
      }
      const uint32_t sb16 = gbest & 0xffff0000u;
      const float rsel = __uint_as_float((sb16 & 0x80000000u) ? (sb16 & 0x7fffffffu) : (~sb16 & 0xffff0000u));
      const float rs = rbf(__fdividef(1.f, 1.f + __expf(-rsel)));
      bar_sync(9, 384);
      #pragma unroll 1
      for (int n = 0; n < WAIT_LIM; n++) { if (poll_y()) break; }
      float y0 = __uint_as_float(ya.x) + __uint_as_float(yb.x), y1 = __uint_as_float(ya.z) + __uint_as_float(yb.z);
      #pragma unroll
      for (int o = 2; o < 32; o <<= 1) { y0 += __shfl_xor_sync(0xffffffff, y0, o); y1 += __shfl_xor_sync(0xffffffff, y1, o); }
      float2* s_y = reinterpret_cast<float2*>(smem_raw + SM_KEY + 64);
      if (lane < 2) s_y[warp * 2 + lane] = make_float2(y0, y1);
      bar_sync(6, 128);
      if (warp == 3 && lane < 2) {
        y0 = 0.f; y1 = 0.f;
        #pragma unroll
        for (int i = 0; i < 4; i++) { y0 += reinterpret_cast<const float*>(s_y)[i * 4 + lane]; y1 += reinterpret_cast<const float*>(s_y)[i * 4 + 2 + lane]; }
        const float o0 = bf_lo(xx.x) + rbf(bf_lo(gbf) * rbf(bf_lo(hh) + rbf(rbf(y0) * rs)));
        const float o1 = bf_hi(xx.x) + rbf(bf_hi(gbf) * rbf(bf_hi(hh) + rbf(rbf(y1) * rs)));
        *reinterpret_cast<uint32_t*>(out + (size_t)((0xffffu - gbest) & (SEQ - 1)) * DM + col) = pack_bf16(o0, o1);
      }
      DBGP(14);
    }
    __syncwarp();
    cluster_wait();
  } else {
    asm volatile("setmaxnreg.inc.sync.aligned.u32 240;");
    Ctx x;
    x.w = wg - 1; x.base = base; x.bars = bars; x.nev = 0; x.sched = &sched;
    const int w = x.w, warp4 = warp & 3;
    x.rel = mapa(bars, (warp4 & 1) ^ 1);
    x.rel1 = (threadIdx.x & 127) == 32 || (threadIdx.x & 127) == 64;
    if (warp != 8 || spare) cluster_wait();
    if (w == 1 || spare) bar_sync(7 + w, 256);
    DBG(1);
    uint32_t PA[32], PB[32];
    int vtile = -1;
    if (spare) {
      mod_cta(x, cvec);
    } else {
      const int lane = wg_tid() & 31;
      Row xn[2];
      float acc0[64], acc1[64];
      int s = 2 * w, ph = w;
      #pragma unroll 1
      for (int u = w; u < 8; u += 2) {
        bar_sync(1 + w, 256);
        DBG(4 + (u >> 1) * 3);
        int ps = 0;
        #pragma unroll 1
        for (int kb = 0; kb < 8; kb++) {
          if (u < 2) mbar_wait(bars + B_AF + 8 * kb, 0);
          mbar_wait(bars + B_WF + 8 * s, ph);
          const uint32_t da = desc_lo(base + k_addrA(kb), 16), dw = desc_lo(base + k_addrW(s), 8192);
          wgmma_fence();
          kblock_n128<0>(acc0, da, dw, kb != 0);
          kblock_n128<512>(acc1, da, dw, kb != 0);
          wgmma_commit();
          if (kb == 7) bar_arrive(1 + (w ^ 1), 256);
          if (kb > 0) {
            wgmma_wait<1>();
            mbar_arrive_remote_if(x.rel + B_WE + 8 * ps, x.rel1);
            if (u == 7 && !(kb & 1)) {
              ring_release(x, kb == 2 ? 0 : kb - 3, false);
              if (kb > 2) ring_release(x, kb - 2, false);
            }
          }
          ps = s;
          if (++s == 6) { s = 0; ph ^= 1; }
        }
        Row t[2];
        const int lrow = blockIdx.x * 16 + w * 8 + warp4 * 2;
        if (u == w) { t[0] = ldg_row(xin + (size_t)lrow * DM, lane); t[1] = ldg_row(xin + (size_t)(lrow + 1) * DM, lane); }
        if (u == LN_AT || u == LN_AT + 1) {
          mbar_wait(bars + R_MOD, 0);
          t[0] = ldca_row(g_mod, lane); t[1] = ldca_row(g_mod + DM, lane);
        }
        wgmma_wait<0>();
        fence_regs(acc0); fence_regs(acc1);
        DBG(5 + (u >> 1) * 3);
        mbar_arrive_remote_if(x.rel + B_WE + 8 * ps, x.rel1);
        if (u == 6) { for (int k = 0; k < 5; k++) ring_release(x, k, false); }
        if (u >= 6) ring_release(x, 5, false);
        if (u == 7) {
          pack_tile(acc0, PA, 1.f, 1.f); pack_tile(acc1, PB, 1.f, 1.f);
          vtile = sp.khead[3] * 16 + mt;
          break;
        }
        s += 2; ph ^= 1; if (s >= 6) { s -= 6; ph ^= 1; }
        if (u == 0) bar_sync(7, 256);
        if (u == w) {
          float st[4] = {0.f, 0.f, 0.f, 0.f};
          #pragma unroll
          for (int i = 0; i < 32; i++) { const float v = row_at(t[i >> 4], i & 15); st[(i >> 4) * 2] += v; st[(i >> 4) * 2 + 1] = fmaf(v, v, st[(i >> 4) * 2 + 1]); }
          warp_sums(st);
          #pragma unroll
          for (int r = 0; r < 2; r++) { ln_stats(st[2*r], st[2*r+1]); xn[r] = ln_apply(t[r], st[2*r], st[2*r+1] * QSCALE); }
        }
        if ((u == LN_AT || u == LN_AT + 1)) {
          #pragma unroll
          for (int r = 0; r < 2; r++) {
            const Row hr = fma_row(xn[r], one_plus(t[1]), t[0]);
            __nv_bfloat16* hp = sched.h1 + (lrow & ~63) * DM + (lane >> 3) * 4096 + ((lrow + r) & 63) * 64 + (((lane ^ (lrow + r)) & 7) << 3);
            stg_v4(hp, hr.v[0], hr.v[1], hr.v[2], hr.v[3]); stg_v4(hp + 4 * 4096, hr.v[4], hr.v[5], hr.v[6], hr.v[7]);
          }
        }
        const int tile = sp.khead[u >> 1] * 16 + mt;
        __nv_bfloat16* dst = kv_tile(x, tile);
        uint32_t D[32];
        pack_tile(acc0, D, 1.f, 1.f); store_tile(dst + 2048, D);
        pack_tile(acc1, D, 1.f, 1.f); store_tile(dst, D);
        if (u == LN_AT || u == LN_AT + 1) publish(x, C_H1);
        publish(x, C_KV + (tile >> 4));
        DBG(6 + (u >> 1) * 3);
      }
    }
    x.tr = base + SM_RED + w * 1024;
    const int last = attention(x, sp.item, nitems, rank, PA, PB, vtile);
    DBG(100);
    const int lane = wg_tid() & 31, cw = w * 4 + warp4, ct = cw * 32 + lane;
    const int row0 = grp * 16 + cw * 2;
    const bool moe_cta = blockIdx.x < FF / 16;
    if (spare) { store_ctx(x, last, PB); __syncwarp(); cluster_arrive(); cluster_wait(); return; }
    const int kl = 3 * nsteps - 3;
    Row ga, sb, cb, gb, wr;
    {
      float accA[64], accB[64];
      const int t0 = oent(0) == oent(1);
      uint32_t pa = 0, pb = 0;
      #pragma unroll 1
      for (int t = t0; t < 2 * nsteps - 2; t++) {
        const uint32_t eb = oent(3 * (t >> 1) + 2 * (t & 1)), ea = oent(3 * (t >> 1) + 1);
        o_wait_full(bars, eb);
        o_wait_full(bars, ea);
        const uint32_t da = desc_lo(base + w * 4096, 16) + (ea & 7) * 2048 + (t & 1) * 1024, db = desc_lo(base, 8192) + (eb & 7) * 2048;
        wgmma_fence();
        kblock_n128<0, 0, SW64>(accA, da, db, t != t0); kblock_n128<0, 1024, SW64>(accB, da, db, t != t0);
        wgmma_commit();
        if (t == CTX_T) store_ctx(x, last, PB);
        if (t > t0) { wgmma_wait<1>(); slot_release(x, pb, false); if (!(t & 1)) slot_release(x, pa, false); }
        pa = ea & 7; pb = eb & 7;
      }
      const uint32_t e0 = oent(kl), ea = oent(kl + 1), eb = oent(kl + 2);
      const uint32_t da = desc_lo(base + w * 4096, 16) + (ea & 7) * 2048;
      const uint32_t db0 = desc_lo(base, 8192) + (e0 & 7) * 2048, db1 = desc_lo(base, 8192) + (eb & 7) * 2048;
      ga = ldca_row(g_mod + 2 * DM, lane); sb = ldca_row(g_mod + 3 * DM, lane); cb = ldca_row(g_mod + 4 * DM, lane); gb = ldca_row(g_mod + 5 * DM, lane);
      wr = ldca_row(w_r, lane);
      o_wait_full(bars, e0);
      o_wait_full(bars, ea);
      o_wait_full(bars, eb);
      wgmma_fence();
      kblock_n128<0, 0, SW64>(accA, da, db0, 1); kblock_n128<1024, 0, SW64>(accA, da, db1, 1);
      wgmma_commit();
      kblock_n128<0, 1024, SW64>(accB, da, db0, 1); kblock_n128<1024, 1024, SW64>(accB, da, db1, 1);
      wgmma_commit();
      __syncwarp();
      cluster_arrive();
      __nv_bfloat16* dst = sched.part + ((m * 8 + cw) * 8 + (ot >> 3)) * 4096;
      auto send = [&](const float (&acc)[64], int h) {
        uint32_t D[32];
        pack_tile(acc, D, 1.f, 1.f);
        #pragma unroll
        for (int i = 0; i < 8; i++) stg_v4(dst + (h * 8 + i) * 256 + ((lane ^ (h * 4 + (i >> 1))) << 3), D[4*i], D[4*i+1], D[4*i+2], D[4*i+3]);
      };
      wgmma_wait<1>();
      fence_regs(accA);
      DBG(120);
      send(accA, 0);
      o_wait_full(bars, eb);
      wgmma_wait<0>();
      fence_regs(accB);
      DBG(101);
      send(accB, 1);
      publish(x, C_PART + (m * 2 + w) * 32 + (ot >> 3));
      DBG(121);
      DBG(102);
    }
    asm volatile("setmaxnreg.dec.sync.aligned.u32 208;");
    const uint32_t sD = base + (oent(kl + 3) & 7) * 32768, sW = base + (oent(kl + 4) & 7) * 32768;
    o_wait_full(bars, oent(kl + 3)); o_wait_full(bars, oent(kl + 4));
    Row x1[2];
    #pragma unroll
    for (int r = 0; r < 2; r++) x1[r] = lds_row(sD + 16384 + (cw * 2 + r) * 1024, lane);
    uint4 wgv[4], wuv[4], wdv[4];
    #pragma unroll
    for (int r = 0; r < 4; r++) {
      const uint32_t k = (lane & 7) + ((lane >> 4) << 3), h = (lane & 8) * 2;
      wgv[r] = ldsm_x4_t(sW + (cw * 64 + r * 16 + k) * 32 + h);
      wuv[r] = ldsm_x4_t(sW + 16384 + (cw * 64 + r * 16 + k) * 32 + h);
      wdv[r] = ldsm_x4_t(sD + k * 1024 + (cw * 64 + r * 16) * 2 + h);
    }
    const Row cb1 = one_plus(cb);
    const unsigned int tag = lds_u32(base + SM_KEY + 48);
    DBG(103);
    float u[16], ub[2] = {0.f, 0.f};
    #pragma unroll
    for (int i = 0; i < 16; i++) { u[i] = row_at(cb1, i) * row_at(wr, i); ub[0] += u[i]; ub[1] = fmaf(row_at(sb, i), row_at(wr, i), ub[1]); }
    warp_sums(ub);
    float st[6] = {0.f, 0.f, 0.f, 0.f, 0.f, 0.f};
    uint32_t key[2];
    {
      const uint32_t po = base + ((lane & 7) * 2 + (cw >> 2)) * 512 + (cw & 3) * 128;
      Row av[2][2];
      #pragma unroll
      for (int k = 0; k < 4; k++) {
        mbar_wait(bars + R_PART + 8 * k, 1);
        const uint32_t pa = po + (oent(kl + (k >> 1)) & 7) * 32768 + (k & 1) * 16384;
        #pragma unroll
        for (int r = 0; r < 2; r++) {
          const uint32_t sw = ((r * 4 + (lane >> 3)) ^ (lane & 7)) << 4;
          const uint4 lo = ldsm_x4(pa + sw), hi = ldsm_x4(pa + 8192 + sw);
          const Row v{{lo.x, lo.y, lo.z, lo.w, hi.x, hi.y, hi.z, hi.w}};
          av[r][k >> 1] = (k & 1) ? add_row(av[r][k >> 1], v) : v;
        }
      }
      DBG(104);
      #pragma unroll
      for (int r = 0; r < 2; r++) {
        x1[r] = fma_row(ga, add_row(av[r][0], av[r][1]), x1[r]);
        #pragma unroll
        for (int i = 0; i < 16; i++) { const float v = row_at(x1[r], i); st[3*r] += v; st[3*r+1] = fmaf(v, v, st[3*r+1]); st[3*r+2] = fmaf(v, u[i], st[3*r+2]); }
      }
      warp_sums(st);
      #pragma unroll
      for (int r = 0; r < 2; r++) {
        ln_stats(st[3*r], st[3*r+1]);
        const uint32_t rb = pack_bf16(0.f, fmaf(st[3*r+1], fmaf(-st[3*r], ub[0], st[3*r+2]), ub[1]));
        key[r] = (((rb & 0x80000000u) ? ~rb : (rb | 0x80000000u)) & 0xffff0000u) | (0xffffu - (uint32_t)(row0 + r));
      }
    }
    DBG(105);
    float* s_red = reinterpret_cast<float*>(smem_raw + SM_RED);
    uint32_t* s_key = reinterpret_cast<uint32_t*>(smem_raw + SM_KEY);
    const int rb = key[1] > key[0];
    const uint32_t wbest = rb ? key[1] : key[0];
    if (lane == 0) s_key[cw] = wbest;
    bar_sync(5, 256);
    const uint32_t cbest = __reduce_max_sync(0xffffffff, s_key[lane & 7]);
    if (wbest == cbest && lane == 0) st_tagged(&g_keys[grp][0], cbest, tag);
    Row xb, xo;
    #pragma unroll
    for (int i = 0; i < 8; i++) { xb.v[i] = rb ? x1[1].v[i] : x1[0].v[i]; xo.v[i] = rb ? x1[0].v[i] : x1[1].v[i]; }
    const Row hb = fma_row(ln_apply(xb, rb ? st[3] : st[0], rb ? st[4] : st[1]), cb1, sb);
    if (wbest == cbest) {
      #pragma unroll
      for (int i = 0; i < 4; i++) st_tagged2(&g_row[grp][0][i * 64 + lane * 2], hb.v[2*i], hb.v[2*i+1], tag);
      #pragma unroll
      for (int i = 0; i < 4; i++) st_tagged2(&g_row[grp][1][i * 64 + lane * 2], xb.v[2*i], xb.v[2*i+1], tag);
    }
    DBG(106);
    const Row ob = fma_row(gb, hb, xb);
    if (wbest != cbest) store_row(out + (size_t)(row0 + rb) * DM, lane, ob);
    store_row(out + (size_t)(row0 + 1 - rb) * DM, lane, fma_row(gb, fma_row(ln_apply(xo, rb ? st[0] : st[3], rb ? st[1] : st[4]), cb1, sb), xo));
    mbar_wait(bars + R_KEY, 1);
    DBG(107);
    if (moe_cta) {
      float cg[4] = {0, 0, 0, 0}, cu[4] = {0, 0, 0, 0};
      #pragma unroll
      for (int r = 0; r < 4; r++) {
        const uint32_t b0 = lds_u32(base + SM_H2 + (cw * 64 + r * 16) * 2 + (lane & 3) * 4), b1 = lds_u32(base + SM_H2 + (cw * 64 + r * 16) * 2 + 16 + (lane & 3) * 4);
        mma16816(cg, wgv[r], b0, b1); mma16816(cu, wuv[r], b0, b1);
      }
      s_red[cw * 32 + (lane & 3) * 8 + (lane >> 2)] = (lane & 2) ? ((lane & 1) ? cu[2] : cu[0]) : ((lane & 1) ? cg[2] : cg[0]);
      bar_sync(5, 256);
      float g = 0.f;
      #pragma unroll
      for (int i = 0; i < 8; i++) g += s_red[i * 32 + lane];
      g = rbf(g);
      const float act = rbf(__fdividef(g, 1.f + __expf(-g))) * __shfl_down_sync(0xffffffff, g, 16);
      const uint32_t a2 = pack_bf16(act, __shfl_down_sync(0xffffffff, act, 1));
      const uint32_t b0 = __shfl_sync(0xffffffff, a2, (lane & 3) * 2), b1 = __shfl_sync(0xffffffff, a2, (lane & 3) * 2 + 8);
      float y0 = 0.f, y1 = 0.f;
      #pragma unroll
      for (int r = 0; r < 4; r++) {
        float c[4] = {0, 0, 0, 0};
        mma16816(c, wdv[r], b0, b1);
        if ((lane & 3) == r) { y0 = c[0]; y1 = c[2]; }
      }
      st_tagged2(&g_yll[blockIdx.x][cw * 64 + (lane & 3) * 16 + (lane >> 2) * 2], __float_as_uint(y0), __float_as_uint(y1), tag);
    }
    bar_arrive(9, 384);
    DBG(108);
    if (wbest == cbest && wbest != s_key[8]) store_row(out + (size_t)(row0 + rb) * DM, lane, ob);
    DBG(109);
    __syncwarp();
    cluster_wait();
  }
}

typedef CUresult (*EncodeFn)(CUtensorMap*, CUtensorMapDataType, cuuint32_t, void*, const cuuint64_t*, const cuuint64_t*, const cuuint32_t*,
                             const cuuint32_t*, CUtensorMapInterleave, CUtensorMapSwizzle, CUtensorMapL2promotion, CUtensorMapFloatOOBfill);

struct HostState {
  bool ready = false;
  EncodeFn encode = nullptr;
  CUtensorMap tmC, tmWq, tmWk, tmWv, tmWo, tmWg, tmWu, tmWm;
  Sched sched;
};

void make_map(EncodeFn enc, CUtensorMap* m, const void* ptr, int rank, const cuuint64_t* dims, const cuuint64_t* strides, const cuuint32_t* box, bool swizzle = true) {
  const cuuint32_t es[3] = {1, 1, 1};
  enc(m, CU_TENSOR_MAP_DATA_TYPE_BFLOAT16, rank, const_cast<void*>(ptr), dims, strides, box, es, CU_TENSOR_MAP_INTERLEAVE_NONE,
      swizzle ? CU_TENSOR_MAP_SWIZZLE_128B : CU_TENSOR_MAP_SWIZZLE_NONE, swizzle ? CU_TENSOR_MAP_L2_PROMOTION_L2_128B : CU_TENSOR_MAP_L2_PROMOTION_NONE, CU_TENSOR_MAP_FLOAT_OOB_FILL_NONE);
}
void make_2d(EncodeFn enc, CUtensorMap* m, const void* ptr, int rows, int cols, int box_rows) {
  const cuuint64_t dims[2] = {(cuuint64_t)cols, (cuuint64_t)rows}, strides[1] = {(cuuint64_t)cols * 2};
  const cuuint32_t box[2] = {64, (cuuint32_t)box_rows};
  make_map(enc, m, ptr, 2, dims, strides, box);
}
void make_3d(EncodeFn enc, CUtensorMap* m, const void* ptr, int rows, int chunks, size_t row_stride, size_t chunk_stride) {
  const cuuint64_t dims[3] = {64, (cuuint64_t)rows, (cuuint64_t)chunks}, strides[2] = {row_stride, chunk_stride};
  const cuuint32_t box[3] = {64, 64, 2};
  make_map(enc, m, ptr, 3, dims, strides, box);
}

void make_ffn(EncodeFn enc, CUtensorMap* m, const void* ptr) {
  const cuuint64_t dims[2] = {(cuuint64_t)FF, (cuuint64_t)DM}, strides[1] = {(cuuint64_t)FF * 2};
  const cuuint32_t box[2] = {16, 256};
  make_map(enc, m, ptr, 2, dims, strides, box, false);
}

#define SR 0x213312
#define SEED 12345
#define LU_MARGIN 0
#define SPARE_N 3
void build_sched(Sched& s) {
  memset(&s, 0, sizeof(s));
  const int NP = NCTA / 2, korder[4] = {(KORDER >> 12) & 3, (KORDER >> 8) & 3, (KORDER >> 4) & 3, KORDER & 3};
  const int sround[4][2][3] = {{}, {{1}, {2}}, {{1, 2}, {1, 2}}, {{(SR >> 20) & 3, (SR >> 16) & 3, (SR >> 12) & 3}, {(SR >> 8) & 3, (SR >> 4) & 3, SR & 3}}};
  int jv[4][NP], used[4][8] = {};
  for (int r = 0; r < 4; r++) for (int p = 0; p < NP; p++) jv[r][p] = (r & 2) ? 7 - ((p + 4 * (r & 1)) & 7) : (p + 4 * (r & 1)) & 7;
  for (int q = 0; q < 2; q++) {
    s.pair[NP + q].nitems = SPARE_N;
    for (int i = 0; i < SPARE_N; i++) {
      const int r = sround[SPARE_N][q][i];
      s.pair[NP + q].item[i] = (uint8_t)((r * 8 + used[r][6]++) * 8 + 6);
      for (int p = 0; p < NP; p++) if (jv[r][p] == 6) { jv[r][p] = -2; break; }
    }
  }
  auto cost = [&](int p) {
    int u = 8 - ((p >> 4) < SPARE_N ? 21 : 22), z = 0, none = 0;
    for (int r = 0; r < 4; r++) { u += jv[r][p]; z += jv[r][p] == 0; none += jv[r][p] < 0; }
    return 4 * u * u + (z > 1) + 4 * (none > 1);
  };
  uint32_t rng = SEED;
  for (int it = 0; it < 2000000; it++) {
    if ((it & 255) == 0) { int t = 0; for (int p = 0; p < NP; p++) t += cost(p); if (t == 0) break; }
    rng = rng * 1664525u + 1013904223u;
    const int r = (rng >> 8) & 3, a = (rng >> 12) & 63, b = (rng >> 20) & 63, before = cost(a) + cost(b);
    int t = jv[r][a]; jv[r][a] = jv[r][b]; jv[r][b] = t;
    if (cost(a) + cost(b) > before) { jv[r][b] = jv[r][a]; jv[r][a] = t; }
  }
  int fin[256], done[256];
  for (int p = 0; p < NP + 2; p++) {
    Sched::Pair& q = s.pair[p];
    if (p < NP) {
      for (int k = 0; k < 4; k++) q.khead[k] = (uint8_t)(korder[k] * 8 + (p >> 3));
      for (int r = 0; r < 4; r++) {
        if (jv[r][p] < 0) continue;
        q.item[q.nitems++] = (uint8_t)((r * 8 + used[r][jv[r][p]]++) * 8 + jv[r][p]);
      }
    }
    int t = p < NP ? 0 : -3, e = 1;
    for (int i = 0; i < q.nitems; i++) { t += (q.item[i] & 7) + 2; fin[q.item[i]] = t; done[q.item[i]] = t + (i + 1 < q.nitems ? 2 : 0); e += 8 + 4 * ((q.item[i] & 7) + 1); }
    for (int k = 0; k < 3 * MAX_STEPS + 6; k++) {
      const int n = k > 0 ? k - (SPARE_N & 1) : 0, r = n % 7, f = (e + (r < 4 ? r : r - 1)) % 12;
      q.oent[k] = (uint8_t)((r == 4 ? 6 : f >= 6 ? f + 2 : f) ^ (((n / 7) & 1) << 3));
    }
  }
  for (int p = 0; p < NP + 2; p++)
    for (int i = 0; i < s.pair[p].nitems; i++) {
      const int it = s.pair[p].item[i];
      for (int n = 0; n < 2 * (it & 7) + 2; n++) {
        bool last = true;
        for (int j = n >> 1; j < 8; j++) { const int o = (it & ~7) + j; if (o != it && fin[o] + LU_MARGIN > fin[it]) last = false; }
        if (last) s.pair[p].lastuse[i] |= (uint16_t)(1 << n);
      }
    }
  for (int j = 0; j < 8; j++) {
    int order[NH], left[4];
    for (int h = 0; h < NH; h++) { int k = h; for (; k > 0 && done[order[k - 1] * 8 + j] < done[h * 8 + j]; k--) order[k] = order[k - 1]; order[k] = h; }
    for (int kq = 0; kq < 4; kq++) {
      left[kq] = SPARE_N == 0 ? 16 : kq < SPARE_N ? 20 - SPARE_N : 16 - SPARE_N;
      for (int nh = 0; nh < 2; nh++) { Sched::Pair& q = s.pair[kq * 16 + nh * 8 + j]; q.otask = (uint8_t)(kq * 16 + nh * 8 + j); q.nsteps = (uint8_t)((left[kq] + 1) / 2); q.ochunk[0][0] = 255; }
    }
    for (int n = 0, kq = 0, run = 0; n < 64; ) {
      if (left[kq] > 0 && run < 2) {
        const int pos = --left[kq] + (SPARE_N & 1);
        for (int nh = 0; nh < 2; nh++) s.pair[kq * 16 + nh * 8 + j].ochunk[pos >> 1][pos & 1] = (uint8_t)(order[n >> 1] * 2 + 1 - (n & 1));
        n++; run++;
      } else { kq = (kq + 1) & 3; run = 0; }
    }
  }
}

}

extern "C" void kernel_launch(void* const* d_in, const int* in_sizes, int n_in, void* d_out, int out_size) {
  (void)in_sizes; (void)n_in; (void)out_size;
  const __nv_bfloat16* x     = (const __nv_bfloat16*)d_in[0];
  const __nv_bfloat16* ckv   = (const __nv_bfloat16*)d_in[1];
  const __nv_bfloat16* w_q   = (const __nv_bfloat16*)d_in[2];
  const __nv_bfloat16* w_uk  = (const __nv_bfloat16*)d_in[3];
  const __nv_bfloat16* w_uv  = (const __nv_bfloat16*)d_in[4];
  const __nv_bfloat16* w_o   = (const __nv_bfloat16*)d_in[5];
  const __nv_bfloat16* w_r   = (const __nv_bfloat16*)d_in[7];
  const __nv_bfloat16* w_g   = (const __nv_bfloat16*)d_in[8];
  const __nv_bfloat16* w_u   = (const __nv_bfloat16*)d_in[9];
  const __nv_bfloat16* w_d   = (const __nv_bfloat16*)d_in[10];
  const __nv_bfloat16* cvec  = (const __nv_bfloat16*)d_in[11];
  const __nv_bfloat16* w_mod = (const __nv_bfloat16*)d_in[12];
  __nv_bfloat16* out = (__nv_bfloat16*)d_out;

  static HostState st;
  if (!st.ready) {
    void* fn = nullptr; cudaDriverEntryPointQueryResult qr;
    cudaGetDriverEntryPoint("cuTensorMapEncodeTiled", &fn, cudaEnableDefault, &qr);
    st.encode = (EncodeFn)fn;
    cudaFuncSetAttribute(k_fused, cudaFuncAttributeMaxDynamicSharedMemorySize, SMEM);
    build_sched(st.sched);
    void *p_kvc, *p_h1, *p_part;
    cudaGetSymbolAddress(&p_kvc, g_kvc); cudaGetSymbolAddress(&p_h1, g_h1); cudaGetSymbolAddress(&p_part, g_part);
    st.sched.kvc = (__nv_bfloat16*)p_kvc; st.sched.h1 = (__nv_bfloat16*)p_h1; st.sched.part = (__nv_bfloat16*)p_part;
    st.ready = true;
  }
  make_2d(st.encode, &st.tmC, ckv, SEQ, DM, 128);
  make_2d(st.encode, &st.tmWq, w_q, DM, NH * DH, 64);
  make_2d(st.encode, &st.tmWk, w_uk, DM, NH * DH, 64);
  make_2d(st.encode, &st.tmWv, w_uv, DM, NH * DH, 64);
  make_3d(st.encode, &st.tmWo, w_o, NH * DH, DM / 64, (size_t)DM * 2, 128);
  make_3d(st.encode, &st.tmWm, w_mod, DM, 6 * DM / 64, (size_t)6 * DM * 2, 128);
  make_ffn(st.encode, &st.tmWg, w_g);
  make_ffn(st.encode, &st.tmWu, w_u);

  k_fused<<<NGRID, 384, SMEM, cudaStreamPerThread>>>(st.tmC, st.tmWq, st.tmWk, st.tmWv, st.tmWo, st.tmWg, st.tmWu, st.tmWm, st.sched,
                                                     x, cvec, w_o, w_r, w_g, w_u, w_d, out);
}
```

```cpp
#include <cuda_runtime.h>
#include <cuda_bf16.h>
#include <cuda.h>
#include <stdint.h>
#include <string.h>
#include <math.h>

namespace {

constexpr int SEQ = 2048, DM = 512, NH = 32, DH = 128, FF = 1792;
constexpr int NCTA = 128, NGRID = 132;

__device__ __align__(128) __nv_bfloat16 g_kvc[192 * SEQ * 64];
__device__ __align__(128) __nv_bfloat16 g_h1[SEQ * DM];
__device__ __align__(128) __nv_bfloat16 g_part[128 * 8 * 4096];
__device__ __align__(16) __nv_bfloat16 g_mod[6 * DM];
constexpr int C_MOD = 0, C_MOD2 = 16, C_H1 = 32, C_KV = 64, C_CTX = 128, C_PART = 384, C_END = C_PART + 32 * 32;
__device__ __align__(128) unsigned int g_cnt[C_END];
__device__ unsigned int g_epoch;
__device__ __align__(128) uint2 g_keys[128][4];
__device__ __align__(16) uint2 g_row[128][2][DM / 2];
__device__ __align__(16) uint2 g_yll[FF / 16][DM];

#define DBG(i)
#define DBGP(i)

__device__ __forceinline__ uint32_t smem_u32(const void* p) { return (uint32_t)__cvta_generic_to_shared(p); }
__device__ __forceinline__ int wg_tid() { int t; asm volatile("mov.u32 %0, %%tid.x;" : "=r"(t)); return t & 127; }
__device__ __forceinline__ uint32_t clk32() { uint32_t c; asm volatile("mov.u32 %0, %%clock;" : "=r"(c)); return c; }
__device__ __forceinline__ void mbar_arrive(uint32_t bar) { asm volatile("mbarrier.arrive.shared::cta.b64 _, [%0];" :: "r"(bar) : "memory"); }
__device__ __forceinline__ uint32_t mapa(uint32_t addr, uint32_t cta) { uint32_t r; asm("mapa.shared::cluster.u32 %0, %1, %2;" : "=r"(r) : "r"(addr), "r"(cta)); return r; }
__device__ __forceinline__ void mbar_arrive_remote_if(uint32_t cluster_addr, bool pred) {
  asm volatile("{\n.reg .pred p;\nsetp.ne.u32 p, %1, 0;\n@p mbarrier.arrive.shared::cluster.b64 _, [%0];\n}" :: "r"(cluster_addr), "r"((uint32_t)pred) : "memory");
}
__device__ __forceinline__ bool mbar_try(uint32_t bar, uint32_t parity) {
  uint32_t done;
  asm volatile("{\n.reg .pred p;\nmbarrier.try_wait.parity.shared::cta.b64 p, [%1], %2;\nselp.u32 %0, 1, 0, p;\n}" : "=r"(done) : "r"(bar), "r"(parity) : "memory");
  return done;
}
__device__ __forceinline__ bool mbar_test2(uint32_t bar, uint32_t parity) {
  uint32_t done;
  asm volatile("{\n.reg .pred p, q;\nmbarrier.test_wait.parity.shared::cta.b64 p, [%1], %2;\nmbarrier.test_wait.parity.shared::cta.b64 q, [%1 + 8], %2;\n"
               "and.pred p, p, q;\nselp.u32 %0, 1, 0, p;\n}" : "=r"(done) : "r"(bar), "r"(parity) : "memory");
  return done;
}
#define WAIT_LIM (1 << 14)
__device__ __forceinline__ void mbar_wait(uint32_t bar, uint32_t parity) {
  #pragma unroll 1
  for (int n = 0; n < WAIT_LIM; n++) { if (mbar_try(bar, parity)) break; }
}
__device__ __forceinline__ unsigned int ld_acquire(const unsigned int* p) {
  unsigned int v; asm volatile("ld.acquire.gpu.global.u32 %0, [%1];" : "=r"(v) : "l"(p) : "memory"); return v;
}
__device__ __forceinline__ unsigned int ld_relaxed(const unsigned int* p) {
  unsigned int v; asm volatile("ld.relaxed.gpu.global.u32 %0, [%1];" : "=r"(v) : "l"(p) : "memory"); return v;
}
__device__ __forceinline__ void wait_count_lazy(int idx, unsigned int target) {
  #pragma unroll 1
  for (int n = 0; n < WAIT_LIM; n++) { if (__all_sync(0xffffffff, (int)(ld_relaxed(&g_cnt[idx]) - target) >= 0)) break; __nanosleep(100); }
  ld_acquire(&g_cnt[idx]);
}
__device__ __forceinline__ uint4 ld_tagged2(const void* p) {
  uint4 v;
  asm volatile("{\n.reg .b64 a, b;\nld.relaxed.gpu.global.v2.u64 {a, b}, [%4];\nmov.b64 {%0, %1}, a;\nmov.b64 {%2, %3}, b;\n}"
    : "=r"(v.x), "=r"(v.y), "=r"(v.z), "=r"(v.w) : "l"(p) : "memory");
  return v;
}
__device__ __forceinline__ uint2 ld_tagged(const void* p) {
  uint2 v; asm volatile("{\n.reg .b64 a;\nld.relaxed.gpu.global.u64 a, [%2];\nmov.b64 {%0, %1}, a;\n}" : "=r"(v.x), "=r"(v.y) : "l"(p) : "memory"); return v;
}
__device__ __forceinline__ void st_tagged2(void* p, uint32_t a, uint32_t b, uint32_t tag) {
  asm volatile("{\n.reg .b64 a, b;\nmov.b64 a, {%1, %3};\nmov.b64 b, {%2, %3};\nst.relaxed.gpu.global.v2.u64 [%0], {a, b};\n}" :: "l"(p), "r"(a), "r"(b), "r"(tag) : "memory");
}
__device__ __forceinline__ void st_tagged(void* p, uint32_t a, uint32_t tag) {
  asm volatile("{\n.reg .b64 a;\nmov.b64 a, {%1, %2};\nst.relaxed.gpu.global.u64 [%0], a;\n}" :: "l"(p), "r"(a), "r"(tag) : "memory");
}
__device__ __forceinline__ void stg_v4(void* p, uint32_t a, uint32_t b, uint32_t c, uint32_t d) {
  asm volatile("st.global.v4.u32 [%0], {%1, %2, %3, %4};" :: "l"(p), "r"(a), "r"(b), "r"(c), "r"(d) : "memory");
}
__device__ __forceinline__ uint4 lds_v4(uint32_t addr) {
  uint4 v; asm volatile("ld.shared.v4.u32 {%0, %1, %2, %3}, [%4];" : "=r"(v.x), "=r"(v.y), "=r"(v.z), "=r"(v.w) : "r"(addr) : "memory"); return v;
}
__device__ __forceinline__ uint32_t lds_u32(uint32_t addr) { uint32_t v; asm volatile("ld.shared.u32 %0, [%1];" : "=r"(v) : "r"(addr) : "memory"); return v; }
__device__ __forceinline__ void sts_v4(uint32_t addr, uint32_t a, uint32_t b, uint32_t c, uint32_t d) {
  asm volatile("st.shared.v4.u32 [%0], {%1, %2, %3, %4};" :: "r"(addr), "r"(a), "r"(b), "r"(c), "r"(d) : "memory");
}
#define ELECT "{\n.reg .pred p;\nelect.sync _|p, 0xffffffff;\n@p "
__device__ __forceinline__ void w_mbar_init(uint32_t bar, uint32_t cnt) { asm volatile(ELECT "mbarrier.init.shared::cta.b64 [%0], %1;\n}" :: "r"(bar), "r"(cnt) : "memory"); }
__device__ __forceinline__ void w_expect_tx(uint32_t bar, uint32_t bytes) { asm volatile(ELECT "mbarrier.arrive.expect_tx.shared::cta.b64 _, [%0], %1;\n}" :: "r"(bar), "r"(bytes) : "memory"); }
__device__ __forceinline__ void w_arrive(uint32_t bar) { asm volatile(ELECT "mbarrier.arrive.shared::cta.b64 _, [%0];\n}" :: "r"(bar) : "memory"); }
__device__ __forceinline__ void tma_load_2d(uint32_t dst, const CUtensorMap* tm, uint32_t bar, int c0, int c1) {
  asm volatile(ELECT "cp.async.bulk.tensor.2d.shared::cluster.global.mbarrier::complete_tx::bytes [%0], [%1, {%3, %4}], [%2];\n}"
    :: "r"(dst), "l"(tm), "r"(bar), "r"(c0), "r"(c1) : "memory");
}
__device__ __forceinline__ void tma_load_2d_mc(uint32_t dst, const CUtensorMap* tm, uint32_t bar, int c0, int c1) {
  asm volatile(ELECT "cp.async.bulk.tensor.2d.shared::cluster.global.mbarrier::complete_tx::bytes.multicast::cluster [%0], [%1, {%3, %4}], [%2], %5;\n}"
    :: "r"(dst), "l"(tm), "r"(bar), "r"(c0), "r"(c1), "h"((uint16_t)3) : "memory");
}
__device__ __forceinline__ void tma_load_3d(uint32_t dst, const CUtensorMap* tm, uint32_t bar, int c0, int c1, int c2) {
  asm volatile(ELECT "cp.async.bulk.tensor.3d.shared::cluster.global.mbarrier::complete_tx::bytes [%0], [%1, {%3, %4, %5}], [%2];\n}"
    :: "r"(dst), "l"(tm), "r"(bar), "r"(c0), "r"(c1), "r"(c2) : "memory");
}
__device__ __forceinline__ void tma_load_3d_mc(uint32_t dst, const CUtensorMap* tm, uint32_t bar, int c0, int c1, int c2) {
  asm volatile(ELECT "cp.async.bulk.tensor.3d.shared::cluster.global.mbarrier::complete_tx::bytes.multicast::cluster [%0], [%1, {%3, %4, %5}], [%2], %6;\n}"
    :: "r"(dst), "l"(tm), "r"(bar), "r"(c0), "r"(c1), "r"(c2), "h"((uint16_t)3) : "memory");
}
__device__ __forceinline__ void bulk_load_mc(uint32_t dst, const void* src, uint32_t bar, bool ef) {
  if (ef) {
    uint64_t pol; asm("createpolicy.fractional.L2::evict_first.b64 %0, 1.0;" : "=l"(pol));
    asm volatile(ELECT "cp.async.bulk.shared::cluster.global.mbarrier::complete_tx::bytes.multicast::cluster.L2::cache_hint [%0], [%1], 16384, [%2], %3, %4;\n}"
      :: "r"(dst), "l"(src), "r"(bar), "h"((uint16_t)3), "l"(pol) : "memory");
  } else
    asm volatile(ELECT "cp.async.bulk.shared::cluster.global.mbarrier::complete_tx::bytes.multicast::cluster [%0], [%1], 16384, [%2], %3;\n}"
      :: "r"(dst), "l"(src), "r"(bar), "h"((uint16_t)3) : "memory");
}
__device__ __forceinline__ void bulk_load(uint32_t dst, const void* src, uint32_t bytes, uint32_t bar) {
  asm volatile(ELECT "cp.async.bulk.shared::cluster.global.mbarrier::complete_tx::bytes [%0], [%1], %2, [%3];\n}" :: "r"(dst), "l"(src), "r"(bytes), "r"(bar) : "memory");
}
__device__ __forceinline__ void tma_prefetch_2d(const CUtensorMap* tm, int c0, int c1) {
  asm volatile(ELECT "cp.async.bulk.prefetch.tensor.2d.L2.global [%0, {%1, %2}];\n}" :: "l"(tm), "r"(c0), "r"(c1) : "memory");
}
__device__ __forceinline__ void bulk_prefetch(const void* p, uint32_t bytes) {
  asm volatile(ELECT "cp.async.bulk.prefetch.L2.global [%0], %1;\n}" :: "l"(p), "r"(bytes) : "memory");
}
__device__ __forceinline__ void red_release(int idx) { asm volatile("red.release.gpu.global.add.u32 [%0], 1;" :: "l"(&g_cnt[idx]) : "memory"); }
__device__ __forceinline__ void prefetch_tmap(const CUtensorMap* tm) { asm volatile("prefetch.tensormap [%0];" :: "l"(tm) : "memory"); }
__device__ __forceinline__ void bar_sync(int id, int n) { asm volatile("bar.sync %0, %1;" :: "r"(id), "r"(n) : "memory"); }
__device__ __forceinline__ void bar_arrive(int id, int n) { asm volatile("bar.arrive %0, %1;" :: "r"(id), "r"(n) : "memory"); }
__device__ __forceinline__ void fence_async_smem() { asm volatile("fence.proxy.async.shared::cta;" ::: "memory"); }
__device__ __forceinline__ void fence_async_global() { asm volatile("fence.proxy.async.global;" ::: "memory"); }
__device__ __forceinline__ void fence_mbar_init() { asm volatile("fence.mbarrier_init.release.cluster;" ::: "memory"); }
__device__ __forceinline__ void cluster_arrive() { asm volatile("barrier.cluster.arrive.relaxed.aligned;" ::: "memory"); }
__device__ __forceinline__ void cluster_wait() { asm volatile("barrier.cluster.wait.aligned;" ::: "memory"); }
__device__ __forceinline__ uint32_t cluster_ctarank() { uint32_t r; asm volatile("mov.u32 %0, %%cluster_ctarank;" : "=r"(r)); return r; }
__device__ __forceinline__ void wgmma_fence() { asm volatile("wgmma.fence.sync.aligned;" ::: "memory"); }
__device__ __forceinline__ void wgmma_commit() { asm volatile("wgmma.commit_group.sync.aligned;" ::: "memory"); }
template<int N> __device__ __forceinline__ void wgmma_wait() { asm volatile("wgmma.wait_group.sync.aligned %0;" :: "n"(N) : "memory"); }
__device__ __forceinline__ float ex2(float x) { float y; asm("ex2.approx.ftz.f32 %0, %1;" : "=f"(y) : "f"(x)); return y; }
__device__ __forceinline__ float rcp_fast(float x) { float y; asm("rcp.approx.ftz.f32 %0, %1;" : "=f"(y) : "f"(x)); return y; }
__device__ __forceinline__ uint32_t pack_bf16(float lo, float hi) { uint32_t r; asm("cvt.rn.bf16x2.f32 %0, %1, %2;" : "=r"(r) : "f"(hi), "f"(lo)); return r; }
__device__ __forceinline__ float rbf(float x) { return __uint_as_float(pack_bf16(0.f, x)); }
__device__ __forceinline__ float bf_lo(uint32_t v) { return __uint_as_float(v << 16); }
__device__ __forceinline__ float bf_hi(uint32_t v) { return __uint_as_float(v & 0xffff0000u); }
__device__ __forceinline__ uint32_t add2(uint32_t a, uint32_t b) { uint32_t r; asm("add.rn.bf16x2 %0, %1, %2;" : "=r"(r) : "r"(a), "r"(b)); return r; }
__device__ __forceinline__ uint32_t fma2(uint32_t a, uint32_t b, uint32_t c) { uint32_t r; asm("fma.rn.bf16x2 %0, %1, %2, %3;" : "=r"(r) : "r"(a), "r"(b), "r"(c)); return r; }
__device__ __forceinline__ uint4 ldsm_x4_t(uint32_t addr) {
  uint4 v; asm volatile("ldmatrix.sync.aligned.m8n8.x4.trans.shared.b16 {%0, %1, %2, %3}, [%4];" : "=r"(v.x), "=r"(v.y), "=r"(v.z), "=r"(v.w) : "r"(addr) : "memory"); return v;
}
__device__ __forceinline__ uint4 ldsm_x4(uint32_t addr) {
  uint4 v; asm volatile("ldmatrix.sync.aligned.m8n8.x4.shared.b16 {%0, %1, %2, %3}, [%4];" : "=r"(v.x), "=r"(v.y), "=r"(v.z), "=r"(v.w) : "r"(addr) : "memory"); return v;
}
__device__ __forceinline__ void mma16816(float (&c)[4], const uint4& a, uint32_t b0, uint32_t b1) {
  asm("mma.sync.aligned.m16n8k16.row.col.f32.bf16.bf16.f32 {%0, %1, %2, %3}, {%4, %5, %6, %7}, {%8, %9}, {%0, %1, %2, %3};"
    : "+f"(c[0]), "+f"(c[1]), "+f"(c[2]), "+f"(c[3]) : "r"(a.x), "r"(a.y), "r"(a.z), "r"(a.w), "r"(b0), "r"(b1));
}
template<int N> __device__ __forceinline__ void fence_regs(float (&a)[N]) {
  #pragma unroll
  for (int i = 0; i < N; i++) asm volatile("" : "+f"(a[i]) :: "memory");
}
template<int N> __device__ __forceinline__ void fence_regs_u(uint32_t (&a)[N]) {
  #pragma unroll
  for (int i = 0; i < N; i++) asm volatile("" : "+r"(a[i]) :: "memory");
}
constexpr uint32_t SW128 = 0x40000040u, SW64 = 0x80000020u;
__device__ __forceinline__ uint32_t desc_lo(uint32_t addr, uint32_t lbo) { return ((addr & 0x3FFFF) >> 4) | ((lbo >> 4) << 16); }

template<int TB, int OA, int OB, uint32_t HA, uint32_t HB> __device__ __forceinline__ void wgmma_ss_n128(float (&d)[64], uint32_t da, uint32_t db, int sd) {
  asm volatile("{\n.reg .pred p;\n.reg .b32 ta, tb;\n.reg .b64 da, db;\nsetp.ne.b32 p, %66, 0;\nadd.u32 ta, %64, %68;\nadd.u32 tb, %65, %69;\nmov.b64 da, {ta, %70};\nmov.b64 db, {tb, %71};\n"
    "wgmma.mma_async.sync.aligned.m64n128k16.f32.bf16.bf16 "
    "{%0, %1, %2, %3, %4, %5, %6, %7, %8, %9, %10, %11, %12, %13, %14, %15, %16, %17, %18, %19, %20, %21, %22, %23, %24, %25, %26, %27, %28, %29, %30, %31, %32, %33, %34, %35, %36, %37, %38, %39, %40, %41, %42, %43, %44, %45, %46, %47, %48, %49, %50, %51, %52, %53, %54, %55, %56, %57, %58, %59, %60, %61, %62, %63}, da, db, p, 1, 1, 0, %67;\n}\n"
    : "+f"(d[0]), "+f"(d[1]), "+f"(d[2]), "+f"(d[3]), "+f"(d[4]), "+f"(d[5]), "+f"(d[6]), "+f"(d[7]), "+f"(d[8]), "+f"(d[9]), "+f"(d[10]), "+f"(d[11]), "+f"(d[12]), "+f"(d[13]), "+f"(d[14]), "+f"(d[15]), "+f"(d[16]), "+f"(d[17]), "+f"(d[18]), "+f"(d[19]), "+f"(d[20]), "+f"(d[21]), "+f"(d[22]), "+f"(d[23]), "+f"(d[24]), "+f"(d[25]), "+f"(d[26]), "+f"(d[27]), "+f"(d[28]), "+f"(d[29]), "+f"(d[30]), "+f"(d[31]), "+f"(d[32]), "+f"(d[33]), "+f"(d[34]), "+f"(d[35]), "+f"(d[36]), "+f"(d[37]), "+f"(d[38]), "+f"(d[39]), "+f"(d[40]), "+f"(d[41]), "+f"(d[42]), "+f"(d[43]), "+f"(d[44]), "+f"(d[45]), "+f"(d[46]), "+f"(d[47]), "+f"(d[48]), "+f"(d[49]), "+f"(d[50]), "+f"(d[51]), "+f"(d[52]), "+f"(d[53]), "+f"(d[54]), "+f"(d[55]), "+f"(d[56]), "+f"(d[57]), "+f"(d[58]), "+f"(d[59]), "+f"(d[60]), "+f"(d[61]), "+f"(d[62]), "+f"(d[63])
    : "r"(da), "r"(db), "r"(sd), "n"(TB), "n"(OA), "n"(OB), "n"(HA), "n"(HB));
}
template<int TB, int OB, uint32_t HB> __device__ __forceinline__ void wgmma_rs_n128(float (&d)[64], uint32_t a0, uint32_t a1, uint32_t a2, uint32_t a3, uint32_t db, int sd) {
  asm volatile("{\n.reg .pred p;\n.reg .b32 tb;\n.reg .b64 db;\nsetp.ne.b32 p, %69, 0;\nadd.u32 tb, %68, %71;\nmov.b64 db, {tb, %72};\n"
    "wgmma.mma_async.sync.aligned.m64n128k16.f32.bf16.bf16 "
    "{%0, %1, %2, %3, %4, %5, %6, %7, %8, %9, %10, %11, %12, %13, %14, %15, %16, %17, %18, %19, %20, %21, %22, %23, %24, %25, %26, %27, %28, %29, %30, %31, %32, %33, %34, %35, %36, %37, %38, %39, %40, %41, %42, %43, %44, %45, %46, %47, %48, %49, %50, %51, %52, %53, %54, %55, %56, %57, %58, %59, %60, %61, %62, %63}, {%64,%65,%66,%67}, db, p, 1, 1, %70;\n}\n"
    : "+f"(d[0]), "+f"(d[1]), "+f"(d[2]), "+f"(d[3]), "+f"(d[4]), "+f"(d[5]), "+f"(d[6]), "+f"(d[7]), "+f"(d[8]), "+f"(d[9]), "+f"(d[10]), "+f"(d[11]), "+f"(d[12]), "+f"(d[13]), "+f"(d[14]), "+f"(d[15]), "+f"(d[16]), "+f"(d[17]), "+f"(d[18]), "+f"(d[19]), "+f"(d[20]), "+f"(d[21]), "+f"(d[22]), "+f"(d[23]), "+f"(d[24]), "+f"(d[25]), "+f"(d[26]), "+f"(d[27]), "+f"(d[28]), "+f"(d[29]), "+f"(d[30]), "+f"(d[31]), "+f"(d[32]), "+f"(d[33]), "+f"(d[34]), "+f"(d[35]), "+f"(d[36]), "+f"(d[37]), "+f"(d[38]), "+f"(d[39]), "+f"(d[40]), "+f"(d[41]), "+f"(d[42]), "+f"(d[43]), "+f"(d[44]), "+f"(d[45]), "+f"(d[46]), "+f"(d[47]), "+f"(d[48]), "+f"(d[49]), "+f"(d[50]), "+f"(d[51]), "+f"(d[52]), "+f"(d[53]), "+f"(d[54]), "+f"(d[55]), "+f"(d[56]), "+f"(d[57]), "+f"(d[58]), "+f"(d[59]), "+f"(d[60]), "+f"(d[61]), "+f"(d[62]), "+f"(d[63])
    : "r"(a0), "r"(a1), "r"(a2), "r"(a3), "r"(db), "r"(sd), "n"(TB), "n"(OB), "n"(HB));
}
template<int TB, int OA, int OB, uint32_t HA, uint32_t HB> __device__ __forceinline__ void wgmma_ss_n64(float (&d)[32], uint32_t da, uint32_t db, int sd) {
  asm volatile("{\n.reg .pred p;\n.reg .b32 ta, tb;\n.reg .b64 da, db;\nsetp.ne.b32 p, %34, 0;\nadd.u32 ta, %32, %36;\nadd.u32 tb, %33, %37;\nmov.b64 da, {ta, %38};\nmov.b64 db, {tb, %39};\n"
    "wgmma.mma_async.sync.aligned.m64n64k16.f32.bf16.bf16 "
    "{%0, %1, %2, %3, %4, %5, %6, %7, %8, %9, %10, %11, %12, %13, %14, %15, %16, %17, %18, %19, %20, %21, %22, %23, %24, %25, %26, %27, %28, %29, %30, %31}, da, db, p, 1, 1, 0, %35;\n}\n"
    : "+f"(d[0]), "+f"(d[1]), "+f"(d[2]), "+f"(d[3]), "+f"(d[4]), "+f"(d[5]), "+f"(d[6]), "+f"(d[7]), "+f"(d[8]), "+f"(d[9]), "+f"(d[10]), "+f"(d[11]), "+f"(d[12]), "+f"(d[13]), "+f"(d[14]), "+f"(d[15]), "+f"(d[16]), "+f"(d[17]), "+f"(d[18]), "+f"(d[19]), "+f"(d[20]), "+f"(d[21]), "+f"(d[22]), "+f"(d[23]), "+f"(d[24]), "+f"(d[25]), "+f"(d[26]), "+f"(d[27]), "+f"(d[28]), "+f"(d[29]), "+f"(d[30]), "+f"(d[31])
    : "r"(da), "r"(db), "r"(sd), "n"(TB), "n"(OA), "n"(OB), "n"(HA), "n"(HB));
}
template<int TB, int OA, int OB, uint32_t HA, uint32_t HB> __device__ __forceinline__ void wgmma_ss_n128_new(float (&d)[64], uint32_t da, uint32_t db) {
  asm volatile("{\n.reg .pred p;\n.reg .b32 ta, tb;\n.reg .b64 da, db;\nsetp.ne.b32 p, %66, 0;\nadd.u32 ta, %64, %68;\nadd.u32 tb, %65, %69;\nmov.b64 da, {ta, %70};\nmov.b64 db, {tb, %71};\n"
    "wgmma.mma_async.sync.aligned.m64n128k16.f32.bf16.bf16 "
    "{%0, %1, %2, %3, %4, %5, %6, %7, %8, %9, %10, %11, %12, %13, %14, %15, %16, %17, %18, %19, %20, %21, %22, %23, %24, %25, %26, %27, %28, %29, %30, %31, %32, %33, %34, %35, %36, %37, %38, %39, %40, %41, %42, %43, %44, %45, %46, %47, %48, %49, %50, %51, %52, %53, %54, %55, %56, %57, %58, %59, %60, %61, %62, %63}, da, db, p, 1, 1, 0, %67;\n}\n"
    : "=f"(d[0]), "=f"(d[1]), "=f"(d[2]), "=f"(d[3]), "=f"(d[4]), "=f"(d[5]), "=f"(d[6]), "=f"(d[7]), "=f"(d[8]), "=f"(d[9]), "=f"(d[10]), "=f"(d[11]), "=f"(d[12]), "=f"(d[13]), "=f"(d[14]), "=f"(d[15]), "=f"(d[16]), "=f"(d[17]), "=f"(d[18]), "=f"(d[19]), "=f"(d[20]), "=f"(d[21]), "=f"(d[22]), "=f"(d[23]), "=f"(d[24]), "=f"(d[25]), "=f"(d[26]), "=f"(d[27]), "=f"(d[28]), "=f"(d[29]), "=f"(d[30]), "=f"(d[31]), "=f"(d[32]), "=f"(d[33]), "=f"(d[34]), "=f"(d[35]), "=f"(d[36]), "=f"(d[37]), "=f"(d[38]), "=f"(d[39]), "=f"(d[40]), "=f"(d[41]), "=f"(d[42]), "=f"(d[43]), "=f"(d[44]), "=f"(d[45]), "=f"(d[46]), "=f"(d[47]), "=f"(d[48]), "=f"(d[49]), "=f"(d[50]), "=f"(d[51]), "=f"(d[52]), "=f"(d[53]), "=f"(d[54]), "=f"(d[55]), "=f"(d[56]), "=f"(d[57]), "=f"(d[58]), "=f"(d[59]), "=f"(d[60]), "=f"(d[61]), "=f"(d[62]), "=f"(d[63])
    : "r"(da), "r"(db), "n"(0), "n"(TB), "n"(OA), "n"(OB), "n"(HA), "n"(HB));
}
template<int TB, int OA, int OB, uint32_t HA, uint32_t HB> __device__ __forceinline__ void wgmma_ss_n64_new(float (&d)[32], uint32_t da, uint32_t db) {
  asm volatile("{\n.reg .pred p;\n.reg .b32 ta, tb;\n.reg .b64 da, db;\nsetp.ne.b32 p, %34, 0;\nadd.u32 ta, %32, %36;\nadd.u32 tb, %33, %37;\nmov.b64 da, {ta, %38};\nmov.b64 db, {tb, %39};\n"
    "wgmma.mma_async.sync.aligned.m64n64k16.f32.bf16.bf16 "
    "{%0, %1, %2, %3, %4, %5, %6, %7, %8, %9, %10, %11, %12, %13, %14, %15, %16, %17, %18, %19, %20, %21, %22, %23, %24, %25, %26, %27, %28, %29, %30, %31}, da, db, p, 1, 1, 0, %35;\n}\n"
    : "=f"(d[0]), "=f"(d[1]), "=f"(d[2]), "=f"(d[3]), "=f"(d[4]), "=f"(d[5]), "=f"(d[6]), "=f"(d[7]), "=f"(d[8]), "=f"(d[9]), "=f"(d[10]), "=f"(d[11]), "=f"(d[12]), "=f"(d[13]), "=f"(d[14]), "=f"(d[15]), "=f"(d[16]), "=f"(d[17]), "=f"(d[18]), "=f"(d[19]), "=f"(d[20]), "=f"(d[21]), "=f"(d[22]), "=f"(d[23]), "=f"(d[24]), "=f"(d[25]), "=f"(d[26]), "=f"(d[27]), "=f"(d[28]), "=f"(d[29]), "=f"(d[30]), "=f"(d[31])
    : "r"(da), "r"(db), "n"(0), "n"(TB), "n"(OA), "n"(OB), "n"(HA), "n"(HB));
}
template<int OA, int OB = 0, uint32_t HA = SW128> __device__ __forceinline__ void kblock_n128(float (&d)[64], uint32_t da, uint32_t db, int sd) {
  constexpr int H = HA == SW128 ? 4 : 512;
  wgmma_ss_n128<1, OA, OB, HA, SW128>(d, da, db, sd); wgmma_ss_n128<1, OA + 2, OB + 128, HA, SW128>(d, da, db, 1);
  wgmma_ss_n128<1, OA + H, OB + 256, HA, SW128>(d, da, db, 1); wgmma_ss_n128<1, OA + H + 2, OB + 384, HA, SW128>(d, da, db, 1);
}

__device__ __forceinline__ float quad_sum(float v) {
  v += __shfl_xor_sync(0xffffffff, v, 1);
  v += __shfl_xor_sync(0xffffffff, v, 2);
  return v;
}
struct Row { uint32_t v[8]; };
template<class F> __device__ __forceinline__ Row load_row(const __nv_bfloat16* p, int lane, F ld) {
  const uint4 a = ld(reinterpret_cast<const uint4*>(p) + lane), b = ld(reinterpret_cast<const uint4*>(p) + 32 + lane);
  return Row{{a.x, a.y, a.z, a.w, b.x, b.y, b.z, b.w}};
}
__device__ __forceinline__ Row ldg_row(const __nv_bfloat16* p, int lane) { return load_row(p, lane, [](const uint4* q) { return __ldg(q); }); }
__device__ __forceinline__ Row ldca_row(const __nv_bfloat16* p, int lane) { return load_row(p, lane, [](const uint4* q) { return __ldca(q); }); }
__device__ __forceinline__ Row lds_row(uint32_t addr, int lane) {
  const uint4 a = lds_v4(addr + lane * 16), b = lds_v4(addr + 512 + lane * 16);
  return Row{{a.x, a.y, a.z, a.w, b.x, b.y, b.z, b.w}};
}
__device__ __forceinline__ void store_row(__nv_bfloat16* p, int lane, const Row& r) {
  stg_v4(p + lane * 8, r.v[0], r.v[1], r.v[2], r.v[3]); stg_v4(p + 256 + lane * 8, r.v[4], r.v[5], r.v[6], r.v[7]);
}
__device__ __forceinline__ Row fma_row(const Row& a, const Row& b, const Row& c) {
  Row r;
  #pragma unroll
  for (int i = 0; i < 8; i++) r.v[i] = fma2(a.v[i], b.v[i], c.v[i]);
  return r;
}
__device__ __forceinline__ Row add_row(const Row& a, const Row& b) {
  Row r;
  #pragma unroll
  for (int i = 0; i < 8; i++) r.v[i] = add2(a.v[i], b.v[i]);
  return r;
}
__device__ __forceinline__ Row one_plus(const Row& a) {
  Row r;
  #pragma unroll
  for (int i = 0; i < 8; i++) r.v[i] = add2(a.v[i], 0x3f803f80u);
  return r;
}
__device__ __forceinline__ float row_at(const Row& x, int i) { return (i & 1) ? bf_hi(x.v[i >> 1]) : bf_lo(x.v[i >> 1]); }
template<int N> __device__ __forceinline__ void warp_sums(float (&s)[N]) {
  #pragma unroll
  for (int o = 16; o > 0; o >>= 1) {
    #pragma unroll
    for (int k = 0; k < N; k++) s[k] += __shfl_xor_sync(0xffffffff, s[k], o);
  }
}
__device__ __forceinline__ void ln_stats(float& s1, float& s2) {
  s1 *= 1.f / DM;
  asm("rsqrt.approx.ftz.f32 %0, %1;" : "=f"(s2) : "f"(fmaxf(fmaf(-s1, s1, s2 * (1.f / DM)), 0.f) + 1e-5f));
}
__device__ __forceinline__ Row ln_apply(const Row& x, float mean, float f) {
  Row n;
  const float o = -mean * f;
  #pragma unroll
  for (int i = 0; i < 8; i++) n.v[i] = pack_bf16(fmaf(bf_lo(x.v[i]), f, o), fmaf(bf_hi(x.v[i]), f, o));
  return n;
}

constexpr int SM_Q = 6 * 32768, SM_BAR = 7 * 32768, SM_MAIL = SM_BAR + 640, SM_RED = SM_MAIL + 128, SM_H2 = SM_RED + 1024, SM_KEY = SM_H2 + 1024, SMEM = SM_KEY + 128;
constexpr int B_AF = 0, B_WF = 64, B_RF = 112, B_WE = 168, B_RE = 216, B_PUB = 272, B_RDY = 496;
constexpr int R_MOD = B_RDY, R_H1 = B_RDY + 8, R_ITEM = B_RDY + 16, R_NEAR = B_RDY + 48, R_CTX = B_RDY + 64;
constexpr int R_KEY = B_AF + 8, R_PART = B_AF + 32;
constexpr int NPUB = 14;
__device__ __forceinline__ uint32_t k_addrA(int kb) { return ((0x6310u >> ((kb >> 1) * 4)) & 15u) * 32768u + (kb & 1) * 16384u; }
__device__ __forceinline__ uint32_t k_addrW(int s) { return ((0x254u >> ((s >> 1) * 4)) & 15u) * 32768u + (s & 1) * 16384u; }

#define KORDER 0x3201
constexpr int KHEAD0 = ((KORDER >> 12) & 3) * 8;
constexpr int MAX_ITEMS = 4;
constexpr int MAX_STEPS = 10;
struct Sched {
  __nv_bfloat16 *kvc, *h1, *part;
  struct Pair {
    uint8_t oent[3 * MAX_STEPS + 6];
    uint16_t lastuse[MAX_ITEMS];
    uint8_t khead[4];
    uint8_t nitems, item[MAX_ITEMS];
    uint8_t otask, nsteps;
    uint8_t ochunk[MAX_STEPS][2];
  } pair[NGRID / 2];
};

__device__ __forceinline__ int ring_add(int e, int n) { e += n; return e >= 12 ? e - 12 : e; }
__device__ __forceinline__ int ring_slot(int e) { return e >= 6 ? e - 6 : e; }
__device__ __forceinline__ void ring_wait_full(uint32_t bars, int e) { mbar_wait(bars + B_RF + 8 * ring_slot(e), e >= 6); }

__device__ __forceinline__ void o_wait_full(uint32_t bars, uint32_t v) { mbar_wait(bars + B_RF + 8 * (v & 7), v >> 3); }

struct Ctx {
  uint32_t base, bars;
  uint32_t rel;
  bool rel1;
  int w, nev;
  const Sched* sched;
  uint32_t tr;
};
#define TR(id)
__device__ __forceinline__ void slot_release(const Ctx& x, int s, bool twice) {
  mbar_arrive_remote_if(x.rel + B_RE + 8 * s, twice ? (wg_tid() & 31) == 0 : x.rel1);
}
__device__ __forceinline__ void ring_release(const Ctx& x, int e, bool twice) { slot_release(x, ring_slot(e), twice); }
__device__ __forceinline__ void publish(Ctx& x, int idx) {
  const uint32_t n = x.w * NPUB + x.nev;
  const int t = wg_tid();
  if (t == 0) asm volatile("st.shared.u32 [%0], %1;" :: "r"(x.base + SM_MAIL + 4 * n), "r"(idx) : "memory");
  __syncwarp();
  if ((t & 31) == 0) mbar_arrive(x.bars + B_PUB + 8 * n);
  x.nev++;
}

template<int KK = 0> __device__ __forceinline__ void issue_qk(float (&S)[64], uint32_t dq, uint32_t dk) {
  constexpr int off = (KK >> 1) * 512 + (KK & 1) * 2;
  if constexpr (KK == 0) wgmma_ss_n128_new<0, 0, 0, SW64, SW64>(S, dq, dk); else wgmma_ss_n128<0, off, off, SW64, SW64>(S, dq, dk, 1);
  if constexpr (KK < 7) issue_qk<KK + 1>(S, dq, dk);
}
template<int KK = 0> __device__ __forceinline__ void issue_qk_half(float (&S)[32], uint32_t dq, uint32_t dk) {
  constexpr int off = (KK >> 1) * 512 + (KK & 1) * 2;
  if constexpr (KK == 0) wgmma_ss_n64_new<0, 0, 256, SW64, SW64>(S, dq, dk); else wgmma_ss_n64<0, off, off + 256, SW64, SW64>(S, dq, dk, 1);
  if constexpr (KK < 7) issue_qk_half<KK + 1>(S, dq, dk);
}
template<int NK, int KK = 0>
__device__ __forceinline__ void issue_pv(float (&O)[64], uint32_t (&P)[32], uint32_t dv, int accumulate) {
  wgmma_rs_n128<1, (KK + 8 - NK) * 64, SW64>(O, P[4*KK], P[4*KK+1], P[4*KK+2], P[4*KK+3], dv, accumulate);
  if constexpr (KK + 1 < NK) issue_pv<NK, KK + 1>(O, P, dv, 1);
}
template<int K0, int K1>
__device__ __forceinline__ void exp_pack(const float (&S)[64], uint32_t (&D)[32], float& s0, float& s1) {
  #pragma unroll
  for (int k = K0; k < K1; k++) {
    const float e0 = ex2(S[2*k]), e1 = ex2(S[2*k+1]);
    D[k] = pack_bf16(e0, e1);
    if (k & 1) s1 += e0 + e1; else s0 += e0 + e1;
  }
}
__device__ __forceinline__ int diag_limit() { const int t = wg_tid(); return 16 * (t >> 5) + ((t & 31) >> 2) - 2 * (t & 3); }
__device__ __forceinline__ void exp_pack_diag(const float (&S)[64], uint32_t (&D)[32], int t, float& s0, float& s1) {
  #pragma unroll
  for (int k = 0; k < 16; k++) {
    const int c = 8 * (k >> 1) - 8 * (k & 1);
    const float e0 = ex2((c <= t) ? S[2*k] : -INFINITY), e1 = ex2((c + 1 <= t) ? S[2*k+1] : -INFINITY);
    D[k] = pack_bf16(e0, e1);
    if (k & 1) s1 += e0 + e1; else s0 += e0 + e1;
  }
}
constexpr float SUM_HI = 1.8446744073709552e19f;
constexpr float SUM_LO = 5.421010862427522e-20f;

__device__ __forceinline__ void classic_tile(const float (&S)[64], uint32_t (&P)[32], bool fresh, bool half, bool was_classic, volatile float* mc,
                                             float& l0, float& l1, float& s0, float& s1, float& sc0, float& sc1) {
  const int tmask = diag_limit();
  float4 t[16];
  #pragma unroll
  for (int j = 0; j < 16; j++) t[j] = make_float4(S[4*j], S[4*j+1], S[4*j+2], S[4*j+3]);
  float mx0 = -INFINITY, mx1 = -INFINITY;
  #pragma unroll 1
  for (int j = 0; j < 16; j++) {
    float4 v = t[j];
    const int lim = !fresh ? 1000 : j < 8 ? tmask - 8 * j : half ? -1000 : 1000;
    v.x = 0 <= lim ? v.x : -INFINITY; v.y = 1 <= lim ? v.y : -INFINITY; v.z = -8 <= lim ? v.z : -INFINITY; v.w = -7 <= lim ? v.w : -INFINITY;
    t[j] = v;
    mx0 = fmaxf(mx0, fmaxf(v.x, v.y)); mx1 = fmaxf(mx1, fmaxf(v.z, v.w));
  }
  mx0 = fmaxf(mx0, __shfl_xor_sync(0xffffffff, mx0, 1));
  mx1 = fmaxf(mx1, __shfl_xor_sync(0xffffffff, mx1, 1));
  mx0 = fmaxf(mx0, __shfl_xor_sync(0xffffffff, mx0, 2));
  mx1 = fmaxf(mx1, __shfl_xor_sync(0xffffffff, mx1, 2));
  const float mc0 = was_classic ? mc[0] : 0.f, mc1 = was_classic ? mc[1] : 0.f;
  const float n0 = fresh ? -mx0 : fminf(mc0, -mx0), n1 = fresh ? -mx1 : fminf(mc1, -mx1);
  sc0 = ex2(n0 - mc0); sc1 = ex2(n1 - mc1);
  mc[0] = n0; mc[1] = n1;
  s0 = 0.f; s1 = 0.f;
  #pragma unroll 1
  for (int j = 0; j < 16; j++) {
    const float4 v = t[j];
    const float e0 = ex2(v.x + n0), e1 = ex2(v.y + n0), e2 = ex2(v.z + n1), e3 = ex2(v.w + n1);
    s0 += e0 + e1; s1 += e2 + e3;
    reinterpret_cast<uint2*>(t)[j] = make_uint2(pack_bf16(e0, e1), pack_bf16(e2, e3));
  }
  #pragma unroll
  for (int j = 0; j < 8; j++) { P[4*j] = __float_as_uint(t[j].x); P[4*j+1] = __float_as_uint(t[j].y); P[4*j+2] = __float_as_uint(t[j].z); P[4*j+3] = __float_as_uint(t[j].w); }
  if (!fresh) { l0 *= sc0; l1 *= sc1; }
}
__device__ __forceinline__ void pack_tile(const float (&A)[64], uint32_t (&D)[32], float f0, float f1) {
  #pragma unroll
  for (int j = 0; j < 16; j++) {
    D[8 * (j >> 2) + (j & 3)] = pack_bf16(A[4*j] * f0, A[4*j+1] * f0);
    D[8 * (j >> 2) + 4 + (j & 3)] = pack_bf16(A[4*j+2] * f1, A[4*j+3] * f1);
  }
}
__device__ __forceinline__ int piece0(int t) { return ((t >> 5) * 16 + ((t & 31) >> 2)) * 32 + (((t ^ (t >> 3)) & 3) << 3); }
__device__ __forceinline__ void store_tile(__nv_bfloat16* p, const uint32_t (&D)[32]) {
  #pragma unroll
  for (int i = 0; i < 8; i++) stg_v4(p + (i >> 2) * (SEQ * 64) + ((i >> 1) & 1) * 4096 + (i & 1) * 256, D[4*i], D[4*i+1], D[4*i+2], D[4*i+3]);
}

enum : int { PV_ACC = 0, PV_ZERO = 1, PV_HALF = 2, PV_NONE = 3 };
struct Att {
  float l0, l1, i0, i1;
  bool classic;
  volatile float* mc;
};
__device__ __forceinline__ void store_ctx(Ctx& x, int code, const uint32_t (&D)[32]) {
  store_tile(x.sched->kvc + ((size_t)(128 + (code >> 5) * 2) * SEQ + ((code >> 1) & 15) * 128) * 64 + (code & 1) * 2048 + piece0(wg_tid()), D);
  publish(x, C_CTX + (code >> 2));
}
__device__ __forceinline__ __nv_bfloat16* kv_tile(const Ctx& x, int code) {
  return x.sched->kvc + ((size_t)(x.w * 64 + (code >> 4) * 2) * SEQ + (code & 15) * 128) * 64 + piece0(wg_tid());
}
#define NO_CLASSIC 0
__device__ __forceinline__ void q_proj(Ctx& x, Att& a, int& e, int& sk, int& sv, int& en, int& sn, bool isY,
                                       const uint32_t (&PA)[32], const uint32_t (&PB)[32], int vtile, bool first, bool dbg = false) {
  float S[64];
  int ek = 0, s = sk, ps = 0, ph = e >= 6, kb = 0;
  uint32_t qa = 0;
  sv = en = sn = 0;
  if (isY) bar_sync(1 + x.w, 256);
  if (dbg) DBG(80);
  TR(1);
  if (first) mbar_wait(x.bars + B_RF + 8 * s, ph);
  #pragma unroll 1
  while (true) {
    #pragma unroll 1
    do {
      if (dbg) DBG(81 + kb);
      TR(2);
      wgmma_fence();
      kblock_n128<0>(S, desc_lo(x.base + x.w * 8192, 16) + s * 2048, desc_lo(x.base + 16384, 8192) + s * 2048, kb != 0);
      wgmma_commit();
      if (kb == 7 && !isY) bar_arrive(1 + (x.w ^ 1), 256);
      wgmma_wait<1>();
      mbar_arrive_remote_if(x.rel + B_RE + 8 * ps, x.rel1 && kb > 0);
      ps = s;
      if (++s == 6) { s = 0; ph ^= 1; }
      if (++kb == 8) break;
      mbar_wait(x.bars + B_RF + 8 * s, ph);
    } while (kb != 4);
    asm volatile("" : "+r"(vtile));
    if (kb == 8) break;
    a.i0 = rcp_fast(quad_sum(a.l0)); a.i1 = rcp_fast(quad_sum(a.l1));
    e = ring_add(e, 8); ek = ring_add(e, isY ? 0 : 2); en = ring_add(e, isY ? 2 : 4);
    sk = ring_slot(ek); sv = ring_slot(e) + 1; sn = ring_slot(en);
    qa = x.base + SM_Q + x.w * 4096 + piece0(wg_tid()) * 2;
    if (vtile >= 0) store_tile(kv_tile(x, vtile) + 2048, PA);
  }
  if (vtile >= 0) { store_tile(kv_tile(x, vtile), PB); publish(x, C_KV + (vtile >> 4)); }
  wgmma_wait<0>();
  fence_regs(S);
  if (dbg) DBG(89);
  TR(3);
  slot_release(x, ps, false);
  const bool landed = isY && mbar_test2(x.bars + B_RF + 8 * sk, e >= 6);
  #pragma unroll
  for (int i = 0; i < 8; i++) {
    const int j = 4 * (i >> 1), o = 2 * (i & 1);
    sts_v4(qa + (i >> 1) * 8192 + (i & 1) * 512,
           pack_bf16(S[4*j+o], S[4*j+o+1]), pack_bf16(S[4*j+4+o], S[4*j+5+o]), pack_bf16(S[4*j+8+o], S[4*j+9+o]), pack_bf16(S[4*j+12+o], S[4*j+13+o]));
  }
  fence_async_smem();
  if (dbg) DBG(90);
  TR(4);
  if (!landed) { mbar_wait(x.bars + B_RF + 8 * sk, ek >= 6); mbar_wait(x.bars + B_RF + 8 * sv, e >= 6); }
}

template<int KIND>
__device__ __forceinline__ void slot(Ctx& x, Att& a, int& e, int& sk, int sv, int en, int sn, float (&O)[64], uint32_t (&Pn)[32], uint32_t (&Po)[32],
                                     bool more, bool isY, bool half, int pv, int pend) {
  float S[64];
  const int w = x.w;
  const uint32_t dq = desc_lo(x.base + SM_Q + w * 4096, 16), dk = desc_lo(x.base, 16) + sk * 2048, dv = desc_lo(x.base, 8192) + sv * 2048;
  bar_sync(1 + w, 256);
  TR(5 + KIND);
  if (KIND == 2) {
    wgmma_fence();
    issue_qk(S, dq, dk); wgmma_commit();
    issue_pv<8>(O, Po, dv, 1); wgmma_commit();
    bar_arrive(1 + (w ^ 1), 256);
    wgmma_wait<1>();
  } else if (KIND == 0 && half) {
    float T[32];
    wgmma_fence(); issue_qk_half(T, dq, dk); wgmma_commit();
    if (pv == PV_NONE) { wgmma_fence(); wgmma_commit(); }
    else               { wgmma_fence(); issue_pv<8>(O, Po, dv, pv == PV_ACC); wgmma_commit(); }
    bar_arrive(1 + (w ^ 1), 256);
    wgmma_wait<1>();
    fence_regs(T);
    #pragma unroll
    for (int i = 0; i < 32; i++) { S[i] = T[i]; asm volatile("" : "=f"(S[32 + i])); }
  } else {
    wgmma_fence(); issue_qk(S, dq, dk); wgmma_commit();
    if (KIND == 1 && pend >= 0) { bar_arrive(1 + (w ^ 1), 256); pack_tile(O, Pn, a.i0, a.i1); store_ctx(x, pend, Pn); TR(8); }
    if (KIND == 0 && pv == PV_NONE) { wgmma_fence(); wgmma_commit(); }
    else if (pv == PV_HALF)         { wgmma_fence(); issue_pv<4>(O, Po, dv, 0); wgmma_commit(); }
    else                            { wgmma_fence(); issue_pv<8>(O, Po, dv, pv == PV_ACC); wgmma_commit(); }
    if (KIND == 0 || pend < 0) bar_arrive(1 + (w ^ 1), 256);
    wgmma_wait<1>();
  }
  fence_regs(S);
  fence_regs_u(Pn);
  TR(9);
  slot_release(x, sk, KIND == 0 && isY);
  const bool landed = mbar_test2(x.bars + B_RF + 8 * sn, en >= 6);
  float s0 = 0.f, s1 = 0.f;
  const bool was_classic = KIND != 0 && a.classic;
  if (KIND == 0) {
    a.l0 = 0.f; a.l1 = 0.f;
    if (!half) exp_pack<16, 32>(S, Pn, s0, s1);
    else {
      #pragma unroll
      for (int i = 16; i < 32; i++) asm volatile("" : "=r"(Pn[i]));
    }
    exp_pack_diag(S, Pn, diag_limit(), s0, s1);
    uint32_t b0 = __ballot_sync(0xffffffff, s0 >= SUM_LO), b1 = __ballot_sync(0xffffffff, s1 >= SUM_LO);
    b0 |= b0 >> 1; b0 |= b0 >> 2; b1 |= b1 >> 1; b1 |= b1 >> 2;
    a.classic = __any_sync(0xffffffff, !(s0 <= SUM_HI && s1 <= SUM_HI)) || (b0 & b1 & 0x11111111u) != 0x11111111u;
  } else {
    exp_pack<0, 32>(S, Pn, s0, s1);
    a.classic = __any_sync(0xffffffff, a.classic || !(s0 <= SUM_HI && s1 <= SUM_HI));
  }
  fence_regs_u(Pn);
  TR(10);
  if (!landed) {
    mbar_wait(x.bars + B_RF + 8 * sn, en >= 6);
    if (more) mbar_wait(x.bars + B_RF + 8 * sn + 8, en >= 6);
  }
  wgmma_wait<0>();
  fence_regs(O);
  fence_regs_u(Po);
  TR(11);
  slot_release(x, sv, KIND == 1 && isY && pv != PV_ACC);
  if (!NO_CLASSIC && __builtin_expect(a.classic, 0)) {
    float sc0, sc1;
    classic_tile(S, Pn, KIND == 0, half, was_classic, a.mc, a.l0, a.l1, s0, s1, sc0, sc1);
    if (KIND != 0) {
      #pragma unroll
      for (int j = 0; j < 16; j++) { O[4*j] *= sc0; O[4*j+1] *= sc0; O[4*j+2] *= sc1; O[4*j+3] *= sc1; }
    }
  }
  a.l0 += s0; a.l1 += s1;
  e = en; sk = sn;
}

__device__ __forceinline__ int attention(Ctx& x, const uint8_t* items, int nitems, int rank, uint32_t (&PA)[32], uint32_t (&PB)[32], int vtile) {
  int e = 0, sk = 0;
  float O[64];
  Att a;
  volatile float mc[2];
  a.l0 = 1.f; a.l1 = 1.f; a.i0 = 0.f; a.i1 = 0.f; a.classic = false; a.mc = mc;
  int pv = PV_NONE, cur = -1;
#define DBGS()
  #pragma unroll 1
  for (int it = 0; ; it++) {
    const bool isY = (it & 1) == x.w;
    int pend = cur;
    if (it < nitems) {
      const bool half = isY == (rank != 0);
      int sv, en, sn;
      DBG(16 + it);
      q_proj(x, a, e, sk, sv, en, sn, isY, PA, PB, vtile, it == 0);
      vtile = -1;
      const int item = items[it];
      cur = item * 4 + (isY ? 3 - rank : rank);
      int rem = 2 * (item & 7) + (isY ? 1 : 0);
      DBGS();
      slot<0>(x, a, e, sk, sv, en, sn, O, PA, PB, rem > 0, isY, half, pv, -1);
      pv = half ? PV_HALF : PV_ZERO;
      #pragma unroll 1
      while (rem > 0) {
        DBGS();
        slot<1>(x, a, e, sk, sk + 1, ring_add(e, 2), sk == 4 ? 0 : sk + 2, O, PB, PA, rem > 1, isY, false, pv, pend);
        pv = PV_ACC; pend = -1;
        if (rem == 1) break;
        rem -= 2;
        DBGS();
        slot<2>(x, a, e, sk, sk + 1, ring_add(e, 2), sk == 4 ? 0 : sk + 2, O, PA, PB, rem > 0, false, false, 0, -1);
      }
      if (isY) continue;
    } else {
      DBGS();
      slot_release(x, 6, false);
      const uint32_t dv = desc_lo(x.base, 8192) + sk * 2048;
      bar_sync(1 + x.w, 256);
      if (pv == PV_HALF) { wgmma_fence(); issue_pv<4>(O, PB, dv, 0); wgmma_commit(); }
      else { wgmma_fence(); issue_pv<8>(O, PB, dv, pv == PV_ACC); wgmma_commit(); }
      if (isY) bar_arrive(1 + (x.w ^ 1), 256);
      a.i0 = rcp_fast(quad_sum(a.l0)); a.i1 = rcp_fast(quad_sum(a.l1));
      ring_wait_full(x.bars, e);
      wgmma_wait<0>();
      fence_regs(O);
      fence_regs_u(PB);
      slot_release(x, sk, false);
    }
    if (pend >= 0) {
      pack_tile(O, PB, a.i0, a.i1);
      if (it == nitems) return pend;
      store_ctx(x, pend, PB);
    }
    #pragma unroll
    for (int i = 0; i < 32; i++) asm volatile("mov.b32 %0, %1;" : "=r"(PB[i]) : "r"(PA[i]));
  }
}

#define LN_AT 2
#define X_AT 6
#define PERT 0
#define CTX_T 3
#define PF_AT 5
#define PF_N 4
#define PF_MOE -3
constexpr float QSCALE = 0.08838834764831845f * 1.4426950408889634f;
__device__ __forceinline__ void mod_cta(Ctx& x, const __nv_bfloat16* cvec) {
  const int t = wg_tid(), ct = x.w * 128 + t;
  #pragma unroll 1
  for (int k = 0; k < 6; k++) slot_release(x, k, false);
  const uint32_t cv = __ldg(reinterpret_cast<const uint32_t*>(cvec) + ct);
  asm volatile("st.shared.u32 [%0], %1;" :: "r"(x.base + SM_H2 + ct * 4),
               "r"(pack_bf16(__fdividef(bf_lo(cv), 1.f + __expf(-bf_lo(cv))), __fdividef(bf_hi(cv), 1.f + __expf(-bf_hi(cv))))) : "memory");
  bar_sync(5, 256);
  float acc[64];
  int e = 0;
  #pragma unroll 1
  for (int g = 0; g < 24; g++) {
    uint32_t a[8];
    #pragma unroll
    for (int i = 0; i < 8; i++) a[i] = lds_u32(x.base + SM_H2 + (g & 7) * 128 + i * 16 + (t & 3) * 4);
    ring_wait_full(x.bars, e);
    const uint32_t db = desc_lo(x.base + x.w * 16384, 8192) + ring_slot(e) * 2048;
    wgmma_fence();
    wgmma_rs_n128<1, 0, SW128>(acc, a[0], a[0], a[1], a[1], db, g & 7);
    wgmma_rs_n128<1, 128, SW128>(acc, a[2], a[2], a[3], a[3], db, 1);
    wgmma_rs_n128<1, 256, SW128>(acc, a[4], a[4], a[5], a[5], db, 1);
    wgmma_rs_n128<1, 384, SW128>(acc, a[6], a[6], a[7], a[7], db, 1);
    wgmma_commit();
    wgmma_wait<0>();
    fence_regs(acc);
    ring_release(x, e, false);
    e = ring_add(e, 1);
    if ((g & 7) == 7) {
      if (t < 4) {
        const float sc = (g == 7 && blockIdx.x < NCTA + 2) ? QSCALE : 1.f;
        uint32_t* dst = reinterpret_cast<uint32_t*>(g_mod + (g >> 3) * 1024 + (blockIdx.x - NCTA) * 256 + x.w * 128) + t;
        #pragma unroll
        for (int j = 0; j < 16; j++) dst[4 * j] = pack_bf16(rbf(acc[4*j]) * sc, rbf(acc[4*j+1]) * sc);
      }
      publish(x, g == 7 ? C_MOD : C_MOD2);
      DBG(1 + (g >> 3));
    }
  }
}

__global__ void __cluster_dims__(2, 1, 1) __launch_bounds__(384, 1)
k_fused(const __grid_constant__ CUtensorMap tmC, const __grid_constant__ CUtensorMap tmWq,
        const __grid_constant__ CUtensorMap tmWk, const __grid_constant__ CUtensorMap tmWv,
        const __grid_constant__ CUtensorMap tmWo, const __grid_constant__ CUtensorMap tmWg,
        const __grid_constant__ CUtensorMap tmWu, const __grid_constant__ CUtensorMap tmWm,
        const __grid_constant__ Sched sched,
        const __nv_bfloat16* __restrict__ xin,
        const __nv_bfloat16* __restrict__ cvec, const __nv_bfloat16* __restrict__ w_o,
        const __nv_bfloat16* __restrict__ w_r, const __nv_bfloat16* __restrict__ w_gate, const __nv_bfloat16* __restrict__ w_up,
        const __nv_bfloat16* __restrict__ w_down, __nv_bfloat16* __restrict__ out) {
  extern __shared__ __align__(1024) uint8_t smem_raw[];
  const uint32_t base = smem_u32(smem_raw), bars = base + SM_BAR;
  const int warp = __shfl_sync(0xffffffff, threadIdx.x >> 5, 0), wg = warp >> 2;
  const int rank = cluster_ctarank(), p = blockIdx.x >> 1;
  const int mt = (p & 7) * 2 + rank;
  const bool spare = blockIdx.x >= NCTA;
  #pragma unroll
  for (int i = 0; i < PERT; i++) { uint32_t d; asm volatile("mov.u32 %0, %%laneid;" : "=r"(d)); }
  {
    const int h0 = KHEAD0 + (p >> 3);
    if (warp == 11) { prefetch_tmap(&tmC); prefetch_tmap(&tmWk); }
    #pragma unroll 1
    for (int t = warp == 8 ? 0 : warp < 8 ? warp + 1 : warp == 11 ? 64 : warp; t < B_PUB / 8; t += (warp == 8 ? 64 : 10))
      w_mbar_init(bars + 8 * t, t < B_WE / 8 ? 1 : t < B_RE / 8 ? 2 : 4);
    fence_mbar_init();
    cluster_arrive();
    if (warp == 9) prefetch_tmap(&tmWv);
    if (wg == 2) bar_arrive(1, 256);
    if (warp == 8 && !spare) {
      #pragma unroll 1
      for (int kb = 0; kb < 8; kb++) {
        w_expect_tx(bars + B_AF + 8 * kb, 16384);
        tma_load_2d(base + k_addrA(kb), &tmC, bars + B_AF + 8 * kb, kb * 64, mt * 128);
        if (kb == 0) cluster_wait();
        if (kb < 6) {
          w_expect_tx(bars + B_WF + 8 * kb, 16384);
          tma_load_2d_mc(base + k_addrW(kb) + rank * 8192, &tmWk, bars + B_WF + 8 * kb, h0 * 128 + rank * 64, kb * 64);
        }
      }
    }
  }
  const Sched::Pair& sp = sched.pair[p];
  const int nitems = sp.nitems, nsteps = sp.nsteps;
  auto oent = [&](int k) -> uint32_t { return sp.oent[k]; };
  const int ot = sp.otask, m = (ot & 7) * 2 + rank, grp = m * 8 + (ot >> 3);

  if (wg == 0) {
    asm volatile("setmaxnreg.dec.sync.aligned.u32 24;");
    const int lane = threadIdx.x & 31;
    #pragma unroll 1
    for (int t = B_PUB / 8 + warp; t < 80; t += 4) w_mbar_init(bars + 8 * t, t < B_RDY / 8 ? 4 : 1);
    bar_sync(6, 128);
    bar_arrive(7, 256); bar_arrive(8, 256);
    cluster_wait();
    const unsigned int tag = ld_relaxed(&g_epoch) + 1;
    if (warp == 0) {
      if (!spare) {
        int s = 0, ph = 0;
        tma_prefetch_2d(&tmWv, sp.khead[0] * 128 + rank * 64, (p & 7) * 64);
        #pragma unroll 1
        for (int g = 6; g < 64; g++) {
          const int u = g >> 3, kb = g & 7;
          if (kb == 0 && u < 7) tma_prefetch_2d((u & 1) ? &tmWk : &tmWv, sp.khead[(u + 1) >> 1] * 128 + rank * 64, (p & 7) * 64);
          mbar_wait(bars + B_WE + 8 * s, ph);
          w_expect_tx(bars + B_WF + 8 * s, 16384);
          tma_load_2d_mc(base + k_addrW(s) + rank * 8192, (u & 1) ? &tmWv : &tmWk, bars + B_WF + 8 * s, sp.khead[u >> 1] * 128 + rank * 64, kb * 64);
          if (++s == 6) { s = 0; ph ^= 1; }
        }
      }
      int s = 0, ph = 0;
      auto next_entry = [&](int bytes) {
        mbar_wait(bars + B_RE + 8 * s, ph);
        w_expect_tx(bars + B_RF + 8 * s, bytes);
      };
      auto advance = [&]() { if (++s == 6) { s = 0; ph ^= 1; } };
      if (spare) {
        #pragma unroll 1
        for (int g = 0; g < 24; g++) {
          if (g == 8) mbar_wait(bars + R_MOD, 0);
          next_entry(32768);
          for (int k = 0; k < 2; k++) tma_load_3d(base + s * 32768 + k * 16384, &tmWm, bars + B_RF + 8 * s, 0, (g & 7) * 64, (g >> 3) * 16 + (blockIdx.x - NCTA) * 4 + k * 2);
          advance();
        }
      }
      mbar_wait(bars + R_H1, 0);
      fence_async_global();
      int vrow = -1;
      #pragma unroll 1
      for (int i = 0; i <= nitems; i++) {
        const int item = sp.item[i & (MAX_ITEMS - 1)], h = item >> 3, j = item & 7;
        if (i < nitems) {
          const int row0 = j * 256 + ((i & 1) ? rank : 3 - rank) * 64, row1 = j * 256 + ((i & 1) ? 3 - rank : rank) * 64;
          #pragma unroll 1
          for (int kb = 0; kb < 8; kb++) {
            next_entry(32768);
            tma_load_2d_mc(base + s * 32768 + 16384 + rank * 8192, &tmWq, bars + B_RF + 8 * s, h * 128 + rank * 64, kb * 64);
            bulk_load(base + s * 32768, sched.h1 + row0 * DM + kb * 4096, 8192, bars + B_RF + 8 * s);
            bulk_load(base + s * 32768 + 8192, sched.h1 + row1 * DM + kb * 4096, 8192, bars + B_RF + 8 * s);
            advance();
          }
          mbar_wait(bars + R_ITEM + 8 * i, 0);
          fence_async_global();
        }
        #pragma unroll 1
        for (int n = i < nitems ? 4 * j + 3 : 0; n >= 0; n--) {
          const int krow = (h * 2 + rank) * SEQ + (n >> 1) * 128 + ((sp.lastuse[i & (MAX_ITEMS - 1)] >> (n >> 1)) & 1);
          const int row = (n & 1) ? krow : vrow;
          if (i + 1 == nitems && n == min(4 * j + 3, 2 * PF_AT + 1)) w_arrive(bars + R_NEAR);
          next_entry(row >= 0 ? 32768 : 0);
          if (row >= 0) bulk_load_mc(base + s * 32768 + rank * 16384, sched.kvc + (size_t)(row & ~1) * 64, bars + B_RF + 8 * s, row & 1);
          advance();
          if (!(n & 1)) vrow = krow + 64 * SEQ;
        }
      }
      if (!spare) {
      const int oc = ((ot >> 3) & 1) * 4 + rank * 2;
      auto o_next = [&](int k, int bytes) {
        const uint32_t v = oent(k); s = v & 7;
        mbar_wait(bars + B_RE + 8 * s, v >> 3);
        w_expect_tx(bars + B_RF + 8 * s, bytes);
      };
      #pragma unroll 1
      for (int i = 0; i < nsteps; i++) {
        const int c0 = sp.ochunk[i][0], c1 = sp.ochunk[i][1];
        const int pf = PF_MOE > 0 ? i - PF_MOE : i - nsteps - PF_MOE;
        if (pf >= 0 && pf < 3)
          bulk_prefetch((pf == 0 ? w_gate : pf == 1 ? w_up : w_down) + (size_t)blockIdx.x * (DM * FF / NCTA), DM * FF / NCTA * 2);
        if (c0 < 64) { o_next(3 * i, 32768); tma_load_3d_mc(base + s * 32768 + rank * 16384, &tmWo, bars + B_RF + 8 * s, 0, c0 * 64, oc); }
        mbar_wait(bars + R_CTX + 8 * i, 0);
        fence_async_global();
        o_next(3 * i + 1, c0 < 64 ? 32768 : 16384);
        if (c0 < 64) bulk_load(base + s * 32768, sched.kvc + (size_t)((128 + c0) * SEQ + m * 128) * 64, 16384, bars + B_RF + 8 * s);
        bulk_load(base + s * 32768 + 16384, sched.kvc + (size_t)((128 + c1) * SEQ + m * 128) * 64, 16384, bars + B_RF + 8 * s);
        o_next(3 * i + 2, 32768);
        tma_load_3d_mc(base + s * 32768 + rank * 16384, &tmWo, bars + B_RF + 8 * s, 0, c1 * 64, oc);
      }
      const int f0 = (blockIdx.x < FF / 16 ? blockIdx.x : 0) * 16;
      o_next(3 * nsteps, 32768);
      bulk_load(base + s * 32768, w_down + (size_t)f0 * DM, 16384, bars + B_RF + 8 * s);
      bulk_load(base + s * 32768 + 16384, xin + (size_t)grp * 16 * DM, 16384, bars + B_RF + 8 * s);
      o_next(3 * nsteps + 1, 32768);
      #pragma unroll 1
      for (int k = 0; k < 4; k++) tma_load_2d(base + s * 32768 + k * 8192, (k & 2) ? &tmWu : &tmWg, bars + B_RF + 8 * s, f0, (k & 1) * 256);
      #pragma unroll 1
      for (int k = 0; k < 4; k++) w_expect_tx(bars + R_PART + 8 * k, 16384);
      mbar_wait(bars + B_PUB + 8 * (5 + nitems), 0);
      mbar_wait(bars + B_PUB + 8 * (NPUB + 5 + nitems), 0);
      uint32_t todo = 0xff;
      #pragma unroll 1
      for (int n = 0; n < WAIT_LIM && todo; n++) {
        uint32_t now = __ballot_sync(0xffffffff, ld_acquire(&g_cnt[C_PART + (m * 2 + (ot >> 5)) * 32 + (lane & 7)]) == tag) & todo;
        todo &= ~now;
        if (now) fence_async_global();
        #pragma unroll 1
        for (; now; now &= now - 1) {
          const int q = __ffs(now) - 1;
          bulk_load(base + (oent(3 * nsteps - 3 + (q >> 2)) & 7) * 32768 + (q & 3) * 8192, sched.part + (grp * 8 + q) * 4096, 8192, bars + R_PART + 8 * (q >> 1));
        }
      }
      DBGP(11);
      }
    } else if (warp < 3) {
      const int w = warp - 1, n1 = w * NPUB + (spare ? 3 : 6) + nitems;
      #pragma unroll 1
      for (int n = w * NPUB; n < n1; n++) {
        #pragma unroll 1
        for (int k = 0; k < 8 * WAIT_LIM; k++) { if (mbar_try(bars + B_PUB + 8 * n, 0)) break; }
        const uint32_t idx = lds_u32(base + SM_MAIL + 4 * n);
        fence_async_global();
        if (lane == 0 && idx < (unsigned)C_END) red_release(idx);
        __syncwarp();
      }
    } else {
      *reinterpret_cast<volatile uint32_t*>(smem_raw + SM_KEY + 48) = tag;
      if (!spare) { mbar_wait(bars + B_AF + 8 * X_AT, 0); bulk_prefetch(xin + (size_t)blockIdx.x * 16 * DM, 16 * DM * 2); }
      #pragma unroll 1
      for (int n = 0; n < 8 + nsteps; n++) {
        if (n == 2 + nitems) n = 7;
        int idx = n == 0 ? C_MOD : n == 1 ? C_H1 : C_MOD2, cnt = n == 0 ? 8 : n == 1 ? 256 : 16;
        if (n == 2) tma_prefetch_2d(&tmWq, (sp.item[0] >> 3) * 128 + rank * 64, (sp.item[0] & 7) * 64);
        if (n >= 2 && n < 7) { idx = C_KV + (sp.item[n - 2] >> 3); cnt = 32; }
        if (n >= 8) { const int c0 = sp.ochunk[n - 8][0], c1 = sp.ochunk[n - 8][1]; idx = C_CTX + (((lane & 1) && c0 < 64 ? c0 : c1) >> 1) * 8 + (ot & 7); cnt = 4; }
        wait_count_lazy(idx, cnt * tag);
        w_arrive(bars + B_RDY + 8 * n);
        if (n == 0) DBGP(12);
        if (n == 8 + PF_N - 1) {
          #pragma unroll 1
          for (int k = 0; k < 8 * WAIT_LIM; k++) { if (mbar_try(bars + R_NEAR, 0)) break; }
          bulk_prefetch(w_o + (size_t)blockIdx.x * (NH * DH * DM / NCTA), NH * DH * DM / NCTA * 2);
          #pragma unroll 1
          for (int k = 0; k < PF_N; k++) {
            const int cc = sp.ochunk[k][(ot >> 3) & 1];
            if (cc < 64) bulk_prefetch(sched.kvc + ((size_t)(128 + cc) * SEQ + m * 128) * 64, 16384);
          }
        }
      }
    }
    __syncwarp();
    cluster_arrive();
    if (!spare) {
      bar_sync(6, 128);
      asm volatile("setmaxnreg.inc.sync.aligned.u32 88;");
      const int pos = blockIdx.x * 4 + (lane & 1) * 2, col = (blockIdx.x >> 2) * 16 + (blockIdx.x & 3) * 2 + (lane & 1) * 8, src = threadIdx.x >> 1;
      uint32_t gbest = 0, hh = 0, gbf = 0;
      uint2 xx = make_uint2(0, 0);
      uint4 ya = make_uint4(0, 0, 0, 0), yb = make_uint4(0, tag, 0, tag);
      auto poll_y = [&]() {
        if (ya.y != tag || ya.w != tag) ya = ld_tagged2(&g_yll[src][pos]);
        if (yb.y != tag || yb.w != tag) yb = ld_tagged2(&g_yll[src + 64][pos]);
        return __all_sync(0xffffffff, ya.y == tag && ya.w == tag && yb.y == tag && yb.w == tag);
      };
      ya.y = tag - 1; if (src + 64 < FF / 16) yb.y = tag - 1;
      poll_y();
      if (warp == 3) {
        gbf = __ldcg(reinterpret_cast<const uint32_t*>(g_mod + 5 * DM + col));
        uint32_t have = 0;
        uint2 k[4];
        #pragma unroll
        for (int i = 0; i < 4; i++) k[i] = make_uint2(0, tag - 1);
        #pragma unroll 1
        for (int n = 0; n < WAIT_LIM; n++) {
          #pragma unroll
          for (int i = 0; i < 4; i++) if (k[i].y != tag) k[i] = ld_tagged(&g_keys[i * 32 + lane][0]);
          if (gbest != have) {
            const int g = ((0xffffu - gbest) >> 4) & 127;
            uint4 hv[4];
            #pragma unroll
            for (int i = 0; i < 4; i++) hv[i] = ld_tagged2(&g_row[g][0][i * 64 + lane * 2]);
            xx = ld_tagged(&g_row[g][1][(col >> 8) * 128 + ((col >> 2) & 1) * 64 + ((col >> 3) & 31) * 2 + ((col >> 1) & 1)]);
            bool ok = xx.y == tag;
            #pragma unroll
            for (int i = 0; i < 4; i++) { ok = ok && hv[i].y == tag && hv[i].w == tag; reinterpret_cast<uint2*>(smem_raw + SM_H2)[(i >> 1) * 64 + lane * 2 + (i & 1)] = make_uint2(hv[i].x, hv[i].z); }
            if (lane == 0) *reinterpret_cast<uint32_t*>(smem_raw + SM_KEY + 32) = gbest;
            have = __all_sync(0xffffffff, ok) ? gbest : 0;
          }
          bool all = true;
          #pragma unroll
          for (int i = 0; i < 4; i++) { all = all && k[i].y == tag; gbest = max(gbest, k[i].y == tag ? k[i].x : 0u); }
          gbest = __reduce_max_sync(0xffffffff, gbest);
          if (__all_sync(0xffffffff, all) && gbest == have) break;
        }
        w_arrive(bars + R_KEY);
        if (blockIdx.x == 0 && lane == 0) g_epoch = tag;
        hh = lds_u32(base + SM_H2 + col * 2);
        DBGP(13);
      }
      const float rsel = rbf(__uint_as_float((((gbest & 0x80000000u) ? gbest & 0x7fffffffu : ~gbest) & 0xfffff000u) | 0x800u));
      const float rs = rbf(__fdividef(1.f, 1.f + __expf(-rsel)));
      bar_sync(9, 384);
      #pragma unroll 1
      for (int n = 0; n < WAIT_LIM; n++) { if (poll_y()) break; }
      float y0 = __uint_as_float(ya.x) + __uint_as_float(yb.x), y1 = __uint_as_float(ya.z) + __uint_as_float(yb.z);
      #pragma unroll
      for (int o = 2; o < 32; o <<= 1) { y0 += __shfl_xor_sync(0xffffffff, y0, o); y1 += __shfl_xor_sync(0xffffffff, y1, o); }
      float2* s_y = reinterpret_cast<float2*>(smem_raw + SM_KEY + 64);
      if (lane < 2) s_y[warp * 2 + lane] = make_float2(y0, y1);
      bar_sync(6, 128);
      if (warp == 3 && lane < 2) {
        y0 = 0.f; y1 = 0.f;
        #pragma unroll
        for (int i = 0; i < 4; i++) { y0 += reinterpret_cast<const float*>(s_y)[i * 4 + lane]; y1 += reinterpret_cast<const float*>(s_y)[i * 4 + 2 + lane]; }
        const float o0 = bf_lo(xx.x) + rbf(bf_lo(gbf) * rbf(bf_lo(hh) + rbf(rbf(y0) * rs)));
        const float o1 = bf_hi(xx.x) + rbf(bf_hi(gbf) * rbf(bf_hi(hh) + rbf(rbf(y1) * rs)));
        *reinterpret_cast<uint32_t*>(out + (size_t)((0xffffu - gbest) & (SEQ - 1)) * DM + col) = pack_bf16(o0, o1);
      }
      DBGP(14);
    }
    __syncwarp();
    cluster_wait();
  } else {
    asm volatile("setmaxnreg.inc.sync.aligned.u32 240;");
    Ctx x;
    x.w = wg - 1; x.base = base; x.bars = bars; x.nev = 0; x.sched = &sched;
    const int w = x.w, warp4 = warp & 3;
    x.rel = mapa(bars, (warp4 & 1) ^ 1);
    x.rel1 = (threadIdx.x & 127) == 32 || (threadIdx.x & 127) == 64;
    if (warp != 8 || spare) cluster_wait();
    if (w == 1 || spare) bar_sync(7 + w, 256);
    DBG(1);
    uint32_t PA[32], PB[32];
    int vtile = -1;
    if (spare) {
      mod_cta(x, cvec);
    } else {
      const int lane = wg_tid() & 31;
      Row xn[2];
      float acc0[64], acc1[64];
      int s = 2 * w, ph = w;
      #pragma unroll 1
      for (int u = w; u < 8; u += 2) {
        bar_sync(1 + w, 256);
        DBG(4 + (u >> 1) * 3);
        int ps = 0;
        #pragma unroll 1
        for (int kb = 0; kb < 8; kb++) {
          if (u < 2) mbar_wait(bars + B_AF + 8 * kb, 0);
          mbar_wait(bars + B_WF + 8 * s, ph);
          const uint32_t da = desc_lo(base + k_addrA(kb), 16), dw = desc_lo(base + k_addrW(s), 8192);
          wgmma_fence();
          kblock_n128<0>(acc0, da, dw, kb != 0);
          kblock_n128<512>(acc1, da, dw, kb != 0);
          wgmma_commit();
          if (kb == 7) bar_arrive(1 + (w ^ 1), 256);
          if (kb > 0) {
            wgmma_wait<1>();
            mbar_arrive_remote_if(x.rel + B_WE + 8 * ps, x.rel1);
            if (u == 7 && !(kb & 1)) {
              ring_release(x, kb == 2 ? 0 : kb - 3, false);
              if (kb > 2) ring_release(x, kb - 2, false);
            }
          }
          ps = s;
          if (++s == 6) { s = 0; ph ^= 1; }
        }
        Row t[2];
        const int lrow = blockIdx.x * 16 + w * 8 + warp4 * 2;
        if (u == w) { t[0] = ldg_row(xin + (size_t)lrow * DM, lane); t[1] = ldg_row(xin + (size_t)(lrow + 1) * DM, lane); }
        if (u == LN_AT || u == LN_AT + 1) {
          mbar_wait(bars + R_MOD, 0);
          t[0] = ldca_row(g_mod, lane); t[1] = ldca_row(g_mod + DM, lane);
        }
        wgmma_wait<0>();
        fence_regs(acc0); fence_regs(acc1);
        DBG(5 + (u >> 1) * 3);
        mbar_arrive_remote_if(x.rel + B_WE + 8 * ps, x.rel1);
        if (u == 6) { for (int k = 0; k < 5; k++) ring_release(x, k, false); }
        if (u >= 6) ring_release(x, 5, false);
        if (u == 7) {
          pack_tile(acc0, PA, 1.f, 1.f); pack_tile(acc1, PB, 1.f, 1.f);
          vtile = sp.khead[3] * 16 + mt;
          break;
        }
        s += 2; ph ^= 1; if (s >= 6) { s -= 6; ph ^= 1; }
        if (u == 0) bar_sync(7, 256);
        if (u == w) {
          float st[4] = {0.f, 0.f, 0.f, 0.f};
          #pragma unroll
          for (int i = 0; i < 32; i++) { const float v = row_at(t[i >> 4], i & 15); st[(i >> 4) * 2] += v; st[(i >> 4) * 2 + 1] = fmaf(v, v, st[(i >> 4) * 2 + 1]); }
          warp_sums(st);
          #pragma unroll
          for (int r = 0; r < 2; r++) { ln_stats(st[2*r], st[2*r+1]); xn[r] = ln_apply(t[r], st[2*r], st[2*r+1] * QSCALE); }
        }
        if ((u == LN_AT || u == LN_AT + 1)) {
          #pragma unroll
          for (int r = 0; r < 2; r++) {
            const Row hr = fma_row(xn[r], one_plus(t[1]), t[0]);
            __nv_bfloat16* hp = sched.h1 + (lrow & ~63) * DM + (lane >> 3) * 4096 + ((lrow + r) & 63) * 64 + (((lane ^ (lrow + r)) & 7) << 3);
            stg_v4(hp, hr.v[0], hr.v[1], hr.v[2], hr.v[3]); stg_v4(hp + 4 * 4096, hr.v[4], hr.v[5], hr.v[6], hr.v[7]);
          }
        }
        const int tile = sp.khead[u >> 1] * 16 + mt;
        __nv_bfloat16* dst = kv_tile(x, tile);
        uint32_t D[32];
        pack_tile(acc0, D, 1.f, 1.f); store_tile(dst + 2048, D);
        pack_tile(acc1, D, 1.f, 1.f); store_tile(dst, D);
        if (u == LN_AT || u == LN_AT + 1) publish(x, C_H1);
        publish(x, C_KV + (tile >> 4));
        DBG(6 + (u >> 1) * 3);
      }
    }
    x.tr = base + SM_RED + w * 1024;
    const int last = attention(x, sp.item, nitems, rank, PA, PB, vtile);
    DBG(100);
    const int lane = wg_tid() & 31, cw = w * 4 + warp4, ct = cw * 32 + lane;
    const int row0 = grp * 16 + cw * 2;
    const bool moe_cta = blockIdx.x < FF / 16;
    if (spare) { store_ctx(x, last, PB); __syncwarp(); cluster_arrive(); cluster_wait(); return; }
    const int kl = 3 * nsteps - 3;
    Row ga, sb, cb, gb, wr;
    {
      float accA[64], accB[64];
      const int t0 = oent(0) == oent(1);
      uint32_t pa = 0, pb = 0;
      #pragma unroll 1
      for (int t = t0; t < 2 * nsteps - 2; t++) {
        const uint32_t eb = oent(3 * (t >> 1) + 2 * (t & 1)), ea = oent(3 * (t >> 1) + 1);
        o_wait_full(bars, eb);
        o_wait_full(bars, ea);
        const uint32_t da = desc_lo(base + w * 4096, 16) + (ea & 7) * 2048 + (t & 1) * 1024, db = desc_lo(base, 8192) + (eb & 7) * 2048;
        wgmma_fence();
        kblock_n128<0, 0, SW64>(accA, da, db, t != t0); kblock_n128<0, 1024, SW64>(accB, da, db, t != t0);
        wgmma_commit();
        if (t == CTX_T) store_ctx(x, last, PB);
        if (t > t0) { wgmma_wait<1>(); slot_release(x, pb, false); if (!(t & 1)) slot_release(x, pa, false); }
        pa = ea & 7; pb = eb & 7;
      }
      const uint32_t e0 = oent(kl), ea = oent(kl + 1), eb = oent(kl + 2);
      const uint32_t da = desc_lo(base + w * 4096, 16) + (ea & 7) * 2048;
      const uint32_t db0 = desc_lo(base, 8192) + (e0 & 7) * 2048, db1 = desc_lo(base, 8192) + (eb & 7) * 2048;
      ga = ldca_row(g_mod + 2 * DM, lane); sb = ldca_row(g_mod + 3 * DM, lane); cb = ldca_row(g_mod + 4 * DM, lane); gb = ldca_row(g_mod + 5 * DM, lane);
      wr = ldca_row(w_r, lane);
      o_wait_full(bars, e0);
      o_wait_full(bars, ea);
      o_wait_full(bars, eb);
      wgmma_fence();
      kblock_n128<0, 0, SW64>(accA, da, db0, 1); kblock_n128<1024, 0, SW64>(accA, da, db1, 1);
      wgmma_commit();
      kblock_n128<0, 1024, SW64>(accB, da, db0, 1); kblock_n128<1024, 1024, SW64>(accB, da, db1, 1);
      wgmma_commit();
      __syncwarp();
      cluster_arrive();
      __nv_bfloat16* dst = sched.part + ((m * 8 + cw) * 8 + (ot >> 3)) * 4096;
      auto send = [&](const float (&acc)[64], int h) {
        uint32_t D[32];
        pack_tile(acc, D, 1.f, 1.f);
        #pragma unroll
        for (int i = 0; i < 8; i++) stg_v4(dst + (h * 8 + i) * 256 + ((lane ^ (h * 4 + (i >> 1))) << 3), D[4*i], D[4*i+1], D[4*i+2], D[4*i+3]);
      };
      wgmma_wait<1>();
      fence_regs(accA);
      DBG(120);
      send(accA, 0);
      o_wait_full(bars, eb);
      wgmma_wait<0>();
      fence_regs(accB);
      DBG(101);
      send(accB, 1);
      publish(x, C_PART + (m * 2 + w) * 32 + (ot >> 3));
      DBG(121);
      DBG(102);
    }
    asm volatile("setmaxnreg.dec.sync.aligned.u32 208;");
    const uint32_t sD = base + (oent(kl + 3) & 7) * 32768, sW = base + (oent(kl + 4) & 7) * 32768;
    o_wait_full(bars, oent(kl + 3)); o_wait_full(bars, oent(kl + 4));
    Row x1[2];
    #pragma unroll
    for (int r = 0; r < 2; r++) x1[r] = lds_row(sD + 16384 + (cw * 2 + r) * 1024, lane);
    uint4 wgv[4], wuv[4], wdv[4];
    #pragma unroll
    for (int r = 0; r < 4; r++) {
      const uint32_t k = (lane & 7) + ((lane >> 4) << 3), h = (lane & 8) * 2;
      wgv[r] = ldsm_x4_t(sW + (cw * 64 + r * 16 + k) * 32 + h);
      wuv[r] = ldsm_x4_t(sW + 16384 + (cw * 64 + r * 16 + k) * 32 + h);
      wdv[r] = ldsm_x4_t(sD + k * 1024 + (cw * 64 + r * 16) * 2 + h);
    }
    const Row cb1 = one_plus(cb);
    const unsigned int tag = lds_u32(base + SM_KEY + 48);
    DBG(103);
    float u[16], ub[2] = {0.f, 0.f};
    #pragma unroll
    for (int i = 0; i < 16; i++) { u[i] = row_at(cb1, i) * row_at(wr, i); ub[0] += u[i]; ub[1] = fmaf(row_at(sb, i), row_at(wr, i), ub[1]); }
    warp_sums(ub);
    float st[6] = {0.f, 0.f, 0.f, 0.f, 0.f, 0.f};
    uint32_t key[2];
    {
      const uint32_t po = base + ((lane & 7) * 2 + (cw >> 2)) * 512 + (cw & 3) * 128;
      Row av[2][2];
      #pragma unroll
      for (int k = 0; k < 4; k++) {
        mbar_wait(bars + R_PART + 8 * k, 1);
        const uint32_t pa = po + (oent(kl + (k >> 1)) & 7) * 32768 + (k & 1) * 16384;
        #pragma unroll
        for (int r = 0; r < 2; r++) {
          const uint32_t sw = ((r * 4 + (lane >> 3)) ^ (lane & 7)) << 4;
          const uint4 lo = ldsm_x4(pa + sw), hi = ldsm_x4(pa + 8192 + sw);
          const Row v{{lo.x, lo.y, lo.z, lo.w, hi.x, hi.y, hi.z, hi.w}};
          av[r][k >> 1] = (k & 1) ? add_row(av[r][k >> 1], v) : v;
        }
      }
      DBG(104);
      #pragma unroll
      for (int r = 0; r < 2; r++) {
        x1[r] = fma_row(ga, add_row(av[r][0], av[r][1]), x1[r]);
        #pragma unroll
        for (int i = 0; i < 16; i++) { const float v = row_at(x1[r], i); st[3*r] += v; st[3*r+1] = fmaf(v, v, st[3*r+1]); st[3*r+2] = fmaf(v, u[i], st[3*r+2]); }
      }
      warp_sums(st);
      #pragma unroll
      for (int r = 0; r < 2; r++) {
        ln_stats(st[3*r], st[3*r+1]);
        const uint32_t rb = __float_as_uint(fmaf(st[3*r+1], fmaf(-st[3*r], ub[0], st[3*r+2]), ub[1]));
        key[r] = (((rb & 0x80000000u) ? ~rb : (rb | 0x80000000u)) & 0xfffff000u) | (0xfffu - (uint32_t)(row0 + r));
      }
    }
    DBG(105);
    float* s_red = reinterpret_cast<float*>(smem_raw + SM_RED);
    uint32_t* s_key = reinterpret_cast<uint32_t*>(smem_raw + SM_KEY);
    const int rb = key[1] > key[0];
    const uint32_t wbest = rb ? key[1] : key[0];
    if (lane == 0) s_key[cw] = wbest;
    bar_sync(5, 256);
    const uint32_t cbest = __reduce_max_sync(0xffffffff, s_key[lane & 7]);
    if (wbest == cbest && lane == 0) st_tagged(&g_keys[grp][0], cbest, tag);
    Row xb, xo;
    #pragma unroll
    for (int i = 0; i < 8; i++) { xb.v[i] = rb ? x1[1].v[i] : x1[0].v[i]; xo.v[i] = rb ? x1[0].v[i] : x1[1].v[i]; }
    const Row hb = fma_row(ln_apply(xb, rb ? st[3] : st[0], rb ? st[4] : st[1]), cb1, sb);
    if (wbest == cbest) {
      #pragma unroll
      for (int i = 0; i < 4; i++) st_tagged2(&g_row[grp][0][i * 64 + lane * 2], hb.v[2*i], hb.v[2*i+1], tag);
      #pragma unroll
      for (int i = 0; i < 4; i++) st_tagged2(&g_row[grp][1][i * 64 + lane * 2], xb.v[2*i], xb.v[2*i+1], tag);
    }
    DBG(106);
    const Row ob = fma_row(gb, hb, xb);
    if (wbest != cbest) store_row(out + (size_t)(row0 + rb) * DM, lane, ob);
    store_row(out + (size_t)(row0 + 1 - rb) * DM, lane, fma_row(gb, fma_row(ln_apply(xo, rb ? st[0] : st[3], rb ? st[1] : st[4]), cb1, sb), xo));
    mbar_wait(bars + R_KEY, 1);
    DBG(107);
    if (moe_cta) {
      float cg[4] = {0, 0, 0, 0}, cu[4] = {0, 0, 0, 0};
      #pragma unroll
      for (int r = 0; r < 4; r++) {
        const uint32_t b0 = lds_u32(base + SM_H2 + (cw * 64 + r * 16) * 2 + (lane & 3) * 4), b1 = lds_u32(base + SM_H2 + (cw * 64 + r * 16) * 2 + 16 + (lane & 3) * 4);
        mma16816(cg, wgv[r], b0, b1); mma16816(cu, wuv[r], b0, b1);
      }
      s_red[cw * 32 + (lane & 3) * 8 + (lane >> 2)] = (lane & 2) ? ((lane & 1) ? cu[2] : cu[0]) : ((lane & 1) ? cg[2] : cg[0]);
      bar_sync(5, 256);
      float g = 0.f;
      #pragma unroll
      for (int i = 0; i < 8; i++) g += s_red[i * 32 + lane];
      g = rbf(g);
      const float act = rbf(__fdividef(g, 1.f + __expf(-g))) * __shfl_down_sync(0xffffffff, g, 16);
      const uint32_t a2 = pack_bf16(act, __shfl_down_sync(0xffffffff, act, 1));
      const uint32_t b0 = __shfl_sync(0xffffffff, a2, (lane & 3) * 2), b1 = __shfl_sync(0xffffffff, a2, (lane & 3) * 2 + 8);
      float y0 = 0.f, y1 = 0.f;
      #pragma unroll
      for (int r = 0; r < 4; r++) {
        float c[4] = {0, 0, 0, 0};
        mma16816(c, wdv[r], b0, b1);
        if ((lane & 3) == r) { y0 = c[0]; y1 = c[2]; }
      }
      st_tagged2(&g_yll[blockIdx.x][cw * 64 + (lane & 3) * 16 + (lane >> 2) * 2], __float_as_uint(y0), __float_as_uint(y1), tag);
    }
    bar_arrive(9, 384);
    DBG(108);
    if (wbest == cbest && wbest != s_key[8]) store_row(out + (size_t)(row0 + rb) * DM, lane, ob);
    DBG(109);
    __syncwarp();
    cluster_wait();
  }
}

typedef CUresult (*EncodeFn)(CUtensorMap*, CUtensorMapDataType, cuuint32_t, void*, const cuuint64_t*, const cuuint64_t*, const cuuint32_t*,
                             const cuuint32_t*, CUtensorMapInterleave, CUtensorMapSwizzle, CUtensorMapL2promotion, CUtensorMapFloatOOBfill);

struct HostState {
  bool ready = false;
  EncodeFn encode = nullptr;
  CUtensorMap tmC, tmWq, tmWk, tmWv, tmWo, tmWg, tmWu, tmWm;
  Sched sched;
};

void make_map(EncodeFn enc, CUtensorMap* m, const void* ptr, int rank, const cuuint64_t* dims, const cuuint64_t* strides, const cuuint32_t* box, bool swizzle = true) {
  const cuuint32_t es[3] = {1, 1, 1};
  enc(m, CU_TENSOR_MAP_DATA_TYPE_BFLOAT16, rank, const_cast<void*>(ptr), dims, strides, box, es, CU_TENSOR_MAP_INTERLEAVE_NONE,
      swizzle ? CU_TENSOR_MAP_SWIZZLE_128B : CU_TENSOR_MAP_SWIZZLE_NONE, swizzle ? CU_TENSOR_MAP_L2_PROMOTION_L2_128B : CU_TENSOR_MAP_L2_PROMOTION_NONE, CU_TENSOR_MAP_FLOAT_OOB_FILL_NONE);
}
void make_2d(EncodeFn enc, CUtensorMap* m, const void* ptr, int rows, int cols, int box_rows) {
  const cuuint64_t dims[2] = {(cuuint64_t)cols, (cuuint64_t)rows}, strides[1] = {(cuuint64_t)cols * 2};
  const cuuint32_t box[2] = {64, (cuuint32_t)box_rows};
  make_map(enc, m, ptr, 2, dims, strides, box);
}
void make_3d(EncodeFn enc, CUtensorMap* m, const void* ptr, int rows, int chunks, size_t row_stride, size_t chunk_stride) {
  const cuuint64_t dims[3] = {64, (cuuint64_t)rows, (cuuint64_t)chunks}, strides[2] = {row_stride, chunk_stride};
  const cuuint32_t box[3] = {64, 64, 2};
  make_map(enc, m, ptr, 3, dims, strides, box);
}

void make_ffn(EncodeFn enc, CUtensorMap* m, const void* ptr) {
  const cuuint64_t dims[2] = {(cuuint64_t)FF, (cuuint64_t)DM}, strides[1] = {(cuuint64_t)FF * 2};
  const cuuint32_t box[2] = {16, 256};
  make_map(enc, m, ptr, 2, dims, strides, box, false);
}

#define SR 0x213312
#define SEED 12345
#define LU_MARGIN 0
#define SPARE_N 3
void build_sched(Sched& s) {
  memset(&s, 0, sizeof(s));
  const int NP = NCTA / 2, korder[4] = {(KORDER >> 12) & 3, (KORDER >> 8) & 3, (KORDER >> 4) & 3, KORDER & 3};
  const int sround[4][2][3] = {{}, {{1}, {2}}, {{1, 2}, {1, 2}}, {{(SR >> 20) & 3, (SR >> 16) & 3, (SR >> 12) & 3}, {(SR >> 8) & 3, (SR >> 4) & 3, SR & 3}}};
  int jv[4][NP], used[4][8] = {};
  for (int r = 0; r < 4; r++) for (int p = 0; p < NP; p++) jv[r][p] = (r & 2) ? 7 - ((p + 4 * (r & 1)) & 7) : (p + 4 * (r & 1)) & 7;
  for (int q = 0; q < 2; q++) {
    s.pair[NP + q].nitems = SPARE_N;
    for (int i = 0; i < SPARE_N; i++) {
      const int r = sround[SPARE_N][q][i];
      s.pair[NP + q].item[i] = (uint8_t)((r * 8 + used[r][6]++) * 8 + 6);
      for (int p = 0; p < NP; p++) if (jv[r][p] == 6) { jv[r][p] = -2; break; }
    }
  }
  auto cost = [&](int p) {
    int u = 8 - ((p >> 4) < SPARE_N ? 21 : 22), z = 0, none = 0;
    for (int r = 0; r < 4; r++) { u += jv[r][p]; z += jv[r][p] == 0; none += jv[r][p] < 0; }
    return 4 * u * u + (z > 1) + 4 * (none > 1);
  };
  uint32_t rng = SEED;
  for (int it = 0; it < 2000000; it++) {
    if ((it & 255) == 0) { int t = 0; for (int p = 0; p < NP; p++) t += cost(p); if (t == 0) break; }
    rng = rng * 1664525u + 1013904223u;
    const int r = (rng >> 8) & 3, a = (rng >> 12) & 63, b = (rng >> 20) & 63, before = cost(a) + cost(b);
    int t = jv[r][a]; jv[r][a] = jv[r][b]; jv[r][b] = t;
    if (cost(a) + cost(b) > before) { jv[r][b] = jv[r][a]; jv[r][a] = t; }
  }
  int fin[256], done[256];
  for (int p = 0; p < NP + 2; p++) {
    Sched::Pair& q = s.pair[p];
    if (p < NP) {
      for (int k = 0; k < 4; k++) q.khead[k] = (uint8_t)(korder[k] * 8 + (p >> 3));
      for (int r = 0; r < 4; r++) {
        if (jv[r][p] < 0) continue;
        q.item[q.nitems++] = (uint8_t)((r * 8 + used[r][jv[r][p]]++) * 8 + jv[r][p]);
      }
    }
    int t = p < NP ? 0 : -3, e = 1;
    for (int i = 0; i < q.nitems; i++) { t += (q.item[i] & 7) + 2; fin[q.item[i]] = t; done[q.item[i]] = t + (i + 1 < q.nitems ? 2 : 0); e += 8 + 4 * ((q.item[i] & 7) + 1); }
    for (int k = 0; k < 3 * MAX_STEPS + 6; k++) {
      const int n = k > 0 ? k - (SPARE_N & 1) : 0, r = n % 7, f = (e + (r < 4 ? r : r - 1)) % 12;
      q.oent[k] = (uint8_t)((r == 4 ? 6 : f >= 6 ? f + 2 : f) ^ (((n / 7) & 1) << 3));
    }
  }
  for (int p = 0; p < NP + 2; p++)
    for (int i = 0; i < s.pair[p].nitems; i++) {
      const int it = s.pair[p].item[i];
      for (int n = 0; n < 2 * (it & 7) + 2; n++) {
        bool last = true;
        for (int j = n >> 1; j < 8; j++) { const int o = (it & ~7) + j; if (o != it && fin[o] + LU_MARGIN > fin[it]) last = false; }
        if (last) s.pair[p].lastuse[i] |= (uint16_t)(1 << n);
      }
    }
  for (int j = 0; j < 8; j++) {
    int order[NH], left[4];
    for (int h = 0; h < NH; h++) { int k = h; for (; k > 0 && done[order[k - 1] * 8 + j] < done[h * 8 + j]; k--) order[k] = order[k - 1]; order[k] = h; }
    for (int kq = 0; kq < 4; kq++) {
      left[kq] = SPARE_N == 0 ? 16 : kq < SPARE_N ? 20 - SPARE_N : 16 - SPARE_N;
      for (int nh = 0; nh < 2; nh++) { Sched::Pair& q = s.pair[kq * 16 + nh * 8 + j]; q.otask = (uint8_t)(kq * 16 + nh * 8 + j); q.nsteps = (uint8_t)((left[kq] + 1) / 2); q.ochunk[0][0] = 255; }
    }
    for (int n = 0, kq = 0, run = 0; n < 64; ) {
      if (left[kq] > 0 && run < 2) {
        const int pos = --left[kq] + (SPARE_N & 1);
        for (int nh = 0; nh < 2; nh++) s.pair[kq * 16 + nh * 8 + j].ochunk[pos >> 1][pos & 1] = (uint8_t)(order[n >> 1] * 2 + 1 - (n & 1));
        n++; run++;
      } else { kq = (kq + 1) & 3; run = 0; }
    }
  }
}

}

extern "C" void kernel_launch(void* const* d_in, const int* in_sizes, int n_in, void* d_out, int out_size) {
  (void)in_sizes; (void)n_in; (void)out_size;
  const __nv_bfloat16* x     = (const __nv_bfloat16*)d_in[0];
  const __nv_bfloat16* ckv   = (const __nv_bfloat16*)d_in[1];
  const __nv_bfloat16* w_q   = (const __nv_bfloat16*)d_in[2];
  const __nv_bfloat16* w_uk  = (const __nv_bfloat16*)d_in[3];
  const __nv_bfloat16* w_uv  = (const __nv_bfloat16*)d_in[4];
  const __nv_bfloat16* w_o   = (const __nv_bfloat16*)d_in[5];
  const __nv_bfloat16* w_r   = (const __nv_bfloat16*)d_in[7];
  const __nv_bfloat16* w_g   = (const __nv_bfloat16*)d_in[8];
  const __nv_bfloat16* w_u   = (const __nv_bfloat16*)d_in[9];
  const __nv_bfloat16* w_d   = (const __nv_bfloat16*)d_in[10];
  const __nv_bfloat16* cvec  = (const __nv_bfloat16*)d_in[11];
  const __nv_bfloat16* w_mod = (const __nv_bfloat16*)d_in[12];
  __nv_bfloat16* out = (__nv_bfloat16*)d_out;

  static HostState st;
  if (!st.ready) {
    void* fn = nullptr; cudaDriverEntryPointQueryResult qr;
    cudaGetDriverEntryPoint("cuTensorMapEncodeTiled", &fn, cudaEnableDefault, &qr);
    st.encode = (EncodeFn)fn;
    cudaFuncSetAttribute(k_fused, cudaFuncAttributeMaxDynamicSharedMemorySize, SMEM);
    build_sched(st.sched);
    void *p_kvc, *p_h1, *p_part;
    cudaGetSymbolAddress(&p_kvc, g_kvc); cudaGetSymbolAddress(&p_h1, g_h1); cudaGetSymbolAddress(&p_part, g_part);
    st.sched.kvc = (__nv_bfloat16*)p_kvc; st.sched.h1 = (__nv_bfloat16*)p_h1; st.sched.part = (__nv_bfloat16*)p_part;
    st.ready = true;
  }
  make_2d(st.encode, &st.tmC, ckv, SEQ, DM, 128);
  make_2d(st.encode, &st.tmWq, w_q, DM, NH * DH, 64);
  make_2d(st.encode, &st.tmWk, w_uk, DM, NH * DH, 64);
  make_2d(st.encode, &st.tmWv, w_uv, DM, NH * DH, 64);
  make_3d(st.encode, &st.tmWo, w_o, NH * DH, DM / 64, (size_t)DM * 2, 128);
  make_3d(st.encode, &st.tmWm, w_mod, DM, 6 * DM / 64, (size_t)6 * DM * 2, 128);
  make_ffn(st.encode, &st.tmWg, w_g);
  make_ffn(st.encode, &st.tmWu, w_u);

  k_fused<<<NGRID, 384, SMEM, cudaStreamPerThread>>>(st.tmC, st.tmWq, st.tmWk, st.tmWv, st.tmWo, st.tmWg, st.tmWu, st.tmWm, st.sched,
                                                     x, cvec, w_o, w_r, w_g, w_u, w_d, out);
}
```

```cpp
#include <cuda_runtime.h>
#include <cuda_bf16.h>
#include <cuda.h>
#include <stdint.h>
#include <string.h>
#include <math.h>

namespace {

constexpr int SEQ = 2048, DM = 512, NH = 32, DH = 128, FF = 1792;
constexpr int NCTA = 128, NGRID = 132;

__device__ __align__(128) __nv_bfloat16 g_kvc[192 * SEQ * 64];
__device__ __align__(128) __nv_bfloat16 g_h1[SEQ * DM];
__device__ __align__(128) __nv_bfloat16 g_part[128 * 8 * 4096];
constexpr int C_MOD = 0, C_MOD2 = 16, C_H1 = 32, C_KV = 64, C_CTX = 128, C_PART = 384, C_END = C_PART + 32 * 32;
struct Exchange {
  uint2 keys[128][4];
  uint2 row[128][2][DM / 2];
  uint2 yll[FF / 16][DM];
  __nv_bfloat16 mod[6 * DM];
  unsigned int cnt[C_END];
  unsigned int epoch;
};
__device__ __align__(4096) Exchange g_x;


__device__ __forceinline__ uint32_t smem_u32(const void* p) { return (uint32_t)__cvta_generic_to_shared(p); }
__device__ __forceinline__ int wg_tid() { int t; asm volatile("mov.u32 %0, %%tid.x;" : "=r"(t)); return t & 127; }
__device__ __forceinline__ void mbar_arrive(uint32_t bar) { asm volatile("mbarrier.arrive.shared::cta.b64 _, [%0];" :: "r"(bar) : "memory"); }
__device__ __forceinline__ uint32_t mapa(uint32_t addr, uint32_t cta) { uint32_t r; asm("mapa.shared::cluster.u32 %0, %1, %2;" : "=r"(r) : "r"(addr), "r"(cta)); return r; }
__device__ __forceinline__ void mbar_arrive_remote_if(uint32_t cluster_addr, bool pred) {
  asm volatile("{\n.reg .pred p;\nsetp.ne.u32 p, %1, 0;\n@p mbarrier.arrive.shared::cluster.b64 _, [%0];\n}" :: "r"(cluster_addr), "r"((uint32_t)pred) : "memory");
}
__device__ __forceinline__ bool mbar_try(uint32_t bar, uint32_t parity) {
  uint32_t done;
  asm volatile("{\n.reg .pred p;\nmbarrier.try_wait.parity.shared::cta.b64 p, [%1], %2;\nselp.u32 %0, 1, 0, p;\n}" : "=r"(done) : "r"(bar), "r"(parity) : "memory");
  return done;
}
__device__ __forceinline__ bool mbar_test2(uint32_t bar, uint32_t parity) {
  uint32_t done;
  asm volatile("{\n.reg .pred p, q;\nmbarrier.test_wait.parity.shared::cta.b64 p, [%1], %2;\nmbarrier.test_wait.parity.shared::cta.b64 q, [%1 + 8], %2;\n"
               "and.pred p, p, q;\nselp.u32 %0, 1, 0, p;\n}" : "=r"(done) : "r"(bar), "r"(parity) : "memory");
  return done;
}
#define WAIT_LIM (1 << 14)
__device__ __forceinline__ void mbar_wait(uint32_t bar, uint32_t parity) {
  #pragma unroll 1
  for (int n = 0; n < WAIT_LIM; n++) { if (mbar_try(bar, parity)) break; }
}
__device__ __forceinline__ unsigned int ld_acquire(const unsigned int* p) {
  unsigned int v; asm volatile("ld.acquire.gpu.global.u32 %0, [%1];" : "=r"(v) : "l"(p) : "memory"); return v;
}
__device__ __forceinline__ unsigned int ld_relaxed(const unsigned int* p) {
  unsigned int v; asm volatile("ld.relaxed.gpu.global.u32 %0, [%1];" : "=r"(v) : "l"(p) : "memory"); return v;
}
__device__ __forceinline__ void wait_count_lazy(int idx, unsigned int target) {
  #pragma unroll 1
  for (int n = 0; n < WAIT_LIM; n++) { if (__all_sync(0xffffffff, (int)(ld_relaxed(&g_x.cnt[idx]) - target) >= 0)) break; __nanosleep(100); }
  ld_acquire(&g_x.cnt[idx]);
}
__device__ __forceinline__ uint4 ld_tagged2(const void* p) {
  uint4 v;
  asm volatile("{\n.reg .b64 a, b;\nld.relaxed.gpu.global.v2.u64 {a, b}, [%4];\nmov.b64 {%0, %1}, a;\nmov.b64 {%2, %3}, b;\n}"
    : "=r"(v.x), "=r"(v.y), "=r"(v.z), "=r"(v.w) : "l"(p) : "memory");
  return v;
}
__device__ __forceinline__ uint2 ld_tagged(const void* p) {
  uint2 v; asm volatile("{\n.reg .b64 a;\nld.relaxed.gpu.global.u64 a, [%2];\nmov.b64 {%0, %1}, a;\n}" : "=r"(v.x), "=r"(v.y) : "l"(p) : "memory"); return v;
}
__device__ __forceinline__ void st_tagged2(void* p, uint32_t a, uint32_t b, uint32_t tag) {
  asm volatile("{\n.reg .b64 a, b;\nmov.b64 a, {%1, %3};\nmov.b64 b, {%2, %3};\nst.relaxed.gpu.global.v2.u64 [%0], {a, b};\n}" :: "l"(p), "r"(a), "r"(b), "r"(tag) : "memory");
}
__device__ __forceinline__ void st_tagged(void* p, uint32_t a, uint32_t tag) {
  asm volatile("{\n.reg .b64 a;\nmov.b64 a, {%1, %2};\nst.relaxed.gpu.global.u64 [%0], a;\n}" :: "l"(p), "r"(a), "r"(tag) : "memory");
}
__device__ __forceinline__ void stg_v4(void* p, uint32_t a, uint32_t b, uint32_t c, uint32_t d) {
  asm volatile("st.global.v4.u32 [%0], {%1, %2, %3, %4};" :: "l"(p), "r"(a), "r"(b), "r"(c), "r"(d) : "memory");
}
__device__ __forceinline__ uint4 lds_v4(uint32_t addr) {
  uint4 v; asm volatile("ld.shared.v4.u32 {%0, %1, %2, %3}, [%4];" : "=r"(v.x), "=r"(v.y), "=r"(v.z), "=r"(v.w) : "r"(addr) : "memory"); return v;
}
__device__ __forceinline__ uint32_t lds_u32(uint32_t addr) { uint32_t v; asm volatile("ld.shared.u32 %0, [%1];" : "=r"(v) : "r"(addr) : "memory"); return v; }
__device__ __forceinline__ void sts_v4(uint32_t addr, uint32_t a, uint32_t b, uint32_t c, uint32_t d) {
  asm volatile("st.shared.v4.u32 [%0], {%1, %2, %3, %4};" :: "r"(addr), "r"(a), "r"(b), "r"(c), "r"(d) : "memory");
}
#define ELECT "{\n.reg .pred p;\nelect.sync _|p, 0xffffffff;\n@p "
__device__ __forceinline__ void w_mbar_init(uint32_t bar, uint32_t cnt) { asm volatile(ELECT "mbarrier.init.shared::cta.b64 [%0], %1;\n}" :: "r"(bar), "r"(cnt) : "memory"); }
__device__ __forceinline__ void w_expect_tx(uint32_t bar, uint32_t bytes) { asm volatile(ELECT "mbarrier.arrive.expect_tx.shared::cta.b64 _, [%0], %1;\n}" :: "r"(bar), "r"(bytes) : "memory"); }
__device__ __forceinline__ void w_arrive(uint32_t bar) { asm volatile(ELECT "mbarrier.arrive.shared::cta.b64 _, [%0];\n}" :: "r"(bar) : "memory"); }
__device__ __forceinline__ void tma_load_2d(uint32_t dst, const CUtensorMap* tm, uint32_t bar, int c0, int c1) {
  asm volatile(ELECT "cp.async.bulk.tensor.2d.shared::cluster.global.mbarrier::complete_tx::bytes [%0], [%1, {%3, %4}], [%2];\n}"
    :: "r"(dst), "l"(tm), "r"(bar), "r"(c0), "r"(c1) : "memory");
}
__device__ __forceinline__ void tma_load_2d_mc(uint32_t dst, const CUtensorMap* tm, uint32_t bar, int c0, int c1) {
  asm volatile(ELECT "cp.async.bulk.tensor.2d.shared::cluster.global.mbarrier::complete_tx::bytes.multicast::cluster [%0], [%1, {%3, %4}], [%2], %5;\n}"
    :: "r"(dst), "l"(tm), "r"(bar), "r"(c0), "r"(c1), "h"((uint16_t)3) : "memory");
}
__device__ __forceinline__ void tma_load_3d(uint32_t dst, const CUtensorMap* tm, uint32_t bar, int c0, int c1, int c2) {
  asm volatile(ELECT "cp.async.bulk.tensor.3d.shared::cluster.global.mbarrier::complete_tx::bytes [%0], [%1, {%3, %4, %5}], [%2];\n}"
    :: "r"(dst), "l"(tm), "r"(bar), "r"(c0), "r"(c1), "r"(c2) : "memory");
}
__device__ __forceinline__ void tma_load_3d_mc(uint32_t dst, const CUtensorMap* tm, uint32_t bar, int c0, int c1, int c2) {
  asm volatile(ELECT "cp.async.bulk.tensor.3d.shared::cluster.global.mbarrier::complete_tx::bytes.multicast::cluster [%0], [%1, {%3, %4, %5}], [%2], %6;\n}"
    :: "r"(dst), "l"(tm), "r"(bar), "r"(c0), "r"(c1), "r"(c2), "h"((uint16_t)3) : "memory");
}
__device__ __forceinline__ void bulk_load_mc(uint32_t dst, const void* src, uint32_t bar, bool ef) {
  if (ef) {
    uint64_t pol; asm("createpolicy.fractional.L2::evict_first.b64 %0, 1.0;" : "=l"(pol));
    asm volatile(ELECT "cp.async.bulk.shared::cluster.global.mbarrier::complete_tx::bytes.multicast::cluster.L2::cache_hint [%0], [%1], 16384, [%2], %3, %4;\n}"
      :: "r"(dst), "l"(src), "r"(bar), "h"((uint16_t)3), "l"(pol) : "memory");
  } else
    asm volatile(ELECT "cp.async.bulk.shared::cluster.global.mbarrier::complete_tx::bytes.multicast::cluster [%0], [%1], 16384, [%2], %3;\n}"
      :: "r"(dst), "l"(src), "r"(bar), "h"((uint16_t)3) : "memory");
}
__device__ __forceinline__ void bulk_load(uint32_t dst, const void* src, uint32_t bytes, uint32_t bar) {
  asm volatile(ELECT "cp.async.bulk.shared::cluster.global.mbarrier::complete_tx::bytes [%0], [%1], %2, [%3];\n}" :: "r"(dst), "l"(src), "r"(bytes), "r"(bar) : "memory");
}
__device__ __forceinline__ void tma_prefetch_2d(const CUtensorMap* tm, int c0, int c1) {
  asm volatile(ELECT "cp.async.bulk.prefetch.tensor.2d.L2.global [%0, {%1, %2}];\n}" :: "l"(tm), "r"(c0), "r"(c1) : "memory");
}
__device__ __forceinline__ void bulk_prefetch(const void* p, uint32_t bytes) {
  asm volatile(ELECT "cp.async.bulk.prefetch.L2.global [%0], %1;\n}" :: "l"(p), "r"(bytes) : "memory");
}
__device__ __forceinline__ void red_release(int idx) { asm volatile("red.release.gpu.global.add.u32 [%0], 1;" :: "l"(&g_x.cnt[idx]) : "memory"); }
__device__ __forceinline__ void prefetch_tmap(const CUtensorMap* tm) { asm volatile("prefetch.tensormap [%0];" :: "l"(tm) : "memory"); }
__device__ __forceinline__ void bar_sync(int id, int n) { asm volatile("bar.sync %0, %1;" :: "r"(id), "r"(n) : "memory"); }
__device__ __forceinline__ void bar_arrive(int id, int n) { asm volatile("bar.arrive %0, %1;" :: "r"(id), "r"(n) : "memory"); }
__device__ __forceinline__ void fence_async_smem() { asm volatile("fence.proxy.async.shared::cta;" ::: "memory"); }
__device__ __forceinline__ void fence_async_global() { asm volatile("fence.proxy.async.global;" ::: "memory"); }
__device__ __forceinline__ void fence_mbar_init() { asm volatile("fence.mbarrier_init.release.cluster;" ::: "memory"); }
__device__ __forceinline__ void cluster_arrive() { asm volatile("barrier.cluster.arrive.relaxed.aligned;" ::: "memory"); }
__device__ __forceinline__ void cluster_wait() { asm volatile("barrier.cluster.wait.aligned;" ::: "memory"); }
__device__ __forceinline__ uint32_t cluster_ctarank() { uint32_t r; asm volatile("mov.u32 %0, %%cluster_ctarank;" : "=r"(r)); return r; }
__device__ __forceinline__ void wgmma_fence() { asm volatile("wgmma.fence.sync.aligned;" ::: "memory"); }
__device__ __forceinline__ void wgmma_commit() { asm volatile("wgmma.commit_group.sync.aligned;" ::: "memory"); }
template<int N> __device__ __forceinline__ void wgmma_wait() { asm volatile("wgmma.wait_group.sync.aligned %0;" :: "n"(N) : "memory"); }
__device__ __forceinline__ float ex2(float x) { float y; asm("ex2.approx.ftz.f32 %0, %1;" : "=f"(y) : "f"(x)); return y; }
__device__ __forceinline__ float rcp_fast(float x) { float y; asm("rcp.approx.ftz.f32 %0, %1;" : "=f"(y) : "f"(x)); return y; }
__device__ __forceinline__ uint32_t pack_bf16(float lo, float hi) { uint32_t r; asm("cvt.rn.bf16x2.f32 %0, %1, %2;" : "=r"(r) : "f"(hi), "f"(lo)); return r; }
__device__ __forceinline__ float rbf(float x) { return __uint_as_float(pack_bf16(0.f, x)); }
__device__ __forceinline__ float bf_lo(uint32_t v) { return __uint_as_float(v << 16); }
__device__ __forceinline__ float bf_hi(uint32_t v) { return __uint_as_float(v & 0xffff0000u); }
__device__ __forceinline__ uint32_t add2(uint32_t a, uint32_t b) { uint32_t r; asm("add.rn.bf16x2 %0, %1, %2;" : "=r"(r) : "r"(a), "r"(b)); return r; }
__device__ __forceinline__ uint32_t fma2(uint32_t a, uint32_t b, uint32_t c) { uint32_t r; asm("fma.rn.bf16x2 %0, %1, %2, %3;" : "=r"(r) : "r"(a), "r"(b), "r"(c)); return r; }
__device__ __forceinline__ uint4 ldsm_x4_t(uint32_t addr) {
  uint4 v; asm volatile("ldmatrix.sync.aligned.m8n8.x4.trans.shared.b16 {%0, %1, %2, %3}, [%4];" : "=r"(v.x), "=r"(v.y), "=r"(v.z), "=r"(v.w) : "r"(addr) : "memory"); return v;
}
__device__ __forceinline__ uint4 ldsm_x4(uint32_t addr) {
  uint4 v; asm volatile("ldmatrix.sync.aligned.m8n8.x4.shared.b16 {%0, %1, %2, %3}, [%4];" : "=r"(v.x), "=r"(v.y), "=r"(v.z), "=r"(v.w) : "r"(addr) : "memory"); return v;
}
__device__ __forceinline__ void mma16816(float (&c)[4], const uint4& a, uint32_t b0, uint32_t b1) {
  asm("mma.sync.aligned.m16n8k16.row.col.f32.bf16.bf16.f32 {%0, %1, %2, %3}, {%4, %5, %6, %7}, {%8, %9}, {%0, %1, %2, %3};"
    : "+f"(c[0]), "+f"(c[1]), "+f"(c[2]), "+f"(c[3]) : "r"(a.x), "r"(a.y), "r"(a.z), "r"(a.w), "r"(b0), "r"(b1));
}
template<int N> __device__ __forceinline__ void fence_regs(float (&a)[N]) {
  #pragma unroll
  for (int i = 0; i < N; i++) asm volatile("" : "+f"(a[i]) :: "memory");
}
template<int N> __device__ __forceinline__ void fence_regs_u(uint32_t (&a)[N]) {
  #pragma unroll
  for (int i = 0; i < N; i++) asm volatile("" : "+r"(a[i]) :: "memory");
}
constexpr uint32_t SW128 = 0x40000040u, SW64 = 0x80000020u;
__device__ __forceinline__ uint32_t desc_lo(uint32_t addr, uint32_t lbo) { return ((addr & 0x3FFFF) >> 4) | ((lbo >> 4) << 16); }

template<int TB, int OA, int OB, uint32_t HA, uint32_t HB> __device__ __forceinline__ void wgmma_ss_n128(float (&d)[64], uint32_t da, uint32_t db, int sd) {
  asm volatile("{\n.reg .pred p;\n.reg .b32 ta, tb;\n.reg .b64 da, db;\nsetp.ne.b32 p, %66, 0;\nadd.u32 ta, %64, %68;\nadd.u32 tb, %65, %69;\nmov.b64 da, {ta, %70};\nmov.b64 db, {tb, %71};\n"
    "wgmma.mma_async.sync.aligned.m64n128k16.f32.bf16.bf16 "
    "{%0, %1, %2, %3, %4, %5, %6, %7, %8, %9, %10, %11, %12, %13, %14, %15, %16, %17, %18, %19, %20, %21, %22, %23, %24, %25, %26, %27, %28, %29, %30, %31, %32, %33, %34, %35, %36, %37, %38, %39, %40, %41, %42, %43, %44, %45, %46, %47, %48, %49, %50, %51, %52, %53, %54, %55, %56, %57, %58, %59, %60, %61, %62, %63}, da, db, p, 1, 1, 0, %67;\n}\n"
    : "+f"(d[0]), "+f"(d[1]), "+f"(d[2]), "+f"(d[3]), "+f"(d[4]), "+f"(d[5]), "+f"(d[6]), "+f"(d[7]), "+f"(d[8]), "+f"(d[9]), "+f"(d[10]), "+f"(d[11]), "+f"(d[12]), "+f"(d[13]), "+f"(d[14]), "+f"(d[15]), "+f"(d[16]), "+f"(d[17]), "+f"(d[18]), "+f"(d[19]), "+f"(d[20]), "+f"(d[21]), "+f"(d[22]), "+f"(d[23]), "+f"(d[24]), "+f"(d[25]), "+f"(d[26]), "+f"(d[27]), "+f"(d[28]), "+f"(d[29]), "+f"(d[30]), "+f"(d[31]), "+f"(d[32]), "+f"(d[33]), "+f"(d[34]), "+f"(d[35]), "+f"(d[36]), "+f"(d[37]), "+f"(d[38]), "+f"(d[39]), "+f"(d[40]), "+f"(d[41]), "+f"(d[42]), "+f"(d[43]), "+f"(d[44]), "+f"(d[45]), "+f"(d[46]), "+f"(d[47]), "+f"(d[48]), "+f"(d[49]), "+f"(d[50]), "+f"(d[51]), "+f"(d[52]), "+f"(d[53]), "+f"(d[54]), "+f"(d[55]), "+f"(d[56]), "+f"(d[57]), "+f"(d[58]), "+f"(d[59]), "+f"(d[60]), "+f"(d[61]), "+f"(d[62]), "+f"(d[63])
    : "r"(da), "r"(db), "r"(sd), "n"(TB), "n"(OA), "n"(OB), "n"(HA), "n"(HB));
}
template<int TB, int OB, uint32_t HB> __device__ __forceinline__ void wgmma_rs_n128(float (&d)[64], uint32_t a0, uint32_t a1, uint32_t a2, uint32_t a3, uint32_t db, int sd) {
  asm volatile("{\n.reg .pred p;\n.reg .b32 tb;\n.reg .b64 db;\nsetp.ne.b32 p, %69, 0;\nadd.u32 tb, %68, %71;\nmov.b64 db, {tb, %72};\n"
    "wgmma.mma_async.sync.aligned.m64n128k16.f32.bf16.bf16 "
    "{%0, %1, %2, %3, %4, %5, %6, %7, %8, %9, %10, %11, %12, %13, %14, %15, %16, %17, %18, %19, %20, %21, %22, %23, %24, %25, %26, %27, %28, %29, %30, %31, %32, %33, %34, %35, %36, %37, %38, %39, %40, %41, %42, %43, %44, %45, %46, %47, %48, %49, %50, %51, %52, %53, %54, %55, %56, %57, %58, %59, %60, %61, %62, %63}, {%64,%65,%66,%67}, db, p, 1, 1, %70;\n}\n"
    : "+f"(d[0]), "+f"(d[1]), "+f"(d[2]), "+f"(d[3]), "+f"(d[4]), "+f"(d[5]), "+f"(d[6]), "+f"(d[7]), "+f"(d[8]), "+f"(d[9]), "+f"(d[10]), "+f"(d[11]), "+f"(d[12]), "+f"(d[13]), "+f"(d[14]), "+f"(d[15]), "+f"(d[16]), "+f"(d[17]), "+f"(d[18]), "+f"(d[19]), "+f"(d[20]), "+f"(d[21]), "+f"(d[22]), "+f"(d[23]), "+f"(d[24]), "+f"(d[25]), "+f"(d[26]), "+f"(d[27]), "+f"(d[28]), "+f"(d[29]), "+f"(d[30]), "+f"(d[31]), "+f"(d[32]), "+f"(d[33]), "+f"(d[34]), "+f"(d[35]), "+f"(d[36]), "+f"(d[37]), "+f"(d[38]), "+f"(d[39]), "+f"(d[40]), "+f"(d[41]), "+f"(d[42]), "+f"(d[43]), "+f"(d[44]), "+f"(d[45]), "+f"(d[46]), "+f"(d[47]), "+f"(d[48]), "+f"(d[49]), "+f"(d[50]), "+f"(d[51]), "+f"(d[52]), "+f"(d[53]), "+f"(d[54]), "+f"(d[55]), "+f"(d[56]), "+f"(d[57]), "+f"(d[58]), "+f"(d[59]), "+f"(d[60]), "+f"(d[61]), "+f"(d[62]), "+f"(d[63])
    : "r"(a0), "r"(a1), "r"(a2), "r"(a3), "r"(db), "r"(sd), "n"(TB), "n"(OB), "n"(HB));
}
template<int TB, int OA, int OB, uint32_t HA, uint32_t HB> __device__ __forceinline__ void wgmma_ss_n64(float (&d)[32], uint32_t da, uint32_t db, int sd) {
  asm volatile("{\n.reg .pred p;\n.reg .b32 ta, tb;\n.reg .b64 da, db;\nsetp.ne.b32 p, %34, 0;\nadd.u32 ta, %32, %36;\nadd.u32 tb, %33, %37;\nmov.b64 da, {ta, %38};\nmov.b64 db, {tb, %39};\n"
    "wgmma.mma_async.sync.aligned.m64n64k16.f32.bf16.bf16 "
    "{%0, %1, %2, %3, %4, %5, %6, %7, %8, %9, %10, %11, %12, %13, %14, %15, %16, %17, %18, %19, %20, %21, %22, %23, %24, %25, %26, %27, %28, %29, %30, %31}, da, db, p, 1, 1, 0, %35;\n}\n"
    : "+f"(d[0]), "+f"(d[1]), "+f"(d[2]), "+f"(d[3]), "+f"(d[4]), "+f"(d[5]), "+f"(d[6]), "+f"(d[7]), "+f"(d[8]), "+f"(d[9]), "+f"(d[10]), "+f"(d[11]), "+f"(d[12]), "+f"(d[13]), "+f"(d[14]), "+f"(d[15]), "+f"(d[16]), "+f"(d[17]), "+f"(d[18]), "+f"(d[19]), "+f"(d[20]), "+f"(d[21]), "+f"(d[22]), "+f"(d[23]), "+f"(d[24]), "+f"(d[25]), "+f"(d[26]), "+f"(d[27]), "+f"(d[28]), "+f"(d[29]), "+f"(d[30]), "+f"(d[31])
    : "r"(da), "r"(db), "r"(sd), "n"(TB), "n"(OA), "n"(OB), "n"(HA), "n"(HB));
}
template<int TB, int OA, int OB, uint32_t HA, uint32_t HB> __device__ __forceinline__ void wgmma_ss_n128_new(float (&d)[64], uint32_t da, uint32_t db) {
  asm volatile("{\n.reg .pred p;\n.reg .b32 ta, tb;\n.reg .b64 da, db;\nsetp.ne.b32 p, %66, 0;\nadd.u32 ta, %64, %68;\nadd.u32 tb, %65, %69;\nmov.b64 da, {ta, %70};\nmov.b64 db, {tb, %71};\n"
    "wgmma.mma_async.sync.aligned.m64n128k16.f32.bf16.bf16 "
    "{%0, %1, %2, %3, %4, %5, %6, %7, %8, %9, %10, %11, %12, %13, %14, %15, %16, %17, %18, %19, %20, %21, %22, %23, %24, %25, %26, %27, %28, %29, %30, %31, %32, %33, %34, %35, %36, %37, %38, %39, %40, %41, %42, %43, %44, %45, %46, %47, %48, %49, %50, %51, %52, %53, %54, %55, %56, %57, %58, %59, %60, %61, %62, %63}, da, db, p, 1, 1, 0, %67;\n}\n"
    : "=f"(d[0]), "=f"(d[1]), "=f"(d[2]), "=f"(d[3]), "=f"(d[4]), "=f"(d[5]), "=f"(d[6]), "=f"(d[7]), "=f"(d[8]), "=f"(d[9]), "=f"(d[10]), "=f"(d[11]), "=f"(d[12]), "=f"(d[13]), "=f"(d[14]), "=f"(d[15]), "=f"(d[16]), "=f"(d[17]), "=f"(d[18]), "=f"(d[19]), "=f"(d[20]), "=f"(d[21]), "=f"(d[22]), "=f"(d[23]), "=f"(d[24]), "=f"(d[25]), "=f"(d[26]), "=f"(d[27]), "=f"(d[28]), "=f"(d[29]), "=f"(d[30]), "=f"(d[31]), "=f"(d[32]), "=f"(d[33]), "=f"(d[34]), "=f"(d[35]), "=f"(d[36]), "=f"(d[37]), "=f"(d[38]), "=f"(d[39]), "=f"(d[40]), "=f"(d[41]), "=f"(d[42]), "=f"(d[43]), "=f"(d[44]), "=f"(d[45]), "=f"(d[46]), "=f"(d[47]), "=f"(d[48]), "=f"(d[49]), "=f"(d[50]), "=f"(d[51]), "=f"(d[52]), "=f"(d[53]), "=f"(d[54]), "=f"(d[55]), "=f"(d[56]), "=f"(d[57]), "=f"(d[58]), "=f"(d[59]), "=f"(d[60]), "=f"(d[61]), "=f"(d[62]), "=f"(d[63])
    : "r"(da), "r"(db), "n"(0), "n"(TB), "n"(OA), "n"(OB), "n"(HA), "n"(HB));
}
template<int TB, int OA, int OB, uint32_t HA, uint32_t HB> __device__ __forceinline__ void wgmma_ss_n64_new(float (&d)[32], uint32_t da, uint32_t db) {
  asm volatile("{\n.reg .pred p;\n.reg .b32 ta, tb;\n.reg .b64 da, db;\nsetp.ne.b32 p, %34, 0;\nadd.u32 ta, %32, %36;\nadd.u32 tb, %33, %37;\nmov.b64 da, {ta, %38};\nmov.b64 db, {tb, %39};\n"
    "wgmma.mma_async.sync.aligned.m64n64k16.f32.bf16.bf16 "
    "{%0, %1, %2, %3, %4, %5, %6, %7, %8, %9, %10, %11, %12, %13, %14, %15, %16, %17, %18, %19, %20, %21, %22, %23, %24, %25, %26, %27, %28, %29, %30, %31}, da, db, p, 1, 1, 0, %35;\n}\n"
    : "=f"(d[0]), "=f"(d[1]), "=f"(d[2]), "=f"(d[3]), "=f"(d[4]), "=f"(d[5]), "=f"(d[6]), "=f"(d[7]), "=f"(d[8]), "=f"(d[9]), "=f"(d[10]), "=f"(d[11]), "=f"(d[12]), "=f"(d[13]), "=f"(d[14]), "=f"(d[15]), "=f"(d[16]), "=f"(d[17]), "=f"(d[18]), "=f"(d[19]), "=f"(d[20]), "=f"(d[21]), "=f"(d[22]), "=f"(d[23]), "=f"(d[24]), "=f"(d[25]), "=f"(d[26]), "=f"(d[27]), "=f"(d[28]), "=f"(d[29]), "=f"(d[30]), "=f"(d[31])
    : "r"(da), "r"(db), "n"(0), "n"(TB), "n"(OA), "n"(OB), "n"(HA), "n"(HB));
}
template<int OA, int OB = 0, uint32_t HA = SW128> __device__ __forceinline__ void kblock_n128(float (&d)[64], uint32_t da, uint32_t db, int sd) {
  constexpr int H = HA == SW128 ? 4 : 512;
  wgmma_ss_n128<1, OA, OB, HA, SW128>(d, da, db, sd); wgmma_ss_n128<1, OA + 2, OB + 128, HA, SW128>(d, da, db, 1);
  wgmma_ss_n128<1, OA + H, OB + 256, HA, SW128>(d, da, db, 1); wgmma_ss_n128<1, OA + H + 2, OB + 384, HA, SW128>(d, da, db, 1);
}

__device__ __forceinline__ float quad_sum(float v) {
  v += __shfl_xor_sync(0xffffffff, v, 1);
  v += __shfl_xor_sync(0xffffffff, v, 2);
  return v;
}
struct Row { uint32_t v[8]; };
template<class F> __device__ __forceinline__ Row load_row(const __nv_bfloat16* p, int lane, F ld) {
  const uint4 a = ld(reinterpret_cast<const uint4*>(p) + lane), b = ld(reinterpret_cast<const uint4*>(p) + 32 + lane);
  return Row{{a.x, a.y, a.z, a.w, b.x, b.y, b.z, b.w}};
}
__device__ __forceinline__ Row ldg_row(const __nv_bfloat16* p, int lane) { return load_row(p, lane, [](const uint4* q) { return __ldg(q); }); }
__device__ __forceinline__ Row ldca_row(const __nv_bfloat16* p, int lane) { return load_row(p, lane, [](const uint4* q) { return __ldca(q); }); }
__device__ __forceinline__ Row lds_row(uint32_t addr, int lane) {
  const uint4 a = lds_v4(addr + lane * 16), b = lds_v4(addr + 512 + lane * 16);
  return Row{{a.x, a.y, a.z, a.w, b.x, b.y, b.z, b.w}};
}
__device__ __forceinline__ void store_row(__nv_bfloat16* p, int lane, const Row& r) {
  stg_v4(p + lane * 8, r.v[0], r.v[1], r.v[2], r.v[3]); stg_v4(p + 256 + lane * 8, r.v[4], r.v[5], r.v[6], r.v[7]);
}
__device__ __forceinline__ Row fma_row(const Row& a, const Row& b, const Row& c) {
  Row r;
  #pragma unroll
  for (int i = 0; i < 8; i++) r.v[i] = fma2(a.v[i], b.v[i], c.v[i]);
  return r;
}
__device__ __forceinline__ Row add_row(const Row& a, const Row& b) {
  Row r;
  #pragma unroll
  for (int i = 0; i < 8; i++) r.v[i] = add2(a.v[i], b.v[i]);
  return r;
}
__device__ __forceinline__ Row one_plus(const Row& a) {
  Row r;
  #pragma unroll
  for (int i = 0; i < 8; i++) r.v[i] = add2(a.v[i], 0x3f803f80u);
  return r;
}
__device__ __forceinline__ float row_at(const Row& x, int i) { return (i & 1) ? bf_hi(x.v[i >> 1]) : bf_lo(x.v[i >> 1]); }
template<int N> __device__ __forceinline__ void warp_sums(float (&s)[N]) {
  #pragma unroll
  for (int o = 16; o > 0; o >>= 1) {
    #pragma unroll
    for (int k = 0; k < N; k++) s[k] += __shfl_xor_sync(0xffffffff, s[k], o);
  }
}
__device__ __forceinline__ void ln_stats(float& s1, float& s2) {
  s1 *= 1.f / DM;
  asm("rsqrt.approx.ftz.f32 %0, %1;" : "=f"(s2) : "f"(fmaxf(fmaf(-s1, s1, s2 * (1.f / DM)), 0.f) + 1e-5f));
}
__device__ __forceinline__ Row ln_apply(const Row& x, float mean, float f) {
  Row n;
  const float o = -mean * f;
  #pragma unroll
  for (int i = 0; i < 8; i++) n.v[i] = pack_bf16(fmaf(bf_lo(x.v[i]), f, o), fmaf(bf_hi(x.v[i]), f, o));
  return n;
}

constexpr int SM_Q = 6 * 32768, SM_BAR = 7 * 32768, SM_MAIL = SM_BAR + 640, SM_RED = SM_MAIL + 128, SM_H2 = SM_RED + 1024, SM_KEY = SM_H2 + 1024, SMEM = SM_KEY + 128;
constexpr int B_AF = 0, B_WF = 64, B_RF = 112, B_WE = 168, B_RE = 216, B_PUB = 272, B_RDY = 496;
constexpr int R_MOD = B_RDY, R_H1 = B_RDY + 8, R_ITEM = B_RDY + 16, R_NEAR = B_RDY + 48, R_CTX = B_RDY + 64;
constexpr int R_KEY = B_AF + 8, R_PART = B_AF + 32;
constexpr int NPUB = 14;
__device__ __forceinline__ uint32_t k_addrA(int kb) { return ((0x6310u >> ((kb >> 1) * 4)) & 15u) * 32768u + (kb & 1) * 16384u; }
__device__ __forceinline__ uint32_t k_addrW(int s) { return ((0x254u >> ((s >> 1) * 4)) & 15u) * 32768u + (s & 1) * 16384u; }

#define KORDER 0x3201
constexpr int KHEAD0 = ((KORDER >> 12) & 3) * 8;
constexpr int MAX_ITEMS = 4;
constexpr int MAX_STEPS = 10;
struct Sched {
  __nv_bfloat16 *kvc, *h1, *part;
  struct Pair {
    uint8_t oent[3 * MAX_STEPS + 6];
    uint16_t lastuse[MAX_ITEMS];
    uint8_t khead[4];
    uint8_t nitems, item[MAX_ITEMS];
    uint8_t otask, nsteps;
    uint8_t ochunk[MAX_STEPS][2];
  } pair[NGRID / 2];
};

__device__ __forceinline__ int ring_add(int e, int n) { e += n; return e >= 12 ? e - 12 : e; }
__device__ __forceinline__ int ring_slot(int e) { return e >= 6 ? e - 6 : e; }
__device__ __forceinline__ void ring_wait_full(uint32_t bars, int e) { mbar_wait(bars + B_RF + 8 * ring_slot(e), e >= 6); }

__device__ __forceinline__ void o_wait_full(uint32_t bars, uint32_t v) { mbar_wait(bars + B_RF + 8 * (v & 7), v >> 3); }

struct Ctx {
  uint32_t base, bars;
  uint32_t rel;
  bool rel1;
  int w, nev;
  const Sched* sched;
};
__device__ __forceinline__ void slot_release(const Ctx& x, int s, bool twice) {
  mbar_arrive_remote_if(x.rel + B_RE + 8 * s, twice ? (wg_tid() & 31) == 0 : x.rel1);
}
__device__ __forceinline__ void ring_release(const Ctx& x, int e, bool twice) { slot_release(x, ring_slot(e), twice); }
__device__ __forceinline__ void publish(Ctx& x, int idx) {
  const uint32_t n = x.w * NPUB + x.nev;
  const int t = wg_tid();
  if (t == 0) asm volatile("st.shared.u32 [%0], %1;" :: "r"(x.base + SM_MAIL + 4 * n), "r"(idx) : "memory");
  __syncwarp();
  if ((t & 31) == 0) mbar_arrive(x.bars + B_PUB + 8 * n);
  x.nev++;
}

template<int KK = 0> __device__ __forceinline__ void issue_qk(float (&S)[64], uint32_t dq, uint32_t dk) {
  constexpr int off = (KK >> 1) * 512 + (KK & 1) * 2;
  if constexpr (KK == 0) wgmma_ss_n128_new<0, 0, 0, SW64, SW64>(S, dq, dk); else wgmma_ss_n128<0, off, off, SW64, SW64>(S, dq, dk, 1);
  if constexpr (KK < 7) issue_qk<KK + 1>(S, dq, dk);
}
template<int KK = 0> __device__ __forceinline__ void issue_qk_half(float (&S)[32], uint32_t dq, uint32_t dk) {
  constexpr int off = (KK >> 1) * 512 + (KK & 1) * 2;
  if constexpr (KK == 0) wgmma_ss_n64_new<0, 0, 256, SW64, SW64>(S, dq, dk); else wgmma_ss_n64<0, off, off + 256, SW64, SW64>(S, dq, dk, 1);
  if constexpr (KK < 7) issue_qk_half<KK + 1>(S, dq, dk);
}
template<int NK, int KK = 0>
__device__ __forceinline__ void issue_pv(float (&O)[64], uint32_t (&P)[32], uint32_t dv, int accumulate) {
  wgmma_rs_n128<1, (KK + 8 - NK) * 64, SW64>(O, P[4*KK], P[4*KK+1], P[4*KK+2], P[4*KK+3], dv, accumulate);
  if constexpr (KK + 1 < NK) issue_pv<NK, KK + 1>(O, P, dv, 1);
}
template<int K0, int K1>
__device__ __forceinline__ void exp_pack(const float (&S)[64], uint32_t (&D)[32], float& s0, float& s1) {
  #pragma unroll
  for (int k = K0; k < K1; k++) {
    const float e0 = ex2(S[2*k]), e1 = ex2(S[2*k+1]);
    D[k] = pack_bf16(e0, e1);
    if (k & 1) s1 += e0 + e1; else s0 += e0 + e1;
  }
}
__device__ __forceinline__ int diag_limit() { const int t = wg_tid(); return 16 * (t >> 5) + ((t & 31) >> 2) - 2 * (t & 3); }
__device__ __forceinline__ void exp_pack_diag(const float (&S)[64], uint32_t (&D)[32], int t, float& s0, float& s1) {
  #pragma unroll
  for (int k = 0; k < 16; k++) {
    const int c = 8 * (k >> 1) - 8 * (k & 1);
    const float e0 = ex2((c <= t) ? S[2*k] : -INFINITY), e1 = ex2((c + 1 <= t) ? S[2*k+1] : -INFINITY);
    D[k] = pack_bf16(e0, e1);
    if (k & 1) s1 += e0 + e1; else s0 += e0 + e1;
  }
}
constexpr float SUM_HI = 1.8446744073709552e19f;
constexpr float SUM_LO = 5.421010862427522e-20f;

__device__ __forceinline__ void classic_tile(const float (&S)[64], uint32_t (&P)[32], bool fresh, bool half, bool was_classic, volatile float* mc,
                                             float& l0, float& l1, float& s0, float& s1, float& sc0, float& sc1) {
  const int tmask = diag_limit();
  float4 t[16];
  #pragma unroll
  for (int j = 0; j < 16; j++) t[j] = make_float4(S[4*j], S[4*j+1], S[4*j+2], S[4*j+3]);
  float mx0 = -INFINITY, mx1 = -INFINITY;
  #pragma unroll 1
  for (int j = 0; j < 16; j++) {
    float4 v = t[j];
    const int lim = !fresh ? 1000 : j < 8 ? tmask - 8 * j : half ? -1000 : 1000;
    v.x = 0 <= lim ? v.x : -INFINITY; v.y = 1 <= lim ? v.y : -INFINITY; v.z = -8 <= lim ? v.z : -INFINITY; v.w = -7 <= lim ? v.w : -INFINITY;
    t[j] = v;
    mx0 = fmaxf(mx0, fmaxf(v.x, v.y)); mx1 = fmaxf(mx1, fmaxf(v.z, v.w));
  }
  mx0 = fmaxf(mx0, __shfl_xor_sync(0xffffffff, mx0, 1));
  mx1 = fmaxf(mx1, __shfl_xor_sync(0xffffffff, mx1, 1));
  mx0 = fmaxf(mx0, __shfl_xor_sync(0xffffffff, mx0, 2));
  mx1 = fmaxf(mx1, __shfl_xor_sync(0xffffffff, mx1, 2));
  const float mc0 = was_classic ? mc[0] : 0.f, mc1 = was_classic ? mc[1] : 0.f;
  const float n0 = fresh ? -mx0 : fminf(mc0, -mx0), n1 = fresh ? -mx1 : fminf(mc1, -mx1);
  sc0 = ex2(n0 - mc0); sc1 = ex2(n1 - mc1);
  mc[0] = n0; mc[1] = n1;
  s0 = 0.f; s1 = 0.f;
  #pragma unroll 1
  for (int j = 0; j < 16; j++) {
    const float4 v = t[j];
    const float e0 = ex2(v.x + n0), e1 = ex2(v.y + n0), e2 = ex2(v.z + n1), e3 = ex2(v.w + n1);
    s0 += e0 + e1; s1 += e2 + e3;
    reinterpret_cast<uint2*>(t)[j] = make_uint2(pack_bf16(e0, e1), pack_bf16(e2, e3));
  }
  #pragma unroll
  for (int j = 0; j < 8; j++) { P[4*j] = __float_as_uint(t[j].x); P[4*j+1] = __float_as_uint(t[j].y); P[4*j+2] = __float_as_uint(t[j].z); P[4*j+3] = __float_as_uint(t[j].w); }
  if (!fresh) { l0 *= sc0; l1 *= sc1; }
}
__device__ __forceinline__ void pack_tile(const float (&A)[64], uint32_t (&D)[32], float f0, float f1) {
  #pragma unroll
  for (int j = 0; j < 16; j++) {
    D[8 * (j >> 2) + (j & 3)] = pack_bf16(A[4*j] * f0, A[4*j+1] * f0);
    D[8 * (j >> 2) + 4 + (j & 3)] = pack_bf16(A[4*j+2] * f1, A[4*j+3] * f1);
  }
}
__device__ __forceinline__ int piece0(int t) { return ((t >> 5) * 16 + ((t & 31) >> 2)) * 32 + (((t ^ (t >> 3)) & 3) << 3); }
__device__ __forceinline__ void store_tile(__nv_bfloat16* p, const uint32_t (&D)[32]) {
  #pragma unroll
  for (int i = 0; i < 8; i++) stg_v4(p + (i >> 2) * (SEQ * 64) + ((i >> 1) & 1) * 4096 + (i & 1) * 256, D[4*i], D[4*i+1], D[4*i+2], D[4*i+3]);
}

enum : int { PV_ACC = 0, PV_ZERO = 1, PV_HALF = 2, PV_NONE = 3 };
struct Att {
  float l0, l1, i0, i1;
  bool classic;
  volatile float* mc;
};
__device__ __forceinline__ void store_ctx(Ctx& x, int code, const uint32_t (&D)[32]) {
  store_tile(x.sched->kvc + ((size_t)(128 + (code >> 5) * 2) * SEQ + ((code >> 1) & 15) * 128) * 64 + (code & 1) * 2048 + piece0(wg_tid()), D);
  publish(x, C_CTX + (code >> 2));
}
__device__ __forceinline__ __nv_bfloat16* kv_tile(const Ctx& x, int code) {
  return x.sched->kvc + ((size_t)(x.w * 64 + (code >> 4) * 2) * SEQ + (code & 15) * 128) * 64 + piece0(wg_tid());
}
__device__ __forceinline__ void q_proj(Ctx& x, Att& a, int& e, int& sk, int& sv, int& en, int& sn, bool isY,
                                       const uint32_t (&PA)[32], const uint32_t (&PB)[32], int vtile, bool first) {
  float S[64];
  int ek = 0, s = sk, ps = 0, ph = e >= 6, kb = 0;
  uint32_t qa = 0;
  sv = en = sn = 0;
  if (isY) bar_sync(1 + x.w, 256);
  if (first) mbar_wait(x.bars + B_RF + 8 * s, ph);
  #pragma unroll 1
  while (true) {
    #pragma unroll 1
    do {
      wgmma_fence();
      kblock_n128<0>(S, desc_lo(x.base + x.w * 8192, 16) + s * 2048, desc_lo(x.base + 16384, 8192) + s * 2048, kb != 0);
      wgmma_commit();
      if (kb == 7 && !isY) bar_arrive(1 + (x.w ^ 1), 256);
      wgmma_wait<1>();
      mbar_arrive_remote_if(x.rel + B_RE + 8 * ps, x.rel1 && kb > 0);
      ps = s;
      if (++s == 6) { s = 0; ph ^= 1; }
      if (++kb == 8) break;
      mbar_wait(x.bars + B_RF + 8 * s, ph);
    } while (kb != 4);
    asm volatile("" : "+r"(vtile));
    if (kb == 8) break;
    a.i0 = rcp_fast(quad_sum(a.l0)); a.i1 = rcp_fast(quad_sum(a.l1));
    e = ring_add(e, 8); ek = ring_add(e, isY ? 0 : 2); en = ring_add(e, isY ? 2 : 4);
    sk = ring_slot(ek); sv = ring_slot(e) + 1; sn = ring_slot(en);
    qa = x.base + SM_Q + x.w * 4096 + piece0(wg_tid()) * 2;
    if (vtile >= 0) store_tile(kv_tile(x, vtile) + 2048, PA);
  }
  if (vtile >= 0) { store_tile(kv_tile(x, vtile), PB); publish(x, C_KV + (vtile >> 4)); }
  wgmma_wait<0>();
  fence_regs(S);
  slot_release(x, ps, false);
  const bool landed = isY && mbar_test2(x.bars + B_RF + 8 * sk, e >= 6);
  #pragma unroll
  for (int i = 0; i < 8; i++) {
    const int j = 4 * (i >> 1), o = 2 * (i & 1);
    sts_v4(qa + (i >> 1) * 8192 + (i & 1) * 512,
           pack_bf16(S[4*j+o], S[4*j+o+1]), pack_bf16(S[4*j+4+o], S[4*j+5+o]), pack_bf16(S[4*j+8+o], S[4*j+9+o]), pack_bf16(S[4*j+12+o], S[4*j+13+o]));
  }
  fence_async_smem();
  if (!landed) { mbar_wait(x.bars + B_RF + 8 * sk, ek >= 6); mbar_wait(x.bars + B_RF + 8 * sv, e >= 6); }
}

template<int KIND>
__device__ __forceinline__ void slot(Ctx& x, Att& a, int& e, int& sk, int sv, int en, int sn, float (&O)[64], uint32_t (&Pn)[32], uint32_t (&Po)[32],
                                     bool more, bool isY, bool half, int pv, int pend) {
  float S[64];
  const int w = x.w;
  const uint32_t dq = desc_lo(x.base + SM_Q + w * 4096, 16), dk = desc_lo(x.base, 16) + sk * 2048, dv = desc_lo(x.base, 8192) + sv * 2048;
  bar_sync(1 + w, 256);
  if (KIND == 2) {
    wgmma_fence();
    issue_qk(S, dq, dk); wgmma_commit();
    issue_pv<8>(O, Po, dv, 1); wgmma_commit();
    bar_arrive(1 + (w ^ 1), 256);
    wgmma_wait<1>();
  } else if (KIND == 0 && half) {
    float T[32];
    wgmma_fence(); issue_qk_half(T, dq, dk); wgmma_commit();
    if (pv == PV_NONE) { wgmma_fence(); wgmma_commit(); }
    else               { wgmma_fence(); issue_pv<8>(O, Po, dv, pv == PV_ACC); wgmma_commit(); }
    bar_arrive(1 + (w ^ 1), 256);
    wgmma_wait<1>();
    fence_regs(T);
    #pragma unroll
    for (int i = 0; i < 32; i++) { S[i] = T[i]; asm volatile("" : "=f"(S[32 + i])); }
  } else {
    wgmma_fence(); issue_qk(S, dq, dk); wgmma_commit();
    if (KIND == 1 && pend >= 0) { bar_arrive(1 + (w ^ 1), 256); pack_tile(O, Pn, a.i0, a.i1); store_ctx(x, pend, Pn); }
    if (KIND == 0 && pv == PV_NONE) { wgmma_fence(); wgmma_commit(); }
    else if (pv == PV_HALF)         { wgmma_fence(); issue_pv<4>(O, Po, dv, 0); wgmma_commit(); }
    else                            { wgmma_fence(); issue_pv<8>(O, Po, dv, pv == PV_ACC); wgmma_commit(); }
    if (KIND == 0 || pend < 0) bar_arrive(1 + (w ^ 1), 256);
    wgmma_wait<1>();
  }
  fence_regs(S);
  fence_regs_u(Pn);
  slot_release(x, sk, KIND == 0 && isY);
  const bool landed = mbar_test2(x.bars + B_RF + 8 * sn, en >= 6);
  float s0 = 0.f, s1 = 0.f;
  const bool was_classic = KIND != 0 && a.classic;
  if (KIND == 0) {
    a.l0 = 0.f; a.l1 = 0.f;
    if (!half) exp_pack<16, 32>(S, Pn, s0, s1);
    else {
      #pragma unroll
      for (int i = 16; i < 32; i++) asm volatile("" : "=r"(Pn[i]));
    }
    exp_pack_diag(S, Pn, diag_limit(), s0, s1);
    uint32_t b0 = __ballot_sync(0xffffffff, s0 >= SUM_LO), b1 = __ballot_sync(0xffffffff, s1 >= SUM_LO);
    b0 |= b0 >> 1; b0 |= b0 >> 2; b1 |= b1 >> 1; b1 |= b1 >> 2;
    a.classic = __any_sync(0xffffffff, !(s0 <= SUM_HI && s1 <= SUM_HI)) || (b0 & b1 & 0x11111111u) != 0x11111111u;
  } else {
    exp_pack<0, 32>(S, Pn, s0, s1);
    a.classic = __any_sync(0xffffffff, a.classic || !(s0 <= SUM_HI && s1 <= SUM_HI));
  }
  fence_regs_u(Pn);
  if (!landed || a.classic) {
    mbar_wait(x.bars + B_RF + 8 * sn, en >= 6);
    if (more) mbar_wait(x.bars + B_RF + 8 * sn + 8, en >= 6);
    if (a.classic) {
      wgmma_wait<0>();
      fence_regs(O);
      float sc0, sc1;
      classic_tile(S, Pn, KIND == 0, half, was_classic, a.mc, a.l0, a.l1, s0, s1, sc0, sc1);
      if (KIND != 0) {
        #pragma unroll
        for (int j = 0; j < 16; j++) { O[4*j] *= sc0; O[4*j+1] *= sc0; O[4*j+2] *= sc1; O[4*j+3] *= sc1; }
      }
    }
  }
  wgmma_wait<0>();
  fence_regs(O);
  fence_regs_u(Po);
  slot_release(x, sv, KIND == 1 && isY && pv != PV_ACC);
  a.l0 += s0; a.l1 += s1;
  e = en; sk = sn;
}

__device__ __forceinline__ int attention(Ctx& x, const uint8_t* items, int nitems, int rank, uint32_t (&PA)[32], uint32_t (&PB)[32], int vtile) {
  int e = 0, sk = 0;
  float O[64];
  Att a;
  volatile float mc[2];
  a.l0 = 1.f; a.l1 = 1.f; a.i0 = 0.f; a.i1 = 0.f; a.classic = false; a.mc = mc;
  int pv = PV_NONE, cur = -1;
  #pragma unroll 1
  for (int it = 0; ; it++) {
    const bool isY = (it & 1) == x.w;
    int pend = cur;
    if (it < nitems) {
      const bool half = isY == (rank != 0);
      int sv, en, sn;
      q_proj(x, a, e, sk, sv, en, sn, isY, PA, PB, vtile, it == 0);
      vtile = -1;
      const int item = items[it];
      cur = item * 4 + (isY ? 3 - rank : rank);
      int rem = 2 * (item & 7) + (isY ? 1 : 0);
      slot<0>(x, a, e, sk, sv, en, sn, O, PA, PB, rem > 0, isY, half, pv, -1);
      pv = half ? PV_HALF : PV_ZERO;
      #pragma unroll 1
      while (rem > 0) {
        slot<1>(x, a, e, sk, sk + 1, ring_add(e, 2), sk == 4 ? 0 : sk + 2, O, PB, PA, rem > 1, isY, false, pv, pend);
        pv = PV_ACC; pend = -1;
        if (rem == 1) break;
        rem -= 2;
        slot<2>(x, a, e, sk, sk + 1, ring_add(e, 2), sk == 4 ? 0 : sk + 2, O, PA, PB, rem > 0, false, false, 0, -1);
      }
      if (isY) continue;
    } else {
      slot_release(x, 6, false);
      const uint32_t dv = desc_lo(x.base, 8192) + sk * 2048;
      bar_sync(1 + x.w, 256);
      if (pv == PV_HALF) { wgmma_fence(); issue_pv<4>(O, PB, dv, 0); wgmma_commit(); }
      else { wgmma_fence(); issue_pv<8>(O, PB, dv, pv == PV_ACC); wgmma_commit(); }
      if (isY) bar_arrive(1 + (x.w ^ 1), 256);
      a.i0 = rcp_fast(quad_sum(a.l0)); a.i1 = rcp_fast(quad_sum(a.l1));
      ring_wait_full(x.bars, e);
      wgmma_wait<0>();
      fence_regs(O);
      fence_regs_u(PB);
      slot_release(x, sk, false);
    }
    if (pend >= 0) {
      pack_tile(O, PB, a.i0, a.i1);
      if (it == nitems) return pend;
      store_ctx(x, pend, PB);
    }
    #pragma unroll
    for (int i = 0; i < 32; i++) asm volatile("mov.b32 %0, %1;" : "=r"(PB[i]) : "r"(PA[i]));
  }
}

#define LN_AT 2
#define X_AT 6
#define PERT 0
#define CTX_T 3
#define PF_AT 5
#define PF_N 4
#define PF_MOE 3
constexpr float QSCALE = 0.08838834764831845f * 1.4426950408889634f;
__device__ __forceinline__ void mod_cta(Ctx& x, const __nv_bfloat16* cvec) {
  const int t = wg_tid(), ct = x.w * 128 + t;
  #pragma unroll 1
  for (int k = 0; k < 6; k++) slot_release(x, k, false);
  const uint32_t cv = __ldg(reinterpret_cast<const uint32_t*>(cvec) + ct);
  asm volatile("st.shared.u32 [%0], %1;" :: "r"(x.base + SM_H2 + ct * 4),
               "r"(pack_bf16(__fdividef(bf_lo(cv), 1.f + __expf(-bf_lo(cv))), __fdividef(bf_hi(cv), 1.f + __expf(-bf_hi(cv))))) : "memory");
  bar_sync(5, 256);
  float acc[64];
  int e = 0;
  #pragma unroll 1
  for (int g = 0; g < 24; g++) {
    uint32_t a[8];
    #pragma unroll
    for (int i = 0; i < 8; i++) a[i] = lds_u32(x.base + SM_H2 + (g & 7) * 128 + i * 16 + (t & 3) * 4);
    ring_wait_full(x.bars, e);
    const uint32_t db = desc_lo(x.base + x.w * 16384, 8192) + ring_slot(e) * 2048;
    wgmma_fence();
    wgmma_rs_n128<1, 0, SW128>(acc, a[0], a[0], a[1], a[1], db, g & 7);
    wgmma_rs_n128<1, 128, SW128>(acc, a[2], a[2], a[3], a[3], db, 1);
    wgmma_rs_n128<1, 256, SW128>(acc, a[4], a[4], a[5], a[5], db, 1);
    wgmma_rs_n128<1, 384, SW128>(acc, a[6], a[6], a[7], a[7], db, 1);
    wgmma_commit();
    wgmma_wait<0>();
    fence_regs(acc);
    ring_release(x, e, false);
    e = ring_add(e, 1);
    if ((g & 7) == 7) {
      if (t < 4) {
        const float sc = (g == 7 && blockIdx.x < NCTA + 2) ? QSCALE : 1.f;
        uint32_t* dst = reinterpret_cast<uint32_t*>(g_x.mod + (g >> 3) * 1024 + (blockIdx.x - NCTA) * 256 + x.w * 128) + t;
        #pragma unroll
        for (int j = 0; j < 16; j++) dst[4 * j] = pack_bf16(rbf(acc[4*j]) * sc, rbf(acc[4*j+1]) * sc);
      }
      publish(x, g == 7 ? C_MOD : C_MOD2);
    }
  }
}

__global__ void __cluster_dims__(2, 1, 1) __launch_bounds__(384, 1)
k_fused(const __grid_constant__ CUtensorMap tmC, const __grid_constant__ CUtensorMap tmWq,
        const __grid_constant__ CUtensorMap tmWk, const __grid_constant__ CUtensorMap tmWv,
        const __grid_constant__ CUtensorMap tmWo, const __grid_constant__ CUtensorMap tmWg,
        const __grid_constant__ CUtensorMap tmWu, const __grid_constant__ CUtensorMap tmWm,
        const __grid_constant__ Sched sched,
        const __nv_bfloat16* __restrict__ xin,
        const __nv_bfloat16* __restrict__ cvec, const __nv_bfloat16* __restrict__ w_o,
        const __nv_bfloat16* __restrict__ w_r, const __nv_bfloat16* __restrict__ w_gate, const __nv_bfloat16* __restrict__ w_up,
        const __nv_bfloat16* __restrict__ w_down, __nv_bfloat16* __restrict__ out) {
  extern __shared__ __align__(1024) uint8_t smem_raw[];
  const uint32_t base = smem_u32(smem_raw), bars = base + SM_BAR;
  const int warp = __shfl_sync(0xffffffff, threadIdx.x >> 5, 0), wg = warp >> 2;
  const int rank = cluster_ctarank(), p = blockIdx.x >> 1;
  const int mt = (p & 7) * 2 + rank;
  const bool spare = blockIdx.x >= NCTA;
  #pragma unroll
  for (int i = 0; i < PERT; i++) { uint32_t d; asm volatile("mov.u32 %0, %%laneid;" : "=r"(d)); (void)d; }
  {
    const int h0 = KHEAD0 + (p >> 3);
    if (warp == 11) { prefetch_tmap(&tmC); prefetch_tmap(&tmWk); }
    #pragma unroll 1
    for (int t = warp == 8 ? 0 : warp < 8 ? warp + 1 : warp == 11 ? 64 : warp; t < B_PUB / 8; t += (warp == 8 ? 64 : 10))
      w_mbar_init(bars + 8 * t, t < B_WE / 8 ? 1 : t < B_RE / 8 ? 2 : 4);
    fence_mbar_init();
    cluster_arrive();
    if (warp == 9) prefetch_tmap(&tmWv);
    if (wg == 2) bar_arrive(1, 256);
    if (warp == 8 && !spare) {
      #pragma unroll 1
      for (int kb = 0; kb < 8; kb++) {
        w_expect_tx(bars + B_AF + 8 * kb, 16384);
        tma_load_2d(base + k_addrA(kb), &tmC, bars + B_AF + 8 * kb, kb * 64, mt * 128);
        if (kb == 0) cluster_wait();
        if (kb < 6) {
          w_expect_tx(bars + B_WF + 8 * kb, 16384);
          tma_load_2d_mc(base + k_addrW(kb) + rank * 8192, &tmWk, bars + B_WF + 8 * kb, h0 * 128 + rank * 64, kb * 64);
        }
      }
    }
  }
  const Sched::Pair& sp = sched.pair[p];
  const int nitems = sp.nitems, nsteps = sp.nsteps;
  auto oent = [&](int k) -> uint32_t { return sp.oent[k]; };
  const int ot = sp.otask, m = (ot & 7) * 2 + rank, grp = m * 8 + (ot >> 3);

  if (wg == 0) {
    asm volatile("setmaxnreg.dec.sync.aligned.u32 24;");
    const int lane = threadIdx.x & 31;
    #pragma unroll 1
    for (int t = B_PUB / 8 + warp; t < 80; t += 4) w_mbar_init(bars + 8 * t, t < B_RDY / 8 ? 4 : 1);
    bar_sync(6, 128);
    bar_arrive(7, 256); bar_arrive(8, 256);
    cluster_wait();
    const unsigned int tag = ld_relaxed(&g_x.epoch) + 1;
    if (warp == 0) {
      if (!spare) {
        int s = 0, ph = 0;
        tma_prefetch_2d(&tmWv, sp.khead[0] * 128 + rank * 64, (p & 7) * 64);
        #pragma unroll 1
        for (int g = 6; g < 64; g++) {
          const int u = g >> 3, kb = g & 7;
          if (kb == 0 && u < 7) tma_prefetch_2d((u & 1) ? &tmWk : &tmWv, sp.khead[(u + 1) >> 1] * 128 + rank * 64, (p & 7) * 64);
          mbar_wait(bars + B_WE + 8 * s, ph);
          w_expect_tx(bars + B_WF + 8 * s, 16384);
          tma_load_2d_mc(base + k_addrW(s) + rank * 8192, (u & 1) ? &tmWv : &tmWk, bars + B_WF + 8 * s, sp.khead[u >> 1] * 128 + rank * 64, kb * 64);
          if (++s == 6) { s = 0; ph ^= 1; }
        }
      }
      int s = 0, ph = 0;
      auto next_entry = [&](int bytes) {
        mbar_wait(bars + B_RE + 8 * s, ph);
        w_expect_tx(bars + B_RF + 8 * s, bytes);
      };
      auto advance = [&]() { if (++s == 6) { s = 0; ph ^= 1; } };
      if (spare) {
        #pragma unroll 1
        for (int g = 0; g < 24; g++) {
          if (g == 8) mbar_wait(bars + R_MOD, 0);
          next_entry(32768);
          for (int k = 0; k < 2; k++) tma_load_3d(base + s * 32768 + k * 16384, &tmWm, bars + B_RF + 8 * s, 0, (g & 7) * 64, (g >> 3) * 16 + (blockIdx.x - NCTA) * 4 + k * 2);
          advance();
        }
      }
      mbar_wait(bars + R_H1, 0);
      fence_async_global();
      int vrow = -1;
      #pragma unroll 1
      for (int i = 0; i <= nitems; i++) {
        const int item = sp.item[i & (MAX_ITEMS - 1)], h = item >> 3, j = item & 7;
        if (i < nitems) {
          const int row0 = j * 256 + ((i & 1) ? rank : 3 - rank) * 64, row1 = j * 256 + ((i & 1) ? 3 - rank : rank) * 64;
          #pragma unroll 1
          for (int kb = 0; kb < 8; kb++) {
            next_entry(32768);
            tma_load_2d_mc(base + s * 32768 + 16384 + rank * 8192, &tmWq, bars + B_RF + 8 * s, h * 128 + rank * 64, kb * 64);
            bulk_load(base + s * 32768, sched.h1 + row0 * DM + kb * 4096, 8192, bars + B_RF + 8 * s);
            bulk_load(base + s * 32768 + 8192, sched.h1 + row1 * DM + kb * 4096, 8192, bars + B_RF + 8 * s);
            advance();
          }
          mbar_wait(bars + R_ITEM + 8 * i, 0);
          fence_async_global();
        }
        #pragma unroll 1
        for (int n = i < nitems ? 4 * j + 3 : 0; n >= 0; n--) {
          const int krow = (h * 2 + rank) * SEQ + (n >> 1) * 128 + ((sp.lastuse[i & (MAX_ITEMS - 1)] >> (n >> 1)) & 1);
          const int row = (n & 1) ? krow : vrow;
          if (i + 1 == nitems && n == min(4 * j + 3, 2 * PF_AT + 1)) w_arrive(bars + R_NEAR);
          next_entry(row >= 0 ? 32768 : 0);
          if (row >= 0) bulk_load_mc(base + s * 32768 + rank * 16384, sched.kvc + (size_t)(row & ~1) * 64, bars + B_RF + 8 * s, row & 1);
          advance();
          if (!(n & 1)) vrow = krow + 64 * SEQ;
        }
      }
      if (!spare) {
      const int oc = ((ot >> 3) & 1) * 4 + rank * 2;
      auto o_next = [&](int k, int bytes) {
        const uint32_t v = oent(k); s = v & 7;
        mbar_wait(bars + B_RE + 8 * s, v >> 3);
        w_expect_tx(bars + B_RF + 8 * s, bytes);
      };
      #pragma unroll 1
      for (int i = 0; i < nsteps; i++) {
        const int c0 = sp.ochunk[i][0], c1 = sp.ochunk[i][1];
        const int pf = i - nsteps + PF_MOE;
        if (pf >= 0 && pf < 3)
          bulk_prefetch((pf == 0 ? w_gate : pf == 1 ? w_up : w_down) + (size_t)blockIdx.x * (DM * FF / NCTA), DM * FF / NCTA * 2);
        if (c0 < 64) { o_next(3 * i, 32768); tma_load_3d_mc(base + s * 32768 + rank * 16384, &tmWo, bars + B_RF + 8 * s, 0, c0 * 64, oc); }
        mbar_wait(bars + R_CTX + 8 * i, 0);
        fence_async_global();
        o_next(3 * i + 1, c0 < 64 ? 32768 : 16384);
        if (c0 < 64) bulk_load(base + s * 32768, sched.kvc + (size_t)((128 + c0) * SEQ + m * 128) * 64, 16384, bars + B_RF + 8 * s);
        bulk_load(base + s * 32768 + 16384, sched.kvc + (size_t)((128 + c1) * SEQ + m * 128) * 64, 16384, bars + B_RF + 8 * s);
        o_next(3 * i + 2, 32768);
        tma_load_3d_mc(base + s * 32768 + rank * 16384, &tmWo, bars + B_RF + 8 * s, 0, c1 * 64, oc);
      }
      const int f0 = (blockIdx.x < FF / 16 ? blockIdx.x : 0) * 16;
      o_next(3 * nsteps, 32768);
      bulk_load(base + s * 32768, w_down + (size_t)f0 * DM, 16384, bars + B_RF + 8 * s);
      bulk_load(base + s * 32768 + 16384, xin + (size_t)grp * 16 * DM, 16384, bars + B_RF + 8 * s);
      o_next(3 * nsteps + 1, 32768);
      #pragma unroll 1
      for (int k = 0; k < 4; k++) tma_load_2d(base + s * 32768 + k * 8192, (k & 2) ? &tmWu : &tmWg, bars + B_RF + 8 * s, f0, (k & 1) * 256);
      #pragma unroll 1
      for (int k = 0; k < 4; k++) w_expect_tx(bars + R_PART + 8 * k, 16384);
      mbar_wait(bars + B_PUB + 8 * (5 + nitems), 0);
      mbar_wait(bars + B_PUB + 8 * (NPUB + 5 + nitems), 0);
      uint32_t todo = 0xff;
      #pragma unroll 1
      for (int n = 0; n < WAIT_LIM && todo; n++) {
        uint32_t now = __ballot_sync(0xffffffff, ld_acquire(&g_x.cnt[C_PART + (m * 2 + (ot >> 5)) * 32 + (lane & 7)]) == tag) & todo;
        todo &= ~now;
        if (now) fence_async_global();
        #pragma unroll 1
        for (; now; now &= now - 1) {
          const int q = __ffs(now) - 1;
          bulk_load(base + (oent(3 * nsteps - 3 + (q >> 2)) & 7) * 32768 + (q & 3) * 8192, sched.part + (grp * 8 + q) * 4096, 8192, bars + R_PART + 8 * (q >> 1));
        }
      }
      }
    } else if (warp < 3) {
      const int w = warp - 1, n1 = w * NPUB + (spare ? 3 : 6) + nitems;
      #pragma unroll 1
      for (int n = w * NPUB; n < n1; n++) {
        #pragma unroll 1
        for (int k = 0; k < 8 * WAIT_LIM; k++) { if (mbar_try(bars + B_PUB + 8 * n, 0)) break; }
        const uint32_t idx = lds_u32(base + SM_MAIL + 4 * n);
        fence_async_global();
        if (lane == 0 && idx < (unsigned)C_END) red_release(idx);
        __syncwarp();
      }
    } else {
      *reinterpret_cast<volatile uint32_t*>(smem_raw + SM_KEY + 48) = tag;
      if (!spare) { mbar_wait(bars + B_AF + 8 * X_AT, 0); bulk_prefetch(xin + (size_t)blockIdx.x * 16 * DM, 16 * DM * 2); }
      #pragma unroll 1
      for (int n = 0; n < 8 + nsteps; n++) {
        if (n == 2 + nitems) n = 7;
        int idx = n == 0 ? C_MOD : n == 1 ? C_H1 : C_MOD2, cnt = n == 0 ? 8 : n == 1 ? 256 : 16;
        if (n == 2) tma_prefetch_2d(&tmWq, (sp.item[0] >> 3) * 128 + rank * 64, (sp.item[0] & 7) * 64);
        if (n >= 2 && n < 7) { idx = C_KV + (sp.item[n - 2] >> 3); cnt = 32; }
        if (n >= 8) { const int c0 = sp.ochunk[n - 8][0], c1 = sp.ochunk[n - 8][1]; idx = C_CTX + (((lane & 1) && c0 < 64 ? c0 : c1) >> 1) * 8 + (ot & 7); cnt = 4; }
        wait_count_lazy(idx, cnt * tag);
        w_arrive(bars + B_RDY + 8 * n);
        if (n == 8 + PF_N - 1) {
          #pragma unroll 1
          for (int k = 0; k < 8 * WAIT_LIM; k++) { if (mbar_try(bars + R_NEAR, 0)) break; }
          bulk_prefetch(w_o + (size_t)blockIdx.x * (NH * DH * DM / NCTA), NH * DH * DM / NCTA * 2);
          #pragma unroll 1
          for (int k = 0; k < PF_N; k++) {
            const int cc = sp.ochunk[k][(ot >> 3) & 1];
            if (cc < 64) bulk_prefetch(sched.kvc + ((size_t)(128 + cc) * SEQ + m * 128) * 64, 16384);
          }
        }
      }
    }
    __syncwarp();
    cluster_arrive();
    if (!spare) {
      bar_sync(6, 128);
      asm volatile("setmaxnreg.inc.sync.aligned.u32 88;");
      const int pos = blockIdx.x * 4 + (lane & 1) * 2, col = (blockIdx.x >> 2) * 16 + (blockIdx.x & 3) * 2 + (lane & 1) * 8, src = threadIdx.x >> 1;
      uint32_t gbest = 0, hh = 0, gbf = 0;
      uint2 xx = make_uint2(0, 0);
      uint4 ya = make_uint4(0, 0, 0, 0), yb = make_uint4(0, tag, 0, tag);
      auto poll_y = [&]() {
        if (ya.y != tag || ya.w != tag) ya = ld_tagged2(&g_x.yll[src][pos]);
        if (yb.y != tag || yb.w != tag) yb = ld_tagged2(&g_x.yll[src + 64][pos]);
        return __all_sync(0xffffffff, ya.y == tag && ya.w == tag && yb.y == tag && yb.w == tag);
      };
      ya.y = tag - 1; if (src + 64 < FF / 16) yb.y = tag - 1;
      if (warp == 3) {
        gbf = __ldcg(reinterpret_cast<const uint32_t*>(g_x.mod + 5 * DM + col));
        uint32_t have = 0;
        uint2 k[4];
        #pragma unroll
        for (int i = 0; i < 4; i++) k[i] = make_uint2(0, tag - 1);
        #pragma unroll 1
        for (int n = 0; n < WAIT_LIM; n++) {
          #pragma unroll
          for (int i = 0; i < 4; i++) if (k[i].y != tag) k[i] = ld_tagged(&g_x.keys[i * 32 + lane][0]);
          if (gbest != have) {
            const int g = ((0xffffu - gbest) >> 4) & 127;
            uint4 hv[4];
            #pragma unroll
            for (int i = 0; i < 4; i++) hv[i] = ld_tagged2(&g_x.row[g][0][i * 64 + lane * 2]);
            xx = ld_tagged(&g_x.row[g][1][(col >> 8) * 128 + ((col >> 2) & 1) * 64 + ((col >> 3) & 31) * 2 + ((col >> 1) & 1)]);
            bool ok = xx.y == tag;
            #pragma unroll
            for (int i = 0; i < 4; i++) { ok = ok && hv[i].y == tag && hv[i].w == tag; reinterpret_cast<uint2*>(smem_raw + SM_H2)[(i >> 1) * 64 + lane * 2 + (i & 1)] = make_uint2(hv[i].x, hv[i].z); }
            if (lane == 0) *reinterpret_cast<uint32_t*>(smem_raw + SM_KEY + 32) = gbest;
            have = __all_sync(0xffffffff, ok) ? gbest : 0;
          }
          bool all = true;
          #pragma unroll
          for (int i = 0; i < 4; i++) { all = all && k[i].y == tag; gbest = max(gbest, k[i].y == tag ? k[i].x : 0u); }
          gbest = __reduce_max_sync(0xffffffff, gbest);
          if (__all_sync(0xffffffff, all) && gbest == have) break;
        }
        w_arrive(bars + R_KEY);
        if (blockIdx.x == 0 && lane == 0) g_x.epoch = tag;
        hh = lds_u32(base + SM_H2 + col * 2);
      }
      const float rsel = rbf(__uint_as_float((((gbest & 0x80000000u) ? gbest & 0x7fffffffu : ~gbest) & 0xfffff000u) | 0x800u));
      const float rs = rbf(__fdividef(1.f, 1.f + __expf(-rsel)));
      bar_sync(9, 384);
      #pragma unroll 1
      for (int n = 0; n < WAIT_LIM; n++) { if (poll_y()) break; }
      float y0 = __uint_as_float(ya.x) + __uint_as_float(yb.x), y1 = __uint_as_float(ya.z) + __uint_as_float(yb.z);
      #pragma unroll
      for (int o = 2; o < 32; o <<= 1) { y0 += __shfl_xor_sync(0xffffffff, y0, o); y1 += __shfl_xor_sync(0xffffffff, y1, o); }
      float2* s_y = reinterpret_cast<float2*>(smem_raw + SM_KEY + 64);
      if (lane < 2) s_y[warp * 2 + lane] = make_float2(y0, y1);
      bar_sync(6, 128);
      if (warp == 3 && lane < 2) {
        y0 = 0.f; y1 = 0.f;
        #pragma unroll
        for (int i = 0; i < 4; i++) { y0 += reinterpret_cast<const float*>(s_y)[i * 4 + lane]; y1 += reinterpret_cast<const float*>(s_y)[i * 4 + 2 + lane]; }
        const float o0 = bf_lo(xx.x) + rbf(bf_lo(gbf) * rbf(bf_lo(hh) + rbf(rbf(y0) * rs)));
        const float o1 = bf_hi(xx.x) + rbf(bf_hi(gbf) * rbf(bf_hi(hh) + rbf(rbf(y1) * rs)));
        *reinterpret_cast<uint32_t*>(out + (size_t)((0xffffu - gbest) & (SEQ - 1)) * DM + col) = pack_bf16(o0, o1);
      }
    }
    __syncwarp();
    cluster_wait();
  } else {
    asm volatile("setmaxnreg.inc.sync.aligned.u32 240;");
    Ctx x;
    x.w = wg - 1; x.base = base; x.bars = bars; x.nev = 0; x.sched = &sched;
    const int w = x.w, warp4 = warp & 3;
    x.rel = mapa(bars, (warp4 & 1) ^ 1);
    x.rel1 = (threadIdx.x & 127) == 32 || (threadIdx.x & 127) == 64;
    if (warp != 8 || spare) cluster_wait();
    if (w == 1 || spare) bar_sync(7 + w, 256);
    uint32_t PA[32], PB[32];
    int vtile = -1;
    if (spare) {
      mod_cta(x, cvec);
    } else {
      const int lane = wg_tid() & 31;
      Row xn[2];
      float acc0[64], acc1[64];
      int s = 2 * w, ph = w;
      #pragma unroll 1
      for (int u = w; u < 8; u += 2) {
        bar_sync(1 + w, 256);
        int ps = 0;
        #pragma unroll 1
        for (int kb = 0; kb < 8; kb++) {
          if (u < 2) mbar_wait(bars + B_AF + 8 * kb, 0);
          mbar_wait(bars + B_WF + 8 * s, ph);
          const uint32_t da = desc_lo(base + k_addrA(kb), 16), dw = desc_lo(base + k_addrW(s), 8192);
          wgmma_fence();
          kblock_n128<0>(acc0, da, dw, kb != 0);
          kblock_n128<512>(acc1, da, dw, kb != 0);
          wgmma_commit();
          if (kb == 7) bar_arrive(1 + (w ^ 1), 256);
          if (kb > 0) {
            wgmma_wait<1>();
            mbar_arrive_remote_if(x.rel + B_WE + 8 * ps, x.rel1);
            if (u == 7 && !(kb & 1)) {
              ring_release(x, kb == 2 ? 0 : kb - 3, false);
              if (kb > 2) ring_release(x, kb - 2, false);
            }
          }
          ps = s;
          if (++s == 6) { s = 0; ph ^= 1; }
        }
        Row t[2];
        const int lrow = blockIdx.x * 16 + w * 8 + warp4 * 2;
        if (u == w) { t[0] = ldg_row(xin + (size_t)lrow * DM, lane); t[1] = ldg_row(xin + (size_t)(lrow + 1) * DM, lane); }
        if (u == LN_AT || u == LN_AT + 1) {
          mbar_wait(bars + R_MOD, 0);
          t[0] = ldca_row(g_x.mod, lane); t[1] = ldca_row(g_x.mod + DM, lane);
        }
        wgmma_wait<0>();
        fence_regs(acc0); fence_regs(acc1);
        mbar_arrive_remote_if(x.rel + B_WE + 8 * ps, x.rel1);
        if (u == 6) { for (int k = 0; k < 5; k++) ring_release(x, k, false); }
        if (u >= 6) ring_release(x, 5, false);
        if (u == 7) {
          pack_tile(acc0, PA, 1.f, 1.f); pack_tile(acc1, PB, 1.f, 1.f);
          vtile = sp.khead[3] * 16 + mt;
          break;
        }
        s += 2; ph ^= 1; if (s >= 6) { s -= 6; ph ^= 1; }
        if (u == 0) bar_sync(7, 256);
        if (u == w) {
          float st[4] = {0.f, 0.f, 0.f, 0.f};
          #pragma unroll
          for (int i = 0; i < 32; i++) { const float v = row_at(t[i >> 4], i & 15); st[(i >> 4) * 2] += v; st[(i >> 4) * 2 + 1] = fmaf(v, v, st[(i >> 4) * 2 + 1]); }
          warp_sums(st);
          #pragma unroll
          for (int r = 0; r < 2; r++) { ln_stats(st[2*r], st[2*r+1]); xn[r] = ln_apply(t[r], st[2*r], st[2*r+1] * QSCALE); }
        }
        if ((u == LN_AT || u == LN_AT + 1)) {
          #pragma unroll
          for (int r = 0; r < 2; r++) {
            const Row hr = fma_row(xn[r], one_plus(t[1]), t[0]);
            __nv_bfloat16* hp = sched.h1 + (lrow & ~63) * DM + (lane >> 3) * 4096 + ((lrow + r) & 63) * 64 + (((lane ^ (lrow + r)) & 7) << 3);
            stg_v4(hp, hr.v[0], hr.v[1], hr.v[2], hr.v[3]); stg_v4(hp + 4 * 4096, hr.v[4], hr.v[5], hr.v[6], hr.v[7]);
          }
        }
        const int tile = sp.khead[u >> 1] * 16 + mt;
        __nv_bfloat16* dst = kv_tile(x, tile);
        uint32_t D[32];
        pack_tile(acc0, D, 1.f, 1.f); store_tile(dst + 2048, D);
        pack_tile(acc1, D, 1.f, 1.f); store_tile(dst, D);
        if (u == LN_AT || u == LN_AT + 1) publish(x, C_H1);
        publish(x, C_KV + (tile >> 4));
      }
    }
    const int last = attention(x, sp.item, nitems, rank, PA, PB, vtile);
    const int lane = wg_tid() & 31, cw = w * 4 + warp4;
    const int row0 = grp * 16 + cw * 2;
    const bool moe_cta = blockIdx.x < FF / 16;
    if (spare) { store_ctx(x, last, PB); __syncwarp(); cluster_arrive(); cluster_wait(); return; }
    const int kl = 3 * nsteps - 3;
    uint2* const yp = &g_x.yll[blockIdx.x][cw * 64 + (lane & 3) * 16 + (lane >> 2) * 2];
    Row ga, sb, cb, gb, wr;
    {
      float accA[64], accB[64];
      const int t0 = oent(0) == oent(1);
      uint32_t pa = 0, pb = 0;
      #pragma unroll 1
      for (int t = t0; t < 2 * nsteps - 2; t++) {
        const uint32_t eb = oent(3 * (t >> 1) + 2 * (t & 1)), ea = oent(3 * (t >> 1) + 1);
        o_wait_full(bars, eb);
        o_wait_full(bars, ea);
        const uint32_t da = desc_lo(base + w * 4096, 16) + (ea & 7) * 2048 + (t & 1) * 1024, db = desc_lo(base, 8192) + (eb & 7) * 2048;
        wgmma_fence();
        kblock_n128<0, 0, SW64>(accA, da, db, t != t0); kblock_n128<0, 1024, SW64>(accB, da, db, t != t0);
        wgmma_commit();
        if (t == CTX_T) store_ctx(x, last, PB);
        if (t > t0) { wgmma_wait<1>(); slot_release(x, pb, false); if (!(t & 1)) slot_release(x, pa, false); }
        pa = ea & 7; pb = eb & 7;
      }
      const uint32_t e0 = oent(kl), ea = oent(kl + 1), eb = oent(kl + 2);
      const uint32_t da = desc_lo(base + w * 4096, 16) + (ea & 7) * 2048;
      const uint32_t db0 = desc_lo(base, 8192) + (e0 & 7) * 2048, db1 = desc_lo(base, 8192) + (eb & 7) * 2048;
      ga = ldca_row(g_x.mod + 2 * DM, lane); sb = ldca_row(g_x.mod + 3 * DM, lane); cb = ldca_row(g_x.mod + 4 * DM, lane); gb = ldca_row(g_x.mod + 5 * DM, lane);
      wr = ldca_row(w_r, lane);
      if (moe_cta) st_tagged2(yp, 0, 0, 0);
      o_wait_full(bars, e0);
      o_wait_full(bars, ea);
      o_wait_full(bars, eb);
      wgmma_fence();
      kblock_n128<0, 0, SW64>(accA, da, db0, 1); kblock_n128<1024, 0, SW64>(accA, da, db1, 1);
      wgmma_commit();
      kblock_n128<0, 1024, SW64>(accB, da, db0, 1); kblock_n128<1024, 1024, SW64>(accB, da, db1, 1);
      wgmma_commit();
      __syncwarp();
      cluster_arrive();
      __nv_bfloat16* dst = sched.part + ((m * 8 + cw) * 8 + (ot >> 3)) * 4096;
      auto send = [&](const float (&acc)[64], int h) {
        uint32_t D[32];
        pack_tile(acc, D, 1.f, 1.f);
        #pragma unroll
        for (int i = 0; i < 8; i++) stg_v4(dst + (h * 8 + i) * 256 + ((lane ^ (h * 4 + (i >> 1))) << 3), D[4*i], D[4*i+1], D[4*i+2], D[4*i+3]);
      };
      wgmma_wait<1>();
      fence_regs(accA);
      send(accA, 0);
      o_wait_full(bars, eb);
      wgmma_wait<0>();
      fence_regs(accB);
      send(accB, 1);
      publish(x, C_PART + (m * 2 + w) * 32 + (ot >> 3));
    }
    asm volatile("setmaxnreg.dec.sync.aligned.u32 208;");
    const uint32_t sD = base + (oent(kl + 3) & 7) * 32768, sW = base + (oent(kl + 4) & 7) * 32768;
    o_wait_full(bars, oent(kl + 3)); o_wait_full(bars, oent(kl + 4));
    Row x1[2];
    #pragma unroll
    for (int r = 0; r < 2; r++) x1[r] = lds_row(sD + 16384 + (cw * 2 + r) * 1024, lane);
    uint4 wgv[4], wuv[4], wdv[4];
    #pragma unroll
    for (int r = 0; r < 4; r++) {
      const uint32_t k = (lane & 7) + ((lane >> 4) << 3), h = (lane & 8) * 2;
      wgv[r] = ldsm_x4_t(sW + (cw * 64 + r * 16 + k) * 32 + h);
      wuv[r] = ldsm_x4_t(sW + 16384 + (cw * 64 + r * 16 + k) * 32 + h);
      wdv[r] = ldsm_x4_t(sD + k * 1024 + (cw * 64 + r * 16) * 2 + h);
    }
    const Row cb1 = one_plus(cb);
    const unsigned int tag = lds_u32(base + SM_KEY + 48);
    float u[16], ub[2] = {0.f, 0.f};
    #pragma unroll
    for (int i = 0; i < 16; i++) { u[i] = row_at(cb1, i) * row_at(wr, i); ub[0] += u[i]; ub[1] = fmaf(row_at(sb, i), row_at(wr, i), ub[1]); }
    warp_sums(ub);
    float st[6] = {0.f, 0.f, 0.f, 0.f, 0.f, 0.f};
    uint32_t key[2];
    {
      const uint32_t po = base + ((lane & 7) * 2 + (cw >> 2)) * 512 + (cw & 3) * 128;
      Row av[2][2];
      #pragma unroll
      for (int k = 0; k < 4; k++) {
        mbar_wait(bars + R_PART + 8 * k, 1);
        const uint32_t pa = po + (oent(kl + (k >> 1)) & 7) * 32768 + (k & 1) * 16384;
        #pragma unroll
        for (int r = 0; r < 2; r++) {
          const uint32_t sw = ((r * 4 + (lane >> 3)) ^ (lane & 7)) << 4;
          const uint4 lo = ldsm_x4(pa + sw), hi = ldsm_x4(pa + 8192 + sw);
          const Row v{{lo.x, lo.y, lo.z, lo.w, hi.x, hi.y, hi.z, hi.w}};
          av[r][k >> 1] = (k & 1) ? add_row(av[r][k >> 1], v) : v;
        }
      }
      #pragma unroll
      for (int r = 0; r < 2; r++) {
        x1[r] = fma_row(ga, add_row(av[r][0], av[r][1]), x1[r]);
        #pragma unroll
        for (int i = 0; i < 16; i++) { const float v = row_at(x1[r], i); st[3*r] += v; st[3*r+1] = fmaf(v, v, st[3*r+1]); st[3*r+2] = fmaf(v, u[i], st[3*r+2]); }
      }
      warp_sums(st);
      #pragma unroll
      for (int r = 0; r < 2; r++) {
        ln_stats(st[3*r], st[3*r+1]);
        const uint32_t rb = __float_as_uint(fmaf(st[3*r+1], fmaf(-st[3*r], ub[0], st[3*r+2]), ub[1]));
        key[r] = (((rb & 0x80000000u) ? ~rb : (rb | 0x80000000u)) & 0xfffff000u) | (0xfffu - (uint32_t)(row0 + r));
      }
    }
    float* s_red = reinterpret_cast<float*>(smem_raw + SM_RED);
    uint32_t* s_key = reinterpret_cast<uint32_t*>(smem_raw + SM_KEY);
    const int rb = key[1] > key[0];
    const uint32_t wbest = rb ? key[1] : key[0];
    if (lane == 0) s_key[cw] = wbest;
    bar_sync(5, 256);
    const uint32_t cbest = __reduce_max_sync(0xffffffff, s_key[lane & 7]);
    if (wbest == cbest && lane == 0) st_tagged(&g_x.keys[grp][0], cbest, tag);
    Row xb, xo;
    #pragma unroll
    for (int i = 0; i < 8; i++) { xb.v[i] = rb ? x1[1].v[i] : x1[0].v[i]; xo.v[i] = rb ? x1[0].v[i] : x1[1].v[i]; }
    const Row hb = fma_row(ln_apply(xb, rb ? st[3] : st[0], rb ? st[4] : st[1]), cb1, sb);
    if (wbest == cbest) {
      #pragma unroll
      for (int i = 0; i < 4; i++) st_tagged2(&g_x.row[grp][0][i * 64 + lane * 2], hb.v[2*i], hb.v[2*i+1], tag);
      #pragma unroll
      for (int i = 0; i < 4; i++) st_tagged2(&g_x.row[grp][1][i * 64 + lane * 2], xb.v[2*i], xb.v[2*i+1], tag);
    }
    const Row ob = fma_row(gb, hb, xb);
    if (wbest != cbest) store_row(out + (size_t)(row0 + rb) * DM, lane, ob);
    store_row(out + (size_t)(row0 + 1 - rb) * DM, lane, fma_row(gb, fma_row(ln_apply(xo, rb ? st[0] : st[3], rb ? st[1] : st[4]), cb1, sb), xo));
    mbar_wait(bars + R_KEY, 1);
    if (moe_cta) {
      float cg[4] = {0, 0, 0, 0}, cu[4] = {0, 0, 0, 0};
      #pragma unroll
      for (int r = 0; r < 4; r++) {
        const uint32_t b0 = lds_u32(base + SM_H2 + (cw * 64 + r * 16) * 2 + (lane & 3) * 4), b1 = lds_u32(base + SM_H2 + (cw * 64 + r * 16) * 2 + 16 + (lane & 3) * 4);
        mma16816(cg, wgv[r], b0, b1); mma16816(cu, wuv[r], b0, b1);
      }
      s_red[cw * 32 + (lane & 3) * 8 + (lane >> 2)] = (lane & 2) ? ((lane & 1) ? cu[2] : cu[0]) : ((lane & 1) ? cg[2] : cg[0]);
      bar_sync(5, 256);
      float g = 0.f;
      #pragma unroll
      for (int i = 0; i < 8; i++) g += s_red[i * 32 + lane];
      g = rbf(g);
      const float act = rbf(__fdividef(g, 1.f + __expf(-g))) * __shfl_down_sync(0xffffffff, g, 16);
      const uint32_t a2 = pack_bf16(act, __shfl_down_sync(0xffffffff, act, 1));
      const uint32_t b0 = __shfl_sync(0xffffffff, a2, (lane & 3) * 2), b1 = __shfl_sync(0xffffffff, a2, (lane & 3) * 2 + 8);
      float y0 = 0.f, y1 = 0.f;
      #pragma unroll
      for (int r = 0; r < 4; r++) {
        float c[4] = {0, 0, 0, 0};
        mma16816(c, wdv[r], b0, b1);
        if ((lane & 3) == r) { y0 = c[0]; y1 = c[2]; }
      }
      st_tagged2(yp, __float_as_uint(y0), __float_as_uint(y1), tag);
    }
    bar_arrive(9, 384);
    if (wbest == cbest && wbest != s_key[8]) store_row(out + (size_t)(row0 + rb) * DM, lane, ob);
    __syncwarp();
    cluster_wait();
  }
}

typedef CUresult (*EncodeFn)(CUtensorMap*, CUtensorMapDataType, cuuint32_t, void*, const cuuint64_t*, const cuuint64_t*, const cuuint32_t*,
                             const cuuint32_t*, CUtensorMapInterleave, CUtensorMapSwizzle, CUtensorMapL2promotion, CUtensorMapFloatOOBfill);

struct HostState {
  bool ready = false;
  EncodeFn encode = nullptr;
  CUtensorMap tmC, tmWq, tmWk, tmWv, tmWo, tmWg, tmWu, tmWm;
  Sched sched;
};

void make_map(EncodeFn enc, CUtensorMap* m, const void* ptr, int rank, const cuuint64_t* dims, const cuuint64_t* strides, const cuuint32_t* box, bool swizzle = true) {
  const cuuint32_t es[3] = {1, 1, 1};
  enc(m, CU_TENSOR_MAP_DATA_TYPE_BFLOAT16, rank, const_cast<void*>(ptr), dims, strides, box, es, CU_TENSOR_MAP_INTERLEAVE_NONE,
      swizzle ? CU_TENSOR_MAP_SWIZZLE_128B : CU_TENSOR_MAP_SWIZZLE_NONE, swizzle ? CU_TENSOR_MAP_L2_PROMOTION_L2_128B : CU_TENSOR_MAP_L2_PROMOTION_NONE, CU_TENSOR_MAP_FLOAT_OOB_FILL_NONE);
}
void make_2d(EncodeFn enc, CUtensorMap* m, const void* ptr, int rows, int cols, int box_rows) {
  const cuuint64_t dims[2] = {(cuuint64_t)cols, (cuuint64_t)rows}, strides[1] = {(cuuint64_t)cols * 2};
  const cuuint32_t box[2] = {64, (cuuint32_t)box_rows};
  make_map(enc, m, ptr, 2, dims, strides, box);
}
void make_3d(EncodeFn enc, CUtensorMap* m, const void* ptr, int rows, int chunks, size_t row_stride, size_t chunk_stride) {
  const cuuint64_t dims[3] = {64, (cuuint64_t)rows, (cuuint64_t)chunks}, strides[2] = {row_stride, chunk_stride};
  const cuuint32_t box[3] = {64, 64, 2};
  make_map(enc, m, ptr, 3, dims, strides, box);
}

void make_ffn(EncodeFn enc, CUtensorMap* m, const void* ptr) {
  const cuuint64_t dims[2] = {(cuuint64_t)FF, (cuuint64_t)DM}, strides[1] = {(cuuint64_t)FF * 2};
  const cuuint32_t box[2] = {16, 256};
  make_map(enc, m, ptr, 2, dims, strides, box, false);
}

#define SR 0x213312
#define SEED 12345
#define LU_MARGIN 0
#define SPARE_N 3
void build_sched(Sched& s) {
  memset(&s, 0, sizeof(s));
  const int NP = NCTA / 2, korder[4] = {(KORDER >> 12) & 3, (KORDER >> 8) & 3, (KORDER >> 4) & 3, KORDER & 3};
  const int sround[4][2][3] = {{}, {{1}, {2}}, {{1, 2}, {1, 2}}, {{(SR >> 20) & 3, (SR >> 16) & 3, (SR >> 12) & 3}, {(SR >> 8) & 3, (SR >> 4) & 3, SR & 3}}};
  int jv[4][NP], used[4][8] = {};
  for (int r = 0; r < 4; r++) for (int p = 0; p < NP; p++) jv[r][p] = (r & 2) ? 7 - ((p + 4 * (r & 1)) & 7) : (p + 4 * (r & 1)) & 7;
  for (int q = 0; q < 2; q++) {
    s.pair[NP + q].nitems = SPARE_N;
    for (int i = 0; i < SPARE_N; i++) {
      const int r = sround[SPARE_N][q][i];
      s.pair[NP + q].item[i] = (uint8_t)((r * 8 + used[r][6]++) * 8 + 6);
      for (int p = 0; p < NP; p++) if (jv[r][p] == 6) { jv[r][p] = -2; break; }
    }
  }
  auto cost = [&](int p) {
    int u = 8 - ((p >> 4) < SPARE_N ? 21 : 22), z = 0, none = 0;
    for (int r = 0; r < 4; r++) { u += jv[r][p]; z += jv[r][p] == 0; none += jv[r][p] < 0; }
    return 4 * u * u + (z > 1) + 4 * (none > 1);
  };
  uint32_t rng = SEED;
  for (int it = 0; it < 2000000; it++) {
    if ((it & 255) == 0) { int t = 0; for (int p = 0; p < NP; p++) t += cost(p); if (t == 0) break; }
    rng = rng * 1664525u + 1013904223u;
    const int r = (rng >> 8) & 3, a = (rng >> 12) & 63, b = (rng >> 20) & 63, before = cost(a) + cost(b);
    int t = jv[r][a]; jv[r][a] = jv[r][b]; jv[r][b] = t;
    if (cost(a) + cost(b) > before) { jv[r][b] = jv[r][a]; jv[r][a] = t; }
  }
  int fin[256], done[256];
  for (int p = 0; p < NP + 2; p++) {
    Sched::Pair& q = s.pair[p];
    if (p < NP) {
      for (int k = 0; k < 4; k++) q.khead[k] = (uint8_t)(korder[k] * 8 + (p >> 3));
      for (int r = 0; r < 4; r++) {
        if (jv[r][p] < 0) continue;
        q.item[q.nitems++] = (uint8_t)((r * 8 + used[r][jv[r][p]]++) * 8 + jv[r][p]);
      }
    }
    int t = p < NP ? 0 : -3, e = 1;
    for (int i = 0; i < q.nitems; i++) { t += (q.item[i] & 7) + 2; fin[q.item[i]] = t; done[q.item[i]] = t + (i + 1 < q.nitems ? 2 : 0); e += 8 + 4 * ((q.item[i] & 7) + 1); }
    for (int k = 0; k < 3 * MAX_STEPS + 6; k++) {
      const int n = k > 0 ? k - (SPARE_N & 1) : 0, r = n % 7, f = (e + (r < 4 ? r : r - 1)) % 12;
      q.oent[k] = (uint8_t)((r == 4 ? 6 : f >= 6 ? f + 2 : f) ^ (((n / 7) & 1) << 3));
    }
  }
  for (int p = 0; p < NP + 2; p++)
    for (int i = 0; i < s.pair[p].nitems; i++) {
      const int it = s.pair[p].item[i];
      for (int n = 0; n < 2 * (it & 7) + 2; n++) {
        bool last = true;
        for (int j = n >> 1; j < 8; j++) { const int o = (it & ~7) + j; if (o != it && fin[o] + LU_MARGIN > fin[it]) last = false; }
        if (last) s.pair[p].lastuse[i] |= (uint16_t)(1 << n);
      }
    }
  for (int j = 0; j < 8; j++) {
    int order[NH], left[4];
    for (int h = 0; h < NH; h++) { int k = h; for (; k > 0 && done[order[k - 1] * 8 + j] < done[h * 8 + j]; k--) order[k] = order[k - 1]; order[k] = h; }
    for (int kq = 0; kq < 4; kq++) {
      left[kq] = SPARE_N == 0 ? 16 : kq < SPARE_N ? 20 - SPARE_N : 16 - SPARE_N;
      for (int nh = 0; nh < 2; nh++) { Sched::Pair& q = s.pair[kq * 16 + nh * 8 + j]; q.otask = (uint8_t)(kq * 16 + nh * 8 + j); q.nsteps = (uint8_t)((left[kq] + 1) / 2); q.ochunk[0][0] = 255; }
    }
    for (int n = 0, kq = 0, run = 0; n < 64; ) {
      if (left[kq] > 0 && run < 2) {
        const int pos = --left[kq] + (SPARE_N & 1);
        for (int nh = 0; nh < 2; nh++) s.pair[kq * 16 + nh * 8 + j].ochunk[pos >> 1][pos & 1] = (uint8_t)(order[n >> 1] * 2 + 1 - (n & 1));
        n++; run++;
      } else { kq = (kq + 1) & 3; run = 0; }
    }
  }
}

}

extern "C" void kernel_launch(void* const* d_in, const int* in_sizes, int n_in, void* d_out, int out_size) {
  (void)in_sizes; (void)n_in; (void)out_size;
  const __nv_bfloat16* x     = (const __nv_bfloat16*)d_in[0];
  const __nv_bfloat16* ckv   = (const __nv_bfloat16*)d_in[1];
  const __nv_bfloat16* w_q   = (const __nv_bfloat16*)d_in[2];
  const __nv_bfloat16* w_uk  = (const __nv_bfloat16*)d_in[3];
  const __nv_bfloat16* w_uv  = (const __nv_bfloat16*)d_in[4];
  const __nv_bfloat16* w_o   = (const __nv_bfloat16*)d_in[5];
  const __nv_bfloat16* w_r   = (const __nv_bfloat16*)d_in[7];
  const __nv_bfloat16* w_g   = (const __nv_bfloat16*)d_in[8];
  const __nv_bfloat16* w_u   = (const __nv_bfloat16*)d_in[9];
  const __nv_bfloat16* w_d   = (const __nv_bfloat16*)d_in[10];
  const __nv_bfloat16* cvec  = (const __nv_bfloat16*)d_in[11];
  const __nv_bfloat16* w_mod = (const __nv_bfloat16*)d_in[12];
  __nv_bfloat16* out = (__nv_bfloat16*)d_out;

  static HostState st;
  if (!st.ready) {
    void* fn = nullptr; cudaDriverEntryPointQueryResult qr;
    cudaGetDriverEntryPoint("cuTensorMapEncodeTiled", &fn, cudaEnableDefault, &qr);
    st.encode = (EncodeFn)fn;
    cudaFuncSetAttribute(k_fused, cudaFuncAttributeMaxDynamicSharedMemorySize, SMEM);
    build_sched(st.sched);
    void *p_kvc, *p_h1, *p_part;
    cudaGetSymbolAddress(&p_kvc, g_kvc); cudaGetSymbolAddress(&p_h1, g_h1); cudaGetSymbolAddress(&p_part, g_part);
    st.sched.kvc = (__nv_bfloat16*)p_kvc; st.sched.h1 = (__nv_bfloat16*)p_h1; st.sched.part = (__nv_bfloat16*)p_part;
    st.ready = true;
  }
  make_2d(st.encode, &st.tmC, ckv, SEQ, DM, 128);
  make_2d(st.encode, &st.tmWq, w_q, DM, NH * DH, 64);
  make_2d(st.encode, &st.tmWk, w_uk, DM, NH * DH, 64);
  make_2d(st.encode, &st.tmWv, w_uv, DM, NH * DH, 64);
  make_3d(st.encode, &st.tmWo, w_o, NH * DH, DM / 64, (size_t)DM * 2, 128);
  make_3d(st.encode, &st.tmWm, w_mod, DM, 6 * DM / 64, (size_t)6 * DM * 2, 128);
  make_ffn(st.encode, &st.tmWg, w_g);
  make_ffn(st.encode, &st.tmWu, w_u);

  k_fused<<<NGRID, 384, SMEM, cudaStreamPerThread>>>(st.tmC, st.tmWq, st.tmWk, st.tmWv, st.tmWo, st.tmWg, st.tmWu, st.tmWm, st.sched,
                                                     x, cvec, w_o, w_r, w_g, w_u, w_d, out);
}
```

```cpp
#include <cuda_runtime.h>
#include <cuda_bf16.h>
#include <cuda.h>
#include <stdint.h>
#include <string.h>
#include <math.h>

namespace {

constexpr int SEQ = 2048, DM = 512, NH = 32, DH = 128, FF = 1792;
constexpr int NCTA = 128, NGRID = 132;

__device__ __align__(128) __nv_bfloat16 g_kvc[192 * SEQ * 64];
__device__ __align__(128) __nv_bfloat16 g_h1[SEQ * DM];
__device__ __align__(128) __nv_bfloat16 g_part[128 * 8 * 4096];
constexpr int C_MOD = 0, C_MOD2 = 16, C_H1 = 32, C_KV = 64, C_CTX = 128, C_PART = 384, C_END = C_PART + 32 * 32;
struct Exchange {
  uint2 keys[128][4];
  uint2 row[128][2][DM / 2];
  uint2 yll[FF / 16][DM];
  __nv_bfloat16 mod[6 * DM];
  unsigned int cnt[C_END];
  unsigned int epoch;
};
__device__ __align__(4096) Exchange g_x;


__device__ __forceinline__ uint32_t smem_u32(const void* p) { return (uint32_t)__cvta_generic_to_shared(p); }
__device__ __forceinline__ int wg_tid() { int t; asm volatile("mov.u32 %0, %%tid.x;" : "=r"(t)); return t & 127; }
__device__ __forceinline__ void mbar_arrive(uint32_t bar) { asm volatile("mbarrier.arrive.shared::cta.b64 _, [%0];" :: "r"(bar) : "memory"); }
__device__ __forceinline__ uint32_t mapa(uint32_t addr, uint32_t cta) { uint32_t r; asm("mapa.shared::cluster.u32 %0, %1, %2;" : "=r"(r) : "r"(addr), "r"(cta)); return r; }
__device__ __forceinline__ void mbar_arrive_remote_if(uint32_t cluster_addr, bool pred) {
  asm volatile("{\n.reg .pred p;\nsetp.ne.u32 p, %1, 0;\n@p mbarrier.arrive.shared::cluster.b64 _, [%0];\n}" :: "r"(cluster_addr), "r"((uint32_t)pred) : "memory");
}
__device__ __forceinline__ bool mbar_try(uint32_t bar, uint32_t parity) {
  uint32_t done;
  asm volatile("{\n.reg .pred p;\nmbarrier.try_wait.parity.shared::cta.b64 p, [%1], %2;\nselp.u32 %0, 1, 0, p;\n}" : "=r"(done) : "r"(bar), "r"(parity) : "memory");
  return done;
}
__device__ __forceinline__ bool mbar_test2(uint32_t bar, uint32_t parity) {
  uint32_t done;
  asm volatile("{\n.reg .pred p, q;\nmbarrier.test_wait.parity.shared::cta.b64 p, [%1], %2;\nmbarrier.test_wait.parity.shared::cta.b64 q, [%1 + 8], %2;\n"
               "and.pred p, p, q;\nselp.u32 %0, 1, 0, p;\n}" : "=r"(done) : "r"(bar), "r"(parity) : "memory");
  return done;
}
#define WAIT_LIM (1 << 14)
__device__ __forceinline__ void mbar_wait(uint32_t bar, uint32_t parity) {
  #pragma unroll 1
  for (int n = 0; n < WAIT_LIM; n++) { if (mbar_try(bar, parity)) break; }
}
__device__ __forceinline__ unsigned int ld_acquire(const unsigned int* p) {
  unsigned int v; asm volatile("ld.acquire.gpu.global.u32 %0, [%1];" : "=r"(v) : "l"(p) : "memory"); return v;
}
__device__ __forceinline__ unsigned int ld_relaxed(const unsigned int* p) {
  unsigned int v; asm volatile("ld.relaxed.gpu.global.u32 %0, [%1];" : "=r"(v) : "l"(p) : "memory"); return v;
}
__device__ __forceinline__ void wait_count_lazy(int idx, unsigned int target) {
  #pragma unroll 1
  for (int n = 0; n < WAIT_LIM; n++) { if (__all_sync(0xffffffff, (int)(ld_relaxed(&g_x.cnt[idx]) - target) >= 0)) break; __nanosleep(100); }
  ld_acquire(&g_x.cnt[idx]);
}
__device__ __forceinline__ uint4 ld_tagged2(const void* p) {
  uint4 v;
  asm volatile("{\n.reg .b64 a, b;\nld.relaxed.gpu.global.v2.u64 {a, b}, [%4];\nmov.b64 {%0, %1}, a;\nmov.b64 {%2, %3}, b;\n}"
    : "=r"(v.x), "=r"(v.y), "=r"(v.z), "=r"(v.w) : "l"(p) : "memory");
  return v;
}
__device__ __forceinline__ uint2 ld_tagged(const void* p) {
  uint2 v; asm volatile("{\n.reg .b64 a;\nld.relaxed.gpu.global.u64 a, [%2];\nmov.b64 {%0, %1}, a;\n}" : "=r"(v.x), "=r"(v.y) : "l"(p) : "memory"); return v;
}
__device__ __forceinline__ void st_tagged2(void* p, uint32_t a, uint32_t b, uint32_t tag) {
  asm volatile("{\n.reg .b64 a, b;\nmov.b64 a, {%1, %3};\nmov.b64 b, {%2, %3};\nst.relaxed.gpu.global.v2.u64 [%0], {a, b};\n}" :: "l"(p), "r"(a), "r"(b), "r"(tag) : "memory");
}
__device__ __forceinline__ void st_tagged(void* p, uint32_t a, uint32_t tag) {
  asm volatile("{\n.reg .b64 a;\nmov.b64 a, {%1, %2};\nst.relaxed.gpu.global.u64 [%0], a;\n}" :: "l"(p), "r"(a), "r"(tag) : "memory");
}
__device__ __forceinline__ void stg_v4(void* p, uint32_t a, uint32_t b, uint32_t c, uint32_t d) {
  asm volatile("st.global.v4.u32 [%0], {%1, %2, %3, %4};" :: "l"(p), "r"(a), "r"(b), "r"(c), "r"(d) : "memory");
}
__device__ __forceinline__ uint4 lds_v4(uint32_t addr) {
  uint4 v; asm volatile("ld.shared.v4.u32 {%0, %1, %2, %3}, [%4];" : "=r"(v.x), "=r"(v.y), "=r"(v.z), "=r"(v.w) : "r"(addr) : "memory"); return v;
}
__device__ __forceinline__ uint32_t lds_u32(uint32_t addr) { uint32_t v; asm volatile("ld.shared.u32 %0, [%1];" : "=r"(v) : "r"(addr) : "memory"); return v; }
__device__ __forceinline__ void sts_v4(uint32_t addr, uint32_t a, uint32_t b, uint32_t c, uint32_t d) {
  asm volatile("st.shared.v4.u32 [%0], {%1, %2, %3, %4};" :: "r"(addr), "r"(a), "r"(b), "r"(c), "r"(d) : "memory");
}
#define ELECT "{\n.reg .pred p;\nelect.sync _|p, 0xffffffff;\n@p "
__device__ __forceinline__ void w_mbar_init(uint32_t bar, uint32_t cnt) { asm volatile(ELECT "mbarrier.init.shared::cta.b64 [%0], %1;\n}" :: "r"(bar), "r"(cnt) : "memory"); }
__device__ __forceinline__ void w_expect_tx(uint32_t bar, uint32_t bytes) { asm volatile(ELECT "mbarrier.arrive.expect_tx.shared::cta.b64 _, [%0], %1;\n}" :: "r"(bar), "r"(bytes) : "memory"); }
__device__ __forceinline__ void w_arrive(uint32_t bar) { asm volatile(ELECT "mbarrier.arrive.shared::cta.b64 _, [%0];\n}" :: "r"(bar) : "memory"); }
__device__ __forceinline__ void tma_load_2d(uint32_t dst, const CUtensorMap* tm, uint32_t bar, int c0, int c1) {
  asm volatile(ELECT "cp.async.bulk.tensor.2d.shared::cluster.global.mbarrier::complete_tx::bytes [%0], [%1, {%3, %4}], [%2];\n}"
    :: "r"(dst), "l"(tm), "r"(bar), "r"(c0), "r"(c1) : "memory");
}
__device__ __forceinline__ void tma_load_2d_mc(uint32_t dst, const CUtensorMap* tm, uint32_t bar, int c0, int c1) {
  asm volatile(ELECT "cp.async.bulk.tensor.2d.shared::cluster.global.mbarrier::complete_tx::bytes.multicast::cluster [%0], [%1, {%3, %4}], [%2], %5;\n}"
    :: "r"(dst), "l"(tm), "r"(bar), "r"(c0), "r"(c1), "h"((uint16_t)3) : "memory");
}
__device__ __forceinline__ void tma_load_3d(uint32_t dst, const CUtensorMap* tm, uint32_t bar, int c0, int c1, int c2) {
  asm volatile(ELECT "cp.async.bulk.tensor.3d.shared::cluster.global.mbarrier::complete_tx::bytes [%0], [%1, {%3, %4, %5}], [%2];\n}"
    :: "r"(dst), "l"(tm), "r"(bar), "r"(c0), "r"(c1), "r"(c2) : "memory");
}
__device__ __forceinline__ void tma_load_3d_mc(uint32_t dst, const CUtensorMap* tm, uint32_t bar, int c0, int c1, int c2) {
  asm volatile(ELECT "cp.async.bulk.tensor.3d.shared::cluster.global.mbarrier::complete_tx::bytes.multicast::cluster [%0], [%1, {%3, %4, %5}], [%2], %6;\n}"
    :: "r"(dst), "l"(tm), "r"(bar), "r"(c0), "r"(c1), "r"(c2), "h"((uint16_t)3) : "memory");
}
__device__ __forceinline__ void bulk_load_mc(uint32_t dst, const void* src, uint32_t bar, bool ef) {
  if (ef) {
    uint64_t pol; asm("createpolicy.fractional.L2::evict_first.b64 %0, 1.0;" : "=l"(pol));
    asm volatile(ELECT "cp.async.bulk.shared::cluster.global.mbarrier::complete_tx::bytes.multicast::cluster.L2::cache_hint [%0], [%1], 16384, [%2], %3, %4;\n}"
      :: "r"(dst), "l"(src), "r"(bar), "h"((uint16_t)3), "l"(pol) : "memory");
  } else
    asm volatile(ELECT "cp.async.bulk.shared::cluster.global.mbarrier::complete_tx::bytes.multicast::cluster [%0], [%1], 16384, [%2], %3;\n}"
      :: "r"(dst), "l"(src), "r"(bar), "h"((uint16_t)3) : "memory");
}
__device__ __forceinline__ void bulk_load(uint32_t dst, const void* src, uint32_t bytes, uint32_t bar) {
  asm volatile(ELECT "cp.async.bulk.shared::cluster.global.mbarrier::complete_tx::bytes [%0], [%1], %2, [%3];\n}" :: "r"(dst), "l"(src), "r"(bytes), "r"(bar) : "memory");
}
__device__ __forceinline__ void tma_prefetch_2d(const CUtensorMap* tm, int c0, int c1) {
  asm volatile(ELECT "cp.async.bulk.prefetch.tensor.2d.L2.global [%0, {%1, %2}];\n}" :: "l"(tm), "r"(c0), "r"(c1) : "memory");
}
__device__ __forceinline__ void bulk_prefetch(const void* p, uint32_t bytes) {
  asm volatile(ELECT "cp.async.bulk.prefetch.L2.global [%0], %1;\n}" :: "l"(p), "r"(bytes) : "memory");
}
__device__ __forceinline__ void red_release(int idx) { asm volatile("red.release.gpu.global.add.u32 [%0], 1;" :: "l"(&g_x.cnt[idx]) : "memory"); }
__device__ __forceinline__ void prefetch_tmap(const CUtensorMap* tm) { asm volatile("prefetch.tensormap [%0];" :: "l"(tm) : "memory"); }
__device__ __forceinline__ void bar_sync(int id, int n) { asm volatile("bar.sync %0, %1;" :: "r"(id), "r"(n) : "memory"); }
__device__ __forceinline__ void bar_arrive(int id, int n) { asm volatile("bar.arrive %0, %1;" :: "r"(id), "r"(n) : "memory"); }
__device__ __forceinline__ void fence_async_smem() { asm volatile("fence.proxy.async.shared::cta;" ::: "memory"); }
__device__ __forceinline__ void fence_async_global() { asm volatile("fence.proxy.async.global;" ::: "memory"); }
__device__ __forceinline__ void fence_mbar_init() { asm volatile("fence.mbarrier_init.release.cluster;" ::: "memory"); }
__device__ __forceinline__ void cluster_arrive() { asm volatile("barrier.cluster.arrive.relaxed.aligned;" ::: "memory"); }
__device__ __forceinline__ void cluster_wait() { asm volatile("barrier.cluster.wait.aligned;" ::: "memory"); }
__device__ __forceinline__ uint32_t cluster_ctarank() { uint32_t r; asm volatile("mov.u32 %0, %%cluster_ctarank;" : "=r"(r)); return r; }
__device__ __forceinline__ void wgmma_fence() { asm volatile("wgmma.fence.sync.aligned;" ::: "memory"); }
__device__ __forceinline__ void wgmma_commit() { asm volatile("wgmma.commit_group.sync.aligned;" ::: "memory"); }
template<int N> __device__ __forceinline__ void wgmma_wait() { asm volatile("wgmma.wait_group.sync.aligned %0;" :: "n"(N) : "memory"); }
__device__ __forceinline__ float ex2(float x) { float y; asm("ex2.approx.ftz.f32 %0, %1;" : "=f"(y) : "f"(x)); return y; }
__device__ __forceinline__ float rcp_fast(float x) { float y; asm("rcp.approx.ftz.f32 %0, %1;" : "=f"(y) : "f"(x)); return y; }
__device__ __forceinline__ uint32_t pack_bf16(float lo, float hi) { uint32_t r; asm("cvt.rn.bf16x2.f32 %0, %1, %2;" : "=r"(r) : "f"(hi), "f"(lo)); return r; }
__device__ __forceinline__ float rbf(float x) { return __uint_as_float(pack_bf16(0.f, x)); }
__device__ __forceinline__ float bf_lo(uint32_t v) { return __uint_as_float(v << 16); }
__device__ __forceinline__ float bf_hi(uint32_t v) { return __uint_as_float(v & 0xffff0000u); }
__device__ __forceinline__ uint32_t add2(uint32_t a, uint32_t b) { uint32_t r; asm("add.rn.bf16x2 %0, %1, %2;" : "=r"(r) : "r"(a), "r"(b)); return r; }
__device__ __forceinline__ uint32_t fma2(uint32_t a, uint32_t b, uint32_t c) { uint32_t r; asm("fma.rn.bf16x2 %0, %1, %2, %3;" : "=r"(r) : "r"(a), "r"(b), "r"(c)); return r; }
__device__ __forceinline__ uint4 ldsm_x4_t(uint32_t addr) {
  uint4 v; asm volatile("ldmatrix.sync.aligned.m8n8.x4.trans.shared.b16 {%0, %1, %2, %3}, [%4];" : "=r"(v.x), "=r"(v.y), "=r"(v.z), "=r"(v.w) : "r"(addr) : "memory"); return v;
}
__device__ __forceinline__ uint4 ldsm_x4(uint32_t addr) {
  uint4 v; asm volatile("ldmatrix.sync.aligned.m8n8.x4.shared.b16 {%0, %1, %2, %3}, [%4];" : "=r"(v.x), "=r"(v.y), "=r"(v.z), "=r"(v.w) : "r"(addr) : "memory"); return v;
}
__device__ __forceinline__ void mma16816(float (&c)[4], const uint4& a, uint32_t b0, uint32_t b1) {
  asm("mma.sync.aligned.m16n8k16.row.col.f32.bf16.bf16.f32 {%0, %1, %2, %3}, {%4, %5, %6, %7}, {%8, %9}, {%0, %1, %2, %3};"
    : "+f"(c[0]), "+f"(c[1]), "+f"(c[2]), "+f"(c[3]) : "r"(a.x), "r"(a.y), "r"(a.z), "r"(a.w), "r"(b0), "r"(b1));
}
template<int N> __device__ __forceinline__ void fence_regs(float (&a)[N]) {
  #pragma unroll
  for (int i = 0; i < N; i++) asm volatile("" : "+f"(a[i]) :: "memory");
}
template<int N> __device__ __forceinline__ void fence_regs_u(uint32_t (&a)[N]) {
  #pragma unroll
  for (int i = 0; i < N; i++) asm volatile("" : "+r"(a[i]) :: "memory");
}
constexpr uint32_t SW128 = 0x40000040u, SW64 = 0x80000020u;
__device__ __forceinline__ uint32_t desc_lo(uint32_t addr, uint32_t lbo) { return ((addr & 0x3FFFF) >> 4) | ((lbo >> 4) << 16); }

template<int TB, int OA, int OB, uint32_t HA, uint32_t HB> __device__ __forceinline__ void wgmma_ss_n128(float (&d)[64], uint32_t da, uint32_t db, int sd) {
  asm volatile("{\n.reg .pred p;\n.reg .b32 ta, tb;\n.reg .b64 da, db;\nsetp.ne.b32 p, %66, 0;\nadd.u32 ta, %64, %68;\nadd.u32 tb, %65, %69;\nmov.b64 da, {ta, %70};\nmov.b64 db, {tb, %71};\n"
    "wgmma.mma_async.sync.aligned.m64n128k16.f32.bf16.bf16 "
    "{%0, %1, %2, %3, %4, %5, %6, %7, %8, %9, %10, %11, %12, %13, %14, %15, %16, %17, %18, %19, %20, %21, %22, %23, %24, %25, %26, %27, %28, %29, %30, %31, %32, %33, %34, %35, %36, %37, %38, %39, %40, %41, %42, %43, %44, %45, %46, %47, %48, %49, %50, %51, %52, %53, %54, %55, %56, %57, %58, %59, %60, %61, %62, %63}, da, db, p, 1, 1, 0, %67;\n}\n"
    : "+f"(d[0]), "+f"(d[1]), "+f"(d[2]), "+f"(d[3]), "+f"(d[4]), "+f"(d[5]), "+f"(d[6]), "+f"(d[7]), "+f"(d[8]), "+f"(d[9]), "+f"(d[10]), "+f"(d[11]), "+f"(d[12]), "+f"(d[13]), "+f"(d[14]), "+f"(d[15]), "+f"(d[16]), "+f"(d[17]), "+f"(d[18]), "+f"(d[19]), "+f"(d[20]), "+f"(d[21]), "+f"(d[22]), "+f"(d[23]), "+f"(d[24]), "+f"(d[25]), "+f"(d[26]), "+f"(d[27]), "+f"(d[28]), "+f"(d[29]), "+f"(d[30]), "+f"(d[31]), "+f"(d[32]), "+f"(d[33]), "+f"(d[34]), "+f"(d[35]), "+f"(d[36]), "+f"(d[37]), "+f"(d[38]), "+f"(d[39]), "+f"(d[40]), "+f"(d[41]), "+f"(d[42]), "+f"(d[43]), "+f"(d[44]), "+f"(d[45]), "+f"(d[46]), "+f"(d[47]), "+f"(d[48]), "+f"(d[49]), "+f"(d[50]), "+f"(d[51]), "+f"(d[52]), "+f"(d[53]), "+f"(d[54]), "+f"(d[55]), "+f"(d[56]), "+f"(d[57]), "+f"(d[58]), "+f"(d[59]), "+f"(d[60]), "+f"(d[61]), "+f"(d[62]), "+f"(d[63])
    : "r"(da), "r"(db), "r"(sd), "n"(TB), "n"(OA), "n"(OB), "n"(HA), "n"(HB));
}
template<int TB, int OB, uint32_t HB> __device__ __forceinline__ void wgmma_rs_n128(float (&d)[64], uint32_t a0, uint32_t a1, uint32_t a2, uint32_t a3, uint32_t db, int sd) {
  asm volatile("{\n.reg .pred p;\n.reg .b32 tb;\n.reg .b64 db;\nsetp.ne.b32 p, %69, 0;\nadd.u32 tb, %68, %71;\nmov.b64 db, {tb, %72};\n"
    "wgmma.mma_async.sync.aligned.m64n128k16.f32.bf16.bf16 "
    "{%0, %1, %2, %3, %4, %5, %6, %7, %8, %9, %10, %11, %12, %13, %14, %15, %16, %17, %18, %19, %20, %21, %22, %23, %24, %25, %26, %27, %28, %29, %30, %31, %32, %33, %34, %35, %36, %37, %38, %39, %40, %41, %42, %43, %44, %45, %46, %47, %48, %49, %50, %51, %52, %53, %54, %55, %56, %57, %58, %59, %60, %61, %62, %63}, {%64,%65,%66,%67}, db, p, 1, 1, %70;\n}\n"
    : "+f"(d[0]), "+f"(d[1]), "+f"(d[2]), "+f"(d[3]), "+f"(d[4]), "+f"(d[5]), "+f"(d[6]), "+f"(d[7]), "+f"(d[8]), "+f"(d[9]), "+f"(d[10]), "+f"(d[11]), "+f"(d[12]), "+f"(d[13]), "+f"(d[14]), "+f"(d[15]), "+f"(d[16]), "+f"(d[17]), "+f"(d[18]), "+f"(d[19]), "+f"(d[20]), "+f"(d[21]), "+f"(d[22]), "+f"(d[23]), "+f"(d[24]), "+f"(d[25]), "+f"(d[26]), "+f"(d[27]), "+f"(d[28]), "+f"(d[29]), "+f"(d[30]), "+f"(d[31]), "+f"(d[32]), "+f"(d[33]), "+f"(d[34]), "+f"(d[35]), "+f"(d[36]), "+f"(d[37]), "+f"(d[38]), "+f"(d[39]), "+f"(d[40]), "+f"(d[41]), "+f"(d[42]), "+f"(d[43]), "+f"(d[44]), "+f"(d[45]), "+f"(d[46]), "+f"(d[47]), "+f"(d[48]), "+f"(d[49]), "+f"(d[50]), "+f"(d[51]), "+f"(d[52]), "+f"(d[53]), "+f"(d[54]), "+f"(d[55]), "+f"(d[56]), "+f"(d[57]), "+f"(d[58]), "+f"(d[59]), "+f"(d[60]), "+f"(d[61]), "+f"(d[62]), "+f"(d[63])
    : "r"(a0), "r"(a1), "r"(a2), "r"(a3), "r"(db), "r"(sd), "n"(TB), "n"(OB), "n"(HB));
}
template<int TB, int OA, int OB, uint32_t HA, uint32_t HB> __device__ __forceinline__ void wgmma_ss_n64(float (&d)[32], uint32_t da, uint32_t db, int sd) {
  asm volatile("{\n.reg .pred p;\n.reg .b32 ta, tb;\n.reg .b64 da, db;\nsetp.ne.b32 p, %34, 0;\nadd.u32 ta, %32, %36;\nadd.u32 tb, %33, %37;\nmov.b64 da, {ta, %38};\nmov.b64 db, {tb, %39};\n"
    "wgmma.mma_async.sync.aligned.m64n64k16.f32.bf16.bf16 "
    "{%0, %1, %2, %3, %4, %5, %6, %7, %8, %9, %10, %11, %12, %13, %14, %15, %16, %17, %18, %19, %20, %21, %22, %23, %24, %25, %26, %27, %28, %29, %30, %31}, da, db, p, 1, 1, 0, %35;\n}\n"
    : "+f"(d[0]), "+f"(d[1]), "+f"(d[2]), "+f"(d[3]), "+f"(d[4]), "+f"(d[5]), "+f"(d[6]), "+f"(d[7]), "+f"(d[8]), "+f"(d[9]), "+f"(d[10]), "+f"(d[11]), "+f"(d[12]), "+f"(d[13]), "+f"(d[14]), "+f"(d[15]), "+f"(d[16]), "+f"(d[17]), "+f"(d[18]), "+f"(d[19]), "+f"(d[20]), "+f"(d[21]), "+f"(d[22]), "+f"(d[23]), "+f"(d[24]), "+f"(d[25]), "+f"(d[26]), "+f"(d[27]), "+f"(d[28]), "+f"(d[29]), "+f"(d[30]), "+f"(d[31])
    : "r"(da), "r"(db), "r"(sd), "n"(TB), "n"(OA), "n"(OB), "n"(HA), "n"(HB));
}
template<int TB, int OA, int OB, uint32_t HA, uint32_t HB> __device__ __forceinline__ void wgmma_ss_n128_new(float (&d)[64], uint32_t da, uint32_t db) {
  asm volatile("{\n.reg .pred p;\n.reg .b32 ta, tb;\n.reg .b64 da, db;\nsetp.ne.b32 p, %66, 0;\nadd.u32 ta, %64, %68;\nadd.u32 tb, %65, %69;\nmov.b64 da, {ta, %70};\nmov.b64 db, {tb, %71};\n"
    "wgmma.mma_async.sync.aligned.m64n128k16.f32.bf16.bf16 "
    "{%0, %1, %2, %3, %4, %5, %6, %7, %8, %9, %10, %11, %12, %13, %14, %15, %16, %17, %18, %19, %20, %21, %22, %23, %24, %25, %26, %27, %28, %29, %30, %31, %32, %33, %34, %35, %36, %37, %38, %39, %40, %41, %42, %43, %44, %45, %46, %47, %48, %49, %50, %51, %52, %53, %54, %55, %56, %57, %58, %59, %60, %61, %62, %63}, da, db, p, 1, 1, 0, %67;\n}\n"
    : "=f"(d[0]), "=f"(d[1]), "=f"(d[2]), "=f"(d[3]), "=f"(d[4]), "=f"(d[5]), "=f"(d[6]), "=f"(d[7]), "=f"(d[8]), "=f"(d[9]), "=f"(d[10]), "=f"(d[11]), "=f"(d[12]), "=f"(d[13]), "=f"(d[14]), "=f"(d[15]), "=f"(d[16]), "=f"(d[17]), "=f"(d[18]), "=f"(d[19]), "=f"(d[20]), "=f"(d[21]), "=f"(d[22]), "=f"(d[23]), "=f"(d[24]), "=f"(d[25]), "=f"(d[26]), "=f"(d[27]), "=f"(d[28]), "=f"(d[29]), "=f"(d[30]), "=f"(d[31]), "=f"(d[32]), "=f"(d[33]), "=f"(d[34]), "=f"(d[35]), "=f"(d[36]), "=f"(d[37]), "=f"(d[38]), "=f"(d[39]), "=f"(d[40]), "=f"(d[41]), "=f"(d[42]), "=f"(d[43]), "=f"(d[44]), "=f"(d[45]), "=f"(d[46]), "=f"(d[47]), "=f"(d[48]), "=f"(d[49]), "=f"(d[50]), "=f"(d[51]), "=f"(d[52]), "=f"(d[53]), "=f"(d[54]), "=f"(d[55]), "=f"(d[56]), "=f"(d[57]), "=f"(d[58]), "=f"(d[59]), "=f"(d[60]), "=f"(d[61]), "=f"(d[62]), "=f"(d[63])
    : "r"(da), "r"(db), "n"(0), "n"(TB), "n"(OA), "n"(OB), "n"(HA), "n"(HB));
}
template<int TB, int OA, int OB, uint32_t HA, uint32_t HB> __device__ __forceinline__ void wgmma_ss_n64_new(float (&d)[32], uint32_t da, uint32_t db) {
  asm volatile("{\n.reg .pred p;\n.reg .b32 ta, tb;\n.reg .b64 da, db;\nsetp.ne.b32 p, %34, 0;\nadd.u32 ta, %32, %36;\nadd.u32 tb, %33, %37;\nmov.b64 da, {ta, %38};\nmov.b64 db, {tb, %39};\n"
    "wgmma.mma_async.sync.aligned.m64n64k16.f32.bf16.bf16 "
    "{%0, %1, %2, %3, %4, %5, %6, %7, %8, %9, %10, %11, %12, %13, %14, %15, %16, %17, %18, %19, %20, %21, %22, %23, %24, %25, %26, %27, %28, %29, %30, %31}, da, db, p, 1, 1, 0, %35;\n}\n"
    : "=f"(d[0]), "=f"(d[1]), "=f"(d[2]), "=f"(d[3]), "=f"(d[4]), "=f"(d[5]), "=f"(d[6]), "=f"(d[7]), "=f"(d[8]), "=f"(d[9]), "=f"(d[10]), "=f"(d[11]), "=f"(d[12]), "=f"(d[13]), "=f"(d[14]), "=f"(d[15]), "=f"(d[16]), "=f"(d[17]), "=f"(d[18]), "=f"(d[19]), "=f"(d[20]), "=f"(d[21]), "=f"(d[22]), "=f"(d[23]), "=f"(d[24]), "=f"(d[25]), "=f"(d[26]), "=f"(d[27]), "=f"(d[28]), "=f"(d[29]), "=f"(d[30]), "=f"(d[31])
    : "r"(da), "r"(db), "n"(0), "n"(TB), "n"(OA), "n"(OB), "n"(HA), "n"(HB));
}
template<int OA, int OB = 0, uint32_t HA = SW128> __device__ __forceinline__ void kblock_n128(float (&d)[64], uint32_t da, uint32_t db, int sd) {
  constexpr int H = HA == SW128 ? 4 : 512;
  wgmma_ss_n128<1, OA, OB, HA, SW128>(d, da, db, sd); wgmma_ss_n128<1, OA + 2, OB + 128, HA, SW128>(d, da, db, 1);
  wgmma_ss_n128<1, OA + H, OB + 256, HA, SW128>(d, da, db, 1); wgmma_ss_n128<1, OA + H + 2, OB + 384, HA, SW128>(d, da, db, 1);
}

__device__ __forceinline__ float quad_sum(float v) {
  v += __shfl_xor_sync(0xffffffff, v, 1);
  v += __shfl_xor_sync(0xffffffff, v, 2);
  return v;
}
struct Row { uint32_t v[8]; };
template<class F> __device__ __forceinline__ Row load_row(const __nv_bfloat16* p, int lane, F ld) {
  const uint4 a = ld(reinterpret_cast<const uint4*>(p) + lane), b = ld(reinterpret_cast<const uint4*>(p) + 32 + lane);
  return Row{{a.x, a.y, a.z, a.w, b.x, b.y, b.z, b.w}};
}
__device__ __forceinline__ Row ldg_row(const __nv_bfloat16* p, int lane) { return load_row(p, lane, [](const uint4* q) { return __ldg(q); }); }
__device__ __forceinline__ Row ldca_row(const __nv_bfloat16* p, int lane) { return load_row(p, lane, [](const uint4* q) { return __ldca(q); }); }
__device__ __forceinline__ Row lds_row(uint32_t addr, int lane) {
  const uint4 a = lds_v4(addr + lane * 16), b = lds_v4(addr + 512 + lane * 16);
  return Row{{a.x, a.y, a.z, a.w, b.x, b.y, b.z, b.w}};
}
__device__ __forceinline__ void store_row(__nv_bfloat16* p, int lane, const Row& r) {
  stg_v4(p + lane * 8, r.v[0], r.v[1], r.v[2], r.v[3]); stg_v4(p + 256 + lane * 8, r.v[4], r.v[5], r.v[6], r.v[7]);
}
__device__ __forceinline__ Row fma_row(const Row& a, const Row& b, const Row& c) {
  Row r;
  #pragma unroll
  for (int i = 0; i < 8; i++) r.v[i] = fma2(a.v[i], b.v[i], c.v[i]);
  return r;
}
__device__ __forceinline__ Row add_row(const Row& a, const Row& b) {
  Row r;
  #pragma unroll
  for (int i = 0; i < 8; i++) r.v[i] = add2(a.v[i], b.v[i]);
  return r;
}
__device__ __forceinline__ Row one_plus(const Row& a) {
  Row r;
  #pragma unroll
  for (int i = 0; i < 8; i++) r.v[i] = add2(a.v[i], 0x3f803f80u);
  return r;
}
__device__ __forceinline__ float row_at(const Row& x, int i) { return (i & 1) ? bf_hi(x.v[i >> 1]) : bf_lo(x.v[i >> 1]); }
template<int N> __device__ __forceinline__ void warp_sums(float (&s)[N]) {
  #pragma unroll
  for (int o = 16; o > 0; o >>= 1) {
    #pragma unroll
    for (int k = 0; k < N; k++) s[k] += __shfl_xor_sync(0xffffffff, s[k], o);
  }
}
__device__ __forceinline__ void ln_stats(float& s1, float& s2) {
  s1 *= 1.f / DM;
  asm("rsqrt.approx.ftz.f32 %0, %1;" : "=f"(s2) : "f"(fmaxf(fmaf(-s1, s1, s2 * (1.f / DM)), 0.f) + 1e-5f));
}
__device__ __forceinline__ Row ln_apply(const Row& x, float mean, float f) {
  Row n;
  const float o = -mean * f;
  #pragma unroll
  for (int i = 0; i < 8; i++) n.v[i] = pack_bf16(fmaf(bf_lo(x.v[i]), f, o), fmaf(bf_hi(x.v[i]), f, o));
  return n;
}

constexpr int SM_Q = 6 * 32768, SM_BAR = 7 * 32768, SM_MAIL = SM_BAR + 640, SM_RED = SM_MAIL + 128, SM_H2 = SM_RED + 1024, SM_KEY = SM_H2 + 1024, SMEM = SM_KEY + 128;
constexpr int B_AF = 0, B_WF = 64, B_RF = 112, B_WE = 168, B_RE = 216, B_PUB = 272, B_RDY = 496;
constexpr int R_MOD = B_RDY, R_H1 = B_RDY + 8, R_ITEM = B_RDY + 16, R_NEAR = B_RDY + 48, R_CTX = B_RDY + 64;
constexpr int R_KEY = B_AF + 8, R_PART = B_AF + 32;
constexpr int NPUB = 14;
__device__ __forceinline__ uint32_t k_addrA(int kb) { return ((0x6310u >> ((kb >> 1) * 4)) & 15u) * 32768u + (kb & 1) * 16384u; }
__device__ __forceinline__ uint32_t k_addrW(int s) { return ((0x254u >> ((s >> 1) * 4)) & 15u) * 32768u + (s & 1) * 16384u; }

#define KORDER 0x3201
constexpr int KHEAD0 = ((KORDER >> 12) & 3) * 8;
constexpr int MAX_ITEMS = 4;
constexpr int MAX_STEPS = 10;
struct Sched {
  __nv_bfloat16 *kvc, *h1, *part;
  struct Pair {
    uint8_t oent[3 * MAX_STEPS + 6];
    uint16_t lastuse[MAX_ITEMS];
    uint8_t khead[4];
    uint8_t nitems, item[MAX_ITEMS];
    uint8_t otask, nsteps;
    uint8_t ochunk[MAX_STEPS][2];
  } pair[NGRID / 2];
};

__device__ __forceinline__ int ring_add(int e, int n) { e += n; return e >= 12 ? e - 12 : e; }
__device__ __forceinline__ int ring_slot(int e) { return e >= 6 ? e - 6 : e; }
__device__ __forceinline__ void ring_wait_full(uint32_t bars, int e) { mbar_wait(bars + B_RF + 8 * ring_slot(e), e >= 6); }

__device__ __forceinline__ void o_wait_full(uint32_t bars, uint32_t v) { mbar_wait(bars + B_RF + 8 * (v & 7), v >> 3); }

struct Ctx {
  uint32_t base, bars;
  uint32_t rel;
  bool rel1;
  int w, nev;
  const Sched* sched;
};
__device__ __forceinline__ void slot_release(const Ctx& x, int s, bool twice) {
  mbar_arrive_remote_if(x.rel + B_RE + 8 * s, twice ? (wg_tid() & 31) == 0 : x.rel1);
}
__device__ __forceinline__ void ring_release(const Ctx& x, int e, bool twice) { slot_release(x, ring_slot(e), twice); }
__device__ __forceinline__ void publish(Ctx& x, int idx) {
  const uint32_t n = x.w * NPUB + x.nev;
  const int t = wg_tid();
  if (t == 0) asm volatile("st.shared.u32 [%0], %1;" :: "r"(x.base + SM_MAIL + 4 * n), "r"(idx) : "memory");
  __syncwarp();
  if ((t & 31) == 0) mbar_arrive(x.bars + B_PUB + 8 * n);
  x.nev++;
}

template<int KK = 0> __device__ __forceinline__ void issue_qk(float (&S)[64], uint32_t dq, uint32_t dk) {
  constexpr int off = (KK >> 1) * 512 + (KK & 1) * 2;
  if constexpr (KK == 0) wgmma_ss_n128_new<0, 0, 0, SW64, SW64>(S, dq, dk); else wgmma_ss_n128<0, off, off, SW64, SW64>(S, dq, dk, 1);
  if constexpr (KK < 7) issue_qk<KK + 1>(S, dq, dk);
}
template<int KK = 0> __device__ __forceinline__ void issue_qk_half(float (&S)[32], uint32_t dq, uint32_t dk) {
  constexpr int off = (KK >> 1) * 512 + (KK & 1) * 2;
  if constexpr (KK == 0) wgmma_ss_n64_new<0, 0, 256, SW64, SW64>(S, dq, dk); else wgmma_ss_n64<0, off, off + 256, SW64, SW64>(S, dq, dk, 1);
  if constexpr (KK < 7) issue_qk_half<KK + 1>(S, dq, dk);
}
template<int NK, int KK = 0>
__device__ __forceinline__ void issue_pv(float (&O)[64], uint32_t (&P)[32], uint32_t dv, int accumulate) {
  wgmma_rs_n128<1, (KK + 8 - NK) * 64, SW64>(O, P[4*KK], P[4*KK+1], P[4*KK+2], P[4*KK+3], dv, accumulate);
  if constexpr (KK + 1 < NK) issue_pv<NK, KK + 1>(O, P, dv, 1);
}
template<int K0, int K1>
__device__ __forceinline__ void exp_pack(const float (&S)[64], uint32_t (&D)[32], float& s0, float& s1) {
  #pragma unroll
  for (int k = K0; k < K1; k++) {
    const float e0 = ex2(S[2*k]), e1 = ex2(S[2*k+1]);
    D[k] = pack_bf16(e0, e1);
    if (k & 1) s1 += e0 + e1; else s0 += e0 + e1;
  }
}
__device__ __forceinline__ int diag_limit() { const int t = wg_tid(); return 16 * (t >> 5) + ((t & 31) >> 2) - 2 * (t & 3); }
__device__ __forceinline__ void exp_pack_diag(const float (&S)[64], uint32_t (&D)[32], int t, float& s0, float& s1) {
  #pragma unroll
  for (int k = 0; k < 16; k++) {
    const int c = 8 * (k >> 1) - 8 * (k & 1);
    const float e0 = ex2((c <= t) ? S[2*k] : -INFINITY), e1 = ex2((c + 1 <= t) ? S[2*k+1] : -INFINITY);
    D[k] = pack_bf16(e0, e1);
    if (k & 1) s1 += e0 + e1; else s0 += e0 + e1;
  }
}
constexpr float SUM_HI = 1.8446744073709552e19f;
constexpr float SUM_LO = 5.421010862427522e-20f;

__device__ __forceinline__ void classic_tile(const float (&S)[64], uint32_t (&P)[32], bool fresh, bool half, bool was_classic, volatile float* mc,
                                             float& l0, float& l1, float& s0, float& s1, float& sc0, float& sc1) {
  const int tmask = diag_limit();
  float4 t[16];
  #pragma unroll
  for (int j = 0; j < 16; j++) t[j] = make_float4(S[4*j], S[4*j+1], S[4*j+2], S[4*j+3]);
  float mx0 = -INFINITY, mx1 = -INFINITY;
  #pragma unroll 1
  for (int j = 0; j < 16; j++) {
    float4 v = t[j];
    const int lim = !fresh ? 1000 : j < 8 ? tmask - 8 * j : half ? -1000 : 1000;
    v.x = 0 <= lim ? v.x : -INFINITY; v.y = 1 <= lim ? v.y : -INFINITY; v.z = -8 <= lim ? v.z : -INFINITY; v.w = -7 <= lim ? v.w : -INFINITY;
    t[j] = v;
    mx0 = fmaxf(mx0, fmaxf(v.x, v.y)); mx1 = fmaxf(mx1, fmaxf(v.z, v.w));
  }
  mx0 = fmaxf(mx0, __shfl_xor_sync(0xffffffff, mx0, 1));
  mx1 = fmaxf(mx1, __shfl_xor_sync(0xffffffff, mx1, 1));
  mx0 = fmaxf(mx0, __shfl_xor_sync(0xffffffff, mx0, 2));
  mx1 = fmaxf(mx1, __shfl_xor_sync(0xffffffff, mx1, 2));
  const float mc0 = was_classic ? mc[0] : 0.f, mc1 = was_classic ? mc[1] : 0.f;
  const float n0 = fresh ? -mx0 : fminf(mc0, -mx0), n1 = fresh ? -mx1 : fminf(mc1, -mx1);
  sc0 = ex2(n0 - mc0); sc1 = ex2(n1 - mc1);
  mc[0] = n0; mc[1] = n1;
  s0 = 0.f; s1 = 0.f;
  #pragma unroll 1
  for (int j = 0; j < 16; j++) {
    const float4 v = t[j];
    const float e0 = ex2(v.x + n0), e1 = ex2(v.y + n0), e2 = ex2(v.z + n1), e3 = ex2(v.w + n1);
    s0 += e0 + e1; s1 += e2 + e3;
    reinterpret_cast<uint2*>(t)[j] = make_uint2(pack_bf16(e0, e1), pack_bf16(e2, e3));
  }
  #pragma unroll
  for (int j = 0; j < 8; j++) { P[4*j] = __float_as_uint(t[j].x); P[4*j+1] = __float_as_uint(t[j].y); P[4*j+2] = __float_as_uint(t[j].z); P[4*j+3] = __float_as_uint(t[j].w); }
  if (!fresh) { l0 *= sc0; l1 *= sc1; }
}
__device__ __forceinline__ void pack_tile(const float (&A)[64], uint32_t (&D)[32], float f0, float f1) {
  #pragma unroll
  for (int j = 0; j < 16; j++) {
    D[8 * (j >> 2) + (j & 3)] = pack_bf16(A[4*j] * f0, A[4*j+1] * f0);
    D[8 * (j >> 2) + 4 + (j & 3)] = pack_bf16(A[4*j+2] * f1, A[4*j+3] * f1);
  }
}
__device__ __forceinline__ int piece0(int t) { return ((t >> 5) * 16 + ((t & 31) >> 2)) * 32 + (((t ^ (t >> 3)) & 3) << 3); }
__device__ __forceinline__ void store_tile(__nv_bfloat16* p, const uint32_t (&D)[32]) {
  #pragma unroll
  for (int i = 0; i < 8; i++) stg_v4(p + (i >> 2) * (SEQ * 64) + ((i >> 1) & 1) * 4096 + (i & 1) * 256, D[4*i], D[4*i+1], D[4*i+2], D[4*i+3]);
}

enum : int { PV_ACC = 0, PV_ZERO = 1, PV_HALF = 2, PV_NONE = 3 };
struct Att {
  float l0, l1, i0, i1;
  bool classic;
  volatile float* mc;
};
__device__ __forceinline__ void store_ctx(Ctx& x, int code, const uint32_t (&D)[32]) {
  store_tile(x.sched->kvc + ((size_t)(128 + (code >> 5) * 2) * SEQ + ((code >> 1) & 15) * 128) * 64 + (code & 1) * 2048 + piece0(wg_tid()), D);
  publish(x, C_CTX + (code >> 2));
}
__device__ __forceinline__ __nv_bfloat16* kv_tile(const Ctx& x, int code) {
  return x.sched->kvc + ((size_t)(x.w * 64 + (code >> 4) * 2) * SEQ + (code & 15) * 128) * 64 + piece0(wg_tid());
}
__device__ __forceinline__ void q_proj(Ctx& x, Att& a, int& e, int& sk, int& sv, int& en, int& sn, bool isY,
                                       const uint32_t (&PA)[32], const uint32_t (&PB)[32], int vtile, bool first) {
  float S[64];
  int ek = 0, s = sk, ps = 0, ph = e >= 6, kb = 0;
  uint32_t qa = 0;
  sv = en = sn = 0;
  if (isY) bar_sync(1 + x.w, 256);
  if (first) mbar_wait(x.bars + B_RF + 8 * s, ph);
  #pragma unroll 1
  while (true) {
    #pragma unroll 1
    do {
      wgmma_fence();
      kblock_n128<0>(S, desc_lo(x.base + x.w * 8192, 16) + s * 2048, desc_lo(x.base + 16384, 8192) + s * 2048, kb != 0);
      wgmma_commit();
      if (kb == 7 && !isY) bar_arrive(1 + (x.w ^ 1), 256);
      wgmma_wait<1>();
      mbar_arrive_remote_if(x.rel + B_RE + 8 * ps, x.rel1 && kb > 0);
      ps = s;
      if (++s == 6) { s = 0; ph ^= 1; }
      if (++kb == 8) break;
      mbar_wait(x.bars + B_RF + 8 * s, ph);
    } while (kb != 4);
    asm volatile("" : "+r"(vtile));
    if (kb == 8) break;
    a.i0 = rcp_fast(quad_sum(a.l0)); a.i1 = rcp_fast(quad_sum(a.l1));
    e = ring_add(e, 8); ek = ring_add(e, isY ? 0 : 2); en = ring_add(e, isY ? 2 : 4);
    sk = ring_slot(ek); sv = ring_slot(e) + 1; sn = ring_slot(en);
    qa = x.base + SM_Q + x.w * 4096 + piece0(wg_tid()) * 2;
    if (vtile >= 0) store_tile(kv_tile(x, vtile) + 2048, PA);
  }
  if (vtile >= 0) { store_tile(kv_tile(x, vtile), PB); publish(x, C_KV + (vtile >> 4)); }
  wgmma_wait<0>();
  fence_regs(S);
  slot_release(x, ps, false);
  const bool landed = isY && mbar_test2(x.bars + B_RF + 8 * sk, e >= 6);
  #pragma unroll
  for (int i = 0; i < 8; i++) {
    const int j = 4 * (i >> 1), o = 2 * (i & 1);
    sts_v4(qa + (i >> 1) * 8192 + (i & 1) * 512,
           pack_bf16(S[4*j+o], S[4*j+o+1]), pack_bf16(S[4*j+4+o], S[4*j+5+o]), pack_bf16(S[4*j+8+o], S[4*j+9+o]), pack_bf16(S[4*j+12+o], S[4*j+13+o]));
  }
  fence_async_smem();
  if (!landed) { mbar_wait(x.bars + B_RF + 8 * sk, ek >= 6); mbar_wait(x.bars + B_RF + 8 * sv, e >= 6); }
}

template<int KIND>
__device__ __forceinline__ void slot(Ctx& x, Att& a, int& e, int& sk, int sv, int en, int sn, float (&O)[64], uint32_t (&Pn)[32], uint32_t (&Po)[32],
                                     bool more, bool isY, bool half, int pv, int pend) {
  float S[64];
  const int w = x.w;
  const uint32_t dq = desc_lo(x.base + SM_Q + w * 4096, 16), dk = desc_lo(x.base, 16) + sk * 2048, dv = desc_lo(x.base, 8192) + sv * 2048;
  bar_sync(1 + w, 256);
  if (KIND == 2) {
    wgmma_fence();
    issue_qk(S, dq, dk); wgmma_commit();
    issue_pv<8>(O, Po, dv, 1); wgmma_commit();
    bar_arrive(1 + (w ^ 1), 256);
    wgmma_wait<1>();
  } else if (KIND == 0 && half) {
    float T[32];
    wgmma_fence(); issue_qk_half(T, dq, dk); wgmma_commit();
    if (pv == PV_NONE) { wgmma_fence(); wgmma_commit(); }
    else               { wgmma_fence(); issue_pv<8>(O, Po, dv, pv == PV_ACC); wgmma_commit(); }
    bar_arrive(1 + (w ^ 1), 256);
    wgmma_wait<1>();
    fence_regs(T);
    #pragma unroll
    for (int i = 0; i < 32; i++) { S[i] = T[i]; asm volatile("" : "=f"(S[32 + i])); }
  } else {
    wgmma_fence(); issue_qk(S, dq, dk); wgmma_commit();
    if (KIND == 1 && pend >= 0) { bar_arrive(1 + (w ^ 1), 256); pack_tile(O, Pn, a.i0, a.i1); store_ctx(x, pend, Pn); }
    if (KIND == 0 && pv == PV_NONE) { wgmma_fence(); wgmma_commit(); }
    else if (pv == PV_HALF)         { wgmma_fence(); issue_pv<4>(O, Po, dv, 0); wgmma_commit(); }
    else                            { wgmma_fence(); issue_pv<8>(O, Po, dv, pv == PV_ACC); wgmma_commit(); }
    if (KIND == 0 || pend < 0) bar_arrive(1 + (w ^ 1), 256);
    wgmma_wait<1>();
  }
  fence_regs(S);
  fence_regs_u(Pn);
  slot_release(x, sk, KIND == 0 && isY);
  const bool landed = mbar_test2(x.bars + B_RF + 8 * sn, en >= 6);
  float s0 = 0.f, s1 = 0.f;
  const bool was_classic = KIND != 0 && a.classic;
  if (KIND == 0) {
    a.l0 = 0.f; a.l1 = 0.f;
    if (!half) exp_pack<16, 32>(S, Pn, s0, s1);
    else {
      #pragma unroll
      for (int i = 16; i < 32; i++) asm volatile("" : "=r"(Pn[i]));
    }
    exp_pack_diag(S, Pn, diag_limit(), s0, s1);
    uint32_t b0 = __ballot_sync(0xffffffff, s0 >= SUM_LO), b1 = __ballot_sync(0xffffffff, s1 >= SUM_LO);
    b0 |= b0 >> 1; b0 |= b0 >> 2; b1 |= b1 >> 1; b1 |= b1 >> 2;
    a.classic = __any_sync(0xffffffff, !(s0 <= SUM_HI && s1 <= SUM_HI)) || (b0 & b1 & 0x11111111u) != 0x11111111u;
  } else {
    exp_pack<0, 32>(S, Pn, s0, s1);
    a.classic = __any_sync(0xffffffff, a.classic || !(s0 <= SUM_HI && s1 <= SUM_HI));
  }
  fence_regs_u(Pn);
  if (!landed) {
    mbar_wait(x.bars + B_RF + 8 * sn, en >= 6);
    if (more) mbar_wait(x.bars + B_RF + 8 * sn + 8, en >= 6);
  }
  wgmma_wait<0>();
  fence_regs(O);
  fence_regs_u(Po);
  slot_release(x, sv, KIND == 1 && isY && pv != PV_ACC);
  if (__builtin_expect(a.classic, 0)) {
    float sc0, sc1;
    classic_tile(S, Pn, KIND == 0, half, was_classic, a.mc, a.l0, a.l1, s0, s1, sc0, sc1);
    if (KIND != 0) {
      #pragma unroll
      for (int j = 0; j < 16; j++) { O[4*j] *= sc0; O[4*j+1] *= sc0; O[4*j+2] *= sc1; O[4*j+3] *= sc1; }
    }
  }
  a.l0 += s0; a.l1 += s1;
  e = en; sk = sn;
}

__device__ __forceinline__ int attention(Ctx& x, const uint8_t* items, int nitems, int rank, uint32_t (&PA)[32], uint32_t (&PB)[32], int vtile) {
  int e = 0, sk = 0;
  float O[64];
  Att a;
  volatile float mc[2];
  a.l0 = 1.f; a.l1 = 1.f; a.i0 = 0.f; a.i1 = 0.f; a.classic = false; a.mc = mc;
  int pv = PV_NONE, cur = -1;
  #pragma unroll 1
  for (int it = 0; ; it++) {
    const bool isY = (it & 1) == x.w;
    int pend = cur;
    if (it < nitems) {
      const bool half = isY == (rank != 0);
      int sv, en, sn;
      q_proj(x, a, e, sk, sv, en, sn, isY, PA, PB, vtile, it == 0);
      vtile = -1;
      const int item = items[it];
      cur = item * 4 + (isY ? 3 - rank : rank);
      int rem = 2 * (item & 7) + (isY ? 1 : 0);
      slot<0>(x, a, e, sk, sv, en, sn, O, PA, PB, rem > 0, isY, half, pv, -1);
      pv = half ? PV_HALF : PV_ZERO;
      #pragma unroll 1
      while (rem > 0) {
        slot<1>(x, a, e, sk, sk + 1, ring_add(e, 2), sk == 4 ? 0 : sk + 2, O, PB, PA, rem > 1, isY, false, pv, pend);
        pv = PV_ACC; pend = -1;
        if (rem == 1) break;
        rem -= 2;
        slot<2>(x, a, e, sk, sk + 1, ring_add(e, 2), sk == 4 ? 0 : sk + 2, O, PA, PB, rem > 0, false, false, 0, -1);
      }
      if (isY) continue;
    } else {
      slot_release(x, 6, false);
      const uint32_t dv = desc_lo(x.base, 8192) + sk * 2048;
      bar_sync(1 + x.w, 256);
      if (pv == PV_HALF) { wgmma_fence(); issue_pv<4>(O, PB, dv, 0); wgmma_commit(); }
      else { wgmma_fence(); issue_pv<8>(O, PB, dv, pv == PV_ACC); wgmma_commit(); }
      if (isY) bar_arrive(1 + (x.w ^ 1), 256);
      a.i0 = rcp_fast(quad_sum(a.l0)); a.i1 = rcp_fast(quad_sum(a.l1));
      ring_wait_full(x.bars, e);
      wgmma_wait<0>();
      fence_regs(O);
      fence_regs_u(PB);
      slot_release(x, sk, false);
    }
    if (pend >= 0) {
      pack_tile(O, PB, a.i0, a.i1);
      if (it == nitems) return pend;
      store_ctx(x, pend, PB);
    }
    #pragma unroll
    for (int i = 0; i < 32; i++) asm volatile("mov.b32 %0, %1;" : "=r"(PB[i]) : "r"(PA[i]));
  }
}

#define LN_AT 2
#define X_AT 6
#define PERT 0
#define CTX_T 3
#define PF_AT 5
#define PF_N 4
#define PF_MOE 3
constexpr float QSCALE = 0.08838834764831845f * 1.4426950408889634f;
__device__ __forceinline__ void mod_cta(Ctx& x, const __nv_bfloat16* cvec) {
  const int t = wg_tid(), ct = x.w * 128 + t;
  #pragma unroll 1
  for (int k = 0; k < 6; k++) slot_release(x, k, false);
  const uint32_t cv = __ldg(reinterpret_cast<const uint32_t*>(cvec) + ct);
  asm volatile("st.shared.u32 [%0], %1;" :: "r"(x.base + SM_H2 + ct * 4),
               "r"(pack_bf16(__fdividef(bf_lo(cv), 1.f + __expf(-bf_lo(cv))), __fdividef(bf_hi(cv), 1.f + __expf(-bf_hi(cv))))) : "memory");
  bar_sync(5, 256);
  float acc[64];
  int e = 0;
  #pragma unroll 1
  for (int g = 0; g < 24; g++) {
    uint32_t a[8];
    #pragma unroll
    for (int i = 0; i < 8; i++) a[i] = lds_u32(x.base + SM_H2 + (g & 7) * 128 + i * 16 + (t & 3) * 4);
    ring_wait_full(x.bars, e);
    const uint32_t db = desc_lo(x.base + x.w * 16384, 8192) + ring_slot(e) * 2048;
    wgmma_fence();
    wgmma_rs_n128<1, 0, SW128>(acc, a[0], a[0], a[1], a[1], db, g & 7);
    wgmma_rs_n128<1, 128, SW128>(acc, a[2], a[2], a[3], a[3], db, 1);
    wgmma_rs_n128<1, 256, SW128>(acc, a[4], a[4], a[5], a[5], db, 1);
    wgmma_rs_n128<1, 384, SW128>(acc, a[6], a[6], a[7], a[7], db, 1);
    wgmma_commit();
    wgmma_wait<0>();
    fence_regs(acc);
    ring_release(x, e, false);
    e = ring_add(e, 1);
    if ((g & 7) == 7) {
      if (t < 4) {
        const float sc = (g == 7 && blockIdx.x < NCTA + 2) ? QSCALE : 1.f;
        uint32_t* dst = reinterpret_cast<uint32_t*>(g_x.mod + (g >> 3) * 1024 + (blockIdx.x - NCTA) * 256 + x.w * 128) + t;
        #pragma unroll
        for (int j = 0; j < 16; j++) dst[4 * j] = pack_bf16(rbf(acc[4*j]) * sc, rbf(acc[4*j+1]) * sc);
      }
      publish(x, g == 7 ? C_MOD : C_MOD2);
    }
  }
}

__global__ void __cluster_dims__(2, 1, 1) __launch_bounds__(384, 1)
k_fused(const __grid_constant__ CUtensorMap tmC, const __grid_constant__ CUtensorMap tmWq,
        const __grid_constant__ CUtensorMap tmWk, const __grid_constant__ CUtensorMap tmWv,
        const __grid_constant__ CUtensorMap tmWo, const __grid_constant__ CUtensorMap tmWg,
        const __grid_constant__ CUtensorMap tmWu, const __grid_constant__ CUtensorMap tmWm,
        const __grid_constant__ Sched sched,
        const __nv_bfloat16* __restrict__ xin,
        const __nv_bfloat16* __restrict__ cvec, const __nv_bfloat16* __restrict__ w_o,
        const __nv_bfloat16* __restrict__ w_r, const __nv_bfloat16* __restrict__ w_gate, const __nv_bfloat16* __restrict__ w_up,
        const __nv_bfloat16* __restrict__ w_down, __nv_bfloat16* __restrict__ out) {
  extern __shared__ __align__(1024) uint8_t smem_raw[];
  const uint32_t base = smem_u32(smem_raw), bars = base + SM_BAR;
  const int warp = __shfl_sync(0xffffffff, threadIdx.x >> 5, 0), wg = warp >> 2;
  const int rank = cluster_ctarank(), p = blockIdx.x >> 1;
  const int mt = (p & 7) * 2 + rank;
  const bool spare = blockIdx.x >= NCTA;
  #pragma unroll
  for (int i = 0; i < PERT; i++) { uint32_t d; asm volatile("mov.u32 %0, %%laneid;" : "=r"(d)); (void)d; }
  {
    const int h0 = KHEAD0 + (p >> 3);
    if (warp == 11) { prefetch_tmap(&tmC); prefetch_tmap(&tmWk); }
    #pragma unroll 1
    for (int t = warp == 8 ? 0 : warp < 8 ? warp + 1 : warp == 11 ? 64 : warp; t < B_PUB / 8; t += (warp == 8 ? 64 : 10))
      w_mbar_init(bars + 8 * t, t < B_WE / 8 ? 1 : t < B_RE / 8 ? 2 : 4);
    fence_mbar_init();
    cluster_arrive();
    if (warp == 9) prefetch_tmap(&tmWv);
    if (wg == 2) bar_arrive(1, 256);
    if (warp == 8 && !spare) {
      #pragma unroll 1
      for (int kb = 0; kb < 8; kb++) {
        w_expect_tx(bars + B_AF + 8 * kb, 16384);
        tma_load_2d(base + k_addrA(kb), &tmC, bars + B_AF + 8 * kb, kb * 64, mt * 128);
        if (kb == 0) cluster_wait();
        if (kb < 6) {
          w_expect_tx(bars + B_WF + 8 * kb, 16384);
          tma_load_2d_mc(base + k_addrW(kb) + rank * 8192, &tmWk, bars + B_WF + 8 * kb, h0 * 128 + rank * 64, kb * 64);
        }
      }
    }
  }
  const Sched::Pair& sp = sched.pair[p];
  const int nitems = sp.nitems, nsteps = sp.nsteps;
  auto oent = [&](int k) -> uint32_t { return sp.oent[k]; };
  const int ot = sp.otask, m = (ot & 7) * 2 + rank, grp = m * 8 + (ot >> 3);

  if (wg == 0) {
    asm volatile("setmaxnreg.dec.sync.aligned.u32 24;");
    const int lane = threadIdx.x & 31;
    #pragma unroll 1
    for (int t = B_PUB / 8 + warp; t < 80; t += 4) w_mbar_init(bars + 8 * t, t < B_RDY / 8 ? 4 : 1);
    bar_sync(6, 128);
    bar_arrive(7, 256); bar_arrive(8, 256);
    cluster_wait();
    const unsigned int tag = ld_relaxed(&g_x.epoch) + 1;
    if (warp == 0) {
      if (!spare) {
        int s = 0, ph = 0;
        tma_prefetch_2d(&tmWv, sp.khead[0] * 128 + rank * 64, (p & 7) * 64);
        #pragma unroll 1
        for (int g = 6; g < 64; g++) {
          const int u = g >> 3, kb = g & 7;
          if (kb == 0 && u < 7) tma_prefetch_2d((u & 1) ? &tmWk : &tmWv, sp.khead[(u + 1) >> 1] * 128 + rank * 64, (p & 7) * 64);
          mbar_wait(bars + B_WE + 8 * s, ph);
          w_expect_tx(bars + B_WF + 8 * s, 16384);
          tma_load_2d_mc(base + k_addrW(s) + rank * 8192, (u & 1) ? &tmWv : &tmWk, bars + B_WF + 8 * s, sp.khead[u >> 1] * 128 + rank * 64, kb * 64);
          if (++s == 6) { s = 0; ph ^= 1; }
        }
      }
      int s = 0, ph = 0;
      auto next_entry = [&](int bytes) {
        mbar_wait(bars + B_RE + 8 * s, ph);
        w_expect_tx(bars + B_RF + 8 * s, bytes);
      };
      auto advance = [&]() { if (++s == 6) { s = 0; ph ^= 1; } };
      if (spare) {
        #pragma unroll 1
        for (int g = 0; g < 24; g++) {
          if (g == 8) mbar_wait(bars + R_MOD, 0);
          next_entry(32768);
          for (int k = 0; k < 2; k++) tma_load_3d(base + s * 32768 + k * 16384, &tmWm, bars + B_RF + 8 * s, 0, (g & 7) * 64, (g >> 3) * 16 + (blockIdx.x - NCTA) * 4 + k * 2);
          advance();
        }
      }
      mbar_wait(bars + R_H1, 0);
      fence_async_global();
      int vrow = -1;
      #pragma unroll 1
      for (int i = 0; i <= nitems; i++) {
        const int item = sp.item[i & (MAX_ITEMS - 1)], h = item >> 3, j = item & 7;
        if (i < nitems) {
          const int row0 = j * 256 + ((i & 1) ? rank : 3 - rank) * 64, row1 = j * 256 + ((i & 1) ? 3 - rank : rank) * 64;
          #pragma unroll 1
          for (int kb = 0; kb < 8; kb++) {
            next_entry(32768);
            tma_load_2d_mc(base + s * 32768 + 16384 + rank * 8192, &tmWq, bars + B_RF + 8 * s, h * 128 + rank * 64, kb * 64);
            bulk_load(base + s * 32768, sched.h1 + row0 * DM + kb * 4096, 8192, bars + B_RF + 8 * s);
            bulk_load(base + s * 32768 + 8192, sched.h1 + row1 * DM + kb * 4096, 8192, bars + B_RF + 8 * s);
            advance();
          }
          mbar_wait(bars + R_ITEM + 8 * i, 0);
          fence_async_global();
        }
        #pragma unroll 1
        for (int n = i < nitems ? 4 * j + 3 : 0; n >= 0; n--) {
          const int krow = (h * 2 + rank) * SEQ + (n >> 1) * 128 + ((sp.lastuse[i & (MAX_ITEMS - 1)] >> (n >> 1)) & 1);
          const int row = (n & 1) ? krow : vrow;
          if (i + 1 == nitems && n == min(4 * j + 3, 2 * PF_AT + 1)) w_arrive(bars + R_NEAR);
          next_entry(row >= 0 ? 32768 : 0);
          if (row >= 0) bulk_load_mc(base + s * 32768 + rank * 16384, sched.kvc + (size_t)(row & ~1) * 64, bars + B_RF + 8 * s, row & 1);
          advance();
          if (!(n & 1)) vrow = krow + 64 * SEQ;
        }
      }
      if (!spare) {
      const int oc = ((ot >> 3) & 1) * 4 + rank * 2;
      auto o_next = [&](int k, int bytes) {
        const uint32_t v = oent(k); s = v & 7;
        mbar_wait(bars + B_RE + 8 * s, v >> 3);
        w_expect_tx(bars + B_RF + 8 * s, bytes);
      };
      #pragma unroll 1
      for (int i = 0; i < nsteps; i++) {
        const int c0 = sp.ochunk[i][0], c1 = sp.ochunk[i][1];
        const int pf = i - nsteps + PF_MOE;
        if (pf >= 0 && pf < 3)
          bulk_prefetch((pf == 0 ? w_gate : pf == 1 ? w_up : w_down) + (size_t)blockIdx.x * (DM * FF / NCTA), DM * FF / NCTA * 2);
        if (c0 < 64) { o_next(3 * i, 32768); tma_load_3d_mc(base + s * 32768 + rank * 16384, &tmWo, bars + B_RF + 8 * s, 0, c0 * 64, oc); }
        mbar_wait(bars + R_CTX + 8 * i, 0);
        fence_async_global();
        o_next(3 * i + 1, c0 < 64 ? 32768 : 16384);
        if (c0 < 64) bulk_load(base + s * 32768, sched.kvc + (size_t)((128 + c0) * SEQ + m * 128) * 64, 16384, bars + B_RF + 8 * s);
        bulk_load(base + s * 32768 + 16384, sched.kvc + (size_t)((128 + c1) * SEQ + m * 128) * 64, 16384, bars + B_RF + 8 * s);
        o_next(3 * i + 2, 32768);
        tma_load_3d_mc(base + s * 32768 + rank * 16384, &tmWo, bars + B_RF + 8 * s, 0, c1 * 64, oc);
      }
      const int f0 = (blockIdx.x < FF / 16 ? blockIdx.x : 0) * 16;
      o_next(3 * nsteps, 32768);
      bulk_load(base + s * 32768, w_down + (size_t)f0 * DM, 16384, bars + B_RF + 8 * s);
      bulk_load(base + s * 32768 + 16384, xin + (size_t)grp * 16 * DM, 16384, bars + B_RF + 8 * s);
      o_next(3 * nsteps + 1, 32768);
      #pragma unroll 1
      for (int k = 0; k < 4; k++) tma_load_2d(base + s * 32768 + k * 8192, (k & 2) ? &tmWu : &tmWg, bars + B_RF + 8 * s, f0, (k & 1) * 256);
      #pragma unroll 1
      for (int k = 0; k < 4; k++) w_expect_tx(bars + R_PART + 8 * k, 16384);
      mbar_wait(bars + B_PUB + 8 * (5 + nitems), 0);
      mbar_wait(bars + B_PUB + 8 * (NPUB + 5 + nitems), 0);
      uint32_t todo = 0xff;
      #pragma unroll 1
      for (int n = 0; n < WAIT_LIM && todo; n++) {
        uint32_t now = __ballot_sync(0xffffffff, ld_acquire(&g_x.cnt[C_PART + (m * 2 + (ot >> 5)) * 32 + (lane & 7)]) == tag) & todo;
        todo &= ~now;
        if (now) fence_async_global();
        #pragma unroll 1
        for (; now; now &= now - 1) {
          const int q = __ffs(now) - 1;
          bulk_load(base + (oent(3 * nsteps - 3 + (q >> 2)) & 7) * 32768 + (q & 3) * 8192, sched.part + (grp * 8 + q) * 4096, 8192, bars + R_PART + 8 * (q >> 1));
        }
      }
      }
    } else if (warp < 3) {
      const int w = warp - 1, n1 = w * NPUB + (spare ? 3 : 6) + nitems;
      #pragma unroll 1
      for (int n = w * NPUB; n < n1; n++) {
        #pragma unroll 1
        for (int k = 0; k < 8 * WAIT_LIM; k++) { if (mbar_try(bars + B_PUB + 8 * n, 0)) break; }
        const uint32_t idx = lds_u32(base + SM_MAIL + 4 * n);
        fence_async_global();
        if (lane == 0 && idx < (unsigned)C_END) red_release(idx);
        __syncwarp();
      }
    } else {
      *reinterpret_cast<volatile uint32_t*>(smem_raw + SM_KEY + 48) = tag;
      if (!spare) { mbar_wait(bars + B_AF + 8 * X_AT, 0); bulk_prefetch(xin + (size_t)blockIdx.x * 16 * DM, 16 * DM * 2); }
      #pragma unroll 1
      for (int n = 0; n < 8 + nsteps; n++) {
        if (n == 2 + nitems) n = 7;
        int idx = n == 0 ? C_MOD : n == 1 ? C_H1 : C_MOD2, cnt = n == 0 ? 8 : n == 1 ? 256 : 16;
        if (n == 2) tma_prefetch_2d(&tmWq, (sp.item[0] >> 3) * 128 + rank * 64, (sp.item[0] & 7) * 64);
        if (n >= 2 && n < 7) { idx = C_KV + (sp.item[n - 2] >> 3); cnt = 32; }
        if (n >= 8) { const int c0 = sp.ochunk[n - 8][0], c1 = sp.ochunk[n - 8][1]; idx = C_CTX + (((lane & 1) && c0 < 64 ? c0 : c1) >> 1) * 8 + (ot & 7); cnt = 4; }
        wait_count_lazy(idx, cnt * tag);
        w_arrive(bars + B_RDY + 8 * n);
        if (n == 8 + PF_N - 1) {
          #pragma unroll 1
          for (int k = 0; k < 8 * WAIT_LIM; k++) { if (mbar_try(bars + R_NEAR, 0)) break; }
          bulk_prefetch(w_o + (size_t)blockIdx.x * (NH * DH * DM / NCTA), NH * DH * DM / NCTA * 2);
          #pragma unroll 1
          for (int k = 0; k < PF_N; k++) {
            const int cc = sp.ochunk[k][(ot >> 3) & 1];
            if (cc < 64) bulk_prefetch(sched.kvc + ((size_t)(128 + cc) * SEQ + m * 128) * 64, 16384);
          }
        }
      }
    }
    __syncwarp();
    cluster_arrive();
    if (!spare) {
      bar_sync(6, 128);
      asm volatile("setmaxnreg.inc.sync.aligned.u32 88;");
      const int pos = blockIdx.x * 4 + (lane & 1) * 2, col = (blockIdx.x >> 2) * 16 + (blockIdx.x & 3) * 2 + (lane & 1) * 8, src = threadIdx.x >> 1;
      uint32_t gbest = 0, hh = 0, gbf = 0;
      uint2 xx = make_uint2(0, 0);
      uint4 ya = make_uint4(0, 0, 0, 0), yb = make_uint4(0, tag, 0, tag);
      auto poll_y = [&]() {
        if (ya.y != tag || ya.w != tag) ya = ld_tagged2(&g_x.yll[src][pos]);
        if (yb.y != tag || yb.w != tag) yb = ld_tagged2(&g_x.yll[src + 64][pos]);
        return __all_sync(0xffffffff, ya.y == tag && ya.w == tag && yb.y == tag && yb.w == tag);
      };
      ya.y = tag - 1; if (src + 64 < FF / 16) yb.y = tag - 1;
      if (warp == 3) {
        gbf = __ldcg(reinterpret_cast<const uint32_t*>(g_x.mod + 5 * DM + col));
        uint32_t have = 0;
        uint2 k[4];
        #pragma unroll
        for (int i = 0; i < 4; i++) k[i] = make_uint2(0, tag - 1);
        #pragma unroll 1
        for (int n = 0; n < WAIT_LIM; n++) {
          #pragma unroll
          for (int i = 0; i < 4; i++) if (k[i].y != tag) k[i] = ld_tagged(&g_x.keys[i * 32 + lane][0]);
          if (gbest != have) {
            const int g = ((0xffffu - gbest) >> 4) & 127;
            uint4 hv[4];
            #pragma unroll
            for (int i = 0; i < 4; i++) hv[i] = ld_tagged2(&g_x.row[g][0][i * 64 + lane * 2]);
            xx = ld_tagged(&g_x.row[g][1][(col >> 8) * 128 + ((col >> 2) & 1) * 64 + ((col >> 3) & 31) * 2 + ((col >> 1) & 1)]);
            bool ok = xx.y == tag;
            #pragma unroll
            for (int i = 0; i < 4; i++) { ok = ok && hv[i].y == tag && hv[i].w == tag; reinterpret_cast<uint2*>(smem_raw + SM_H2)[(i >> 1) * 64 + lane * 2 + (i & 1)] = make_uint2(hv[i].x, hv[i].z); }
            if (lane == 0) *reinterpret_cast<uint32_t*>(smem_raw + SM_KEY + 32) = gbest;
            have = __all_sync(0xffffffff, ok) ? gbest : 0;
          }
          bool all = true;
          #pragma unroll
          for (int i = 0; i < 4; i++) { all = all && k[i].y == tag; gbest = max(gbest, k[i].y == tag ? k[i].x : 0u); }
          gbest = __reduce_max_sync(0xffffffff, gbest);
          if (__all_sync(0xffffffff, all) && gbest == have) break;
        }
        __syncwarp();
        w_arrive(bars + R_KEY);
        if (blockIdx.x == 0 && lane == 0) g_x.epoch = tag;
        hh = lds_u32(base + SM_H2 + col * 2);
      }
      const float rsel = rbf(__uint_as_float((((gbest & 0x80000000u) ? gbest & 0x7fffffffu : ~gbest) & 0xfffff000u) | 0x800u));
      const float rs = rbf(__fdividef(1.f, 1.f + __expf(-rsel)));
      bar_sync(9, 384);
      #pragma unroll 1
      for (int n = 0; n < WAIT_LIM; n++) { if (poll_y()) break; }
      float y0 = __uint_as_float(ya.x) + __uint_as_float(yb.x), y1 = __uint_as_float(ya.z) + __uint_as_float(yb.z);
      #pragma unroll
      for (int o = 2; o < 32; o <<= 1) { y0 += __shfl_xor_sync(0xffffffff, y0, o); y1 += __shfl_xor_sync(0xffffffff, y1, o); }
      float2* s_y = reinterpret_cast<float2*>(smem_raw + SM_KEY + 64);
      if (lane < 2) s_y[warp * 2 + lane] = make_float2(y0, y1);
      bar_sync(6, 128);
      if (warp == 3 && lane < 2) {
        y0 = 0.f; y1 = 0.f;
        #pragma unroll
        for (int i = 0; i < 4; i++) { y0 += reinterpret_cast<const float*>(s_y)[i * 4 + lane]; y1 += reinterpret_cast<const float*>(s_y)[i * 4 + 2 + lane]; }
        const float o0 = bf_lo(xx.x) + rbf(bf_lo(gbf) * rbf(bf_lo(hh) + rbf(rbf(y0) * rs)));
        const float o1 = bf_hi(xx.x) + rbf(bf_hi(gbf) * rbf(bf_hi(hh) + rbf(rbf(y1) * rs)));
        *reinterpret_cast<uint32_t*>(out + (size_t)((0xffffu - gbest) & (SEQ - 1)) * DM + col) = pack_bf16(o0, o1);
      }
    }
    __syncwarp();
    cluster_wait();
  } else {
    asm volatile("setmaxnreg.inc.sync.aligned.u32 240;");
    Ctx x;
    x.w = wg - 1; x.base = base; x.bars = bars; x.nev = 0; x.sched = &sched;
    const int w = x.w, warp4 = warp & 3;
    x.rel = mapa(bars, (warp4 & 1) ^ 1);
    x.rel1 = (threadIdx.x & 127) == 32 || (threadIdx.x & 127) == 64;
    if (warp != 8 || spare) cluster_wait();
    if (w == 1 || spare) bar_sync(7 + w, 256);
    uint32_t PA[32], PB[32];
    int vtile = -1;
    if (spare) {
      mod_cta(x, cvec);
    } else {
      const int lane = wg_tid() & 31;
      Row xn[2];
      float acc0[64], acc1[64];
      int s = 2 * w, ph = w;
      #pragma unroll 1
      for (int u = w; u < 8; u += 2) {
        bar_sync(1 + w, 256);
        int ps = 0;
        #pragma unroll 1
        for (int kb = 0; kb < 8; kb++) {
          if (u < 2) mbar_wait(bars + B_AF + 8 * kb, 0);
          mbar_wait(bars + B_WF + 8 * s, ph);
          const uint32_t da = desc_lo(base + k_addrA(kb), 16), dw = desc_lo(base + k_addrW(s), 8192);
          wgmma_fence();
          kblock_n128<0>(acc0, da, dw, kb != 0);
          kblock_n128<512>(acc1, da, dw, kb != 0);
          wgmma_commit();
          if (kb == 7) bar_arrive(1 + (w ^ 1), 256);
          if (kb > 0) {
            wgmma_wait<1>();
            mbar_arrive_remote_if(x.rel + B_WE + 8 * ps, x.rel1);
            if (u == 7 && !(kb & 1)) {
              ring_release(x, kb == 2 ? 0 : kb - 3, false);
              if (kb > 2) ring_release(x, kb - 2, false);
            }
          }
          ps = s;
          if (++s == 6) { s = 0; ph ^= 1; }
        }
        Row t[2];
        const int lrow = blockIdx.x * 16 + w * 8 + warp4 * 2;
        if (u == w) { t[0] = ldg_row(xin + (size_t)lrow * DM, lane); t[1] = ldg_row(xin + (size_t)(lrow + 1) * DM, lane); }
        if (u == LN_AT || u == LN_AT + 1) {
          mbar_wait(bars + R_MOD, 0);
          t[0] = ldca_row(g_x.mod, lane); t[1] = ldca_row(g_x.mod + DM, lane);
        }
        wgmma_wait<0>();
        fence_regs(acc0); fence_regs(acc1);
        mbar_arrive_remote_if(x.rel + B_WE + 8 * ps, x.rel1);
        if (u == 6) { for (int k = 0; k < 5; k++) ring_release(x, k, false); }
        if (u >= 6) ring_release(x, 5, false);
        if (u == 7) {
          pack_tile(acc0, PA, 1.f, 1.f); pack_tile(acc1, PB, 1.f, 1.f);
          vtile = sp.khead[3] * 16 + mt;
          break;
        }
        s += 2; ph ^= 1; if (s >= 6) { s -= 6; ph ^= 1; }
        if (u == 0) bar_sync(7, 256);
        if (u == w) {
          float st[4] = {0.f, 0.f, 0.f, 0.f};
          #pragma unroll
          for (int i = 0; i < 32; i++) { const float v = row_at(t[i >> 4], i & 15); st[(i >> 4) * 2] += v; st[(i >> 4) * 2 + 1] = fmaf(v, v, st[(i >> 4) * 2 + 1]); }
          warp_sums(st);
          #pragma unroll
          for (int r = 0; r < 2; r++) { ln_stats(st[2*r], st[2*r+1]); xn[r] = ln_apply(t[r], st[2*r], st[2*r+1] * QSCALE); }
        }
        if ((u == LN_AT || u == LN_AT + 1)) {
          #pragma unroll
          for (int r = 0; r < 2; r++) {
            const Row hr = fma_row(xn[r], one_plus(t[1]), t[0]);
            __nv_bfloat16* hp = sched.h1 + (lrow & ~63) * DM + (lane >> 3) * 4096 + ((lrow + r) & 63) * 64 + (((lane ^ (lrow + r)) & 7) << 3);
            stg_v4(hp, hr.v[0], hr.v[1], hr.v[2], hr.v[3]); stg_v4(hp + 4 * 4096, hr.v[4], hr.v[5], hr.v[6], hr.v[7]);
          }
        }
        const int tile = sp.khead[u >> 1] * 16 + mt;
        __nv_bfloat16* dst = kv_tile(x, tile);
        uint32_t D[32];
        pack_tile(acc0, D, 1.f, 1.f); store_tile(dst + 2048, D);
        pack_tile(acc1, D, 1.f, 1.f); store_tile(dst, D);
        if (u == LN_AT || u == LN_AT + 1) publish(x, C_H1);
        publish(x, C_KV + (tile >> 4));
      }
    }
    const int last = attention(x, sp.item, nitems, rank, PA, PB, vtile);
    const int lane = wg_tid() & 31, cw = w * 4 + warp4;
    const int row0 = grp * 16 + cw * 2;
    const bool moe_cta = blockIdx.x < FF / 16;
    if (spare) { store_ctx(x, last, PB); __syncwarp(); cluster_arrive(); cluster_wait(); return; }
    const int kl = 3 * nsteps - 3;
    uint2* const yp = &g_x.yll[blockIdx.x][cw * 64 + (lane & 3) * 16 + (lane >> 2) * 2];
    Row ga, sb, cb, gb, wr;
    {
      float accA[64], accB[64];
      const int t0 = oent(0) == oent(1);
      uint32_t pa = 0, pb = 0;
      #pragma unroll 1
      for (int t = t0; t < 2 * nsteps - 2; t++) {
        const uint32_t eb = oent(3 * (t >> 1) + 2 * (t & 1)), ea = oent(3 * (t >> 1) + 1);
        o_wait_full(bars, eb);
        o_wait_full(bars, ea);
        const uint32_t da = desc_lo(base + w * 4096, 16) + (ea & 7) * 2048 + (t & 1) * 1024, db = desc_lo(base, 8192) + (eb & 7) * 2048;
        wgmma_fence();
        kblock_n128<0, 0, SW64>(accA, da, db, t != t0); kblock_n128<0, 1024, SW64>(accB, da, db, t != t0);
        wgmma_commit();
        if (t == CTX_T) store_ctx(x, last, PB);
        if (t > t0) { wgmma_wait<1>(); slot_release(x, pb, false); if (!(t & 1)) slot_release(x, pa, false); }
        pa = ea & 7; pb = eb & 7;
      }
      const uint32_t e0 = oent(kl), ea = oent(kl + 1), eb = oent(kl + 2);
      const uint32_t da = desc_lo(base + w * 4096, 16) + (ea & 7) * 2048;
      const uint32_t db0 = desc_lo(base, 8192) + (e0 & 7) * 2048, db1 = desc_lo(base, 8192) + (eb & 7) * 2048;
      ga = ldca_row(g_x.mod + 2 * DM, lane); sb = ldca_row(g_x.mod + 3 * DM, lane); cb = ldca_row(g_x.mod + 4 * DM, lane); gb = ldca_row(g_x.mod + 5 * DM, lane);
      wr = ldca_row(w_r, lane);
      if (moe_cta) st_tagged2(yp, 0, 0, 0);
      o_wait_full(bars, e0);
      o_wait_full(bars, ea);
      o_wait_full(bars, eb);
      wgmma_fence();
      kblock_n128<0, 0, SW64>(accA, da, db0, 1); kblock_n128<1024, 0, SW64>(accA, da, db1, 1);
      wgmma_commit();
      kblock_n128<0, 1024, SW64>(accB, da, db0, 1); kblock_n128<1024, 1024, SW64>(accB, da, db1, 1);
      wgmma_commit();
      __syncwarp();
      cluster_arrive();
      __nv_bfloat16* dst = sched.part + ((m * 8 + cw) * 8 + (ot >> 3)) * 4096;
      auto send = [&](const float (&acc)[64], int h) {
        uint32_t D[32];
        pack_tile(acc, D, 1.f, 1.f);
        #pragma unroll
        for (int i = 0; i < 8; i++) stg_v4(dst + (h * 8 + i) * 256 + ((lane ^ (h * 4 + (i >> 1))) << 3), D[4*i], D[4*i+1], D[4*i+2], D[4*i+3]);
      };
      wgmma_wait<1>();
      fence_regs(accA);
      send(accA, 0);
      o_wait_full(bars, eb);
      wgmma_wait<0>();
      fence_regs(accB);
      send(accB, 1);
      publish(x, C_PART + (m * 2 + w) * 32 + (ot >> 3));
    }
    asm volatile("setmaxnreg.dec.sync.aligned.u32 208;");
    const uint32_t sD = base + (oent(kl + 3) & 7) * 32768, sW = base + (oent(kl + 4) & 7) * 32768;
    o_wait_full(bars, oent(kl + 3)); o_wait_full(bars, oent(kl + 4));
    Row x1[2];
    #pragma unroll
    for (int r = 0; r < 2; r++) x1[r] = lds_row(sD + 16384 + (cw * 2 + r) * 1024, lane);
    uint4 wgv[4], wuv[4], wdv[4];
    #pragma unroll
    for (int r = 0; r < 4; r++) {
      const uint32_t k = (lane & 7) + ((lane >> 4) << 3), h = (lane & 8) * 2;
      wgv[r] = ldsm_x4_t(sW + (cw * 64 + r * 16 + k) * 32 + h);
      wuv[r] = ldsm_x4_t(sW + 16384 + (cw * 64 + r * 16 + k) * 32 + h);
      wdv[r] = ldsm_x4_t(sD + k * 1024 + (cw * 64 + r * 16) * 2 + h);
    }
    const Row cb1 = one_plus(cb);
    const unsigned int tag = lds_u32(base + SM_KEY + 48);
    float u[16], ub[2] = {0.f, 0.f};
    #pragma unroll
    for (int i = 0; i < 16; i++) { u[i] = row_at(cb1, i) * row_at(wr, i); ub[0] += u[i]; ub[1] = fmaf(row_at(sb, i), row_at(wr, i), ub[1]); }
    warp_sums(ub);
    float st[6] = {0.f, 0.f, 0.f, 0.f, 0.f, 0.f};
    uint32_t key[2];
    {
      const uint32_t po = base + ((lane & 7) * 2 + (cw >> 2)) * 512 + (cw & 3) * 128;
      Row av[2][2];
      #pragma unroll
      for (int k = 0; k < 4; k++) {
        mbar_wait(bars + R_PART + 8 * k, 1);
        const uint32_t pa = po + (oent(kl + (k >> 1)) & 7) * 32768 + (k & 1) * 16384;
        #pragma unroll
        for (int r = 0; r < 2; r++) {
          const uint32_t sw = ((r * 4 + (lane >> 3)) ^ (lane & 7)) << 4;
          const uint4 lo = ldsm_x4(pa + sw), hi = ldsm_x4(pa + 8192 + sw);
          const Row v{{lo.x, lo.y, lo.z, lo.w, hi.x, hi.y, hi.z, hi.w}};
          av[r][k >> 1] = (k & 1) ? add_row(av[r][k >> 1], v) : v;
        }
      }
      #pragma unroll
      for (int r = 0; r < 2; r++) {
        x1[r] = fma_row(ga, add_row(av[r][0], av[r][1]), x1[r]);
        #pragma unroll
        for (int i = 0; i < 16; i++) { const float v = row_at(x1[r], i); st[3*r] += v; st[3*r+1] = fmaf(v, v, st[3*r+1]); st[3*r+2] = fmaf(v, u[i], st[3*r+2]); }
      }
      warp_sums(st);
      #pragma unroll
      for (int r = 0; r < 2; r++) {
        ln_stats(st[3*r], st[3*r+1]);
        const uint32_t rb = __float_as_uint(fmaf(st[3*r+1], fmaf(-st[3*r], ub[0], st[3*r+2]), ub[1]));
        key[r] = (((rb & 0x80000000u) ? ~rb : (rb | 0x80000000u)) & 0xfffff000u) | (0xfffu - (uint32_t)(row0 + r));
      }
    }
    float* s_red = reinterpret_cast<float*>(smem_raw + SM_RED);
    uint32_t* s_key = reinterpret_cast<uint32_t*>(smem_raw + SM_KEY);
    const int rb = key[1] > key[0];
    const uint32_t wbest = rb ? key[1] : key[0];
    if (lane == 0) s_key[cw] = wbest;
    bar_sync(5, 256);
    const uint32_t cbest = __reduce_max_sync(0xffffffff, s_key[lane & 7]);
    if (wbest == cbest && lane == 0) st_tagged(&g_x.keys[grp][0], cbest, tag);
    Row xb, xo;
    #pragma unroll
    for (int i = 0; i < 8; i++) { xb.v[i] = rb ? x1[1].v[i] : x1[0].v[i]; xo.v[i] = rb ? x1[0].v[i] : x1[1].v[i]; }
    const Row hb = fma_row(ln_apply(xb, rb ? st[3] : st[0], rb ? st[4] : st[1]), cb1, sb);
    if (wbest == cbest) {
      #pragma unroll
      for (int i = 0; i < 4; i++) st_tagged2(&g_x.row[grp][0][i * 64 + lane * 2], hb.v[2*i], hb.v[2*i+1], tag);
      #pragma unroll
      for (int i = 0; i < 4; i++) st_tagged2(&g_x.row[grp][1][i * 64 + lane * 2], xb.v[2*i], xb.v[2*i+1], tag);
    }
    const Row ob = fma_row(gb, hb, xb);
    if (wbest != cbest) store_row(out + (size_t)(row0 + rb) * DM, lane, ob);
    store_row(out + (size_t)(row0 + 1 - rb) * DM, lane, fma_row(gb, fma_row(ln_apply(xo, rb ? st[0] : st[3], rb ? st[1] : st[4]), cb1, sb), xo));
    mbar_wait(bars + R_KEY, 1);
    if (moe_cta) {
      float cg[4] = {0, 0, 0, 0}, cu[4] = {0, 0, 0, 0};
      #pragma unroll
      for (int r = 0; r < 4; r++) {
        const uint32_t b0 = lds_u32(base + SM_H2 + (cw * 64 + r * 16) * 2 + (lane & 3) * 4), b1 = lds_u32(base + SM_H2 + (cw * 64 + r * 16) * 2 + 16 + (lane & 3) * 4);
        mma16816(cg, wgv[r], b0, b1); mma16816(cu, wuv[r], b0, b1);
      }
      s_red[cw * 32 + (lane & 3) * 8 + (lane >> 2)] = (lane & 2) ? ((lane & 1) ? cu[2] : cu[0]) : ((lane & 1) ? cg[2] : cg[0]);
      bar_sync(5, 256);
      float g = 0.f;
      #pragma unroll
      for (int i = 0; i < 8; i++) g += s_red[i * 32 + lane];
      g = rbf(g);
      const float act = rbf(__fdividef(g, 1.f + __expf(-g))) * __shfl_down_sync(0xffffffff, g, 16);
      const uint32_t a2 = pack_bf16(act, __shfl_down_sync(0xffffffff, act, 1));
      const uint32_t b0 = __shfl_sync(0xffffffff, a2, (lane & 3) * 2), b1 = __shfl_sync(0xffffffff, a2, (lane & 3) * 2 + 8);
      float y0 = 0.f, y1 = 0.f;
      #pragma unroll
      for (int r = 0; r < 4; r++) {
        float c[4] = {0, 0, 0, 0};
        mma16816(c, wdv[r], b0, b1);
        if ((lane & 3) == r) { y0 = c[0]; y1 = c[2]; }
      }
      st_tagged2(yp, __float_as_uint(y0), __float_as_uint(y1), tag);
    }
    bar_arrive(9, 384);
    if (wbest == cbest && wbest != s_key[8]) store_row(out + (size_t)(row0 + rb) * DM, lane, ob);
    __syncwarp();
    cluster_wait();
  }
}

typedef CUresult (*EncodeFn)(CUtensorMap*, CUtensorMapDataType, cuuint32_t, void*, const cuuint64_t*, const cuuint64_t*, const cuuint32_t*,
                             const cuuint32_t*, CUtensorMapInterleave, CUtensorMapSwizzle, CUtensorMapL2promotion, CUtensorMapFloatOOBfill);

struct HostState {
  bool ready = false;
  EncodeFn encode = nullptr;
  CUtensorMap tmC, tmWq, tmWk, tmWv, tmWo, tmWg, tmWu, tmWm;
  Sched sched;
};

void make_map(EncodeFn enc, CUtensorMap* m, const void* ptr, int rank, const cuuint64_t* dims, const cuuint64_t* strides, const cuuint32_t* box, bool swizzle = true) {
  const cuuint32_t es[3] = {1, 1, 1};
  enc(m, CU_TENSOR_MAP_DATA_TYPE_BFLOAT16, rank, const_cast<void*>(ptr), dims, strides, box, es, CU_TENSOR_MAP_INTERLEAVE_NONE,
      swizzle ? CU_TENSOR_MAP_SWIZZLE_128B : CU_TENSOR_MAP_SWIZZLE_NONE, swizzle ? CU_TENSOR_MAP_L2_PROMOTION_L2_128B : CU_TENSOR_MAP_L2_PROMOTION_NONE, CU_TENSOR_MAP_FLOAT_OOB_FILL_NONE);
}
void make_2d(EncodeFn enc, CUtensorMap* m, const void* ptr, int rows, int cols, int box_rows) {
  const cuuint64_t dims[2] = {(cuuint64_t)cols, (cuuint64_t)rows}, strides[1] = {(cuuint64_t)cols * 2};
  const cuuint32_t box[2] = {64, (cuuint32_t)box_rows};
  make_map(enc, m, ptr, 2, dims, strides, box);
}
void make_3d(EncodeFn enc, CUtensorMap* m, const void* ptr, int rows, int chunks, size_t row_stride, size_t chunk_stride) {
  const cuuint64_t dims[3] = {64, (cuuint64_t)rows, (cuuint64_t)chunks}, strides[2] = {row_stride, chunk_stride};
  const cuuint32_t box[3] = {64, 64, 2};
  make_map(enc, m, ptr, 3, dims, strides, box);
}

void make_ffn(EncodeFn enc, CUtensorMap* m, const void* ptr) {
  const cuuint64_t dims[2] = {(cuuint64_t)FF, (cuuint64_t)DM}, strides[1] = {(cuuint64_t)FF * 2};
  const cuuint32_t box[2] = {16, 256};
  make_map(enc, m, ptr, 2, dims, strides, box, false);
}

#define SR 0x213312
#define SEED 12345
#define LU_MARGIN 0
#define SPARE_N 3
void build_sched(Sched& s) {
  memset(&s, 0, sizeof(s));
  const int NP = NCTA / 2, korder[4] = {(KORDER >> 12) & 3, (KORDER >> 8) & 3, (KORDER >> 4) & 3, KORDER & 3};
  const int sround[4][2][3] = {{}, {{1}, {2}}, {{1, 2}, {1, 2}}, {{(SR >> 20) & 3, (SR >> 16) & 3, (SR >> 12) & 3}, {(SR >> 8) & 3, (SR >> 4) & 3, SR & 3}}};
  int jv[4][NP], used[4][8] = {};
  for (int r = 0; r < 4; r++) for (int p = 0; p < NP; p++) jv[r][p] = (r & 2) ? 7 - ((p + 4 * (r & 1)) & 7) : (p + 4 * (r & 1)) & 7;
  for (int q = 0; q < 2; q++) {
    s.pair[NP + q].nitems = SPARE_N;
    for (int i = 0; i < SPARE_N; i++) {
      const int r = sround[SPARE_N][q][i];
      s.pair[NP + q].item[i] = (uint8_t)((r * 8 + used[r][6]++) * 8 + 6);
      for (int p = 0; p < NP; p++) if (jv[r][p] == 6) { jv[r][p] = -2; break; }
    }
  }
  auto cost = [&](int p) {
    int u = 8 - ((p >> 4) < SPARE_N ? 21 : 22), z = 0, none = 0;
    for (int r = 0; r < 4; r++) { u += jv[r][p]; z += jv[r][p] == 0; none += jv[r][p] < 0; }
    return 4 * u * u + (z > 1) + 4 * (none > 1);
  };
  uint32_t rng = SEED;
  for (int it = 0; it < 2000000; it++) {
    if ((it & 255) == 0) { int t = 0; for (int p = 0; p < NP; p++) t += cost(p); if (t == 0) break; }
    rng = rng * 1664525u + 1013904223u;
    const int r = (rng >> 8) & 3, a = (rng >> 12) & 63, b = (rng >> 20) & 63, before = cost(a) + cost(b);
    int t = jv[r][a]; jv[r][a] = jv[r][b]; jv[r][b] = t;
    if (cost(a) + cost(b) > before) { jv[r][b] = jv[r][a]; jv[r][a] = t; }
  }
  int fin[256], done[256];
  for (int p = 0; p < NP + 2; p++) {
    Sched::Pair& q = s.pair[p];
    if (p < NP) {
      for (int k = 0; k < 4; k++) q.khead[k] = (uint8_t)(korder[k] * 8 + (p >> 3));
      for (int r = 0; r < 4; r++) {
        if (jv[r][p] < 0) continue;
        q.item[q.nitems++] = (uint8_t)((r * 8 + used[r][jv[r][p]]++) * 8 + jv[r][p]);
      }
    }
    int t = p < NP ? 0 : -3, e = 1;
    for (int i = 0; i < q.nitems; i++) { t += (q.item[i] & 7) + 2; fin[q.item[i]] = t; done[q.item[i]] = t + (i + 1 < q.nitems ? 2 : 0); e += 8 + 4 * ((q.item[i] & 7) + 1); }
    for (int k = 0; k < 3 * MAX_STEPS + 6; k++) {
      const int n = k > 0 ? k - (SPARE_N & 1) : 0, r = n % 7, f = (e + (r < 4 ? r : r - 1)) % 12;
      q.oent[k] = (uint8_t)((r == 4 ? 6 : f >= 6 ? f + 2 : f) ^ (((n / 7) & 1) << 3));
    }
  }
  for (int p = 0; p < NP + 2; p++)
    for (int i = 0; i < s.pair[p].nitems; i++) {
      const int it = s.pair[p].item[i];
      for (int n = 0; n < 2 * (it & 7) + 2; n++) {
        bool last = true;
        for (int j = n >> 1; j < 8; j++) { const int o = (it & ~7) + j; if (o != it && fin[o] + LU_MARGIN > fin[it]) last = false; }
        if (last) s.pair[p].lastuse[i] |= (uint16_t)(1 << n);
      }
    }
  for (int j = 0; j < 8; j++) {
    int order[NH], left[4];
    for (int h = 0; h < NH; h++) { int k = h; for (; k > 0 && done[order[k - 1] * 8 + j] < done[h * 8 + j]; k--) order[k] = order[k - 1]; order[k] = h; }
    for (int kq = 0; kq < 4; kq++) {
      left[kq] = SPARE_N == 0 ? 16 : kq < SPARE_N ? 20 - SPARE_N : 16 - SPARE_N;
      for (int nh = 0; nh < 2; nh++) { Sched::Pair& q = s.pair[kq * 16 + nh * 8 + j]; q.otask = (uint8_t)(kq * 16 + nh * 8 + j); q.nsteps = (uint8_t)((left[kq] + 1) / 2); q.ochunk[0][0] = 255; }
    }
    for (int n = 0, kq = 0, run = 0; n < 64; ) {
      if (left[kq] > 0 && run < 2) {
        const int pos = --left[kq] + (SPARE_N & 1);
        for (int nh = 0; nh < 2; nh++) s.pair[kq * 16 + nh * 8 + j].ochunk[pos >> 1][pos & 1] = (uint8_t)(order[n >> 1] * 2 + 1 - (n & 1));
        n++; run++;
      } else { kq = (kq + 1) & 3; run = 0; }
    }
  }
}

}

extern "C" void kernel_launch(void* const* d_in, const int* in_sizes, int n_in, void* d_out, int out_size) {
  (void)in_sizes; (void)n_in; (void)out_size;
  const __nv_bfloat16* x     = (const __nv_bfloat16*)d_in[0];
  const __nv_bfloat16* ckv   = (const __nv_bfloat16*)d_in[1];
  const __nv_bfloat16* w_q   = (const __nv_bfloat16*)d_in[2];
  const __nv_bfloat16* w_uk  = (const __nv_bfloat16*)d_in[3];
  const __nv_bfloat16* w_uv  = (const __nv_bfloat16*)d_in[4];
  const __nv_bfloat16* w_o   = (const __nv_bfloat16*)d_in[5];
  const __nv_bfloat16* w_r   = (const __nv_bfloat16*)d_in[7];
  const __nv_bfloat16* w_g   = (const __nv_bfloat16*)d_in[8];
  const __nv_bfloat16* w_u   = (const __nv_bfloat16*)d_in[9];
  const __nv_bfloat16* w_d   = (const __nv_bfloat16*)d_in[10];
  const __nv_bfloat16* cvec  = (const __nv_bfloat16*)d_in[11];
  const __nv_bfloat16* w_mod = (const __nv_bfloat16*)d_in[12];
  __nv_bfloat16* out = (__nv_bfloat16*)d_out;

  static HostState st;
  if (!st.ready) {
    void* fn = nullptr; cudaDriverEntryPointQueryResult qr;
    cudaGetDriverEntryPoint("cuTensorMapEncodeTiled", &fn, cudaEnableDefault, &qr);
    st.encode = (EncodeFn)fn;
    cudaFuncSetAttribute(k_fused, cudaFuncAttributeMaxDynamicSharedMemorySize, SMEM);
    build_sched(st.sched);
    void *p_kvc, *p_h1, *p_part;
    cudaGetSymbolAddress(&p_kvc, g_kvc); cudaGetSymbolAddress(&p_h1, g_h1); cudaGetSymbolAddress(&p_part, g_part);
    st.sched.kvc = (__nv_bfloat16*)p_kvc; st.sched.h1 = (__nv_bfloat16*)p_h1; st.sched.part = (__nv_bfloat16*)p_part;
    st.ready = true;
  }
  make_2d(st.encode, &st.tmC, ckv, SEQ, DM, 128);
  make_2d(st.encode, &st.tmWq, w_q, DM, NH * DH, 64);
  make_2d(st.encode, &st.tmWk, w_uk, DM, NH * DH, 64);
  make_2d(st.encode, &st.tmWv, w_uv, DM, NH * DH, 64);
  make_3d(st.encode, &st.tmWo, w_o, NH * DH, DM / 64, (size_t)DM * 2, 128);
  make_3d(st.encode, &st.tmWm, w_mod, DM, 6 * DM / 64, (size_t)6 * DM * 2, 128);
  make_ffn(st.encode, &st.tmWg, w_g);
  make_ffn(st.encode, &st.tmWu, w_u);

  k_fused<<<NGRID, 384, SMEM, cudaStreamPerThread>>>(st.tmC, st.tmWq, st.tmWk, st.tmWv, st.tmWo, st.tmWg, st.tmWu, st.tmWm, st.sched,
                                                     x, cvec, w_o, w_r, w_g, w_u, w_d, out);
}
```

```cpp
#include <cuda_runtime.h>
#include <cuda_bf16.h>
#include <cuda.h>
#include <stdint.h>
#include <string.h>
#include <math.h>

namespace {

constexpr int SEQ = 2048, DM = 512, NH = 32, DH = 128, FF = 1792;
constexpr int NCTA = 128, NGRID = 132;

__device__ __align__(128) __nv_bfloat16 g_kvc[192 * SEQ * 64];
__device__ __align__(128) __nv_bfloat16 g_h1[SEQ * DM];
__device__ __align__(128) __nv_bfloat16 g_part[128 * 8 * 4096];
constexpr int C_MOD = 0, C_MOD2 = 16, C_H1 = 32, C_KV = 64, C_CTX = 128, C_PART = 384, C_END = C_PART + 32 * 32;
struct Exchange {
  uint2 keys[128][4];
  uint2 row[128][2][DM / 2];
  uint2 yll[FF / 16][DM];
  __nv_bfloat16 mod[6 * DM];
  unsigned int cnt[C_END];
  unsigned int epoch;
};
__device__ __align__(4096) Exchange g_x;


__device__ __forceinline__ uint32_t smem_u32(const void* p) { return (uint32_t)__cvta_generic_to_shared(p); }
__device__ __forceinline__ int wg_tid() { int t; asm volatile("mov.u32 %0, %%tid.x;" : "=r"(t)); return t & 127; }
__device__ __forceinline__ void mbar_arrive(uint32_t bar) { asm volatile("mbarrier.arrive.shared::cta.b64 _, [%0];" :: "r"(bar) : "memory"); }
__device__ __forceinline__ uint32_t mapa(uint32_t addr, uint32_t cta) { uint32_t r; asm("mapa.shared::cluster.u32 %0, %1, %2;" : "=r"(r) : "r"(addr), "r"(cta)); return r; }
__device__ __forceinline__ void mbar_arrive_remote_if(uint32_t cluster_addr, bool pred) {
  asm volatile("{\n.reg .pred p;\nsetp.ne.u32 p, %1, 0;\n@p mbarrier.arrive.shared::cluster.b64 _, [%0];\n}" :: "r"(cluster_addr), "r"((uint32_t)pred) : "memory");
}
__device__ __forceinline__ bool mbar_try(uint32_t bar, uint32_t parity) {
  uint32_t done;
  asm volatile("{\n.reg .pred p;\nmbarrier.try_wait.parity.shared::cta.b64 p, [%1], %2;\nselp.u32 %0, 1, 0, p;\n}" : "=r"(done) : "r"(bar), "r"(parity) : "memory");
  return done;
}
__device__ __forceinline__ bool mbar_test2(uint32_t bar, uint32_t parity) {
  uint32_t done;
  asm volatile("{\n.reg .pred p, q;\nmbarrier.test_wait.parity.shared::cta.b64 p, [%1], %2;\nmbarrier.test_wait.parity.shared::cta.b64 q, [%1 + 8], %2;\n"
               "and.pred p, p, q;\nselp.u32 %0, 1, 0, p;\n}" : "=r"(done) : "r"(bar), "r"(parity) : "memory");
  return done;
}
#define WAIT_LIM (1 << 14)
__device__ __forceinline__ void mbar_wait(uint32_t bar, uint32_t parity) {
  #pragma unroll 1
  for (int n = 0; n < WAIT_LIM; n++) { if (mbar_try(bar, parity)) break; }
}
__device__ __forceinline__ unsigned int ld_acquire(const unsigned int* p) {
  unsigned int v; asm volatile("ld.acquire.gpu.global.u32 %0, [%1];" : "=r"(v) : "l"(p) : "memory"); return v;
}
__device__ __forceinline__ unsigned int ld_relaxed(const unsigned int* p) {
  unsigned int v; asm volatile("ld.relaxed.gpu.global.u32 %0, [%1];" : "=r"(v) : "l"(p) : "memory"); return v;
}
__device__ __forceinline__ void wait_count_lazy(int idx, unsigned int target) {
  #pragma unroll 1
  for (int n = 0; n < WAIT_LIM; n++) { if (__all_sync(0xffffffff, (int)(ld_relaxed(&g_x.cnt[idx]) - target) >= 0)) break; __nanosleep(100); }
  ld_acquire(&g_x.cnt[idx]);
}
__device__ __forceinline__ uint4 ld_tagged2(const void* p) {
  uint4 v;
  asm volatile("{\n.reg .b64 a, b;\nld.relaxed.gpu.global.v2.u64 {a, b}, [%4];\nmov.b64 {%0, %1}, a;\nmov.b64 {%2, %3}, b;\n}"
    : "=r"(v.x), "=r"(v.y), "=r"(v.z), "=r"(v.w) : "l"(p) : "memory");
  return v;
}
__device__ __forceinline__ uint2 ld_tagged(const void* p) {
  uint2 v; asm volatile("{\n.reg .b64 a;\nld.relaxed.gpu.global.u64 a, [%2];\nmov.b64 {%0, %1}, a;\n}" : "=r"(v.x), "=r"(v.y) : "l"(p) : "memory"); return v;
}
__device__ __forceinline__ void st_tagged2(void* p, uint32_t a, uint32_t b, uint32_t tag) {
  asm volatile("{\n.reg .b64 a, b;\nmov.b64 a, {%1, %3};\nmov.b64 b, {%2, %3};\nst.relaxed.gpu.global.v2.u64 [%0], {a, b};\n}" :: "l"(p), "r"(a), "r"(b), "r"(tag) : "memory");
}
__device__ __forceinline__ void st_tagged(void* p, uint32_t a, uint32_t tag) {
  asm volatile("{\n.reg .b64 a;\nmov.b64 a, {%1, %2};\nst.relaxed.gpu.global.u64 [%0], a;\n}" :: "l"(p), "r"(a), "r"(tag) : "memory");
}
__device__ __forceinline__ void stg_v4(void* p, uint32_t a, uint32_t b, uint32_t c, uint32_t d) {
  asm volatile("st.global.v4.u32 [%0], {%1, %2, %3, %4};" :: "l"(p), "r"(a), "r"(b), "r"(c), "r"(d) : "memory");
}
__device__ __forceinline__ uint4 lds_v4(uint32_t addr) {
  uint4 v; asm volatile("ld.shared.v4.u32 {%0, %1, %2, %3}, [%4];" : "=r"(v.x), "=r"(v.y), "=r"(v.z), "=r"(v.w) : "r"(addr) : "memory"); return v;
}
__device__ __forceinline__ uint32_t lds_u32(uint32_t addr) { uint32_t v; asm volatile("ld.shared.u32 %0, [%1];" : "=r"(v) : "r"(addr) : "memory"); return v; }
__device__ __forceinline__ void sts_v4(uint32_t addr, uint32_t a, uint32_t b, uint32_t c, uint32_t d) {
  asm volatile("st.shared.v4.u32 [%0], {%1, %2, %3, %4};" :: "r"(addr), "r"(a), "r"(b), "r"(c), "r"(d) : "memory");
}
#define ELECT "{\n.reg .pred p;\nelect.sync _|p, 0xffffffff;\n@p "
__device__ __forceinline__ void w_mbar_init(uint32_t bar, uint32_t cnt) { asm volatile(ELECT "mbarrier.init.shared::cta.b64 [%0], %1;\n}" :: "r"(bar), "r"(cnt) : "memory"); }
__device__ __forceinline__ void w_expect_tx(uint32_t bar, uint32_t bytes) { asm volatile(ELECT "mbarrier.arrive.expect_tx.shared::cta.b64 _, [%0], %1;\n}" :: "r"(bar), "r"(bytes) : "memory"); }
__device__ __forceinline__ void w_arrive(uint32_t bar) { asm volatile(ELECT "mbarrier.arrive.shared::cta.b64 _, [%0];\n}" :: "r"(bar) : "memory"); }
__device__ __forceinline__ void tma_load_2d(uint32_t dst, const CUtensorMap* tm, uint32_t bar, int c0, int c1) {
  asm volatile(ELECT "cp.async.bulk.tensor.2d.shared::cluster.global.mbarrier::complete_tx::bytes [%0], [%1, {%3, %4}], [%2];\n}"
    :: "r"(dst), "l"(tm), "r"(bar), "r"(c0), "r"(c1) : "memory");
}
__device__ __forceinline__ void tma_load_2d_mc(uint32_t dst, const CUtensorMap* tm, uint32_t bar, int c0, int c1) {
  asm volatile(ELECT "cp.async.bulk.tensor.2d.shared::cluster.global.mbarrier::complete_tx::bytes.multicast::cluster [%0], [%1, {%3, %4}], [%2], %5;\n}"
    :: "r"(dst), "l"(tm), "r"(bar), "r"(c0), "r"(c1), "h"((uint16_t)3) : "memory");
}
__device__ __forceinline__ void tma_load_3d(uint32_t dst, const CUtensorMap* tm, uint32_t bar, int c0, int c1, int c2) {
  asm volatile(ELECT "cp.async.bulk.tensor.3d.shared::cluster.global.mbarrier::complete_tx::bytes [%0], [%1, {%3, %4, %5}], [%2];\n}"
    :: "r"(dst), "l"(tm), "r"(bar), "r"(c0), "r"(c1), "r"(c2) : "memory");
}
__device__ __forceinline__ void tma_load_3d_mc(uint32_t dst, const CUtensorMap* tm, uint32_t bar, int c0, int c1, int c2) {
  asm volatile(ELECT "cp.async.bulk.tensor.3d.shared::cluster.global.mbarrier::complete_tx::bytes.multicast::cluster [%0], [%1, {%3, %4, %5}], [%2], %6;\n}"
    :: "r"(dst), "l"(tm), "r"(bar), "r"(c0), "r"(c1), "r"(c2), "h"((uint16_t)3) : "memory");
}
__device__ __forceinline__ void bulk_load_mc(uint32_t dst, const void* src, uint32_t bar, bool ef) {
  if (ef) {
    uint64_t pol; asm("createpolicy.fractional.L2::evict_first.b64 %0, 1.0;" : "=l"(pol));
    asm volatile(ELECT "cp.async.bulk.shared::cluster.global.mbarrier::complete_tx::bytes.multicast::cluster.L2::cache_hint [%0], [%1], 16384, [%2], %3, %4;\n}"
      :: "r"(dst), "l"(src), "r"(bar), "h"((uint16_t)3), "l"(pol) : "memory");
  } else
    asm volatile(ELECT "cp.async.bulk.shared::cluster.global.mbarrier::complete_tx::bytes.multicast::cluster [%0], [%1], 16384, [%2], %3;\n}"
      :: "r"(dst), "l"(src), "r"(bar), "h"((uint16_t)3) : "memory");
}
__device__ __forceinline__ void bulk_load(uint32_t dst, const void* src, uint32_t bytes, uint32_t bar) {
  asm volatile(ELECT "cp.async.bulk.shared::cluster.global.mbarrier::complete_tx::bytes [%0], [%1], %2, [%3];\n}" :: "r"(dst), "l"(src), "r"(bytes), "r"(bar) : "memory");
}
__device__ __forceinline__ void tma_prefetch_2d(const CUtensorMap* tm, int c0, int c1) {
  asm volatile(ELECT "cp.async.bulk.prefetch.tensor.2d.L2.global [%0, {%1, %2}];\n}" :: "l"(tm), "r"(c0), "r"(c1) : "memory");
}
__device__ __forceinline__ void bulk_prefetch(const void* p, uint32_t bytes) {
  asm volatile(ELECT "cp.async.bulk.prefetch.L2.global [%0], %1;\n}" :: "l"(p), "r"(bytes) : "memory");
}
__device__ __forceinline__ void red_release(int idx) { asm volatile("red.release.gpu.global.add.u32 [%0], 1;" :: "l"(&g_x.cnt[idx]) : "memory"); }
__device__ __forceinline__ void prefetch_tmap(const CUtensorMap* tm) { asm volatile("prefetch.tensormap [%0];" :: "l"(tm) : "memory"); }
__device__ __forceinline__ void bar_sync(int id, int n) { asm volatile("bar.sync %0, %1;" :: "r"(id), "r"(n) : "memory"); }
__device__ __forceinline__ void bar_arrive(int id, int n) { asm volatile("bar.arrive %0, %1;" :: "r"(id), "r"(n) : "memory"); }
__device__ __forceinline__ void fence_async_smem() { asm volatile("fence.proxy.async.shared::cta;" ::: "memory"); }
__device__ __forceinline__ void fence_async_global() { asm volatile("fence.proxy.async.global;" ::: "memory"); }
__device__ __forceinline__ void fence_mbar_init() { asm volatile("fence.mbarrier_init.release.cluster;" ::: "memory"); }
__device__ __forceinline__ void cluster_arrive() { asm volatile("barrier.cluster.arrive.relaxed.aligned;" ::: "memory"); }
__device__ __forceinline__ void cluster_wait() { asm volatile("barrier.cluster.wait.aligned;" ::: "memory"); }
__device__ __forceinline__ uint32_t cluster_ctarank() { uint32_t r; asm volatile("mov.u32 %0, %%cluster_ctarank;" : "=r"(r)); return r; }
__device__ __forceinline__ void wgmma_fence() { asm volatile("wgmma.fence.sync.aligned;" ::: "memory"); }
__device__ __forceinline__ void wgmma_commit() { asm volatile("wgmma.commit_group.sync.aligned;" ::: "memory"); }
template<int N> __device__ __forceinline__ void wgmma_wait() { asm volatile("wgmma.wait_group.sync.aligned %0;" :: "n"(N) : "memory"); }
__device__ __forceinline__ float ex2(float x) { float y; asm("ex2.approx.ftz.f32 %0, %1;" : "=f"(y) : "f"(x)); return y; }
__device__ __forceinline__ float rcp_fast(float x) { float y; asm("rcp.approx.ftz.f32 %0, %1;" : "=f"(y) : "f"(x)); return y; }
__device__ __forceinline__ uint32_t pack_bf16(float lo, float hi) { uint32_t r; asm("cvt.rn.bf16x2.f32 %0, %1, %2;" : "=r"(r) : "f"(hi), "f"(lo)); return r; }
__device__ __forceinline__ float rbf(float x) { return __uint_as_float(pack_bf16(0.f, x)); }
__device__ __forceinline__ float bf_lo(uint32_t v) { return __uint_as_float(v << 16); }
__device__ __forceinline__ float bf_hi(uint32_t v) { return __uint_as_float(v & 0xffff0000u); }
__device__ __forceinline__ uint32_t add2(uint32_t a, uint32_t b) { uint32_t r; asm("add.rn.bf16x2 %0, %1, %2;" : "=r"(r) : "r"(a), "r"(b)); return r; }
__device__ __forceinline__ uint32_t fma2(uint32_t a, uint32_t b, uint32_t c) { uint32_t r; asm("fma.rn.bf16x2 %0, %1, %2, %3;" : "=r"(r) : "r"(a), "r"(b), "r"(c)); return r; }
__device__ __forceinline__ uint4 ldsm_x4_t(uint32_t addr) {
  uint4 v; asm volatile("ldmatrix.sync.aligned.m8n8.x4.trans.shared.b16 {%0, %1, %2, %3}, [%4];" : "=r"(v.x), "=r"(v.y), "=r"(v.z), "=r"(v.w) : "r"(addr) : "memory"); return v;
}
__device__ __forceinline__ uint4 ldsm_x4(uint32_t addr) {
  uint4 v; asm volatile("ldmatrix.sync.aligned.m8n8.x4.shared.b16 {%0, %1, %2, %3}, [%4];" : "=r"(v.x), "=r"(v.y), "=r"(v.z), "=r"(v.w) : "r"(addr) : "memory"); return v;
}
__device__ __forceinline__ void mma16816(float (&c)[4], const uint4& a, uint32_t b0, uint32_t b1) {
  asm("mma.sync.aligned.m16n8k16.row.col.f32.bf16.bf16.f32 {%0, %1, %2, %3}, {%4, %5, %6, %7}, {%8, %9}, {%0, %1, %2, %3};"
    : "+f"(c[0]), "+f"(c[1]), "+f"(c[2]), "+f"(c[3]) : "r"(a.x), "r"(a.y), "r"(a.z), "r"(a.w), "r"(b0), "r"(b1));
}
template<int N> __device__ __forceinline__ void fence_regs(float (&a)[N]) {
  #pragma unroll
  for (int i = 0; i < N; i++) asm volatile("" : "+f"(a[i]) :: "memory");
}
template<int N> __device__ __forceinline__ void fence_regs_u(uint32_t (&a)[N]) {
  #pragma unroll
  for (int i = 0; i < N; i++) asm volatile("" : "+r"(a[i]) :: "memory");
}
constexpr uint32_t SW128 = 0x40000040u, SW64 = 0x80000020u;
__device__ __forceinline__ uint32_t desc_lo(uint32_t addr, uint32_t lbo) { return ((addr & 0x3FFFF) >> 4) | ((lbo >> 4) << 16); }

template<int TB, int OA, int OB, uint32_t HA, uint32_t HB> __device__ __forceinline__ void wgmma_ss_n128(float (&d)[64], uint32_t da, uint32_t db, int sd) {
  asm volatile("{\n.reg .pred p;\n.reg .b32 ta, tb;\n.reg .b64 da, db;\nsetp.ne.b32 p, %66, 0;\nadd.u32 ta, %64, %68;\nadd.u32 tb, %65, %69;\nmov.b64 da, {ta, %70};\nmov.b64 db, {tb, %71};\n"
    "wgmma.mma_async.sync.aligned.m64n128k16.f32.bf16.bf16 "
    "{%0, %1, %2, %3, %4, %5, %6, %7, %8, %9, %10, %11, %12, %13, %14, %15, %16, %17, %18, %19, %20, %21, %22, %23, %24, %25, %26, %27, %28, %29, %30, %31, %32, %33, %34, %35, %36, %37, %38, %39, %40, %41, %42, %43, %44, %45, %46, %47, %48, %49, %50, %51, %52, %53, %54, %55, %56, %57, %58, %59, %60, %61, %62, %63}, da, db, p, 1, 1, 0, %67;\n}\n"
    : "+f"(d[0]), "+f"(d[1]), "+f"(d[2]), "+f"(d[3]), "+f"(d[4]), "+f"(d[5]), "+f"(d[6]), "+f"(d[7]), "+f"(d[8]), "+f"(d[9]), "+f"(d[10]), "+f"(d[11]), "+f"(d[12]), "+f"(d[13]), "+f"(d[14]), "+f"(d[15]), "+f"(d[16]), "+f"(d[17]), "+f"(d[18]), "+f"(d[19]), "+f"(d[20]), "+f"(d[21]), "+f"(d[22]), "+f"(d[23]), "+f"(d[24]), "+f"(d[25]), "+f"(d[26]), "+f"(d[27]), "+f"(d[28]), "+f"(d[29]), "+f"(d[30]), "+f"(d[31]), "+f"(d[32]), "+f"(d[33]), "+f"(d[34]), "+f"(d[35]), "+f"(d[36]), "+f"(d[37]), "+f"(d[38]), "+f"(d[39]), "+f"(d[40]), "+f"(d[41]), "+f"(d[42]), "+f"(d[43]), "+f"(d[44]), "+f"(d[45]), "+f"(d[46]), "+f"(d[47]), "+f"(d[48]), "+f"(d[49]), "+f"(d[50]), "+f"(d[51]), "+f"(d[52]), "+f"(d[53]), "+f"(d[54]), "+f"(d[55]), "+f"(d[56]), "+f"(d[57]), "+f"(d[58]), "+f"(d[59]), "+f"(d[60]), "+f"(d[61]), "+f"(d[62]), "+f"(d[63])
    : "r"(da), "r"(db), "r"(sd), "n"(TB), "n"(OA), "n"(OB), "n"(HA), "n"(HB));
}
template<int TB, int OB, uint32_t HB> __device__ __forceinline__ void wgmma_rs_n128(float (&d)[64], uint32_t a0, uint32_t a1, uint32_t a2, uint32_t a3, uint32_t db, int sd) {
  asm volatile("{\n.reg .pred p;\n.reg .b32 tb;\n.reg .b64 db;\nsetp.ne.b32 p, %69, 0;\nadd.u32 tb, %68, %71;\nmov.b64 db, {tb, %72};\n"
    "wgmma.mma_async.sync.aligned.m64n128k16.f32.bf16.bf16 "
    "{%0, %1, %2, %3, %4, %5, %6, %7, %8, %9, %10, %11, %12, %13, %14, %15, %16, %17, %18, %19, %20, %21, %22, %23, %24, %25, %26, %27, %28, %29, %30, %31, %32, %33, %34, %35, %36, %37, %38, %39, %40, %41, %42, %43, %44, %45, %46, %47, %48, %49, %50, %51, %52, %53, %54, %55, %56, %57, %58, %59, %60, %61, %62, %63}, {%64,%65,%66,%67}, db, p, 1, 1, %70;\n}\n"
    : "+f"(d[0]), "+f"(d[1]), "+f"(d[2]), "+f"(d[3]), "+f"(d[4]), "+f"(d[5]), "+f"(d[6]), "+f"(d[7]), "+f"(d[8]), "+f"(d[9]), "+f"(d[10]), "+f"(d[11]), "+f"(d[12]), "+f"(d[13]), "+f"(d[14]), "+f"(d[15]), "+f"(d[16]), "+f"(d[17]), "+f"(d[18]), "+f"(d[19]), "+f"(d[20]), "+f"(d[21]), "+f"(d[22]), "+f"(d[23]), "+f"(d[24]), "+f"(d[25]), "+f"(d[26]), "+f"(d[27]), "+f"(d[28]), "+f"(d[29]), "+f"(d[30]), "+f"(d[31]), "+f"(d[32]), "+f"(d[33]), "+f"(d[34]), "+f"(d[35]), "+f"(d[36]), "+f"(d[37]), "+f"(d[38]), "+f"(d[39]), "+f"(d[40]), "+f"(d[41]), "+f"(d[42]), "+f"(d[43]), "+f"(d[44]), "+f"(d[45]), "+f"(d[46]), "+f"(d[47]), "+f"(d[48]), "+f"(d[49]), "+f"(d[50]), "+f"(d[51]), "+f"(d[52]), "+f"(d[53]), "+f"(d[54]), "+f"(d[55]), "+f"(d[56]), "+f"(d[57]), "+f"(d[58]), "+f"(d[59]), "+f"(d[60]), "+f"(d[61]), "+f"(d[62]), "+f"(d[63])
    : "r"(a0), "r"(a1), "r"(a2), "r"(a3), "r"(db), "r"(sd), "n"(TB), "n"(OB), "n"(HB));
}
template<int TB, int OA, int OB, uint32_t HA, uint32_t HB> __device__ __forceinline__ void wgmma_ss_n64(float (&d)[32], uint32_t da, uint32_t db, int sd) {
  asm volatile("{\n.reg .pred p;\n.reg .b32 ta, tb;\n.reg .b64 da, db;\nsetp.ne.b32 p, %34, 0;\nadd.u32 ta, %32, %36;\nadd.u32 tb, %33, %37;\nmov.b64 da, {ta, %38};\nmov.b64 db, {tb, %39};\n"
    "wgmma.mma_async.sync.aligned.m64n64k16.f32.bf16.bf16 "
    "{%0, %1, %2, %3, %4, %5, %6, %7, %8, %9, %10, %11, %12, %13, %14, %15, %16, %17, %18, %19, %20, %21, %22, %23, %24, %25, %26, %27, %28, %29, %30, %31}, da, db, p, 1, 1, 0, %35;\n}\n"
    : "+f"(d[0]), "+f"(d[1]), "+f"(d[2]), "+f"(d[3]), "+f"(d[4]), "+f"(d[5]), "+f"(d[6]), "+f"(d[7]), "+f"(d[8]), "+f"(d[9]), "+f"(d[10]), "+f"(d[11]), "+f"(d[12]), "+f"(d[13]), "+f"(d[14]), "+f"(d[15]), "+f"(d[16]), "+f"(d[17]), "+f"(d[18]), "+f"(d[19]), "+f"(d[20]), "+f"(d[21]), "+f"(d[22]), "+f"(d[23]), "+f"(d[24]), "+f"(d[25]), "+f"(d[26]), "+f"(d[27]), "+f"(d[28]), "+f"(d[29]), "+f"(d[30]), "+f"(d[31])
    : "r"(da), "r"(db), "r"(sd), "n"(TB), "n"(OA), "n"(OB), "n"(HA), "n"(HB));
}
template<int TB, int OA, int OB, uint32_t HA, uint32_t HB> __device__ __forceinline__ void wgmma_ss_n128_new(float (&d)[64], uint32_t da, uint32_t db) {
  asm volatile("{\n.reg .pred p;\n.reg .b32 ta, tb;\n.reg .b64 da, db;\nsetp.ne.b32 p, %66, 0;\nadd.u32 ta, %64, %68;\nadd.u32 tb, %65, %69;\nmov.b64 da, {ta, %70};\nmov.b64 db, {tb, %71};\n"
    "wgmma.mma_async.sync.aligned.m64n128k16.f32.bf16.bf16 "
    "{%0, %1, %2, %3, %4, %5, %6, %7, %8, %9, %10, %11, %12, %13, %14, %15, %16, %17, %18, %19, %20, %21, %22, %23, %24, %25, %26, %27, %28, %29, %30, %31, %32, %33, %34, %35, %36, %37, %38, %39, %40, %41, %42, %43, %44, %45, %46, %47, %48, %49, %50, %51, %52, %53, %54, %55, %56, %57, %58, %59, %60, %61, %62, %63}, da, db, p, 1, 1, 0, %67;\n}\n"
    : "=f"(d[0]), "=f"(d[1]), "=f"(d[2]), "=f"(d[3]), "=f"(d[4]), "=f"(d[5]), "=f"(d[6]), "=f"(d[7]), "=f"(d[8]), "=f"(d[9]), "=f"(d[10]), "=f"(d[11]), "=f"(d[12]), "=f"(d[13]), "=f"(d[14]), "=f"(d[15]), "=f"(d[16]), "=f"(d[17]), "=f"(d[18]), "=f"(d[19]), "=f"(d[20]), "=f"(d[21]), "=f"(d[22]), "=f"(d[23]), "=f"(d[24]), "=f"(d[25]), "=f"(d[26]), "=f"(d[27]), "=f"(d[28]), "=f"(d[29]), "=f"(d[30]), "=f"(d[31]), "=f"(d[32]), "=f"(d[33]), "=f"(d[34]), "=f"(d[35]), "=f"(d[36]), "=f"(d[37]), "=f"(d[38]), "=f"(d[39]), "=f"(d[40]), "=f"(d[41]), "=f"(d[42]), "=f"(d[43]), "=f"(d[44]), "=f"(d[45]), "=f"(d[46]), "=f"(d[47]), "=f"(d[48]), "=f"(d[49]), "=f"(d[50]), "=f"(d[51]), "=f"(d[52]), "=f"(d[53]), "=f"(d[54]), "=f"(d[55]), "=f"(d[56]), "=f"(d[57]), "=f"(d[58]), "=f"(d[59]), "=f"(d[60]), "=f"(d[61]), "=f"(d[62]), "=f"(d[63])
    : "r"(da), "r"(db), "n"(0), "n"(TB), "n"(OA), "n"(OB), "n"(HA), "n"(HB));
}
template<int TB, int OA, int OB, uint32_t HA, uint32_t HB> __device__ __forceinline__ void wgmma_ss_n64_new(float (&d)[32], uint32_t da, uint32_t db) {
  asm volatile("{\n.reg .pred p;\n.reg .b32 ta, tb;\n.reg .b64 da, db;\nsetp.ne.b32 p, %34, 0;\nadd.u32 ta, %32, %36;\nadd.u32 tb, %33, %37;\nmov.b64 da, {ta, %38};\nmov.b64 db, {tb, %39};\n"
    "wgmma.mma_async.sync.aligned.m64n64k16.f32.bf16.bf16 "
    "{%0, %1, %2, %3, %4, %5, %6, %7, %8, %9, %10, %11, %12, %13, %14, %15, %16, %17, %18, %19, %20, %21, %22, %23, %24, %25, %26, %27, %28, %29, %30, %31}, da, db, p, 1, 1, 0, %35;\n}\n"
    : "=f"(d[0]), "=f"(d[1]), "=f"(d[2]), "=f"(d[3]), "=f"(d[4]), "=f"(d[5]), "=f"(d[6]), "=f"(d[7]), "=f"(d[8]), "=f"(d[9]), "=f"(d[10]), "=f"(d[11]), "=f"(d[12]), "=f"(d[13]), "=f"(d[14]), "=f"(d[15]), "=f"(d[16]), "=f"(d[17]), "=f"(d[18]), "=f"(d[19]), "=f"(d[20]), "=f"(d[21]), "=f"(d[22]), "=f"(d[23]), "=f"(d[24]), "=f"(d[25]), "=f"(d[26]), "=f"(d[27]), "=f"(d[28]), "=f"(d[29]), "=f"(d[30]), "=f"(d[31])
    : "r"(da), "r"(db), "n"(0), "n"(TB), "n"(OA), "n"(OB), "n"(HA), "n"(HB));
}
template<int OA, int OB = 0, uint32_t HA = SW128> __device__ __forceinline__ void kblock_n128(float (&d)[64], uint32_t da, uint32_t db, int sd) {
  constexpr int H = HA == SW128 ? 4 : 512;
  wgmma_ss_n128<1, OA, OB, HA, SW128>(d, da, db, sd); wgmma_ss_n128<1, OA + 2, OB + 128, HA, SW128>(d, da, db, 1);
  wgmma_ss_n128<1, OA + H, OB + 256, HA, SW128>(d, da, db, 1); wgmma_ss_n128<1, OA + H + 2, OB + 384, HA, SW128>(d, da, db, 1);
}

__device__ __forceinline__ float quad_sum(float v) {
  v += __shfl_xor_sync(0xffffffff, v, 1);
  v += __shfl_xor_sync(0xffffffff, v, 2);
  return v;
}
struct Row { uint32_t v[8]; };
template<class F> __device__ __forceinline__ Row load_row(const __nv_bfloat16* p, int lane, F ld) {
  const uint4 a = ld(reinterpret_cast<const uint4*>(p) + lane), b = ld(reinterpret_cast<const uint4*>(p) + 32 + lane);
  return Row{{a.x, a.y, a.z, a.w, b.x, b.y, b.z, b.w}};
}
__device__ __forceinline__ Row ldg_row(const __nv_bfloat16* p, int lane) { return load_row(p, lane, [](const uint4* q) { return __ldg(q); }); }
__device__ __forceinline__ Row ldca_row(const __nv_bfloat16* p, int lane) { return load_row(p, lane, [](const uint4* q) { return __ldca(q); }); }
__device__ __forceinline__ Row lds_row(uint32_t addr, int lane) {
  const uint4 a = lds_v4(addr + lane * 16), b = lds_v4(addr + 512 + lane * 16);
  return Row{{a.x, a.y, a.z, a.w, b.x, b.y, b.z, b.w}};
}
__device__ __forceinline__ void store_row(__nv_bfloat16* p, int lane, const Row& r) {
  stg_v4(p + lane * 8, r.v[0], r.v[1], r.v[2], r.v[3]); stg_v4(p + 256 + lane * 8, r.v[4], r.v[5], r.v[6], r.v[7]);
}
__device__ __forceinline__ Row fma_row(const Row& a, const Row& b, const Row& c) {
  Row r;
  #pragma unroll
  for (int i = 0; i < 8; i++) r.v[i] = fma2(a.v[i], b.v[i], c.v[i]);
  return r;
}
__device__ __forceinline__ Row add_row(const Row& a, const Row& b) {
  Row r;
  #pragma unroll
  for (int i = 0; i < 8; i++) r.v[i] = add2(a.v[i], b.v[i]);
  return r;
}
__device__ __forceinline__ Row one_plus(const Row& a) {
  Row r;
  #pragma unroll
  for (int i = 0; i < 8; i++) r.v[i] = add2(a.v[i], 0x3f803f80u);
  return r;
}
__device__ __forceinline__ float row_at(const Row& x, int i) { return (i & 1) ? bf_hi(x.v[i >> 1]) : bf_lo(x.v[i >> 1]); }
template<int N> __device__ __forceinline__ void warp_sums(float (&s)[N]) {
  #pragma unroll
  for (int o = 16; o > 0; o >>= 1) {
    #pragma unroll
    for (int k = 0; k < N; k++) s[k] += __shfl_xor_sync(0xffffffff, s[k], o);
  }
}
__device__ __forceinline__ void ln_stats(float& s1, float& s2) {
  s1 *= 1.f / DM;
  asm("rsqrt.approx.ftz.f32 %0, %1;" : "=f"(s2) : "f"(fmaxf(fmaf(-s1, s1, s2 * (1.f / DM)), 0.f) + 1e-5f));
}
__device__ __forceinline__ Row ln_apply(const Row& x, float mean, float f) {
  Row n;
  const float o = -mean * f;
  #pragma unroll
  for (int i = 0; i < 8; i++) n.v[i] = pack_bf16(fmaf(bf_lo(x.v[i]), f, o), fmaf(bf_hi(x.v[i]), f, o));
  return n;
}

constexpr int SM_Q = 6 * 32768, SM_BAR = 7 * 32768, SM_MAIL = SM_BAR + 640, SM_RED = SM_MAIL + 128, SM_H2 = SM_RED + 1024, SM_KEY = SM_H2 + 1024, SMEM = SM_KEY + 128;
constexpr int B_AF = 0, B_WF = 64, B_RF = 112, B_WE = 168, B_RE = 216, B_PUB = 272, B_RDY = 496;
constexpr int R_MOD = B_RDY, R_H1 = B_RDY + 8, R_ITEM = B_RDY + 16, R_NEAR = B_RDY + 48, R_CTX = B_RDY + 64;
constexpr int R_KEY = B_AF + 8, R_PART = B_AF + 32;
constexpr int NPUB = 14;
__device__ __forceinline__ uint32_t k_addrA(int kb) { return ((0x6310u >> ((kb >> 1) * 4)) & 15u) * 32768u + (kb & 1) * 16384u; }
__device__ __forceinline__ uint32_t k_addrW(int s) { return ((0x254u >> ((s >> 1) * 4)) & 15u) * 32768u + (s & 1) * 16384u; }

#define KORDER 0x3201
constexpr int KHEAD0 = ((KORDER >> 12) & 3) * 8;
constexpr int MAX_ITEMS = 4;
constexpr int MAX_STEPS = 10;
struct Sched {
  __nv_bfloat16 *kvc, *h1, *part;
  struct Pair {
    uint8_t oent[3 * MAX_STEPS + 6];
    uint16_t lastuse[MAX_ITEMS];
    uint8_t khead[4];
    uint8_t nitems, item[MAX_ITEMS];
    uint8_t otask, nsteps;
    uint8_t ochunk[MAX_STEPS][2];
  } pair[NGRID / 2];
};

__device__ __forceinline__ int ring_add(int e, int n) { e += n; return e >= 12 ? e - 12 : e; }
__device__ __forceinline__ int ring_slot(int e) { return e >= 6 ? e - 6 : e; }
__device__ __forceinline__ void ring_wait_full(uint32_t bars, int e) { mbar_wait(bars + B_RF + 8 * ring_slot(e), e >= 6); }

__device__ __forceinline__ void o_wait_full(uint32_t bars, uint32_t v) { mbar_wait(bars + B_RF + 8 * (v & 7), v >> 3); }

struct Ctx {
  uint32_t base, bars;
  uint32_t rel;
  bool rel1;
  int w, nev;
  const Sched* sched;
};
__device__ __forceinline__ void slot_release(const Ctx& x, int s, bool twice) {
  mbar_arrive_remote_if(x.rel + B_RE + 8 * s, twice ? (wg_tid() & 31) == 0 : x.rel1);
}
__device__ __forceinline__ void ring_release(const Ctx& x, int e, bool twice) { slot_release(x, ring_slot(e), twice); }
__device__ __forceinline__ void publish(Ctx& x, int idx) {
  const uint32_t n = x.w * NPUB + x.nev;
  const int t = wg_tid();
  if (t == 0) asm volatile("st.shared.u32 [%0], %1;" :: "r"(x.base + SM_MAIL + 4 * n), "r"(idx) : "memory");
  __syncwarp();
  if ((t & 31) == 0) mbar_arrive(x.bars + B_PUB + 8 * n);
  x.nev++;
}

template<int KK = 0> __device__ __forceinline__ void issue_qk(float (&S)[64], uint32_t dq, uint32_t dk) {
  constexpr int off = (KK >> 1) * 512 + (KK & 1) * 2;
  if constexpr (KK == 0) wgmma_ss_n128_new<0, 0, 0, SW64, SW64>(S, dq, dk); else wgmma_ss_n128<0, off, off, SW64, SW64>(S, dq, dk, 1);
  if constexpr (KK < 7) issue_qk<KK + 1>(S, dq, dk);
}
template<int KK = 0> __device__ __forceinline__ void issue_qk_half(float (&S)[32], uint32_t dq, uint32_t dk) {
  constexpr int off = (KK >> 1) * 512 + (KK & 1) * 2;
  if constexpr (KK == 0) wgmma_ss_n64_new<0, 0, 256, SW64, SW64>(S, dq, dk); else wgmma_ss_n64<0, off, off + 256, SW64, SW64>(S, dq, dk, 1);
  if constexpr (KK < 7) issue_qk_half<KK + 1>(S, dq, dk);
}
template<int NK, int KK = 0>
__device__ __forceinline__ void issue_pv(float (&O)[64], uint32_t (&P)[32], uint32_t dv, int accumulate) {
  wgmma_rs_n128<1, (KK + 8 - NK) * 64, SW64>(O, P[4*KK], P[4*KK+1], P[4*KK+2], P[4*KK+3], dv, accumulate);
  if constexpr (KK + 1 < NK) issue_pv<NK, KK + 1>(O, P, dv, 1);
}
template<int K0, int K1>
__device__ __forceinline__ void exp_pack(const float (&S)[64], uint32_t (&D)[32], float& s0, float& s1) {
  #pragma unroll
  for (int k = K0; k < K1; k++) {
    const float e0 = ex2(S[2*k]), e1 = ex2(S[2*k+1]);
    D[k] = pack_bf16(e0, e1);
    if (k & 1) s1 += e0 + e1; else s0 += e0 + e1;
  }
}
__device__ __forceinline__ int diag_limit() { const int t = wg_tid(); return 16 * (t >> 5) + ((t & 31) >> 2) - 2 * (t & 3); }
__device__ __forceinline__ void exp_pack_diag(const float (&S)[64], uint32_t (&D)[32], int t, float& s0, float& s1) {
  #pragma unroll
  for (int k = 0; k < 16; k++) {
    const int c = 8 * (k >> 1) - 8 * (k & 1);
    const float e0 = ex2((c <= t) ? S[2*k] : -INFINITY), e1 = ex2((c + 1 <= t) ? S[2*k+1] : -INFINITY);
    D[k] = pack_bf16(e0, e1);
    if (k & 1) s1 += e0 + e1; else s0 += e0 + e1;
  }
}
constexpr float SUM_HI = 1.8446744073709552e19f;
constexpr float SUM_LO = 5.421010862427522e-20f;

__device__ __forceinline__ void classic_tile(const float (&S)[64], uint32_t (&P)[32], bool fresh, bool half, bool was_classic, volatile float* mc,
                                             float& l0, float& l1, float& s0, float& s1, float& sc0, float& sc1) {
  const int tmask = diag_limit();
  float4 t[16];
  #pragma unroll
  for (int j = 0; j < 16; j++) t[j] = make_float4(S[4*j], S[4*j+1], S[4*j+2], S[4*j+3]);
  float mx0 = -INFINITY, mx1 = -INFINITY;
  #pragma unroll 1
  for (int j = 0; j < 16; j++) {
    float4 v = t[j];
    const int lim = !fresh ? 1000 : j < 8 ? tmask - 8 * j : half ? -1000 : 1000;
    v.x = 0 <= lim ? v.x : -INFINITY; v.y = 1 <= lim ? v.y : -INFINITY; v.z = -8 <= lim ? v.z : -INFINITY; v.w = -7 <= lim ? v.w : -INFINITY;
    t[j] = v;
    mx0 = fmaxf(mx0, fmaxf(v.x, v.y)); mx1 = fmaxf(mx1, fmaxf(v.z, v.w));
  }
  mx0 = fmaxf(mx0, __shfl_xor_sync(0xffffffff, mx0, 1));
  mx1 = fmaxf(mx1, __shfl_xor_sync(0xffffffff, mx1, 1));
  mx0 = fmaxf(mx0, __shfl_xor_sync(0xffffffff, mx0, 2));
  mx1 = fmaxf(mx1, __shfl_xor_sync(0xffffffff, mx1, 2));
  const float mc0 = was_classic ? mc[0] : 0.f, mc1 = was_classic ? mc[1] : 0.f;
  const float n0 = fresh ? -mx0 : fminf(mc0, -mx0), n1 = fresh ? -mx1 : fminf(mc1, -mx1);
  sc0 = ex2(n0 - mc0); sc1 = ex2(n1 - mc1);
  mc[0] = n0; mc[1] = n1;
  s0 = 0.f; s1 = 0.f;
  #pragma unroll 1
  for (int j = 0; j < 16; j++) {
    const float4 v = t[j];
    const float e0 = ex2(v.x + n0), e1 = ex2(v.y + n0), e2 = ex2(v.z + n1), e3 = ex2(v.w + n1);
    s0 += e0 + e1; s1 += e2 + e3;
    reinterpret_cast<uint2*>(t)[j] = make_uint2(pack_bf16(e0, e1), pack_bf16(e2, e3));
  }
  #pragma unroll
  for (int j = 0; j < 8; j++) { P[4*j] = __float_as_uint(t[j].x); P[4*j+1] = __float_as_uint(t[j].y); P[4*j+2] = __float_as_uint(t[j].z); P[4*j+3] = __float_as_uint(t[j].w); }
  if (!fresh) { l0 *= sc0; l1 *= sc1; }
}
__device__ __forceinline__ void pack_tile(const float (&A)[64], uint32_t (&D)[32], float f0, float f1) {
  #pragma unroll
  for (int j = 0; j < 16; j++) {
    D[8 * (j >> 2) + (j & 3)] = pack_bf16(A[4*j] * f0, A[4*j+1] * f0);
    D[8 * (j >> 2) + 4 + (j & 3)] = pack_bf16(A[4*j+2] * f1, A[4*j+3] * f1);
  }
}
__device__ __forceinline__ int piece0(int t) { return ((t >> 5) * 16 + ((t & 31) >> 2)) * 32 + (((t ^ (t >> 3)) & 3) << 3); }
__device__ __forceinline__ void store_tile(__nv_bfloat16* p, const uint32_t (&D)[32]) {
  #pragma unroll
  for (int i = 0; i < 8; i++) stg_v4(p + (i >> 2) * (SEQ * 64) + ((i >> 1) & 1) * 4096 + (i & 1) * 256, D[4*i], D[4*i+1], D[4*i+2], D[4*i+3]);
}

enum : int { PV_ACC = 0, PV_ZERO = 1, PV_HALF = 2, PV_NONE = 3 };
struct Att {
  float l0, l1, i0, i1;
  bool classic;
  volatile float* mc;
};
__device__ __forceinline__ void store_ctx(Ctx& x, int code, const uint32_t (&D)[32]) {
  store_tile(x.sched->kvc + ((size_t)(128 + (code >> 5) * 2) * SEQ + ((code >> 1) & 15) * 128) * 64 + (code & 1) * 2048 + piece0(wg_tid()), D);
  publish(x, C_CTX + (code >> 2));
}
__device__ __forceinline__ __nv_bfloat16* kv_tile(const Ctx& x, int code) {
  return x.sched->kvc + ((size_t)(x.w * 64 + (code >> 4) * 2) * SEQ + (code & 15) * 128) * 64 + piece0(wg_tid());
}
__device__ __forceinline__ void q_proj(Ctx& x, Att& a, int& e, int& sk, int& sv, int& en, int& sn, bool isY,
                                       const uint32_t (&PA)[32], const uint32_t (&PB)[32], int vtile, bool first) {
  float S[64];
  int ek = 0, s = sk, ps = 0, ph = e >= 6, kb = 0;
  uint32_t qa = 0;
  sv = en = sn = 0;
  if (isY) bar_sync(1 + x.w, 256);
  if (first) mbar_wait(x.bars + B_RF + 8 * s, ph);
  #pragma unroll 1
  while (true) {
    #pragma unroll 1
    do {
      wgmma_fence();
      kblock_n128<0>(S, desc_lo(x.base + x.w * 8192, 16) + s * 2048, desc_lo(x.base + 16384, 8192) + s * 2048, kb != 0);
      wgmma_commit();
      if (kb == 7 && !isY) bar_arrive(1 + (x.w ^ 1), 256);
      wgmma_wait<1>();
      mbar_arrive_remote_if(x.rel + B_RE + 8 * ps, x.rel1 && kb > 0);
      ps = s;
      if (++s == 6) { s = 0; ph ^= 1; }
      if (++kb == 8) break;
      mbar_wait(x.bars + B_RF + 8 * s, ph);
    } while (kb != 4);
    asm volatile("" : "+r"(vtile));
    if (kb == 8) break;
    a.i0 = rcp_fast(quad_sum(a.l0)); a.i1 = rcp_fast(quad_sum(a.l1));
    e = ring_add(e, 8); ek = ring_add(e, isY ? 0 : 2); en = ring_add(e, isY ? 2 : 4);
    sk = ring_slot(ek); sv = ring_slot(e) + 1; sn = ring_slot(en);
    qa = x.base + SM_Q + x.w * 4096 + piece0(wg_tid()) * 2;
    if (vtile >= 0) store_tile(kv_tile(x, vtile) + 2048, PA);
  }
  if (vtile >= 0) { store_tile(kv_tile(x, vtile), PB); publish(x, C_KV + (vtile >> 4)); }
  wgmma_wait<0>();
  fence_regs(S);
  slot_release(x, ps, false);
  const bool landed = isY && mbar_test2(x.bars + B_RF + 8 * sk, e >= 6);
  #pragma unroll
  for (int i = 0; i < 8; i++) {
    const int j = 4 * (i >> 1), o = 2 * (i & 1);
    sts_v4(qa + (i >> 1) * 8192 + (i & 1) * 512,
           pack_bf16(S[4*j+o], S[4*j+o+1]), pack_bf16(S[4*j+4+o], S[4*j+5+o]), pack_bf16(S[4*j+8+o], S[4*j+9+o]), pack_bf16(S[4*j+12+o], S[4*j+13+o]));
  }
  fence_async_smem();
  if (!landed) { mbar_wait(x.bars + B_RF + 8 * sk, ek >= 6); mbar_wait(x.bars + B_RF + 8 * sv, e >= 6); }
}

template<int KIND>
__device__ __forceinline__ void slot(Ctx& x, Att& a, int& e, int& sk, int sv, int en, int sn, float (&O)[64], uint32_t (&Pn)[32], uint32_t (&Po)[32],
                                     bool more, bool isY, bool half, int pv, int pend) {
  float S[64];
  const int w = x.w;
  const uint32_t dq = desc_lo(x.base + SM_Q + w * 4096, 16), dk = desc_lo(x.base, 16) + sk * 2048, dv = desc_lo(x.base, 8192) + sv * 2048;
  bar_sync(1 + w, 256);
  if (KIND == 2) {
    wgmma_fence();
    issue_qk(S, dq, dk); wgmma_commit();
    issue_pv<8>(O, Po, dv, 1); wgmma_commit();
    bar_arrive(1 + (w ^ 1), 256);
    wgmma_wait<1>();
  } else if (KIND == 0 && half) {
    float T[32];
    wgmma_fence(); issue_qk_half(T, dq, dk); wgmma_commit();
    if (pv == PV_NONE) { wgmma_fence(); wgmma_commit(); }
    else               { wgmma_fence(); issue_pv<8>(O, Po, dv, pv == PV_ACC); wgmma_commit(); }
    bar_arrive(1 + (w ^ 1), 256);
    wgmma_wait<1>();
    fence_regs(T);
    #pragma unroll
    for (int i = 0; i < 32; i++) { S[i] = T[i]; asm volatile("" : "=f"(S[32 + i])); }
  } else {
    wgmma_fence(); issue_qk(S, dq, dk); wgmma_commit();
    if (KIND == 1 && pend >= 0) { bar_arrive(1 + (w ^ 1), 256); pack_tile(O, Pn, a.i0, a.i1); store_ctx(x, pend, Pn); }
    if (KIND == 0 && pv == PV_NONE) { wgmma_fence(); wgmma_commit(); }
    else if (pv == PV_HALF)         { wgmma_fence(); issue_pv<4>(O, Po, dv, 0); wgmma_commit(); }
    else                            { wgmma_fence(); issue_pv<8>(O, Po, dv, pv == PV_ACC); wgmma_commit(); }
    if (KIND == 0 || pend < 0) bar_arrive(1 + (w ^ 1), 256);
    wgmma_wait<1>();
  }
  fence_regs(S);
  fence_regs_u(Pn);
  slot_release(x, sk, KIND == 0 && isY);
  const bool landed = mbar_test2(x.bars + B_RF + 8 * sn, en >= 6);
  float s0 = 0.f, s1 = 0.f;
  const bool was_classic = KIND != 0 && a.classic;
  if (KIND == 0) {
    a.l0 = 0.f; a.l1 = 0.f;
    if (!half) exp_pack<16, 32>(S, Pn, s0, s1);
    else {
      #pragma unroll
      for (int i = 16; i < 32; i++) asm volatile("" : "=r"(Pn[i]));
    }
    exp_pack_diag(S, Pn, diag_limit(), s0, s1);
    uint32_t b0 = __ballot_sync(0xffffffff, s0 >= SUM_LO), b1 = __ballot_sync(0xffffffff, s1 >= SUM_LO);
    b0 |= b0 >> 1; b0 |= b0 >> 2; b1 |= b1 >> 1; b1 |= b1 >> 2;
    a.classic = __any_sync(0xffffffff, !(s0 <= SUM_HI && s1 <= SUM_HI)) || (b0 & b1 & 0x11111111u) != 0x11111111u;
  } else {
    exp_pack<0, 32>(S, Pn, s0, s1);
    a.classic = __any_sync(0xffffffff, a.classic || !(s0 <= SUM_HI && s1 <= SUM_HI));
  }
  fence_regs_u(Pn);
  if (!landed) {
    mbar_wait(x.bars + B_RF + 8 * sn, en >= 6);
    if (more) mbar_wait(x.bars + B_RF + 8 * sn + 8, en >= 6);
  }
  wgmma_wait<0>();
  fence_regs(O);
  fence_regs_u(Po);
  slot_release(x, sv, KIND == 1 && isY && pv != PV_ACC);
  if (__builtin_expect(a.classic, 0)) {
    float sc0, sc1;
    classic_tile(S, Pn, KIND == 0, half, was_classic, a.mc, a.l0, a.l1, s0, s1, sc0, sc1);
    if (KIND != 0) {
      #pragma unroll
      for (int j = 0; j < 16; j++) { O[4*j] *= sc0; O[4*j+1] *= sc0; O[4*j+2] *= sc1; O[4*j+3] *= sc1; }
    }
  }
  a.l0 += s0; a.l1 += s1;
  e = en; sk = sn;
}

__device__ __forceinline__ int attention(Ctx& x, const uint8_t* items, int nitems, int rank, uint32_t (&PA)[32], uint32_t (&PB)[32], int vtile) {
  int e = 0, sk = 0;
  float O[64];
  Att a;
  volatile float mc[2];
  a.l0 = 1.f; a.l1 = 1.f; a.i0 = 0.f; a.i1 = 0.f; a.classic = false; a.mc = mc;
  int pv = PV_NONE, cur = -1;
  #pragma unroll 1
  for (int it = 0; ; it++) {
    const bool isY = (it & 1) == x.w;
    int pend = cur;
    if (it < nitems) {
      const bool half = isY == (rank != 0);
      int sv, en, sn;
      q_proj(x, a, e, sk, sv, en, sn, isY, PA, PB, vtile, it == 0);
      vtile = -1;
      const int item = items[it];
      cur = item * 4 + (isY ? 3 - rank : rank);
      int rem = 2 * (item & 7) + (isY ? 1 : 0);
      slot<0>(x, a, e, sk, sv, en, sn, O, PA, PB, rem > 0, isY, half, pv, -1);
      pv = half ? PV_HALF : PV_ZERO;
      #pragma unroll 1
      while (rem > 0) {
        slot<1>(x, a, e, sk, sk + 1, ring_add(e, 2), sk == 4 ? 0 : sk + 2, O, PB, PA, rem > 1, isY, false, pv, pend);
        pv = PV_ACC; pend = -1;
        if (rem == 1) break;
        rem -= 2;
        slot<2>(x, a, e, sk, sk + 1, ring_add(e, 2), sk == 4 ? 0 : sk + 2, O, PA, PB, rem > 0, false, false, 0, -1);
      }
      if (isY) continue;
    } else {
      slot_release(x, 6, false);
      const uint32_t dv = desc_lo(x.base, 8192) + sk * 2048;
      bar_sync(1 + x.w, 256);
      if (pv == PV_HALF) { wgmma_fence(); issue_pv<4>(O, PB, dv, 0); wgmma_commit(); }
      else { wgmma_fence(); issue_pv<8>(O, PB, dv, pv == PV_ACC); wgmma_commit(); }
      if (isY) bar_arrive(1 + (x.w ^ 1), 256);
      a.i0 = rcp_fast(quad_sum(a.l0)); a.i1 = rcp_fast(quad_sum(a.l1));
      ring_wait_full(x.bars, e);
      wgmma_wait<0>();
      fence_regs(O);
      fence_regs_u(PB);
      slot_release(x, sk, false);
    }
    if (pend >= 0) {
      pack_tile(O, PB, a.i0, a.i1);
      if (it == nitems) return pend;
      store_ctx(x, pend, PB);
    }
    #pragma unroll
    for (int i = 0; i < 32; i++) asm volatile("mov.b32 %0, %1;" : "=r"(PB[i]) : "r"(PA[i]));
  }
}

#define LN_AT 2
#define X_AT 6
#define PERT 0
#define CTX_T 3
#define PF_AT 5
#define PF_N 4
#define PF_MOE 3
constexpr float QSCALE = 0.08838834764831845f * 1.4426950408889634f;
__device__ __forceinline__ void mod_cta(Ctx& x, const __nv_bfloat16* cvec) {
  const int t = wg_tid(), ct = x.w * 128 + t;
  #pragma unroll 1
  for (int k = 0; k < 6; k++) slot_release(x, k, false);
  const uint32_t cv = __ldg(reinterpret_cast<const uint32_t*>(cvec) + ct);
  asm volatile("st.shared.u32 [%0], %1;" :: "r"(x.base + SM_H2 + ct * 4),
               "r"(pack_bf16(__fdividef(bf_lo(cv), 1.f + __expf(-bf_lo(cv))), __fdividef(bf_hi(cv), 1.f + __expf(-bf_hi(cv))))) : "memory");
  bar_sync(5, 256);
  float acc[64];
  int e = 0;
  #pragma unroll 1
  for (int g = 0; g < 24; g++) {
    uint32_t a[8];
    #pragma unroll
    for (int i = 0; i < 8; i++) a[i] = lds_u32(x.base + SM_H2 + (g & 7) * 128 + i * 16 + (t & 3) * 4);
    ring_wait_full(x.bars, e);
    const uint32_t db = desc_lo(x.base + x.w * 16384, 8192) + ring_slot(e) * 2048;
    wgmma_fence();
    wgmma_rs_n128<1, 0, SW128>(acc, a[0], a[0], a[1], a[1], db, g & 7);
    wgmma_rs_n128<1, 128, SW128>(acc, a[2], a[2], a[3], a[3], db, 1);
    wgmma_rs_n128<1, 256, SW128>(acc, a[4], a[4], a[5], a[5], db, 1);
    wgmma_rs_n128<1, 384, SW128>(acc, a[6], a[6], a[7], a[7], db, 1);
    wgmma_commit();
    wgmma_wait<0>();
    fence_regs(acc);
    ring_release(x, e, false);
    e = ring_add(e, 1);
    if ((g & 7) == 7) {
      if (t < 4) {
        const float sc = (g == 7 && blockIdx.x < NCTA + 2) ? QSCALE : 1.f;
        uint32_t* dst = reinterpret_cast<uint32_t*>(g_x.mod + (g >> 3) * 1024 + (blockIdx.x - NCTA) * 256 + x.w * 128) + t;
        #pragma unroll
        for (int j = 0; j < 16; j++) dst[4 * j] = pack_bf16(rbf(acc[4*j]) * sc, rbf(acc[4*j+1]) * sc);
      }
      publish(x, g == 7 ? C_MOD : C_MOD2);
    }
  }
}

__global__ void __cluster_dims__(2, 1, 1) __launch_bounds__(384, 1)
k_fused(const __grid_constant__ CUtensorMap tmC, const __grid_constant__ CUtensorMap tmWq,
        const __grid_constant__ CUtensorMap tmWk, const __grid_constant__ CUtensorMap tmWv,
        const __grid_constant__ CUtensorMap tmWo, const __grid_constant__ CUtensorMap tmWg,
        const __grid_constant__ CUtensorMap tmWu, const __grid_constant__ CUtensorMap tmWd, const __grid_constant__ CUtensorMap tmWm,
        const __grid_constant__ Sched sched,
        const __nv_bfloat16* __restrict__ xin,
        const __nv_bfloat16* __restrict__ cvec, const __nv_bfloat16* __restrict__ w_o,
        const __nv_bfloat16* __restrict__ w_r, const __nv_bfloat16* __restrict__ w_gate, const __nv_bfloat16* __restrict__ w_up,
        const __nv_bfloat16* __restrict__ w_down, __nv_bfloat16* __restrict__ out) {
  extern __shared__ __align__(1024) uint8_t smem_raw[];
  const uint32_t base = smem_u32(smem_raw), bars = base + SM_BAR;
  const int warp = __shfl_sync(0xffffffff, threadIdx.x >> 5, 0), wg = warp >> 2;
  const int rank = cluster_ctarank(), p = blockIdx.x >> 1;
  const int mt = (p & 7) * 2 + rank;
  const bool spare = blockIdx.x >= NCTA;
  #pragma unroll
  for (int i = 0; i < PERT; i++) { uint32_t d; asm volatile("mov.u32 %0, %%laneid;" : "=r"(d)); (void)d; }
  {
    const int h0 = KHEAD0 + (p >> 3);
    if (warp == 11) { prefetch_tmap(&tmC); prefetch_tmap(&tmWk); }
    #pragma unroll 1
    for (int t = warp == 8 ? 0 : warp < 8 ? warp + 1 : warp == 11 ? 64 : warp; t < B_PUB / 8; t += (warp == 8 ? 64 : 10))
      w_mbar_init(bars + 8 * t, t < B_WE / 8 ? 1 : t < B_RE / 8 ? 2 : 4);
    fence_mbar_init();
    cluster_arrive();
    if (warp == 9) prefetch_tmap(&tmWv);
    if (wg == 2) bar_arrive(1, 256);
    if (warp == 8 && !spare) {
      #pragma unroll 1
      for (int kb = 0; kb < 8; kb++) {
        w_expect_tx(bars + B_AF + 8 * kb, 16384);
        tma_load_2d(base + k_addrA(kb), &tmC, bars + B_AF + 8 * kb, kb * 64, mt * 128);
        if (kb == 0) cluster_wait();
        if (kb < 6) {
          w_expect_tx(bars + B_WF + 8 * kb, 16384);
          tma_load_2d_mc(base + k_addrW(kb) + rank * 8192, &tmWk, bars + B_WF + 8 * kb, h0 * 128 + rank * 64, kb * 64);
        }
      }
    }
  }
  const Sched::Pair& sp = sched.pair[p];
  const int nitems = sp.nitems, nsteps = sp.nsteps;
  auto oent = [&](int k) -> uint32_t { return sp.oent[k]; };
  const int ot = sp.otask, m = (ot & 7) * 2 + rank, grp = m * 8 + (ot >> 3);

  if (wg == 0) {
    asm volatile("setmaxnreg.dec.sync.aligned.u32 24;");
    const int lane = threadIdx.x & 31;
    #pragma unroll 1
    for (int t = B_PUB / 8 + warp; t < 80; t += 4) w_mbar_init(bars + 8 * t, t < B_RDY / 8 ? 4 : 1);
    bar_sync(6, 128);
    bar_arrive(7, 256); bar_arrive(8, 256);
    cluster_wait();
    const unsigned int tag = ld_relaxed(&g_x.epoch) + 1;
    if (warp == 0) {
      if (!spare) {
        int s = 0, ph = 0;
        tma_prefetch_2d(&tmWv, sp.khead[0] * 128 + rank * 64, (p & 7) * 64);
        #pragma unroll 1
        for (int g = 6; g < 64; g++) {
          const int u = g >> 3, kb = g & 7;
          if (kb == 0 && u < 7) tma_prefetch_2d((u & 1) ? &tmWk : &tmWv, sp.khead[(u + 1) >> 1] * 128 + rank * 64, (p & 7) * 64);
          mbar_wait(bars + B_WE + 8 * s, ph);
          w_expect_tx(bars + B_WF + 8 * s, 16384);
          tma_load_2d_mc(base + k_addrW(s) + rank * 8192, (u & 1) ? &tmWv : &tmWk, bars + B_WF + 8 * s, sp.khead[u >> 1] * 128 + rank * 64, kb * 64);
          if (++s == 6) { s = 0; ph ^= 1; }
        }
      }
      int s = 0, ph = 0;
      auto next_entry = [&](int bytes) {
        mbar_wait(bars + B_RE + 8 * s, ph);
        w_expect_tx(bars + B_RF + 8 * s, bytes);
      };
      auto advance = [&]() { if (++s == 6) { s = 0; ph ^= 1; } };
      if (spare) {
        #pragma unroll 1
        for (int g = 0; g < 24; g++) {
          if (g == 8) mbar_wait(bars + R_MOD, 0);
          next_entry(32768);
          for (int k = 0; k < 2; k++) tma_load_3d(base + s * 32768 + k * 16384, &tmWm, bars + B_RF + 8 * s, 0, (g & 7) * 64, (g >> 3) * 16 + (blockIdx.x - NCTA) * 4 + k * 2);
          advance();
        }
      }
      mbar_wait(bars + R_H1, 0);
      fence_async_global();
      int vrow = -1;
      #pragma unroll 1
      for (int i = 0; i <= nitems; i++) {
        const int item = sp.item[i & (MAX_ITEMS - 1)], h = item >> 3, j = item & 7;
        if (i < nitems) {
          const int row0 = j * 256 + ((i & 1) ? rank : 3 - rank) * 64, row1 = j * 256 + ((i & 1) ? 3 - rank : rank) * 64;
          #pragma unroll 1
          for (int kb = 0; kb < 8; kb++) {
            next_entry(32768);
            tma_load_2d_mc(base + s * 32768 + 16384 + rank * 8192, &tmWq, bars + B_RF + 8 * s, h * 128 + rank * 64, kb * 64);
            bulk_load(base + s * 32768, sched.h1 + row0 * DM + kb * 4096, 8192, bars + B_RF + 8 * s);
            bulk_load(base + s * 32768 + 8192, sched.h1 + row1 * DM + kb * 4096, 8192, bars + B_RF + 8 * s);
            advance();
          }
          mbar_wait(bars + R_ITEM + 8 * i, 0);
          fence_async_global();
        }
        #pragma unroll 1
        for (int n = i < nitems ? 4 * j + 3 : 0; n >= 0; n--) {
          const int krow = (h * 2 + rank) * SEQ + (n >> 1) * 128 + ((sp.lastuse[i & (MAX_ITEMS - 1)] >> (n >> 1)) & 1);
          const int row = (n & 1) ? krow : vrow;
          if (i + 1 == nitems && n == min(4 * j + 3, 2 * PF_AT + 1)) w_arrive(bars + R_NEAR);
          next_entry(row >= 0 ? 32768 : 0);
          if (row >= 0) bulk_load_mc(base + s * 32768 + rank * 16384, sched.kvc + (size_t)(row & ~1) * 64, bars + B_RF + 8 * s, row & 1);
          advance();
          if (!(n & 1)) vrow = krow + 64 * SEQ;
        }
      }
      if (!spare) {
      const int oc = ((ot >> 3) & 1) * 4 + rank * 2;
      auto o_next = [&](int k, int bytes) {
        const uint32_t v = oent(k); s = v & 7;
        mbar_wait(bars + B_RE + 8 * s, v >> 3);
        w_expect_tx(bars + B_RF + 8 * s, bytes);
      };
      #pragma unroll 1
      for (int i = 0; i < nsteps; i++) {
        const int c0 = sp.ochunk[i][0], c1 = sp.ochunk[i][1];
        const int pf = i - nsteps + PF_MOE;
        if (pf >= 0 && pf < 3)
          bulk_prefetch((pf == 0 ? w_gate : pf == 1 ? w_up : w_down) + (size_t)blockIdx.x * (DM * FF / NCTA), DM * FF / NCTA * 2);
        if (c0 < 64) { o_next(3 * i, 32768); tma_load_3d_mc(base + s * 32768 + rank * 16384, &tmWo, bars + B_RF + 8 * s, 0, c0 * 64, oc); }
        mbar_wait(bars + R_CTX + 8 * i, 0);
        fence_async_global();
        o_next(3 * i + 1, c0 < 64 ? 32768 : 16384);
        if (c0 < 64) bulk_load(base + s * 32768, sched.kvc + (size_t)((128 + c0) * SEQ + m * 128) * 64, 16384, bars + B_RF + 8 * s);
        bulk_load(base + s * 32768 + 16384, sched.kvc + (size_t)((128 + c1) * SEQ + m * 128) * 64, 16384, bars + B_RF + 8 * s);
        o_next(3 * i + 2, 32768);
        tma_load_3d_mc(base + s * 32768 + rank * 16384, &tmWo, bars + B_RF + 8 * s, 0, c1 * 64, oc);
      }
      const int f0 = (blockIdx.x < FF / 16 ? blockIdx.x : 0) * 16;
      o_next(3 * nsteps, 32768);
      tma_load_3d(base + s * 32768, &tmWd, bars + B_RF + 8 * s, 0, f0, 0);
      bulk_load(base + s * 32768 + 16384, xin + (size_t)grp * 16 * DM, 16384, bars + B_RF + 8 * s);
      o_next(3 * nsteps + 1, 32768);
      #pragma unroll 1
      for (int k = 0; k < 4; k++) tma_load_2d(base + s * 32768 + k * 8192, (k & 2) ? &tmWu : &tmWg, bars + B_RF + 8 * s, f0, (k & 1) * 256);
      #pragma unroll 1
      for (int k = 0; k < 4; k++) w_expect_tx(bars + R_PART + 8 * k, 16384);
      mbar_wait(bars + B_PUB + 8 * (5 + nitems), 0);
      mbar_wait(bars + B_PUB + 8 * (NPUB + 5 + nitems), 0);
      uint32_t todo = 0xff;
      #pragma unroll 1
      for (int n = 0; n < WAIT_LIM && todo; n++) {
        uint32_t now = __ballot_sync(0xffffffff, ld_acquire(&g_x.cnt[C_PART + (m * 2 + (ot >> 5)) * 32 + (lane & 7)]) == tag) & todo;
        todo &= ~now;
        if (now) fence_async_global();
        #pragma unroll 1
        for (; now; now &= now - 1) {
          const int q = __ffs(now) - 1;
          bulk_load(base + (oent(3 * nsteps - 3 + (q >> 2)) & 7) * 32768 + (q & 3) * 8192, sched.part + (grp * 8 + q) * 4096, 8192, bars + R_PART + 8 * (q >> 1));
        }
      }
      }
    } else if (warp < 3) {
      const int w = warp - 1, n1 = w * NPUB + (spare ? 3 : 6) + nitems;
      #pragma unroll 1
      for (int n = w * NPUB; n < n1; n++) {
        #pragma unroll 1
        for (int k = 0; k < 8 * WAIT_LIM; k++) { if (mbar_try(bars + B_PUB + 8 * n, 0)) break; }
        const uint32_t idx = lds_u32(base + SM_MAIL + 4 * n);
        fence_async_global();
        if (lane == 0 && idx < (unsigned)C_END) red_release(idx);
        __syncwarp();
      }
    } else {
      *reinterpret_cast<volatile uint32_t*>(smem_raw + SM_KEY + 48) = tag;
      if (!spare) { mbar_wait(bars + B_AF + 8 * X_AT, 0); bulk_prefetch(xin + (size_t)blockIdx.x * 16 * DM, 16 * DM * 2); }
      #pragma unroll 1
      for (int n = 0; n < 8 + nsteps; n++) {
        if (n == 2 + nitems) n = 7;
        int idx = n == 0 ? C_MOD : n == 1 ? C_H1 : C_MOD2, cnt = n == 0 ? 8 : n == 1 ? 256 : 16;
        if (n == 2) tma_prefetch_2d(&tmWq, (sp.item[0] >> 3) * 128 + rank * 64, (sp.item[0] & 7) * 64);
        if (n >= 2 && n < 7) { idx = C_KV + (sp.item[n - 2] >> 3); cnt = 32; }
        if (n >= 8) { const int c0 = sp.ochunk[n - 8][0], c1 = sp.ochunk[n - 8][1]; idx = C_CTX + (((lane & 1) && c0 < 64 ? c0 : c1) >> 1) * 8 + (ot & 7); cnt = 4; }
        wait_count_lazy(idx, cnt * tag);
        w_arrive(bars + B_RDY + 8 * n);
        if (n == 8 + PF_N - 1) {
          #pragma unroll 1
          for (int k = 0; k < 8 * WAIT_LIM; k++) { if (mbar_try(bars + R_NEAR, 0)) break; }
          bulk_prefetch(w_o + (size_t)blockIdx.x * (NH * DH * DM / NCTA), NH * DH * DM / NCTA * 2);
          #pragma unroll 1
          for (int k = 0; k < PF_N; k++) {
            const int cc = sp.ochunk[k][(ot >> 3) & 1];
            if (cc < 64) bulk_prefetch(sched.kvc + ((size_t)(128 + cc) * SEQ + m * 128) * 64, 16384);
          }
        }
      }
    }
    __syncwarp();
    cluster_arrive();
    if (!spare) {
      bar_sync(6, 128);
      asm volatile("setmaxnreg.inc.sync.aligned.u32 88;");
      const int pos = blockIdx.x * 4 + (lane & 1) * 2, col = (blockIdx.x >> 2) * 16 + (blockIdx.x & 3) * 2 + (lane & 1) * 8, src = threadIdx.x >> 1;
      uint32_t gbest = 0, hh = 0, gbf = 0;
      uint2 xx = make_uint2(0, 0);
      uint4 ya = make_uint4(0, 0, 0, 0), yb = make_uint4(0, tag, 0, tag);
      auto poll_y = [&]() {
        if (ya.y != tag || ya.w != tag) ya = ld_tagged2(&g_x.yll[src][pos]);
        if (yb.y != tag || yb.w != tag) yb = ld_tagged2(&g_x.yll[src + 64][pos]);
        return __all_sync(0xffffffff, ya.y == tag && ya.w == tag && yb.y == tag && yb.w == tag);
      };
      ya.y = tag - 1; if (src + 64 < FF / 16) yb.y = tag - 1;
      if (warp == 3) {
        gbf = __ldcg(reinterpret_cast<const uint32_t*>(g_x.mod + 5 * DM + col));
        uint32_t have = 0;
        uint2 k[4];
        #pragma unroll
        for (int i = 0; i < 4; i++) k[i] = make_uint2(0, tag - 1);
        #pragma unroll 1
        for (int n = 0; n < WAIT_LIM; n++) {
          #pragma unroll
          for (int i = 0; i < 4; i++) if (k[i].y != tag) k[i] = ld_tagged(&g_x.keys[i * 32 + lane][0]);
          if (gbest != have) {
            const int g = ((0xffffu - gbest) >> 4) & 127;
            uint4 hv[4];
            #pragma unroll
            for (int i = 0; i < 4; i++) hv[i] = ld_tagged2(&g_x.row[g][0][i * 64 + lane * 2]);
            xx = ld_tagged(&g_x.row[g][1][(col >> 8) * 128 + ((col >> 2) & 1) * 64 + ((col >> 3) & 31) * 2 + ((col >> 1) & 1)]);
            bool ok = xx.y == tag;
            #pragma unroll
            for (int i = 0; i < 4; i++) { ok = ok && hv[i].y == tag && hv[i].w == tag; reinterpret_cast<uint2*>(smem_raw + SM_H2)[(i >> 1) * 64 + lane * 2 + (i & 1)] = make_uint2(hv[i].x, hv[i].z); }
            if (lane == 0) *reinterpret_cast<uint32_t*>(smem_raw + SM_KEY + 32) = gbest;
            have = __all_sync(0xffffffff, ok) ? gbest : 0;
          }
          bool all = true;
          #pragma unroll
          for (int i = 0; i < 4; i++) { all = all && k[i].y == tag; gbest = max(gbest, k[i].y == tag ? k[i].x : 0u); }
          gbest = __reduce_max_sync(0xffffffff, gbest);
          if (__all_sync(0xffffffff, all) && gbest == have) break;
        }
        __syncwarp();
        w_arrive(bars + R_KEY);
        if (blockIdx.x == 0 && lane == 0) g_x.epoch = tag;
        hh = lds_u32(base + SM_H2 + col * 2);
      }
      const float rsel = rbf(__uint_as_float((((gbest & 0x80000000u) ? gbest & 0x7fffffffu : ~gbest) & 0xfffff000u) | 0x800u));
      const float rs = rbf(__fdividef(1.f, 1.f + __expf(-rsel)));
      bar_sync(9, 384);
      #pragma unroll 1
      for (int n = 0; n < WAIT_LIM; n++) { if (poll_y()) break; }
      float y0 = __uint_as_float(ya.x) + __uint_as_float(yb.x), y1 = __uint_as_float(ya.z) + __uint_as_float(yb.z);
      #pragma unroll
      for (int o = 2; o < 32; o <<= 1) { y0 += __shfl_xor_sync(0xffffffff, y0, o); y1 += __shfl_xor_sync(0xffffffff, y1, o); }
      float2* s_y = reinterpret_cast<float2*>(smem_raw + SM_KEY + 64);
      if (lane < 2) s_y[warp * 2 + lane] = make_float2(y0, y1);
      bar_sync(6, 128);
      if (warp == 3 && lane < 2) {
        y0 = 0.f; y1 = 0.f;
        #pragma unroll
        for (int i = 0; i < 4; i++) { y0 += reinterpret_cast<const float*>(s_y)[i * 4 + lane]; y1 += reinterpret_cast<const float*>(s_y)[i * 4 + 2 + lane]; }
        const float o0 = bf_lo(xx.x) + rbf(bf_lo(gbf) * rbf(bf_lo(hh) + rbf(rbf(y0) * rs)));
        const float o1 = bf_hi(xx.x) + rbf(bf_hi(gbf) * rbf(bf_hi(hh) + rbf(rbf(y1) * rs)));
        *reinterpret_cast<uint32_t*>(out + (size_t)((0xffffu - gbest) & (SEQ - 1)) * DM + col) = pack_bf16(o0, o1);
      }
    }
    __syncwarp();
    cluster_wait();
  } else {
    asm volatile("setmaxnreg.inc.sync.aligned.u32 240;");
    Ctx x;
    x.w = wg - 1; x.base = base; x.bars = bars; x.nev = 0; x.sched = &sched;
    const int w = x.w, warp4 = warp & 3;
    x.rel = mapa(bars, (warp4 & 1) ^ 1);
    x.rel1 = (threadIdx.x & 127) == 32 || (threadIdx.x & 127) == 64;
    if (warp != 8 || spare) cluster_wait();
    if (w == 1 || spare) bar_sync(7 + w, 256);
    uint32_t PA[32], PB[32];
    int vtile = -1;
    if (spare) {
      mod_cta(x, cvec);
    } else {
      const int lane = wg_tid() & 31;
      Row xn[2];
      float acc0[64], acc1[64];
      int s = 2 * w, ph = w;
      #pragma unroll 1
      for (int u = w; u < 8; u += 2) {
        bar_sync(1 + w, 256);
        int ps = 0;
        #pragma unroll 1
        for (int kb = 0; kb < 8; kb++) {
          if (u < 2) mbar_wait(bars + B_AF + 8 * kb, 0);
          mbar_wait(bars + B_WF + 8 * s, ph);
          const uint32_t da = desc_lo(base + k_addrA(kb), 16), dw = desc_lo(base + k_addrW(s), 8192);
          wgmma_fence();
          kblock_n128<0>(acc0, da, dw, kb != 0);
          kblock_n128<512>(acc1, da, dw, kb != 0);
          wgmma_commit();
          if (kb == 7) bar_arrive(1 + (w ^ 1), 256);
          if (kb > 0) {
            wgmma_wait<1>();
            mbar_arrive_remote_if(x.rel + B_WE + 8 * ps, x.rel1);
            if (u == 7 && !(kb & 1)) {
              ring_release(x, kb == 2 ? 0 : kb - 3, false);
              if (kb > 2) ring_release(x, kb - 2, false);
            }
          }
          ps = s;
          if (++s == 6) { s = 0; ph ^= 1; }
        }
        Row t[2];
        const int lrow = blockIdx.x * 16 + w * 8 + warp4 * 2;
        if (u == w) { t[0] = ldg_row(xin + (size_t)lrow * DM, lane); t[1] = ldg_row(xin + (size_t)(lrow + 1) * DM, lane); }
        if (u == LN_AT || u == LN_AT + 1) {
          mbar_wait(bars + R_MOD, 0);
          t[0] = ldca_row(g_x.mod, lane); t[1] = ldca_row(g_x.mod + DM, lane);
        }
        wgmma_wait<0>();
        fence_regs(acc0); fence_regs(acc1);
        mbar_arrive_remote_if(x.rel + B_WE + 8 * ps, x.rel1);
        if (u == 6) { for (int k = 0; k < 5; k++) ring_release(x, k, false); }
        if (u >= 6) ring_release(x, 5, false);
        if (u == 7) {
          pack_tile(acc0, PA, 1.f, 1.f); pack_tile(acc1, PB, 1.f, 1.f);
          vtile = sp.khead[3] * 16 + mt;
          break;
        }
        s += 2; ph ^= 1; if (s >= 6) { s -= 6; ph ^= 1; }
        if (u == 0) bar_sync(7, 256);
        if (u == w) {
          float st[4] = {0.f, 0.f, 0.f, 0.f};
          #pragma unroll
          for (int i = 0; i < 32; i++) { const float v = row_at(t[i >> 4], i & 15); st[(i >> 4) * 2] += v; st[(i >> 4) * 2 + 1] = fmaf(v, v, st[(i >> 4) * 2 + 1]); }
          warp_sums(st);
          #pragma unroll
          for (int r = 0; r < 2; r++) { ln_stats(st[2*r], st[2*r+1]); xn[r] = ln_apply(t[r], st[2*r], st[2*r+1] * QSCALE); }
        }
        if ((u == LN_AT || u == LN_AT + 1)) {
          #pragma unroll
          for (int r = 0; r < 2; r++) {
            const Row hr = fma_row(xn[r], one_plus(t[1]), t[0]);
            __nv_bfloat16* hp = sched.h1 + (lrow & ~63) * DM + (lane >> 3) * 4096 + ((lrow + r) & 63) * 64 + (((lane ^ (lrow + r)) & 7) << 3);
            stg_v4(hp, hr.v[0], hr.v[1], hr.v[2], hr.v[3]); stg_v4(hp + 4 * 4096, hr.v[4], hr.v[5], hr.v[6], hr.v[7]);
          }
        }
        const int tile = sp.khead[u >> 1] * 16 + mt;
        __nv_bfloat16* dst = kv_tile(x, tile);
        uint32_t D[32];
        pack_tile(acc0, D, 1.f, 1.f); store_tile(dst + 2048, D);
        pack_tile(acc1, D, 1.f, 1.f); store_tile(dst, D);
        if (u == LN_AT || u == LN_AT + 1) publish(x, C_H1);
        publish(x, C_KV + (tile >> 4));
      }
    }
    const int last = attention(x, sp.item, nitems, rank, PA, PB, vtile);
    const int lane = wg_tid() & 31, cw = w * 4 + warp4;
    const int row0 = grp * 16 + cw * 2;
    const bool moe_cta = blockIdx.x < FF / 16;
    if (spare) { store_ctx(x, last, PB); __syncwarp(); cluster_arrive(); cluster_wait(); return; }
    const int kl = 3 * nsteps - 3;
    uint2* const yp = &g_x.yll[blockIdx.x][cw * 64 + (lane & 3) * 16 + (lane >> 2) * 2];
    Row ga, sb, cb, gb, wr;
    {
      float accA[64], accB[64];
      const int t0 = oent(0) == oent(1);
      uint32_t pa = 0, pb = 0;
      #pragma unroll 1
      for (int t = t0; t < 2 * nsteps - 2; t++) {
        const uint32_t eb = oent(3 * (t >> 1) + 2 * (t & 1)), ea = oent(3 * (t >> 1) + 1);
        o_wait_full(bars, eb);
        o_wait_full(bars, ea);
        const uint32_t da = desc_lo(base + w * 4096, 16) + (ea & 7) * 2048 + (t & 1) * 1024, db = desc_lo(base, 8192) + (eb & 7) * 2048;
        wgmma_fence();
        kblock_n128<0, 0, SW64>(accA, da, db, t != t0); kblock_n128<0, 1024, SW64>(accB, da, db, t != t0);
        wgmma_commit();
        if (t == CTX_T) store_ctx(x, last, PB);
        if (t > t0) { wgmma_wait<1>(); slot_release(x, pb, false); if (!(t & 1)) slot_release(x, pa, false); }
        pa = ea & 7; pb = eb & 7;
      }
      const uint32_t e0 = oent(kl), ea = oent(kl + 1), eb = oent(kl + 2);
      const uint32_t da = desc_lo(base + w * 4096, 16) + (ea & 7) * 2048;
      const uint32_t db0 = desc_lo(base, 8192) + (e0 & 7) * 2048, db1 = desc_lo(base, 8192) + (eb & 7) * 2048;
      ga = ldca_row(g_x.mod + 2 * DM, lane); sb = ldca_row(g_x.mod + 3 * DM, lane); cb = ldca_row(g_x.mod + 4 * DM, lane); gb = ldca_row(g_x.mod + 5 * DM, lane);
      wr = ldca_row(w_r, lane);
      if (moe_cta) st_tagged2(yp, 0, 0, 0);
      o_wait_full(bars, e0);
      o_wait_full(bars, ea);
      o_wait_full(bars, eb);
      wgmma_fence();
      kblock_n128<0, 0, SW64>(accA, da, db0, 1); kblock_n128<1024, 0, SW64>(accA, da, db1, 1);
      wgmma_commit();
      kblock_n128<0, 1024, SW64>(accB, da, db0, 1); kblock_n128<1024, 1024, SW64>(accB, da, db1, 1);
      wgmma_commit();
      __syncwarp();
      cluster_arrive();
      __nv_bfloat16* dst = sched.part + ((m * 8 + cw) * 8 + (ot >> 3)) * 4096;
      auto send = [&](const float (&acc)[64], int h) {
        uint32_t D[32];
        pack_tile(acc, D, 1.f, 1.f);
        #pragma unroll
        for (int i = 0; i < 8; i++) stg_v4(dst + (h * 8 + i) * 256 + ((lane ^ (h * 4 + (i >> 1))) << 3), D[4*i], D[4*i+1], D[4*i+2], D[4*i+3]);
      };
      wgmma_wait<1>();
      fence_regs(accA);
      send(accA, 0);
      o_wait_full(bars, eb);
      wgmma_wait<0>();
      fence_regs(accB);
      send(accB, 1);
      publish(x, C_PART + (m * 2 + w) * 32 + (ot >> 3));
    }
    asm volatile("setmaxnreg.dec.sync.aligned.u32 208;");
    const uint32_t sD = base + (oent(kl + 3) & 7) * 32768, sW = base + (oent(kl + 4) & 7) * 32768;
    o_wait_full(bars, oent(kl + 3)); o_wait_full(bars, oent(kl + 4));
    Row x1[2];
    #pragma unroll
    for (int r = 0; r < 2; r++) x1[r] = lds_row(sD + 16384 + (cw * 2 + r) * 1024, lane);
    uint4 wgv[4], wuv[4], wdv[4];
    #pragma unroll
    for (int r = 0; r < 4; r++) {
      const uint32_t k = (lane & 7) + ((lane >> 4) << 3), h = (lane >> 3) & 1;
      wgv[r] = ldsm_x4_t(sW + (cw * 64 + r * 16 + k) * 32 + ((h ^ ((lane >> 2) & 1)) << 4));
      wuv[r] = ldsm_x4_t(sW + 16384 + (cw * 64 + r * 16 + k) * 32 + ((h ^ ((lane >> 2) & 1)) << 4));
      wdv[r] = ldsm_x4_t(sD + cw * 2048 + k * 128 + (((r * 2 + h) ^ (lane & 7)) << 4));
    }
    const Row cb1 = one_plus(cb);
    const unsigned int tag = lds_u32(base + SM_KEY + 48);
    float u[16], ub[2] = {0.f, 0.f};
    #pragma unroll
    for (int i = 0; i < 16; i++) { u[i] = row_at(cb1, i) * row_at(wr, i); ub[0] += u[i]; ub[1] = fmaf(row_at(sb, i), row_at(wr, i), ub[1]); }
    warp_sums(ub);
    float st[6] = {0.f, 0.f, 0.f, 0.f, 0.f, 0.f};
    uint32_t key[2];
    {
      const uint32_t po = base + ((lane & 7) * 2 + (cw >> 2)) * 512 + (cw & 3) * 128;
      Row av[2][2];
      #pragma unroll
      for (int k = 0; k < 4; k++) {
        mbar_wait(bars + R_PART + 8 * k, 1);
        const uint32_t pa = po + (oent(kl + (k >> 1)) & 7) * 32768 + (k & 1) * 16384;
        #pragma unroll
        for (int r = 0; r < 2; r++) {
          const uint32_t sw = ((r * 4 + (lane >> 3)) ^ (lane & 7)) << 4;
          const uint4 lo = ldsm_x4(pa + sw), hi = ldsm_x4(pa + 8192 + sw);
          const Row v{{lo.x, lo.y, lo.z, lo.w, hi.x, hi.y, hi.z, hi.w}};
          av[r][k >> 1] = (k & 1) ? add_row(av[r][k >> 1], v) : v;
        }
      }
      #pragma unroll
      for (int r = 0; r < 2; r++) {
        x1[r] = fma_row(ga, add_row(av[r][0], av[r][1]), x1[r]);
        #pragma unroll
        for (int i = 0; i < 16; i++) { const float v = row_at(x1[r], i); st[3*r] += v; st[3*r+1] = fmaf(v, v, st[3*r+1]); st[3*r+2] = fmaf(v, u[i], st[3*r+2]); }
      }
      warp_sums(st);
      #pragma unroll
      for (int r = 0; r < 2; r++) {
        ln_stats(st[3*r], st[3*r+1]);
        const uint32_t rb = __float_as_uint(fmaf(st[3*r+1], fmaf(-st[3*r], ub[0], st[3*r+2]), ub[1]));
        key[r] = (((rb & 0x80000000u) ? ~rb : (rb | 0x80000000u)) & 0xfffff000u) | (0xfffu - (uint32_t)(row0 + r));
      }
    }
    float* s_red = reinterpret_cast<float*>(smem_raw + SM_RED);
    uint32_t* s_key = reinterpret_cast<uint32_t*>(smem_raw + SM_KEY);
    const int rb = key[1] > key[0];
    const uint32_t wbest = rb ? key[1] : key[0];
    if (lane == 0) s_key[cw] = wbest;
    bar_sync(5, 256);
    const uint32_t cbest = __reduce_max_sync(0xffffffff, s_key[lane & 7]);
    if (wbest == cbest && lane == 0) st_tagged(&g_x.keys[grp][0], cbest, tag);
    Row xb, xo;
    #pragma unroll
    for (int i = 0; i < 8; i++) { xb.v[i] = rb ? x1[1].v[i] : x1[0].v[i]; xo.v[i] = rb ? x1[0].v[i] : x1[1].v[i]; }
    const Row hb = fma_row(ln_apply(xb, rb ? st[3] : st[0], rb ? st[4] : st[1]), cb1, sb);
    if (wbest == cbest) {
      #pragma unroll
      for (int i = 0; i < 4; i++) st_tagged2(&g_x.row[grp][0][i * 64 + lane * 2], hb.v[2*i], hb.v[2*i+1], tag);
      #pragma unroll
      for (int i = 0; i < 4; i++) st_tagged2(&g_x.row[grp][1][i * 64 + lane * 2], xb.v[2*i], xb.v[2*i+1], tag);
    }
    const Row ob = fma_row(gb, hb, xb);
    if (wbest != cbest) store_row(out + (size_t)(row0 + rb) * DM, lane, ob);
    store_row(out + (size_t)(row0 + 1 - rb) * DM, lane, fma_row(gb, fma_row(ln_apply(xo, rb ? st[0] : st[3], rb ? st[1] : st[4]), cb1, sb), xo));
    mbar_wait(bars + R_KEY, 1);
    if (moe_cta) {
      float cg[4] = {0, 0, 0, 0}, cu[4] = {0, 0, 0, 0};
      #pragma unroll
      for (int r = 0; r < 4; r++) {
        const uint32_t b0 = lds_u32(base + SM_H2 + (cw * 64 + r * 16) * 2 + (lane & 3) * 4), b1 = lds_u32(base + SM_H2 + (cw * 64 + r * 16) * 2 + 16 + (lane & 3) * 4);
        mma16816(cg, wgv[r], b0, b1); mma16816(cu, wuv[r], b0, b1);
      }
      s_red[cw * 32 + (lane & 3) * 8 + (lane >> 2)] = (lane & 2) ? ((lane & 1) ? cu[2] : cu[0]) : ((lane & 1) ? cg[2] : cg[0]);
      bar_sync(5, 256);
      float g = 0.f;
      #pragma unroll
      for (int i = 0; i < 8; i++) g += s_red[i * 32 + lane];
      g = rbf(g);
      const float act = rbf(__fdividef(g, 1.f + __expf(-g))) * __shfl_down_sync(0xffffffff, g, 16);
      const uint32_t a2 = pack_bf16(act, __shfl_down_sync(0xffffffff, act, 1));
      const uint32_t b0 = __shfl_sync(0xffffffff, a2, (lane & 3) * 2), b1 = __shfl_sync(0xffffffff, a2, (lane & 3) * 2 + 8);
      float y0 = 0.f, y1 = 0.f;
      #pragma unroll
      for (int r = 0; r < 4; r++) {
        float c[4] = {0, 0, 0, 0};
        mma16816(c, wdv[r], b0, b1);
        if ((lane & 3) == r) { y0 = c[0]; y1 = c[2]; }
      }
      st_tagged2(yp, __float_as_uint(y0), __float_as_uint(y1), tag);
    }
    bar_arrive(9, 384);
    if (wbest == cbest && wbest != s_key[8]) store_row(out + (size_t)(row0 + rb) * DM, lane, ob);
    __syncwarp();
    cluster_wait();
  }
}

typedef CUresult (*EncodeFn)(CUtensorMap*, CUtensorMapDataType, cuuint32_t, void*, const cuuint64_t*, const cuuint64_t*, const cuuint32_t*,
                             const cuuint32_t*, CUtensorMapInterleave, CUtensorMapSwizzle, CUtensorMapL2promotion, CUtensorMapFloatOOBfill);

struct HostState {
  bool ready = false;
  EncodeFn encode = nullptr;
  CUtensorMap tmC, tmWq, tmWk, tmWv, tmWo, tmWg, tmWu, tmWd, tmWm;
  Sched sched;
};

void make_map(EncodeFn enc, CUtensorMap* m, const void* ptr, int rank, const cuuint64_t* dims, const cuuint64_t* strides, const cuuint32_t* box, bool wide = true) {
  const cuuint32_t es[3] = {1, 1, 1};
  enc(m, CU_TENSOR_MAP_DATA_TYPE_BFLOAT16, rank, const_cast<void*>(ptr), dims, strides, box, es, CU_TENSOR_MAP_INTERLEAVE_NONE,
      wide ? CU_TENSOR_MAP_SWIZZLE_128B : CU_TENSOR_MAP_SWIZZLE_32B, wide ? CU_TENSOR_MAP_L2_PROMOTION_L2_128B : CU_TENSOR_MAP_L2_PROMOTION_NONE, CU_TENSOR_MAP_FLOAT_OOB_FILL_NONE);
}
void make_2d(EncodeFn enc, CUtensorMap* m, const void* ptr, int rows, int cols, int box_rows) {
  const cuuint64_t dims[2] = {(cuuint64_t)cols, (cuuint64_t)rows}, strides[1] = {(cuuint64_t)cols * 2};
  const cuuint32_t box[2] = {64, (cuuint32_t)box_rows};
  make_map(enc, m, ptr, 2, dims, strides, box);
}
void make_3d(EncodeFn enc, CUtensorMap* m, const void* ptr, int rows, int chunks, size_t row_stride, size_t chunk_stride, int box_rows = 64, int box_chunks = 2) {
  const cuuint64_t dims[3] = {64, (cuuint64_t)rows, (cuuint64_t)chunks}, strides[2] = {row_stride, chunk_stride};
  const cuuint32_t box[3] = {64, (cuuint32_t)box_rows, (cuuint32_t)box_chunks};
  make_map(enc, m, ptr, 3, dims, strides, box);
}

void make_ffn(EncodeFn enc, CUtensorMap* m, const void* ptr) {
  const cuuint64_t dims[2] = {(cuuint64_t)FF, (cuuint64_t)DM}, strides[1] = {(cuuint64_t)FF * 2};
  const cuuint32_t box[2] = {16, 256};
  make_map(enc, m, ptr, 2, dims, strides, box, false);
}

#define SR 0x213312
#define SEED 12345
#define LU_MARGIN 0
#define SPARE_N 3
void build_sched(Sched& s) {
  memset(&s, 0, sizeof(s));
  const int NP = NCTA / 2, korder[4] = {(KORDER >> 12) & 3, (KORDER >> 8) & 3, (KORDER >> 4) & 3, KORDER & 3};
  const int sround[4][2][3] = {{}, {{1}, {2}}, {{1, 2}, {1, 2}}, {{(SR >> 20) & 3, (SR >> 16) & 3, (SR >> 12) & 3}, {(SR >> 8) & 3, (SR >> 4) & 3, SR & 3}}};
  int jv[4][NP], used[4][8] = {};
  for (int r = 0; r < 4; r++) for (int p = 0; p < NP; p++) jv[r][p] = (r & 2) ? 7 - ((p + 4 * (r & 1)) & 7) : (p + 4 * (r & 1)) & 7;
  for (int q = 0; q < 2; q++) {
    s.pair[NP + q].nitems = SPARE_N;
    for (int i = 0; i < SPARE_N; i++) {
      const int r = sround[SPARE_N][q][i];
      s.pair[NP + q].item[i] = (uint8_t)((r * 8 + used[r][6]++) * 8 + 6);
      for (int p = 0; p < NP; p++) if (jv[r][p] == 6) { jv[r][p] = -2; break; }
    }
  }
  auto cost = [&](int p) {
    int u = 8 - ((p >> 4) < SPARE_N ? 21 : 22), z = 0, none = 0;
    for (int r = 0; r < 4; r++) { u += jv[r][p]; z += jv[r][p] == 0; none += jv[r][p] < 0; }
    return 4 * u * u + (z > 1) + 4 * (none > 1);
  };
  uint32_t rng = SEED;
  for (int it = 0; it < 2000000; it++) {
    if ((it & 255) == 0) { int t = 0; for (int p = 0; p < NP; p++) t += cost(p); if (t == 0) break; }
    rng = rng * 1664525u + 1013904223u;
    const int r = (rng >> 8) & 3, a = (rng >> 12) & 63, b = (rng >> 20) & 63, before = cost(a) + cost(b);
    int t = jv[r][a]; jv[r][a] = jv[r][b]; jv[r][b] = t;
    if (cost(a) + cost(b) > before) { jv[r][b] = jv[r][a]; jv[r][a] = t; }
  }
  int fin[256], done[256];
  for (int p = 0; p < NP + 2; p++) {
    Sched::Pair& q = s.pair[p];
    if (p < NP) {
      for (int k = 0; k < 4; k++) q.khead[k] = (uint8_t)(korder[k] * 8 + (p >> 3));
      for (int r = 0; r < 4; r++) {
        if (jv[r][p] < 0) continue;
        q.item[q.nitems++] = (uint8_t)((r * 8 + used[r][jv[r][p]]++) * 8 + jv[r][p]);
      }
    }
    int t = p < NP ? 0 : -3, e = 1;
    for (int i = 0; i < q.nitems; i++) { t += (q.item[i] & 7) + 2; fin[q.item[i]] = t; done[q.item[i]] = t + (i + 1 < q.nitems ? 2 : 0); e += 8 + 4 * ((q.item[i] & 7) + 1); }
    for (int k = 0; k < 3 * MAX_STEPS + 6; k++) {
      const int n = k > 0 ? k - (SPARE_N & 1) : 0, r = n % 7, f = (e + (r < 4 ? r : r - 1)) % 12;
      q.oent[k] = (uint8_t)((r == 4 ? 6 : f >= 6 ? f + 2 : f) ^ (((n / 7) & 1) << 3));
    }
  }
  for (int p = 0; p < NP + 2; p++)
    for (int i = 0; i < s.pair[p].nitems; i++) {
      const int it = s.pair[p].item[i];
      for (int n = 0; n < 2 * (it & 7) + 2; n++) {
        bool last = true;
        for (int j = n >> 1; j < 8; j++) { const int o = (it & ~7) + j; if (o != it && fin[o] + LU_MARGIN > fin[it]) last = false; }
        if (last) s.pair[p].lastuse[i] |= (uint16_t)(1 << n);
      }
    }
  for (int j = 0; j < 8; j++) {
    int order[NH], left[4];
    for (int h = 0; h < NH; h++) { int k = h; for (; k > 0 && done[order[k - 1] * 8 + j] < done[h * 8 + j]; k--) order[k] = order[k - 1]; order[k] = h; }
    for (int kq = 0; kq < 4; kq++) {
      left[kq] = SPARE_N == 0 ? 16 : kq < SPARE_N ? 20 - SPARE_N : 16 - SPARE_N;
      for (int nh = 0; nh < 2; nh++) { Sched::Pair& q = s.pair[kq * 16 + nh * 8 + j]; q.otask = (uint8_t)(kq * 16 + nh * 8 + j); q.nsteps = (uint8_t)((left[kq] + 1) / 2); q.ochunk[0][0] = 255; }
    }
    for (int n = 0, kq = 0, run = 0; n < 64; ) {
      if (left[kq] > 0 && run < 2) {
        const int pos = --left[kq] + (SPARE_N & 1);
        for (int nh = 0; nh < 2; nh++) s.pair[kq * 16 + nh * 8 + j].ochunk[pos >> 1][pos & 1] = (uint8_t)(order[n >> 1] * 2 + 1 - (n & 1));
        n++; run++;
      } else { kq = (kq + 1) & 3; run = 0; }
    }
  }
}

}

extern "C" void kernel_launch(void* const* d_in, const int* in_sizes, int n_in, void* d_out, int out_size) {
  (void)in_sizes; (void)n_in; (void)out_size;
  const __nv_bfloat16* x     = (const __nv_bfloat16*)d_in[0];
  const __nv_bfloat16* ckv   = (const __nv_bfloat16*)d_in[1];
  const __nv_bfloat16* w_q   = (const __nv_bfloat16*)d_in[2];
  const __nv_bfloat16* w_uk  = (const __nv_bfloat16*)d_in[3];
  const __nv_bfloat16* w_uv  = (const __nv_bfloat16*)d_in[4];
  const __nv_bfloat16* w_o   = (const __nv_bfloat16*)d_in[5];
  const __nv_bfloat16* w_r   = (const __nv_bfloat16*)d_in[7];
  const __nv_bfloat16* w_g   = (const __nv_bfloat16*)d_in[8];
  const __nv_bfloat16* w_u   = (const __nv_bfloat16*)d_in[9];
  const __nv_bfloat16* w_d   = (const __nv_bfloat16*)d_in[10];
  const __nv_bfloat16* cvec  = (const __nv_bfloat16*)d_in[11];
  const __nv_bfloat16* w_mod = (const __nv_bfloat16*)d_in[12];
  __nv_bfloat16* out = (__nv_bfloat16*)d_out;

  static HostState st;
  if (!st.ready) {
    void* fn = nullptr; cudaDriverEntryPointQueryResult qr;
    cudaGetDriverEntryPoint("cuTensorMapEncodeTiled", &fn, cudaEnableDefault, &qr);
    st.encode = (EncodeFn)fn;
    cudaFuncSetAttribute(k_fused, cudaFuncAttributeMaxDynamicSharedMemorySize, SMEM);
    build_sched(st.sched);
    void *p_kvc, *p_h1, *p_part;
    cudaGetSymbolAddress(&p_kvc, g_kvc); cudaGetSymbolAddress(&p_h1, g_h1); cudaGetSymbolAddress(&p_part, g_part);
    st.sched.kvc = (__nv_bfloat16*)p_kvc; st.sched.h1 = (__nv_bfloat16*)p_h1; st.sched.part = (__nv_bfloat16*)p_part;
    st.ready = true;
  }
  make_2d(st.encode, &st.tmC, ckv, SEQ, DM, 128);
  make_2d(st.encode, &st.tmWq, w_q, DM, NH * DH, 64);
  make_2d(st.encode, &st.tmWk, w_uk, DM, NH * DH, 64);
  make_2d(st.encode, &st.tmWv, w_uv, DM, NH * DH, 64);
  make_3d(st.encode, &st.tmWo, w_o, NH * DH, DM / 64, (size_t)DM * 2, 128);
  make_3d(st.encode, &st.tmWm, w_mod, DM, 6 * DM / 64, (size_t)6 * DM * 2, 128);
  make_3d(st.encode, &st.tmWd, w_d, FF, DM / 64, (size_t)DM * 2, 128, 16, 8);
  make_ffn(st.encode, &st.tmWg, w_g);
  make_ffn(st.encode, &st.tmWu, w_u);

  k_fused<<<NGRID, 384, SMEM, cudaStreamPerThread>>>(st.tmC, st.tmWq, st.tmWk, st.tmWv, st.tmWo, st.tmWg, st.tmWu, st.tmWd, st.tmWm, st.sched,
                                                     x, cvec, w_o, w_r, w_g, w_u, w_d, out);
}
```

```cpp
#include <cuda_runtime.h>
#include <cuda_bf16.h>
#include <cuda.h>
#include <stdint.h>
#include <string.h>
#include <math.h>

namespace {

constexpr int SEQ = 2048, DM = 512, NH = 32, DH = 128, FF = 1792;
constexpr int NCTA = 128, NGRID = 132;

__device__ __align__(128) __nv_bfloat16 g_kvc[192 * SEQ * 64];
__device__ __align__(128) __nv_bfloat16 g_h1[SEQ * DM];
__device__ __align__(128) __nv_bfloat16 g_part[128 * 8 * 4096];
constexpr int C_MOD = 0, C_MOD2 = 16, C_H1 = 32, C_KV = 64, C_CTX = 128, C_PART = 384, C_END = C_PART + 32 * 32;
struct Exchange {
  uint2 keys[128][4];
  uint2 row[128][2][DM / 2];
  uint2 yll[FF / 16][DM];
  __nv_bfloat16 mod[6 * DM];
  unsigned int cnt[C_END];
  unsigned int epoch;
};
__device__ __align__(4096) Exchange g_x;


__device__ __forceinline__ uint32_t smem_u32(const void* p) { return (uint32_t)__cvta_generic_to_shared(p); }
__device__ __forceinline__ int wg_tid() { int t; asm volatile("mov.u32 %0, %%tid.x;" : "=r"(t)); return t & 127; }
__device__ __forceinline__ void mbar_arrive(uint32_t bar) { asm volatile("mbarrier.arrive.shared::cta.b64 _, [%0];" :: "r"(bar) : "memory"); }
__device__ __forceinline__ uint32_t mapa(uint32_t addr, uint32_t cta) { uint32_t r; asm("mapa.shared::cluster.u32 %0, %1, %2;" : "=r"(r) : "r"(addr), "r"(cta)); return r; }
__device__ __forceinline__ void mbar_arrive_remote_if(uint32_t cluster_addr, bool pred) {
  asm volatile("{\n.reg .pred p;\nsetp.ne.u32 p, %1, 0;\n@p mbarrier.arrive.shared::cluster.b64 _, [%0];\n}" :: "r"(cluster_addr), "r"((uint32_t)pred) : "memory");
}
__device__ __forceinline__ bool mbar_try(uint32_t bar, uint32_t parity) {
  uint32_t done;
  asm volatile("{\n.reg .pred p;\nmbarrier.try_wait.parity.shared::cta.b64 p, [%1], %2;\nselp.u32 %0, 1, 0, p;\n}" : "=r"(done) : "r"(bar), "r"(parity) : "memory");
  return done;
}
__device__ __forceinline__ bool mbar_test2(uint32_t bar, uint32_t parity) {
  uint32_t done;
  asm volatile("{\n.reg .pred p, q;\nmbarrier.test_wait.parity.shared::cta.b64 p, [%1], %2;\nmbarrier.test_wait.parity.shared::cta.b64 q, [%1 + 8], %2;\n"
               "and.pred p, p, q;\nselp.u32 %0, 1, 0, p;\n}" : "=r"(done) : "r"(bar), "r"(parity) : "memory");
  return done;
}
#define WAIT_LIM (1 << 14)
__device__ __forceinline__ void mbar_wait(uint32_t bar, uint32_t parity) {
  #pragma unroll 1
  for (int n = 0; n < WAIT_LIM; n++) { if (mbar_try(bar, parity)) break; }
}
__device__ __forceinline__ unsigned int ld_acquire(const unsigned int* p) {
  unsigned int v; asm volatile("ld.acquire.gpu.global.u32 %0, [%1];" : "=r"(v) : "l"(p) : "memory"); return v;
}
__device__ __forceinline__ unsigned int ld_relaxed(const unsigned int* p) {
  unsigned int v; asm volatile("ld.relaxed.gpu.global.u32 %0, [%1];" : "=r"(v) : "l"(p) : "memory"); return v;
}
__device__ __forceinline__ void wait_count_lazy(int idx, unsigned int target) {
  #pragma unroll 1
  for (int n = 0; n < WAIT_LIM; n++) { if (__all_sync(0xffffffff, (int)(ld_acquire(&g_x.cnt[idx]) - target) >= 0)) break; __nanosleep(100); }
}
__device__ __forceinline__ uint4 ld_tagged2(const void* p) {
  uint4 v;
  asm volatile("{\n.reg .b64 a, b;\nld.relaxed.gpu.global.v2.u64 {a, b}, [%4];\nmov.b64 {%0, %1}, a;\nmov.b64 {%2, %3}, b;\n}"
    : "=r"(v.x), "=r"(v.y), "=r"(v.z), "=r"(v.w) : "l"(p) : "memory");
  return v;
}
__device__ __forceinline__ uint2 ld_tagged(const void* p) {
  uint2 v; asm volatile("{\n.reg .b64 a;\nld.relaxed.gpu.global.u64 a, [%2];\nmov.b64 {%0, %1}, a;\n}" : "=r"(v.x), "=r"(v.y) : "l"(p) : "memory"); return v;
}
__device__ __forceinline__ void st_tagged2(void* p, uint32_t a, uint32_t b, uint32_t tag) {
  asm volatile("{\n.reg .b64 a, b;\nmov.b64 a, {%1, %3};\nmov.b64 b, {%2, %3};\nst.relaxed.gpu.global.v2.u64 [%0], {a, b};\n}" :: "l"(p), "r"(a), "r"(b), "r"(tag) : "memory");
}
__device__ __forceinline__ void st_tagged(void* p, uint32_t a, uint32_t tag) {
  asm volatile("{\n.reg .b64 a;\nmov.b64 a, {%1, %2};\nst.relaxed.gpu.global.u64 [%0], a;\n}" :: "l"(p), "r"(a), "r"(tag) : "memory");
}
__device__ __forceinline__ void stg_v4(void* p, uint32_t a, uint32_t b, uint32_t c, uint32_t d) {
  asm volatile("st.global.v4.u32 [%0], {%1, %2, %3, %4};" :: "l"(p), "r"(a), "r"(b), "r"(c), "r"(d) : "memory");
}
__device__ __forceinline__ uint4 lds_v4(uint32_t addr) {
  uint4 v; asm volatile("ld.shared.v4.u32 {%0, %1, %2, %3}, [%4];" : "=r"(v.x), "=r"(v.y), "=r"(v.z), "=r"(v.w) : "r"(addr) : "memory"); return v;
}
__device__ __forceinline__ uint32_t lds_u32(uint32_t addr) { uint32_t v; asm volatile("ld.shared.u32 %0, [%1];" : "=r"(v) : "r"(addr) : "memory"); return v; }
__device__ __forceinline__ void sts_v4(uint32_t addr, uint32_t a, uint32_t b, uint32_t c, uint32_t d) {
  asm volatile("st.shared.v4.u32 [%0], {%1, %2, %3, %4};" :: "r"(addr), "r"(a), "r"(b), "r"(c), "r"(d) : "memory");
}
#define ELECT "{\n.reg .pred p;\nelect.sync _|p, 0xffffffff;\n@p "
__device__ __forceinline__ void w_mbar_init(uint32_t bar, uint32_t cnt) { asm volatile(ELECT "mbarrier.init.shared::cta.b64 [%0], %1;\n}" :: "r"(bar), "r"(cnt) : "memory"); }
__device__ __forceinline__ void w_expect_tx(uint32_t bar, uint32_t bytes) { asm volatile(ELECT "mbarrier.arrive.expect_tx.shared::cta.b64 _, [%0], %1;\n}" :: "r"(bar), "r"(bytes) : "memory"); }
__device__ __forceinline__ void w_arrive(uint32_t bar) { asm volatile(ELECT "mbarrier.arrive.shared::cta.b64 _, [%0];\n}" :: "r"(bar) : "memory"); }
__device__ __forceinline__ void tma_load_2d(uint32_t dst, const CUtensorMap* tm, uint32_t bar, int c0, int c1) {
  asm volatile(ELECT "cp.async.bulk.tensor.2d.shared::cluster.global.mbarrier::complete_tx::bytes [%0], [%1, {%3, %4}], [%2];\n}"
    :: "r"(dst), "l"(tm), "r"(bar), "r"(c0), "r"(c1) : "memory");
}
__device__ __forceinline__ void tma_load_2d_mc(uint32_t dst, const CUtensorMap* tm, uint32_t bar, int c0, int c1) {
  asm volatile(ELECT "cp.async.bulk.tensor.2d.shared::cluster.global.mbarrier::complete_tx::bytes.multicast::cluster [%0], [%1, {%3, %4}], [%2], %5;\n}"
    :: "r"(dst), "l"(tm), "r"(bar), "r"(c0), "r"(c1), "h"((uint16_t)3) : "memory");
}
__device__ __forceinline__ void tma_load_3d(uint32_t dst, const CUtensorMap* tm, uint32_t bar, int c0, int c1, int c2) {
  asm volatile(ELECT "cp.async.bulk.tensor.3d.shared::cluster.global.mbarrier::complete_tx::bytes [%0], [%1, {%3, %4, %5}], [%2];\n}"
    :: "r"(dst), "l"(tm), "r"(bar), "r"(c0), "r"(c1), "r"(c2) : "memory");
}
__device__ __forceinline__ void tma_load_3d_mc(uint32_t dst, const CUtensorMap* tm, uint32_t bar, int c0, int c1, int c2) {
  asm volatile(ELECT "cp.async.bulk.tensor.3d.shared::cluster.global.mbarrier::complete_tx::bytes.multicast::cluster [%0], [%1, {%3, %4, %5}], [%2], %6;\n}"
    :: "r"(dst), "l"(tm), "r"(bar), "r"(c0), "r"(c1), "r"(c2), "h"((uint16_t)3) : "memory");
}
__device__ __forceinline__ void bulk_load_mc(uint32_t dst, const void* src, uint32_t bar) {
  asm volatile(ELECT "cp.async.bulk.shared::cluster.global.mbarrier::complete_tx::bytes.multicast::cluster [%0], [%1], 16384, [%2], %3;\n}"
    :: "r"(dst), "l"(src), "r"(bar), "h"((uint16_t)3) : "memory");
}
__device__ __forceinline__ void bulk_load(uint32_t dst, const void* src, uint32_t bytes, uint32_t bar) {
  asm volatile(ELECT "cp.async.bulk.shared::cluster.global.mbarrier::complete_tx::bytes [%0], [%1], %2, [%3];\n}" :: "r"(dst), "l"(src), "r"(bytes), "r"(bar) : "memory");
}
__device__ __forceinline__ void tma_prefetch_2d(const CUtensorMap* tm, int c0, int c1) {
  asm volatile(ELECT "cp.async.bulk.prefetch.tensor.2d.L2.global [%0, {%1, %2}];\n}" :: "l"(tm), "r"(c0), "r"(c1) : "memory");
}
__device__ __forceinline__ void bulk_prefetch(const void* p, uint32_t bytes) {
  asm volatile(ELECT "cp.async.bulk.prefetch.L2.global [%0], %1;\n}" :: "l"(p), "r"(bytes) : "memory");
}
__device__ __forceinline__ void red_release(int idx) { asm volatile("red.release.gpu.global.add.u32 [%0], 1;" :: "l"(&g_x.cnt[idx]) : "memory"); }
__device__ __forceinline__ void prefetch_tmap(const CUtensorMap* tm) { asm volatile("prefetch.tensormap [%0];" :: "l"(tm) : "memory"); }
__device__ __forceinline__ void bar_sync(int id, int n) { asm volatile("bar.sync %0, %1;" :: "r"(id), "r"(n) : "memory"); }
__device__ __forceinline__ void bar_arrive(int id, int n) { asm volatile("bar.arrive %0, %1;" :: "r"(id), "r"(n) : "memory"); }
__device__ __forceinline__ void fence_async_smem() { asm volatile("fence.proxy.async.shared::cta;" ::: "memory"); }
__device__ __forceinline__ void fence_async_global() { asm volatile("fence.proxy.async.global;" ::: "memory"); }
__device__ __forceinline__ void fence_mbar_init() { asm volatile("fence.mbarrier_init.release.cluster;" ::: "memory"); }
__device__ __forceinline__ void cluster_arrive() { asm volatile("barrier.cluster.arrive.relaxed.aligned;" ::: "memory"); }
__device__ __forceinline__ void cluster_wait() { asm volatile("barrier.cluster.wait.aligned;" ::: "memory"); }
__device__ __forceinline__ uint32_t cluster_ctarank() { uint32_t r; asm volatile("mov.u32 %0, %%cluster_ctarank;" : "=r"(r)); return r; }
__device__ __forceinline__ void wgmma_fence() { asm volatile("wgmma.fence.sync.aligned;" ::: "memory"); }
__device__ __forceinline__ void wgmma_commit() { asm volatile("wgmma.commit_group.sync.aligned;" ::: "memory"); }
template<int N> __device__ __forceinline__ void wgmma_wait() { asm volatile("wgmma.wait_group.sync.aligned %0;" :: "n"(N) : "memory"); }
__device__ __forceinline__ float ex2(float x) { float y; asm("ex2.approx.ftz.f32 %0, %1;" : "=f"(y) : "f"(x)); return y; }
__device__ __forceinline__ float rcp_fast(float x) { float y; asm("rcp.approx.ftz.f32 %0, %1;" : "=f"(y) : "f"(x)); return y; }
__device__ __forceinline__ uint32_t pack_bf16(float lo, float hi) { uint32_t r; asm("cvt.rn.bf16x2.f32 %0, %1, %2;" : "=r"(r) : "f"(hi), "f"(lo)); return r; }
__device__ __forceinline__ float rbf(float x) { return __uint_as_float(pack_bf16(0.f, x)); }
__device__ __forceinline__ float bf_lo(uint32_t v) { return __uint_as_float(v << 16); }
__device__ __forceinline__ float bf_hi(uint32_t v) { return __uint_as_float(v & 0xffff0000u); }
__device__ __forceinline__ uint32_t add2(uint32_t a, uint32_t b) { uint32_t r; asm("add.rn.bf16x2 %0, %1, %2;" : "=r"(r) : "r"(a), "r"(b)); return r; }
__device__ __forceinline__ uint32_t fma2(uint32_t a, uint32_t b, uint32_t c) { uint32_t r; asm("fma.rn.bf16x2 %0, %1, %2, %3;" : "=r"(r) : "r"(a), "r"(b), "r"(c)); return r; }
__device__ __forceinline__ uint4 ldsm_x4_t(uint32_t addr) {
  uint4 v; asm volatile("ldmatrix.sync.aligned.m8n8.x4.trans.shared.b16 {%0, %1, %2, %3}, [%4];" : "=r"(v.x), "=r"(v.y), "=r"(v.z), "=r"(v.w) : "r"(addr) : "memory"); return v;
}
__device__ __forceinline__ uint4 ldsm_x4(uint32_t addr) {
  uint4 v; asm volatile("ldmatrix.sync.aligned.m8n8.x4.shared.b16 {%0, %1, %2, %3}, [%4];" : "=r"(v.x), "=r"(v.y), "=r"(v.z), "=r"(v.w) : "r"(addr) : "memory"); return v;
}
__device__ __forceinline__ void mma16816(float (&c)[4], const uint4& a, uint32_t b0, uint32_t b1) {
  asm("mma.sync.aligned.m16n8k16.row.col.f32.bf16.bf16.f32 {%0, %1, %2, %3}, {%4, %5, %6, %7}, {%8, %9}, {%0, %1, %2, %3};"
    : "+f"(c[0]), "+f"(c[1]), "+f"(c[2]), "+f"(c[3]) : "r"(a.x), "r"(a.y), "r"(a.z), "r"(a.w), "r"(b0), "r"(b1));
}
template<int N> __device__ __forceinline__ void fence_regs(float (&a)[N]) {
  #pragma unroll
  for (int i = 0; i < N; i++) asm volatile("" : "+f"(a[i]) :: "memory");
}
template<int N> __device__ __forceinline__ void fence_regs_u(uint32_t (&a)[N]) {
  #pragma unroll
  for (int i = 0; i < N; i++) asm volatile("" : "+r"(a[i]) :: "memory");
}
constexpr uint32_t SW128 = 0x40000040u, SW64 = 0x80000020u;
__device__ __forceinline__ uint32_t desc_lo(uint32_t addr, uint32_t lbo) { return ((addr & 0x3FFFF) >> 4) | ((lbo >> 4) << 16); }

template<int TB, int OA, int OB, uint32_t HA, uint32_t HB> __device__ __forceinline__ void wgmma_ss_n128(float (&d)[64], uint32_t da, uint32_t db, int sd) {
  asm volatile("{\n.reg .pred p;\n.reg .b32 ta, tb;\n.reg .b64 da, db;\nsetp.ne.b32 p, %66, 0;\nadd.u32 ta, %64, %68;\nadd.u32 tb, %65, %69;\nmov.b64 da, {ta, %70};\nmov.b64 db, {tb, %71};\n"
    "wgmma.mma_async.sync.aligned.m64n128k16.f32.bf16.bf16 "
    "{%0, %1, %2, %3, %4, %5, %6, %7, %8, %9, %10, %11, %12, %13, %14, %15, %16, %17, %18, %19, %20, %21, %22, %23, %24, %25, %26, %27, %28, %29, %30, %31, %32, %33, %34, %35, %36, %37, %38, %39, %40, %41, %42, %43, %44, %45, %46, %47, %48, %49, %50, %51, %52, %53, %54, %55, %56, %57, %58, %59, %60, %61, %62, %63}, da, db, p, 1, 1, 0, %67;\n}\n"
    : "+f"(d[0]), "+f"(d[1]), "+f"(d[2]), "+f"(d[3]), "+f"(d[4]), "+f"(d[5]), "+f"(d[6]), "+f"(d[7]), "+f"(d[8]), "+f"(d[9]), "+f"(d[10]), "+f"(d[11]), "+f"(d[12]), "+f"(d[13]), "+f"(d[14]), "+f"(d[15]), "+f"(d[16]), "+f"(d[17]), "+f"(d[18]), "+f"(d[19]), "+f"(d[20]), "+f"(d[21]), "+f"(d[22]), "+f"(d[23]), "+f"(d[24]), "+f"(d[25]), "+f"(d[26]), "+f"(d[27]), "+f"(d[28]), "+f"(d[29]), "+f"(d[30]), "+f"(d[31]), "+f"(d[32]), "+f"(d[33]), "+f"(d[34]), "+f"(d[35]), "+f"(d[36]), "+f"(d[37]), "+f"(d[38]), "+f"(d[39]), "+f"(d[40]), "+f"(d[41]), "+f"(d[42]), "+f"(d[43]), "+f"(d[44]), "+f"(d[45]), "+f"(d[46]), "+f"(d[47]), "+f"(d[48]), "+f"(d[49]), "+f"(d[50]), "+f"(d[51]), "+f"(d[52]), "+f"(d[53]), "+f"(d[54]), "+f"(d[55]), "+f"(d[56]), "+f"(d[57]), "+f"(d[58]), "+f"(d[59]), "+f"(d[60]), "+f"(d[61]), "+f"(d[62]), "+f"(d[63])
    : "r"(da), "r"(db), "r"(sd), "n"(TB), "n"(OA), "n"(OB), "n"(HA), "n"(HB));
}
template<int TB, int OB, uint32_t HB> __device__ __forceinline__ void wgmma_rs_n128(float (&d)[64], uint32_t a0, uint32_t a1, uint32_t a2, uint32_t a3, uint32_t db, int sd) {
  asm volatile("{\n.reg .pred p;\n.reg .b32 tb;\n.reg .b64 db;\nsetp.ne.b32 p, %69, 0;\nadd.u32 tb, %68, %71;\nmov.b64 db, {tb, %72};\n"
    "wgmma.mma_async.sync.aligned.m64n128k16.f32.bf16.bf16 "
    "{%0, %1, %2, %3, %4, %5, %6, %7, %8, %9, %10, %11, %12, %13, %14, %15, %16, %17, %18, %19, %20, %21, %22, %23, %24, %25, %26, %27, %28, %29, %30, %31, %32, %33, %34, %35, %36, %37, %38, %39, %40, %41, %42, %43, %44, %45, %46, %47, %48, %49, %50, %51, %52, %53, %54, %55, %56, %57, %58, %59, %60, %61, %62, %63}, {%64,%65,%66,%67}, db, p, 1, 1, %70;\n}\n"
    : "+f"(d[0]), "+f"(d[1]), "+f"(d[2]), "+f"(d[3]), "+f"(d[4]), "+f"(d[5]), "+f"(d[6]), "+f"(d[7]), "+f"(d[8]), "+f"(d[9]), "+f"(d[10]), "+f"(d[11]), "+f"(d[12]), "+f"(d[13]), "+f"(d[14]), "+f"(d[15]), "+f"(d[16]), "+f"(d[17]), "+f"(d[18]), "+f"(d[19]), "+f"(d[20]), "+f"(d[21]), "+f"(d[22]), "+f"(d[23]), "+f"(d[24]), "+f"(d[25]), "+f"(d[26]), "+f"(d[27]), "+f"(d[28]), "+f"(d[29]), "+f"(d[30]), "+f"(d[31]), "+f"(d[32]), "+f"(d[33]), "+f"(d[34]), "+f"(d[35]), "+f"(d[36]), "+f"(d[37]), "+f"(d[38]), "+f"(d[39]), "+f"(d[40]), "+f"(d[41]), "+f"(d[42]), "+f"(d[43]), "+f"(d[44]), "+f"(d[45]), "+f"(d[46]), "+f"(d[47]), "+f"(d[48]), "+f"(d[49]), "+f"(d[50]), "+f"(d[51]), "+f"(d[52]), "+f"(d[53]), "+f"(d[54]), "+f"(d[55]), "+f"(d[56]), "+f"(d[57]), "+f"(d[58]), "+f"(d[59]), "+f"(d[60]), "+f"(d[61]), "+f"(d[62]), "+f"(d[63])
    : "r"(a0), "r"(a1), "r"(a2), "r"(a3), "r"(db), "r"(sd), "n"(TB), "n"(OB), "n"(HB));
}
template<int TB, int OA, int OB, uint32_t HA, uint32_t HB> __device__ __forceinline__ void wgmma_ss_n64(float (&d)[32], uint32_t da, uint32_t db, int sd) {
  asm volatile("{\n.reg .pred p;\n.reg .b32 ta, tb;\n.reg .b64 da, db;\nsetp.ne.b32 p, %34, 0;\nadd.u32 ta, %32, %36;\nadd.u32 tb, %33, %37;\nmov.b64 da, {ta, %38};\nmov.b64 db, {tb, %39};\n"
    "wgmma.mma_async.sync.aligned.m64n64k16.f32.bf16.bf16 "
    "{%0, %1, %2, %3, %4, %5, %6, %7, %8, %9, %10, %11, %12, %13, %14, %15, %16, %17, %18, %19, %20, %21, %22, %23, %24, %25, %26, %27, %28, %29, %30, %31}, da, db, p, 1, 1, 0, %35;\n}\n"
    : "+f"(d[0]), "+f"(d[1]), "+f"(d[2]), "+f"(d[3]), "+f"(d[4]), "+f"(d[5]), "+f"(d[6]), "+f"(d[7]), "+f"(d[8]), "+f"(d[9]), "+f"(d[10]), "+f"(d[11]), "+f"(d[12]), "+f"(d[13]), "+f"(d[14]), "+f"(d[15]), "+f"(d[16]), "+f"(d[17]), "+f"(d[18]), "+f"(d[19]), "+f"(d[20]), "+f"(d[21]), "+f"(d[22]), "+f"(d[23]), "+f"(d[24]), "+f"(d[25]), "+f"(d[26]), "+f"(d[27]), "+f"(d[28]), "+f"(d[29]), "+f"(d[30]), "+f"(d[31])
    : "r"(da), "r"(db), "r"(sd), "n"(TB), "n"(OA), "n"(OB), "n"(HA), "n"(HB));
}
template<int TB, int OA, int OB, uint32_t HA, uint32_t HB> __device__ __forceinline__ void wgmma_ss_n128_new(float (&d)[64], uint32_t da, uint32_t db) {
  asm volatile("{\n.reg .pred p;\n.reg .b32 ta, tb;\n.reg .b64 da, db;\nsetp.ne.b32 p, %66, 0;\nadd.u32 ta, %64, %68;\nadd.u32 tb, %65, %69;\nmov.b64 da, {ta, %70};\nmov.b64 db, {tb, %71};\n"
    "wgmma.mma_async.sync.aligned.m64n128k16.f32.bf16.bf16 "
    "{%0, %1, %2, %3, %4, %5, %6, %7, %8, %9, %10, %11, %12, %13, %14, %15, %16, %17, %18, %19, %20, %21, %22, %23, %24, %25, %26, %27, %28, %29, %30, %31, %32, %33, %34, %35, %36, %37, %38, %39, %40, %41, %42, %43, %44, %45, %46, %47, %48, %49, %50, %51, %52, %53, %54, %55, %56, %57, %58, %59, %60, %61, %62, %63}, da, db, p, 1, 1, 0, %67;\n}\n"
    : "=f"(d[0]), "=f"(d[1]), "=f"(d[2]), "=f"(d[3]), "=f"(d[4]), "=f"(d[5]), "=f"(d[6]), "=f"(d[7]), "=f"(d[8]), "=f"(d[9]), "=f"(d[10]), "=f"(d[11]), "=f"(d[12]), "=f"(d[13]), "=f"(d[14]), "=f"(d[15]), "=f"(d[16]), "=f"(d[17]), "=f"(d[18]), "=f"(d[19]), "=f"(d[20]), "=f"(d[21]), "=f"(d[22]), "=f"(d[23]), "=f"(d[24]), "=f"(d[25]), "=f"(d[26]), "=f"(d[27]), "=f"(d[28]), "=f"(d[29]), "=f"(d[30]), "=f"(d[31]), "=f"(d[32]), "=f"(d[33]), "=f"(d[34]), "=f"(d[35]), "=f"(d[36]), "=f"(d[37]), "=f"(d[38]), "=f"(d[39]), "=f"(d[40]), "=f"(d[41]), "=f"(d[42]), "=f"(d[43]), "=f"(d[44]), "=f"(d[45]), "=f"(d[46]), "=f"(d[47]), "=f"(d[48]), "=f"(d[49]), "=f"(d[50]), "=f"(d[51]), "=f"(d[52]), "=f"(d[53]), "=f"(d[54]), "=f"(d[55]), "=f"(d[56]), "=f"(d[57]), "=f"(d[58]), "=f"(d[59]), "=f"(d[60]), "=f"(d[61]), "=f"(d[62]), "=f"(d[63])
    : "r"(da), "r"(db), "n"(0), "n"(TB), "n"(OA), "n"(OB), "n"(HA), "n"(HB));
}
template<int TB, int OA, int OB, uint32_t HA, uint32_t HB> __device__ __forceinline__ void wgmma_ss_n64_new(float (&d)[32], uint32_t da, uint32_t db) {
  asm volatile("{\n.reg .pred p;\n.reg .b32 ta, tb;\n.reg .b64 da, db;\nsetp.ne.b32 p, %34, 0;\nadd.u32 ta, %32, %36;\nadd.u32 tb, %33, %37;\nmov.b64 da, {ta, %38};\nmov.b64 db, {tb, %39};\n"
    "wgmma.mma_async.sync.aligned.m64n64k16.f32.bf16.bf16 "
    "{%0, %1, %2, %3, %4, %5, %6, %7, %8, %9, %10, %11, %12, %13, %14, %15, %16, %17, %18, %19, %20, %21, %22, %23, %24, %25, %26, %27, %28, %29, %30, %31}, da, db, p, 1, 1, 0, %35;\n}\n"
    : "=f"(d[0]), "=f"(d[1]), "=f"(d[2]), "=f"(d[3]), "=f"(d[4]), "=f"(d[5]), "=f"(d[6]), "=f"(d[7]), "=f"(d[8]), "=f"(d[9]), "=f"(d[10]), "=f"(d[11]), "=f"(d[12]), "=f"(d[13]), "=f"(d[14]), "=f"(d[15]), "=f"(d[16]), "=f"(d[17]), "=f"(d[18]), "=f"(d[19]), "=f"(d[20]), "=f"(d[21]), "=f"(d[22]), "=f"(d[23]), "=f"(d[24]), "=f"(d[25]), "=f"(d[26]), "=f"(d[27]), "=f"(d[28]), "=f"(d[29]), "=f"(d[30]), "=f"(d[31])
    : "r"(da), "r"(db), "n"(0), "n"(TB), "n"(OA), "n"(OB), "n"(HA), "n"(HB));
}
template<int OA, int OB = 0, uint32_t HA = SW128> __device__ __forceinline__ void kblock_n128(float (&d)[64], uint32_t da, uint32_t db, int sd) {
  constexpr int H = HA == SW128 ? 4 : 512;
  wgmma_ss_n128<1, OA, OB, HA, SW128>(d, da, db, sd); wgmma_ss_n128<1, OA + 2, OB + 128, HA, SW128>(d, da, db, 1);
  wgmma_ss_n128<1, OA + H, OB + 256, HA, SW128>(d, da, db, 1); wgmma_ss_n128<1, OA + H + 2, OB + 384, HA, SW128>(d, da, db, 1);
}

__device__ __forceinline__ float quad_sum(float v) {
  v += __shfl_xor_sync(0xffffffff, v, 1);
  v += __shfl_xor_sync(0xffffffff, v, 2);
  return v;
}
struct Row { uint32_t v[8]; };
template<class F> __device__ __forceinline__ Row load_row(const __nv_bfloat16* p, int lane, F ld) {
  const uint4 a = ld(reinterpret_cast<const uint4*>(p) + lane), b = ld(reinterpret_cast<const uint4*>(p) + 32 + lane);
  return Row{{a.x, a.y, a.z, a.w, b.x, b.y, b.z, b.w}};
}
__device__ __forceinline__ Row ldg_row(const __nv_bfloat16* p, int lane) { return load_row(p, lane, [](const uint4* q) { return __ldg(q); }); }
__device__ __forceinline__ Row ldca_row(const __nv_bfloat16* p, int lane) { return load_row(p, lane, [](const uint4* q) { return __ldca(q); }); }
__device__ __forceinline__ Row lds_row(uint32_t addr, int lane) {
  const uint4 a = lds_v4(addr + lane * 16), b = lds_v4(addr + 512 + lane * 16);
  return Row{{a.x, a.y, a.z, a.w, b.x, b.y, b.z, b.w}};
}
__device__ __forceinline__ void store_row(__nv_bfloat16* p, int lane, const Row& r) {
  stg_v4(p + lane * 8, r.v[0], r.v[1], r.v[2], r.v[3]); stg_v4(p + 256 + lane * 8, r.v[4], r.v[5], r.v[6], r.v[7]);
}
__device__ __forceinline__ Row fma_row(const Row& a, const Row& b, const Row& c) {
  Row r;
  #pragma unroll
  for (int i = 0; i < 8; i++) r.v[i] = fma2(a.v[i], b.v[i], c.v[i]);
  return r;
}
__device__ __forceinline__ Row add_row(const Row& a, const Row& b) {
  Row r;
  #pragma unroll
  for (int i = 0; i < 8; i++) r.v[i] = add2(a.v[i], b.v[i]);
  return r;
}
__device__ __forceinline__ Row one_plus(const Row& a) {
  Row r;
  #pragma unroll
  for (int i = 0; i < 8; i++) r.v[i] = add2(a.v[i], 0x3f803f80u);
  return r;
}
__device__ __forceinline__ float row_at(const Row& x, int i) { return (i & 1) ? bf_hi(x.v[i >> 1]) : bf_lo(x.v[i >> 1]); }
template<int N> __device__ __forceinline__ void warp_sums(float (&s)[N]) {
  #pragma unroll
  for (int o = 16; o > 0; o >>= 1) {
    #pragma unroll
    for (int k = 0; k < N; k++) s[k] += __shfl_xor_sync(0xffffffff, s[k], o);
  }
}
__device__ __forceinline__ void ln_stats(float& s1, float& s2) {
  s1 *= 1.f / DM;
  asm("rsqrt.approx.ftz.f32 %0, %1;" : "=f"(s2) : "f"(fmaxf(fmaf(-s1, s1, s2 * (1.f / DM)), 0.f) + 1e-5f));
}
__device__ __forceinline__ Row ln_apply(const Row& x, float mean, float f) {
  Row n;
  const float o = -mean * f;
  #pragma unroll
  for (int i = 0; i < 8; i++) n.v[i] = pack_bf16(fmaf(bf_lo(x.v[i]), f, o), fmaf(bf_hi(x.v[i]), f, o));
  return n;
}

constexpr int SM_Q = 6 * 32768, SM_BAR = 7 * 32768, SM_MAIL = SM_BAR + 640, SM_RED = SM_MAIL + 128, SM_H2 = SM_RED + 1024, SM_KEY = SM_H2 + 1024, SMEM = SM_KEY + 128;
constexpr int B_AF = 0, B_WF = 64, B_RF = 112, B_WE = 168, B_RE = 216, B_PUB = 272, B_RDY = 496;
constexpr int R_MOD = B_RDY, R_H1 = B_RDY + 8, R_ITEM = B_RDY + 16, R_NEAR = B_RDY + 48, R_CTX = B_RDY + 64;
constexpr int R_KEY = B_AF + 8, R_PART = B_AF + 32;
constexpr int NPUB = 14;
__device__ __forceinline__ uint32_t k_addrA(int kb) { return ((0x6310u >> ((kb >> 1) * 4)) & 15u) * 32768u + (kb & 1) * 16384u; }
__device__ __forceinline__ uint32_t k_addrW(int s) { return ((0x254u >> ((s >> 1) * 4)) & 15u) * 32768u + (s & 1) * 16384u; }

#define KORDER 0x3201
constexpr int KHEAD0 = ((KORDER >> 12) & 3) * 8;
constexpr int MAX_ITEMS = 4;
constexpr int MAX_STEPS = 10;
struct Sched {
  __nv_bfloat16 *kvc, *h1, *part;
  struct Pair {
    uint8_t oent[3 * MAX_STEPS + 6];
    uint8_t khead[4];
    uint8_t nitems, item[MAX_ITEMS];
    uint8_t otask, nsteps;
    uint8_t ochunk[MAX_STEPS][2];
  } pair[NGRID / 2];
};

__device__ __forceinline__ int ring_add(int e, int n) { e += n; return e >= 12 ? e - 12 : e; }
__device__ __forceinline__ int ring_slot(int e) { return e >= 6 ? e - 6 : e; }
__device__ __forceinline__ void ring_wait_full(uint32_t bars, int e) { mbar_wait(bars + B_RF + 8 * ring_slot(e), e >= 6); }

__device__ __forceinline__ void o_wait_full(uint32_t bars, uint32_t v) { mbar_wait(bars + B_RF + 8 * (v & 7), v >> 3); }

struct Ctx {
  uint32_t base, bars;
  uint32_t rel;
  bool rel1;
  int w, nev;
  const Sched* sched;
};
__device__ __forceinline__ void slot_release(const Ctx& x, int s, bool twice) {
  mbar_arrive_remote_if(x.rel + B_RE + 8 * s, twice ? (wg_tid() & 31) == 0 : x.rel1);
}
__device__ __forceinline__ void ring_release(const Ctx& x, int e, bool twice) { slot_release(x, ring_slot(e), twice); }
__device__ __forceinline__ void publish(Ctx& x, int idx) {
  const uint32_t n = x.w * NPUB + x.nev;
  const int t = wg_tid();
  if (t == 0) asm volatile("st.shared.u32 [%0], %1;" :: "r"(x.base + SM_MAIL + 4 * n), "r"(idx) : "memory");
  __syncwarp();
  if ((t & 31) == 0) mbar_arrive(x.bars + B_PUB + 8 * n);
  x.nev++;
}

template<int KK = 0> __device__ __forceinline__ void issue_qk(float (&S)[64], uint32_t dq, uint32_t dk) {
  constexpr int off = (KK >> 1) * 512 + (KK & 1) * 2;
  if constexpr (KK == 0) wgmma_ss_n128_new<0, 0, 0, SW64, SW64>(S, dq, dk); else wgmma_ss_n128<0, off, off, SW64, SW64>(S, dq, dk, 1);
  if constexpr (KK < 7) issue_qk<KK + 1>(S, dq, dk);
}
template<int KK = 0> __device__ __forceinline__ void issue_qk_half(float (&S)[32], uint32_t dq, uint32_t dk) {
  constexpr int off = (KK >> 1) * 512 + (KK & 1) * 2;
  if constexpr (KK == 0) wgmma_ss_n64_new<0, 0, 256, SW64, SW64>(S, dq, dk); else wgmma_ss_n64<0, off, off + 256, SW64, SW64>(S, dq, dk, 1);
  if constexpr (KK < 7) issue_qk_half<KK + 1>(S, dq, dk);
}
template<int NK, int KK = 0>
__device__ __forceinline__ void issue_pv(float (&O)[64], uint32_t (&P)[32], uint32_t dv, int accumulate) {
  wgmma_rs_n128<1, (KK + 8 - NK) * 64, SW64>(O, P[4*KK], P[4*KK+1], P[4*KK+2], P[4*KK+3], dv, accumulate);
  if constexpr (KK + 1 < NK) issue_pv<NK, KK + 1>(O, P, dv, 1);
}
template<int K0, int K1>
__device__ __forceinline__ void exp_pack(const float (&S)[64], uint32_t (&D)[32], float& s0, float& s1) {
  #pragma unroll
  for (int k = K0; k < K1; k++) {
    const float e0 = ex2(S[2*k]), e1 = ex2(S[2*k+1]);
    D[k] = pack_bf16(e0, e1);
    if (k & 1) s1 += e0 + e1; else s0 += e0 + e1;
  }
}
__device__ __forceinline__ int diag_limit() { const int t = wg_tid(); return 16 * (t >> 5) + ((t & 31) >> 2) - 2 * (t & 3); }
__device__ __forceinline__ void exp_pack_diag(const float (&S)[64], uint32_t (&D)[32], int t, float& s0, float& s1) {
  #pragma unroll
  for (int k = 0; k < 16; k++) {
    const int c = 8 * (k >> 1) - 8 * (k & 1);
    const float e0 = ex2((c <= t) ? S[2*k] : -INFINITY), e1 = ex2((c + 1 <= t) ? S[2*k+1] : -INFINITY);
    D[k] = pack_bf16(e0, e1);
    if (k & 1) s1 += e0 + e1; else s0 += e0 + e1;
  }
}
constexpr float SUM_HI = 1.8446744073709552e19f;
constexpr float SUM_LO = 5.421010862427522e-20f;

__device__ __forceinline__ void classic_tile(const float (&S)[64], uint32_t (&P)[32], bool fresh, bool half, bool was_classic, volatile float* mc,
                                             float& l0, float& l1, float& s0, float& s1, float& sc0, float& sc1) {
  const int tmask = diag_limit();
  float4 t[16];
  #pragma unroll
  for (int j = 0; j < 16; j++) t[j] = make_float4(S[4*j], S[4*j+1], S[4*j+2], S[4*j+3]);
  float mx0 = -INFINITY, mx1 = -INFINITY;
  #pragma unroll 1
  for (int j = 0; j < 16; j++) {
    float4 v = t[j];
    const int lim = !fresh ? 1000 : j < 8 ? tmask - 8 * j : half ? -1000 : 1000;
    v.x = 0 <= lim ? v.x : -INFINITY; v.y = 1 <= lim ? v.y : -INFINITY; v.z = -8 <= lim ? v.z : -INFINITY; v.w = -7 <= lim ? v.w : -INFINITY;
    t[j] = v;
    mx0 = fmaxf(mx0, fmaxf(v.x, v.y)); mx1 = fmaxf(mx1, fmaxf(v.z, v.w));
  }
  mx0 = fmaxf(mx0, __shfl_xor_sync(0xffffffff, mx0, 1));
  mx1 = fmaxf(mx1, __shfl_xor_sync(0xffffffff, mx1, 1));
  mx0 = fmaxf(mx0, __shfl_xor_sync(0xffffffff, mx0, 2));
  mx1 = fmaxf(mx1, __shfl_xor_sync(0xffffffff, mx1, 2));
  const float mc0 = was_classic ? mc[0] : 0.f, mc1 = was_classic ? mc[1] : 0.f;
  const float n0 = fresh ? -mx0 : fminf(mc0, -mx0), n1 = fresh ? -mx1 : fminf(mc1, -mx1);
  sc0 = ex2(n0 - mc0); sc1 = ex2(n1 - mc1);
  mc[0] = n0; mc[1] = n1;
  s0 = 0.f; s1 = 0.f;
  #pragma unroll 1
  for (int j = 0; j < 16; j++) {
    const float4 v = t[j];
    const float e0 = ex2(v.x + n0), e1 = ex2(v.y + n0), e2 = ex2(v.z + n1), e3 = ex2(v.w + n1);
    s0 += e0 + e1; s1 += e2 + e3;
    reinterpret_cast<uint2*>(t)[j] = make_uint2(pack_bf16(e0, e1), pack_bf16(e2, e3));
  }
  #pragma unroll
  for (int j = 0; j < 8; j++) { P[4*j] = __float_as_uint(t[j].x); P[4*j+1] = __float_as_uint(t[j].y); P[4*j+2] = __float_as_uint(t[j].z); P[4*j+3] = __float_as_uint(t[j].w); }
  if (!fresh) { l0 *= sc0; l1 *= sc1; }
}
__device__ __forceinline__ void pack_tile(const float (&A)[64], uint32_t (&D)[32], float f0, float f1) {
  #pragma unroll
  for (int j = 0; j < 16; j++) {
    D[8 * (j >> 2) + (j & 3)] = pack_bf16(A[4*j] * f0, A[4*j+1] * f0);
    D[8 * (j >> 2) + 4 + (j & 3)] = pack_bf16(A[4*j+2] * f1, A[4*j+3] * f1);
  }
}
__device__ __forceinline__ int piece0(int t) { return ((t >> 5) * 16 + ((t & 31) >> 2)) * 32 + (((t ^ (t >> 3)) & 3) << 3); }
__device__ __forceinline__ void store_tile(__nv_bfloat16* p, const uint32_t (&D)[32]) {
  #pragma unroll
  for (int i = 0; i < 8; i++) stg_v4(p + (i >> 2) * (SEQ * 64) + ((i >> 1) & 1) * 4096 + (i & 1) * 256, D[4*i], D[4*i+1], D[4*i+2], D[4*i+3]);
}

enum : int { PV_ACC = 0, PV_ZERO = 1, PV_HALF = 2, PV_NONE = 3 };
struct Att {
  float l0, l1, i0, i1;
  bool classic;
  volatile float* mc;
};
__device__ __forceinline__ void store_ctx(Ctx& x, int code, const uint32_t (&D)[32]) {
  store_tile(x.sched->kvc + ((size_t)(128 + (code >> 5) * 2) * SEQ + ((code >> 1) & 15) * 128) * 64 + (code & 1) * 2048 + piece0(wg_tid()), D);
  publish(x, C_CTX + (code >> 2));
}
__device__ __forceinline__ __nv_bfloat16* kv_tile(const Ctx& x, int code) {
  return x.sched->kvc + ((size_t)(x.w * 64 + (code >> 4) * 2) * SEQ + (code & 15) * 128) * 64 + piece0(wg_tid());
}
__device__ __forceinline__ void q_proj(Ctx& x, Att& a, int& e, int& sk, int& sv, int& en, int& sn, bool isY,
                                       const uint32_t (&PA)[32], const uint32_t (&PB)[32], int vtile, bool first) {
  float S[64];
  int ek = 0, s = sk, ps = 0, ph = e >= 6, kb = 0;
  uint32_t qa = 0;
  sv = en = sn = 0;
  if (isY) bar_sync(1 + x.w, 256);
  if (first) mbar_wait(x.bars + B_RF + 8 * s, ph);
  #pragma unroll 1
  while (true) {
    #pragma unroll 1
    do {
      wgmma_fence();
      kblock_n128<0>(S, desc_lo(x.base + x.w * 8192, 16) + s * 2048, desc_lo(x.base + 16384, 8192) + s * 2048, kb != 0);
      wgmma_commit();
      if (kb == 7 && !isY) bar_arrive(1 + (x.w ^ 1), 256);
      wgmma_wait<1>();
      mbar_arrive_remote_if(x.rel + B_RE + 8 * ps, x.rel1 && kb > 0);
      ps = s;
      if (++s == 6) { s = 0; ph ^= 1; }
      if (++kb == 8) break;
      mbar_wait(x.bars + B_RF + 8 * s, ph);
    } while (kb != 4);
    asm volatile("" : "+r"(vtile));
    if (kb == 8) break;
    a.i0 = rcp_fast(quad_sum(a.l0)); a.i1 = rcp_fast(quad_sum(a.l1));
    e = ring_add(e, 8); ek = ring_add(e, isY ? 0 : 2); en = ring_add(e, isY ? 2 : 4);
    sk = ring_slot(ek); sv = ring_slot(e) + 1; sn = ring_slot(en);
    qa = x.base + SM_Q + x.w * 4096 + piece0(wg_tid()) * 2;
    if (vtile >= 0) store_tile(kv_tile(x, vtile) + 2048, PA);
  }
  if (vtile >= 0) { store_tile(kv_tile(x, vtile), PB); publish(x, C_KV + (vtile >> 4)); }
  wgmma_wait<0>();
  fence_regs(S);
  slot_release(x, ps, false);
  const bool landed = isY && mbar_test2(x.bars + B_RF + 8 * sk, e >= 6);
  #pragma unroll
  for (int i = 0; i < 8; i++) {
    const int j = 4 * (i >> 1), o = 2 * (i & 1);
    sts_v4(qa + (i >> 1) * 8192 + (i & 1) * 512,
           pack_bf16(S[4*j+o], S[4*j+o+1]), pack_bf16(S[4*j+4+o], S[4*j+5+o]), pack_bf16(S[4*j+8+o], S[4*j+9+o]), pack_bf16(S[4*j+12+o], S[4*j+13+o]));
  }
  fence_async_smem();
  if (!landed) { mbar_wait(x.bars + B_RF + 8 * sk, ek >= 6); mbar_wait(x.bars + B_RF + 8 * sv, e >= 6); }
}

template<int KIND>
__device__ __forceinline__ void slot(Ctx& x, Att& a, int& e, int& sk, int sv, int en, int sn, float (&O)[64], uint32_t (&Pn)[32], uint32_t (&Po)[32],
                                     bool more, bool isY, bool half, int pv, int pend) {
  float S[64];
  const int w = x.w;
  const uint32_t dq = desc_lo(x.base + SM_Q + w * 4096, 16), dk = desc_lo(x.base, 16) + sk * 2048, dv = desc_lo(x.base, 8192) + sv * 2048;
  bar_sync(1 + w, 256);
  if (KIND == 2) {
    wgmma_fence();
    issue_qk(S, dq, dk); wgmma_commit();
    issue_pv<8>(O, Po, dv, 1); wgmma_commit();
    bar_arrive(1 + (w ^ 1), 256);
    wgmma_wait<1>();
  } else if (KIND == 0 && half) {
    float T[32];
    wgmma_fence(); issue_qk_half(T, dq, dk); wgmma_commit();
    if (pv == PV_NONE) { wgmma_fence(); wgmma_commit(); }
    else               { wgmma_fence(); issue_pv<8>(O, Po, dv, pv == PV_ACC); wgmma_commit(); }
    bar_arrive(1 + (w ^ 1), 256);
    wgmma_wait<1>();
    fence_regs(T);
    #pragma unroll
    for (int i = 0; i < 32; i++) { S[i] = T[i]; asm volatile("" : "=f"(S[32 + i])); }
  } else {
    wgmma_fence(); issue_qk(S, dq, dk); wgmma_commit();
    if (KIND == 1 && pend >= 0) { bar_arrive(1 + (w ^ 1), 256); pack_tile(O, Pn, a.i0, a.i1); store_ctx(x, pend, Pn); }
    if (KIND == 0 && pv == PV_NONE) { wgmma_fence(); wgmma_commit(); }
    else if (pv == PV_HALF)         { wgmma_fence(); issue_pv<4>(O, Po, dv, 0); wgmma_commit(); }
    else                            { wgmma_fence(); issue_pv<8>(O, Po, dv, pv == PV_ACC); wgmma_commit(); }
    if (KIND == 0 || pend < 0) bar_arrive(1 + (w ^ 1), 256);
    wgmma_wait<1>();
  }
  fence_regs(S);
  fence_regs_u(Pn);
  slot_release(x, sk, KIND == 0 && isY);
  const bool landed = mbar_test2(x.bars + B_RF + 8 * sn, en >= 6);
  float s0 = 0.f, s1 = 0.f;
  const bool was_classic = KIND != 0 && a.classic;
  if (KIND == 0) {
    a.l0 = 0.f; a.l1 = 0.f;
    if (!half) exp_pack<16, 32>(S, Pn, s0, s1);
    else {
      #pragma unroll
      for (int i = 16; i < 32; i++) asm volatile("" : "=r"(Pn[i]));
    }
    exp_pack_diag(S, Pn, diag_limit(), s0, s1);
    uint32_t b0 = __ballot_sync(0xffffffff, s0 >= SUM_LO), b1 = __ballot_sync(0xffffffff, s1 >= SUM_LO);
    b0 |= b0 >> 1; b0 |= b0 >> 2; b1 |= b1 >> 1; b1 |= b1 >> 2;
    a.classic = __any_sync(0xffffffff, !(s0 <= SUM_HI && s1 <= SUM_HI)) || (b0 & b1 & 0x11111111u) != 0x11111111u;
  } else {
    exp_pack<0, 32>(S, Pn, s0, s1);
    a.classic = __any_sync(0xffffffff, a.classic || !(s0 <= SUM_HI && s1 <= SUM_HI));
  }
  fence_regs_u(Pn);
  if (!landed) {
    mbar_wait(x.bars + B_RF + 8 * sn, en >= 6);
    if (more) mbar_wait(x.bars + B_RF + 8 * sn + 8, en >= 6);
  }
  wgmma_wait<0>();
  fence_regs(O);
  fence_regs_u(Po);
  slot_release(x, sv, KIND == 1 && isY && pv != PV_ACC);
  if (__builtin_expect(a.classic, 0)) {
    float sc0, sc1;
    classic_tile(S, Pn, KIND == 0, half, was_classic, a.mc, a.l0, a.l1, s0, s1, sc0, sc1);
    if (KIND != 0) {
      #pragma unroll
      for (int j = 0; j < 16; j++) { O[4*j] *= sc0; O[4*j+1] *= sc0; O[4*j+2] *= sc1; O[4*j+3] *= sc1; }
    }
  }
  a.l0 += s0; a.l1 += s1;
  e = en; sk = sn;
}

__device__ __forceinline__ int attention(Ctx& x, const uint8_t* items, int nitems, int rank, uint32_t (&PA)[32], uint32_t (&PB)[32], int vtile) {
  int e = 0, sk = 0;
  float O[64];
  Att a;
  volatile float mc[2];
  a.l0 = 1.f; a.l1 = 1.f; a.i0 = 0.f; a.i1 = 0.f; a.classic = false; a.mc = mc;
  int pv = PV_NONE, cur = -1;
  #pragma unroll 1
  for (int it = 0; ; it++) {
    const bool isY = (it & 1) == x.w;
    int pend = cur;
    if (it < nitems) {
      const bool half = isY == (rank != 0);
      int sv, en, sn;
      q_proj(x, a, e, sk, sv, en, sn, isY, PA, PB, vtile, it == 0);
      vtile = -1;
      const int item = items[it];
      cur = item * 4 + (isY ? 3 - rank : rank);
      int rem = 2 * (item & 7) + (isY ? 1 : 0);
      slot<0>(x, a, e, sk, sv, en, sn, O, PA, PB, rem > 0, isY, half, pv, -1);
      pv = half ? PV_HALF : PV_ZERO;
      #pragma unroll 1
      while (rem > 0) {
        slot<1>(x, a, e, sk, sk + 1, ring_add(e, 2), sk == 4 ? 0 : sk + 2, O, PB, PA, rem > 1, isY, false, pv, pend);
        pv = PV_ACC; pend = -1;
        if (rem == 1) break;
        rem -= 2;
        slot<2>(x, a, e, sk, sk + 1, ring_add(e, 2), sk == 4 ? 0 : sk + 2, O, PA, PB, rem > 0, false, false, 0, -1);
      }
      if (isY) continue;
    } else {
      slot_release(x, 6, false);
      const uint32_t dv = desc_lo(x.base, 8192) + sk * 2048;
      bar_sync(1 + x.w, 256);
      if (pv == PV_HALF) { wgmma_fence(); issue_pv<4>(O, PB, dv, 0); wgmma_commit(); }
      else { wgmma_fence(); issue_pv<8>(O, PB, dv, pv == PV_ACC); wgmma_commit(); }
      if (isY) bar_arrive(1 + (x.w ^ 1), 256);
      a.i0 = rcp_fast(quad_sum(a.l0)); a.i1 = rcp_fast(quad_sum(a.l1));
      ring_wait_full(x.bars, e);
      wgmma_wait<0>();
      fence_regs(O);
      fence_regs_u(PB);
      slot_release(x, sk, false);
    }
    if (pend >= 0) {
      pack_tile(O, PB, a.i0, a.i1);
      if (it == nitems) return pend;
      store_ctx(x, pend, PB);
    }
    #pragma unroll
    for (int i = 0; i < 32; i++) asm volatile("mov.b32 %0, %1;" : "=r"(PB[i]) : "r"(PA[i]));
  }
}

#define LN_AT 2
#define X_AT 6
#define PERT 0
#define CTX_T 3
#define PF_AT 5
#define PF_N 4
#define PF_MOE 3
constexpr float QSCALE = 0.08838834764831845f * 1.4426950408889634f;
__device__ __forceinline__ void mod_cta(Ctx& x, const __nv_bfloat16* cvec) {
  const int t = wg_tid(), ct = x.w * 128 + t;
  #pragma unroll 1
  for (int k = 0; k < 6; k++) slot_release(x, k, false);
  const uint32_t cv = __ldg(reinterpret_cast<const uint32_t*>(cvec) + ct);
  asm volatile("st.shared.u32 [%0], %1;" :: "r"(x.base + SM_H2 + ct * 4),
               "r"(pack_bf16(__fdividef(bf_lo(cv), 1.f + __expf(-bf_lo(cv))), __fdividef(bf_hi(cv), 1.f + __expf(-bf_hi(cv))))) : "memory");
  bar_sync(5, 256);
  float acc[64];
  int e = 0;
  #pragma unroll 1
  for (int g = 0; g < 24; g++) {
    uint32_t a[8];
    #pragma unroll
    for (int i = 0; i < 8; i++) a[i] = lds_u32(x.base + SM_H2 + (g & 7) * 128 + i * 16 + (t & 3) * 4);
    ring_wait_full(x.bars, e);
    const uint32_t db = desc_lo(x.base + x.w * 16384, 8192) + ring_slot(e) * 2048;
    wgmma_fence();
    wgmma_rs_n128<1, 0, SW128>(acc, a[0], a[0], a[1], a[1], db, g & 7);
    wgmma_rs_n128<1, 128, SW128>(acc, a[2], a[2], a[3], a[3], db, 1);
    wgmma_rs_n128<1, 256, SW128>(acc, a[4], a[4], a[5], a[5], db, 1);
    wgmma_rs_n128<1, 384, SW128>(acc, a[6], a[6], a[7], a[7], db, 1);
    wgmma_commit();
    wgmma_wait<0>();
    fence_regs(acc);
    ring_release(x, e, false);
    e = ring_add(e, 1);
    if ((g & 7) == 7) {
      if (t < 4) {
        const float sc = (g == 7 && blockIdx.x < NCTA + 2) ? QSCALE : 1.f;
        uint32_t* dst = reinterpret_cast<uint32_t*>(g_x.mod + (g >> 3) * 1024 + (blockIdx.x - NCTA) * 256 + x.w * 128) + t;
        #pragma unroll
        for (int j = 0; j < 16; j++) dst[4 * j] = pack_bf16(rbf(acc[4*j]) * sc, rbf(acc[4*j+1]) * sc);
      }
      publish(x, g == 7 ? C_MOD : C_MOD2);
    }
  }
}

__global__ void __cluster_dims__(2, 1, 1) __launch_bounds__(384, 1)
k_fused(const __grid_constant__ CUtensorMap tmC, const __grid_constant__ CUtensorMap tmWq,
        const __grid_constant__ CUtensorMap tmWk, const __grid_constant__ CUtensorMap tmWv,
        const __grid_constant__ CUtensorMap tmWo, const __grid_constant__ CUtensorMap tmWg,
        const __grid_constant__ CUtensorMap tmWu, const __grid_constant__ CUtensorMap tmWd, const __grid_constant__ CUtensorMap tmWm,
        const __grid_constant__ Sched sched,
        const __nv_bfloat16* __restrict__ xin,
        const __nv_bfloat16* __restrict__ cvec, const __nv_bfloat16* __restrict__ w_o,
        const __nv_bfloat16* __restrict__ w_r, const __nv_bfloat16* __restrict__ w_gate, const __nv_bfloat16* __restrict__ w_up,
        const __nv_bfloat16* __restrict__ w_down, __nv_bfloat16* __restrict__ out) {
  extern __shared__ __align__(1024) uint8_t smem_raw[];
  const uint32_t base = smem_u32(smem_raw), bars = base + SM_BAR;
  const int warp = __shfl_sync(0xffffffff, threadIdx.x >> 5, 0), wg = warp >> 2;
  const int rank = cluster_ctarank(), p = blockIdx.x >> 1;
  const int mt = (p & 7) * 2 + rank;
  const bool spare = blockIdx.x >= NCTA;
  #pragma unroll
  for (int i = 0; i < PERT; i++) { uint32_t d; asm volatile("mov.u32 %0, %%laneid;" : "=r"(d)); (void)d; }
  {
    const int h0 = KHEAD0 + (p >> 3);
    if (warp == 11) { prefetch_tmap(&tmC); prefetch_tmap(&tmWk); }
    #pragma unroll 1
    for (int t = warp == 8 ? 0 : warp < 8 ? warp + 1 : warp == 11 ? 64 : warp; t < B_PUB / 8; t += (warp == 8 ? 64 : 10))
      w_mbar_init(bars + 8 * t, t < B_WE / 8 ? 1 : t < B_RE / 8 ? 2 : 4);
    fence_mbar_init();
    cluster_arrive();
    if (warp == 9) prefetch_tmap(&tmWv);
    if (wg == 2) bar_arrive(1, 256);
    if (warp == 8 && !spare) {
      #pragma unroll 1
      for (int kb = 0; kb < 8; kb++) {
        w_expect_tx(bars + B_AF + 8 * kb, 16384);
        tma_load_2d(base + k_addrA(kb), &tmC, bars + B_AF + 8 * kb, kb * 64, mt * 128);
        if (kb == 0) cluster_wait();
        if (kb < 6) {
          w_expect_tx(bars + B_WF + 8 * kb, 16384);
          tma_load_2d_mc(base + k_addrW(kb) + rank * 8192, &tmWk, bars + B_WF + 8 * kb, h0 * 128 + rank * 64, kb * 64);
        }
      }
    }
  }
  const Sched::Pair& sp = sched.pair[p];
  const int nitems = sp.nitems, nsteps = sp.nsteps;
  auto oent = [&](int k) -> uint32_t { return sp.oent[k]; };
  const int ot = sp.otask, m = (ot & 7) * 2 + rank, grp = m * 8 + (ot >> 3);

  if (wg == 0) {
    asm volatile("setmaxnreg.dec.sync.aligned.u32 24;");
    const int lane = threadIdx.x & 31;
    #pragma unroll 1
    for (int t = B_PUB / 8 + warp; t < 80; t += 4) w_mbar_init(bars + 8 * t, t < B_RDY / 8 ? 4 : 1);
    bar_sync(6, 128);
    bar_arrive(7, 256); bar_arrive(8, 256);
    cluster_wait();
    const unsigned int tag = ld_relaxed(&g_x.epoch) + 1;
    if (warp == 0) {
      if (!spare) {
        int s = 0, ph = 0;
        tma_prefetch_2d(&tmWv, sp.khead[0] * 128 + rank * 64, (p & 7) * 64);
        #pragma unroll 1
        for (int g = 6; g < 64; g++) {
          const int u = g >> 3, kb = g & 7;
          if (kb == 0 && u < 7) tma_prefetch_2d((u & 1) ? &tmWk : &tmWv, sp.khead[(u + 1) >> 1] * 128 + rank * 64, (p & 7) * 64);
          mbar_wait(bars + B_WE + 8 * s, ph);
          w_expect_tx(bars + B_WF + 8 * s, 16384);
          tma_load_2d_mc(base + k_addrW(s) + rank * 8192, (u & 1) ? &tmWv : &tmWk, bars + B_WF + 8 * s, sp.khead[u >> 1] * 128 + rank * 64, kb * 64);
          if (++s == 6) { s = 0; ph ^= 1; }
        }
      }
      int s = 0, ph = 0;
      auto next_entry = [&](int bytes) {
        mbar_wait(bars + B_RE + 8 * s, ph);
        w_expect_tx(bars + B_RF + 8 * s, bytes);
      };
      auto advance = [&]() { if (++s == 6) { s = 0; ph ^= 1; } };
      if (spare) {
        #pragma unroll 1
        for (int g = 0; g < 24; g++) {
          if (g == 8) mbar_wait(bars + R_MOD, 0);
          next_entry(32768);
          for (int k = 0; k < 2; k++) tma_load_3d(base + s * 32768 + k * 16384, &tmWm, bars + B_RF + 8 * s, 0, (g & 7) * 64, (g >> 3) * 16 + (blockIdx.x - NCTA) * 4 + k * 2);
          advance();
        }
      }
      mbar_wait(bars + R_H1, 0);
      fence_async_global();
      int vrow = -1;
      #pragma unroll 1
      for (int i = 0; i <= nitems; i++) {
        const int item = sp.item[i & (MAX_ITEMS - 1)], h = item >> 3, j = item & 7;
        if (i < nitems) {
          const int row0 = j * 256 + ((i & 1) ? rank : 3 - rank) * 64, row1 = j * 256 + ((i & 1) ? 3 - rank : rank) * 64;
          #pragma unroll 1
          for (int kb = 0; kb < 8; kb++) {
            next_entry(32768);
            tma_load_2d_mc(base + s * 32768 + 16384 + rank * 8192, &tmWq, bars + B_RF + 8 * s, h * 128 + rank * 64, kb * 64);
            bulk_load(base + s * 32768, sched.h1 + row0 * DM + kb * 4096, 8192, bars + B_RF + 8 * s);
            bulk_load(base + s * 32768 + 8192, sched.h1 + row1 * DM + kb * 4096, 8192, bars + B_RF + 8 * s);
            advance();
          }
          mbar_wait(bars + R_ITEM + 8 * i, 0);
          fence_async_global();
        }
        #pragma unroll 1
        for (int n = i < nitems ? 4 * j + 3 : 0; n >= 0; n--) {
          const int krow = (h * 2 + rank) * SEQ + (n >> 1) * 128;
          const int row = (n & 1) ? krow : vrow;
          if (i + 1 == nitems && n == min(4 * j + 3, 2 * PF_AT + 1)) w_arrive(bars + R_NEAR);
          next_entry(row >= 0 ? 32768 : 0);
          if (row >= 0) bulk_load_mc(base + s * 32768 + rank * 16384, sched.kvc + (size_t)row * 64, bars + B_RF + 8 * s);
          advance();
          if (!(n & 1)) vrow = krow + 64 * SEQ;
        }
      }
      if (!spare) {
      const int oc = ((ot >> 3) & 1) * 4 + rank * 2;
      auto o_next = [&](int k, int bytes) {
        const uint32_t v = oent(k); s = v & 7;
        mbar_wait(bars + B_RE + 8 * s, v >> 3);
        w_expect_tx(bars + B_RF + 8 * s, bytes);
      };
      #pragma unroll 1
      for (int i = 0; i < nsteps; i++) {
        const int c0 = sp.ochunk[i][0], c1 = sp.ochunk[i][1];
        const int pf = i - nsteps + PF_MOE;
        if (pf >= 0 && pf < 3)
          bulk_prefetch((pf == 0 ? w_gate : pf == 1 ? w_up : w_down) + (size_t)blockIdx.x * (DM * FF / NCTA), DM * FF / NCTA * 2);
        if (c0 < 64) { o_next(3 * i, 32768); tma_load_3d_mc(base + s * 32768 + rank * 16384, &tmWo, bars + B_RF + 8 * s, 0, c0 * 64, oc); }
        mbar_wait(bars + R_CTX + 8 * i, 0);
        fence_async_global();
        o_next(3 * i + 1, c0 < 64 ? 32768 : 16384);
        if (c0 < 64) bulk_load(base + s * 32768, sched.kvc + (size_t)((128 + c0) * SEQ + m * 128) * 64, 16384, bars + B_RF + 8 * s);
        bulk_load(base + s * 32768 + 16384, sched.kvc + (size_t)((128 + c1) * SEQ + m * 128) * 64, 16384, bars + B_RF + 8 * s);
        o_next(3 * i + 2, 32768);
        tma_load_3d_mc(base + s * 32768 + rank * 16384, &tmWo, bars + B_RF + 8 * s, 0, c1 * 64, oc);
      }
      const int f0 = (blockIdx.x < FF / 16 ? blockIdx.x : 0) * 16;
      o_next(3 * nsteps, 32768);
      tma_load_3d(base + s * 32768, &tmWd, bars + B_RF + 8 * s, 0, f0, 0);
      bulk_load(base + s * 32768 + 16384, xin + (size_t)grp * 16 * DM, 16384, bars + B_RF + 8 * s);
      o_next(3 * nsteps + 1, 32768);
      #pragma unroll 1
      for (int k = 0; k < 4; k++) tma_load_2d(base + s * 32768 + k * 8192, (k & 2) ? &tmWu : &tmWg, bars + B_RF + 8 * s, f0, (k & 1) * 256);
      #pragma unroll 1
      for (int k = 0; k < 4; k++) w_expect_tx(bars + R_PART + 8 * k, 16384);
      mbar_wait(bars + B_PUB + 8 * (5 + nitems), 0);
      mbar_wait(bars + B_PUB + 8 * (NPUB + 5 + nitems), 0);
      uint32_t todo = 0xff;
      #pragma unroll 1
      for (int n = 0; n < WAIT_LIM && todo; n++) {
        uint32_t now = __ballot_sync(0xffffffff, ld_acquire(&g_x.cnt[C_PART + (m * 2 + (ot >> 5)) * 32 + (lane & 7)]) == tag) & todo;
        todo &= ~now;
        if (now) fence_async_global();
        #pragma unroll 1
        for (; now; now &= now - 1) {
          const int q = __ffs(now) - 1;
          bulk_load(base + (oent(3 * nsteps - 3 + (q >> 2)) & 7) * 32768 + (q & 3) * 8192, sched.part + (grp * 8 + q) * 4096, 8192, bars + R_PART + 8 * (q >> 1));
        }
      }
      }
    } else if (warp < 3) {
      const int w = warp - 1, n1 = w * NPUB + (spare ? 3 : 6) + nitems;
      #pragma unroll 1
      for (int n = w * NPUB; n < n1; n++) {
        #pragma unroll 1
        for (int k = 0; k < 8 * WAIT_LIM; k++) { if (mbar_try(bars + B_PUB + 8 * n, 0)) break; }
        const uint32_t idx = lds_u32(base + SM_MAIL + 4 * n);
        fence_async_global();
        if (lane == 0 && idx < (unsigned)C_END) red_release(idx);
        __syncwarp();
      }
    } else {
      *reinterpret_cast<volatile uint32_t*>(smem_raw + SM_KEY + 48) = tag;
      if (!spare) { mbar_wait(bars + B_AF + 8 * X_AT, 0); bulk_prefetch(xin + (size_t)blockIdx.x * 16 * DM, 16 * DM * 2); }
      #pragma unroll 1
      for (int n = 0; n < 8 + nsteps; n++) {
        if (n == 2 + nitems) n = 7;
        int idx = n == 0 ? C_MOD : n == 1 ? C_H1 : C_MOD2, cnt = n == 0 ? 8 : n == 1 ? 256 : 16;
        if (n == 2) tma_prefetch_2d(&tmWq, (sp.item[0] >> 3) * 128 + rank * 64, (sp.item[0] & 7) * 64);
        if (n >= 2 && n < 7) { idx = C_KV + (sp.item[n - 2] >> 3); cnt = 32; }
        if (n >= 8) { const int c0 = sp.ochunk[n - 8][0], c1 = sp.ochunk[n - 8][1]; idx = C_CTX + (((lane & 1) && c0 < 64 ? c0 : c1) >> 1) * 8 + (ot & 7); cnt = 4; }
        wait_count_lazy(idx, cnt * tag);
        w_arrive(bars + B_RDY + 8 * n);
        if (n == 8 + PF_N - 1) {
          #pragma unroll 1
          for (int k = 0; k < 8 * WAIT_LIM; k++) { if (mbar_try(bars + R_NEAR, 0)) break; }
          bulk_prefetch(w_o + (size_t)blockIdx.x * (NH * DH * DM / NCTA), NH * DH * DM / NCTA * 2);
          #pragma unroll 1
          for (int k = 0; k < PF_N; k++) {
            const int cc = sp.ochunk[k][(ot >> 3) & 1];
            if (cc < 64) bulk_prefetch(sched.kvc + ((size_t)(128 + cc) * SEQ + m * 128) * 64, 16384);
          }
        }
      }
    }
    __syncwarp();
    cluster_arrive();
    if (!spare) {
      bar_sync(6, 128);
      asm volatile("setmaxnreg.inc.sync.aligned.u32 88;");
      const int pos = blockIdx.x * 4 + (lane & 1) * 2, col = (blockIdx.x >> 2) * 16 + (blockIdx.x & 3) * 2 + (lane & 1) * 8, src = threadIdx.x >> 1;
      uint32_t gbest = 0, hh = 0, gbf = 0;
      uint2 xx = make_uint2(0, 0);
      uint4 ya = make_uint4(0, 0, 0, 0), yb = make_uint4(0, tag, 0, tag);
      auto poll_y = [&]() {
        if (ya.y != tag || ya.w != tag) ya = ld_tagged2(&g_x.yll[src][pos]);
        if (yb.y != tag || yb.w != tag) yb = ld_tagged2(&g_x.yll[src + 64][pos]);
        return __all_sync(0xffffffff, ya.y == tag && ya.w == tag && yb.y == tag && yb.w == tag);
      };
      ya.y = tag - 1; if (src + 64 < FF / 16) yb.y = tag - 1;
      if (warp == 3) {
        gbf = __ldcg(reinterpret_cast<const uint32_t*>(g_x.mod + 5 * DM + col));
        uint32_t have = 0;
        uint2 k[4];
        #pragma unroll
        for (int i = 0; i < 4; i++) k[i] = make_uint2(0, tag - 1);
        #pragma unroll 1
        for (int n = 0; n < WAIT_LIM; n++) {
          #pragma unroll
          for (int i = 0; i < 4; i++) if (k[i].y != tag) k[i] = ld_tagged(&g_x.keys[i * 32 + lane][0]);
          if (gbest != have) {
            const int g = ((0xffffu - gbest) >> 4) & 127;
            uint4 hv[4];
            #pragma unroll
            for (int i = 0; i < 4; i++) hv[i] = ld_tagged2(&g_x.row[g][0][i * 64 + lane * 2]);
            xx = ld_tagged(&g_x.row[g][1][(col >> 8) * 128 + ((col >> 2) & 1) * 64 + ((col >> 3) & 31) * 2 + ((col >> 1) & 1)]);
            bool ok = xx.y == tag;
            #pragma unroll
            for (int i = 0; i < 4; i++) { ok = ok && hv[i].y == tag && hv[i].w == tag; reinterpret_cast<uint2*>(smem_raw + SM_H2)[(i >> 1) * 64 + lane * 2 + (i & 1)] = make_uint2(hv[i].x, hv[i].z); }
            if (lane == 0) *reinterpret_cast<uint32_t*>(smem_raw + SM_KEY + 32) = gbest;
            have = __all_sync(0xffffffff, ok) ? gbest : 0;
          }
          bool all = true;
          #pragma unroll
          for (int i = 0; i < 4; i++) { all = all && k[i].y == tag; gbest = max(gbest, k[i].y == tag ? k[i].x : 0u); }
          gbest = __reduce_max_sync(0xffffffff, gbest);
          if (__all_sync(0xffffffff, all) && gbest == have) break;
        }
        __syncwarp();
        w_arrive(bars + R_KEY);
        if (blockIdx.x == 0 && lane == 0) g_x.epoch = tag;
        hh = lds_u32(base + SM_H2 + col * 2);
      }
      const float rsel = rbf(__uint_as_float((((gbest & 0x80000000u) ? gbest & 0x7fffffffu : ~gbest) & 0xfffff000u) | 0x800u));
      const float rs = rbf(__fdividef(1.f, 1.f + __expf(-rsel)));
      bar_sync(9, 384);
      #pragma unroll 1
      for (int n = 0; n < WAIT_LIM; n++) { if (poll_y()) break; }
      float y0 = __uint_as_float(ya.x) + __uint_as_float(yb.x), y1 = __uint_as_float(ya.z) + __uint_as_float(yb.z);
      #pragma unroll
      for (int o = 2; o < 32; o <<= 1) { y0 += __shfl_xor_sync(0xffffffff, y0, o); y1 += __shfl_xor_sync(0xffffffff, y1, o); }
      float2* s_y = reinterpret_cast<float2*>(smem_raw + SM_KEY + 64);
      if (lane < 2) s_y[warp * 2 + lane] = make_float2(y0, y1);
      bar_sync(6, 128);
      if (warp == 3 && lane < 2) {
        y0 = 0.f; y1 = 0.f;
        #pragma unroll
        for (int i = 0; i < 4; i++) { y0 += reinterpret_cast<const float*>(s_y)[i * 4 + lane]; y1 += reinterpret_cast<const float*>(s_y)[i * 4 + 2 + lane]; }
        const float o0 = bf_lo(xx.x) + rbf(bf_lo(gbf) * rbf(bf_lo(hh) + rbf(rbf(y0) * rs)));
        const float o1 = bf_hi(xx.x) + rbf(bf_hi(gbf) * rbf(bf_hi(hh) + rbf(rbf(y1) * rs)));
        *reinterpret_cast<uint32_t*>(out + (size_t)((0xffffu - gbest) & (SEQ - 1)) * DM + col) = pack_bf16(o0, o1);
      }
    }
    __syncwarp();
    cluster_wait();
  } else {
    asm volatile("setmaxnreg.inc.sync.aligned.u32 240;");
    Ctx x;
    x.w = wg - 1; x.base = base; x.bars = bars; x.nev = 0; x.sched = &sched;
    const int w = x.w, warp4 = warp & 3;
    x.rel = mapa(bars, (warp4 & 1) ^ 1);
    x.rel1 = (threadIdx.x & 127) == 32 || (threadIdx.x & 127) == 64;
    if (warp != 8 || spare) cluster_wait();
    if (w == 1 || spare) bar_sync(7 + w, 256);
    uint32_t PA[32], PB[32];
    int vtile = -1;
    if (spare) {
      mod_cta(x, cvec);
    } else {
      const int lane = wg_tid() & 31;
      Row xn[2];
      float acc0[64], acc1[64];
      int s = 2 * w, ph = w;
      #pragma unroll 1
      for (int u = w; u < 8; u += 2) {
        bar_sync(1 + w, 256);
        int ps = 0;
        #pragma unroll 1
        for (int kb = 0; kb < 8; kb++) {
          if (u < 2) mbar_wait(bars + B_AF + 8 * kb, 0);
          mbar_wait(bars + B_WF + 8 * s, ph);
          const uint32_t da = desc_lo(base + k_addrA(kb), 16), dw = desc_lo(base + k_addrW(s), 8192);
          wgmma_fence();
          kblock_n128<0>(acc0, da, dw, kb != 0);
          kblock_n128<512>(acc1, da, dw, kb != 0);
          wgmma_commit();
          if (kb == 7) bar_arrive(1 + (w ^ 1), 256);
          if (kb > 0) {
            wgmma_wait<1>();
            mbar_arrive_remote_if(x.rel + B_WE + 8 * ps, x.rel1);
            if (u == 7 && !(kb & 1)) {
              ring_release(x, kb == 2 ? 0 : kb - 3, false);
              if (kb > 2) ring_release(x, kb - 2, false);
            }
          }
          ps = s;
          if (++s == 6) { s = 0; ph ^= 1; }
        }
        Row t[2];
        const int lrow = blockIdx.x * 16 + w * 8 + warp4 * 2;
        if (u == w) { t[0] = ldg_row(xin + (size_t)lrow * DM, lane); t[1] = ldg_row(xin + (size_t)(lrow + 1) * DM, lane); }
        if (u == LN_AT || u == LN_AT + 1) {
          mbar_wait(bars + R_MOD, 0);
          t[0] = ldca_row(g_x.mod, lane); t[1] = ldca_row(g_x.mod + DM, lane);
        }
        wgmma_wait<0>();
        fence_regs(acc0); fence_regs(acc1);
        mbar_arrive_remote_if(x.rel + B_WE + 8 * ps, x.rel1);
        if (u == 6) { for (int k = 0; k < 5; k++) ring_release(x, k, false); }
        if (u >= 6) ring_release(x, 5, false);
        if (u == 7) {
          pack_tile(acc0, PA, 1.f, 1.f); pack_tile(acc1, PB, 1.f, 1.f);
          vtile = sp.khead[3] * 16 + mt;
          break;
        }
        s += 2; ph ^= 1; if (s >= 6) { s -= 6; ph ^= 1; }
        if (u == 0) bar_sync(7, 256);
        if (u == w) {
          float st[4] = {0.f, 0.f, 0.f, 0.f};
          #pragma unroll
          for (int i = 0; i < 32; i++) { const float v = row_at(t[i >> 4], i & 15); st[(i >> 4) * 2] += v; st[(i >> 4) * 2 + 1] = fmaf(v, v, st[(i >> 4) * 2 + 1]); }
          warp_sums(st);
          #pragma unroll
          for (int r = 0; r < 2; r++) { ln_stats(st[2*r], st[2*r+1]); xn[r] = ln_apply(t[r], st[2*r], st[2*r+1] * QSCALE); }
        }
        if ((u == LN_AT || u == LN_AT + 1)) {
          #pragma unroll
          for (int r = 0; r < 2; r++) {
            const Row hr = fma_row(xn[r], one_plus(t[1]), t[0]);
            __nv_bfloat16* hp = sched.h1 + (lrow & ~63) * DM + (lane >> 3) * 4096 + ((lrow + r) & 63) * 64 + (((lane ^ (lrow + r)) & 7) << 3);
            stg_v4(hp, hr.v[0], hr.v[1], hr.v[2], hr.v[3]); stg_v4(hp + 4 * 4096, hr.v[4], hr.v[5], hr.v[6], hr.v[7]);
          }
        }
        const int tile = sp.khead[u >> 1] * 16 + mt;
        __nv_bfloat16* dst = kv_tile(x, tile);
        uint32_t D[32];
        pack_tile(acc0, D, 1.f, 1.f); store_tile(dst + 2048, D);
        pack_tile(acc1, D, 1.f, 1.f); store_tile(dst, D);
        if (u == LN_AT || u == LN_AT + 1) publish(x, C_H1);
        publish(x, C_KV + (tile >> 4));
      }
    }
    const int last = attention(x, sp.item, nitems, rank, PA, PB, vtile);
    const int lane = wg_tid() & 31, cw = w * 4 + warp4;
    const int row0 = grp * 16 + cw * 2;
    const bool moe_cta = blockIdx.x < FF / 16;
    if (spare) { store_ctx(x, last, PB); __syncwarp(); cluster_arrive(); cluster_wait(); return; }
    const int kl = 3 * nsteps - 3;
    uint2* const yp = &g_x.yll[blockIdx.x][cw * 64 + (lane & 3) * 16 + (lane >> 2) * 2];
    Row ga, sb, cb, gb, wr;
    {
      float accA[64], accB[64];
      const int t0 = oent(0) == oent(1);
      uint32_t pa = 0, pb = 0;
      #pragma unroll 1
      for (int t = t0; t < 2 * nsteps - 2; t++) {
        const uint32_t eb = oent(3 * (t >> 1) + 2 * (t & 1)), ea = oent(3 * (t >> 1) + 1);
        o_wait_full(bars, eb);
        o_wait_full(bars, ea);
        const uint32_t da = desc_lo(base + w * 4096, 16) + (ea & 7) * 2048 + (t & 1) * 1024, db = desc_lo(base, 8192) + (eb & 7) * 2048;
        wgmma_fence();
        kblock_n128<0, 0, SW64>(accA, da, db, t != t0); kblock_n128<0, 1024, SW64>(accB, da, db, t != t0);
        wgmma_commit();
        if (t == CTX_T) store_ctx(x, last, PB);
        if (t > t0) { wgmma_wait<1>(); slot_release(x, pb, false); if (!(t & 1)) slot_release(x, pa, false); }
        pa = ea & 7; pb = eb & 7;
      }
      const uint32_t e0 = oent(kl), ea = oent(kl + 1), eb = oent(kl + 2);
      const uint32_t da = desc_lo(base + w * 4096, 16) + (ea & 7) * 2048;
      const uint32_t db0 = desc_lo(base, 8192) + (e0 & 7) * 2048, db1 = desc_lo(base, 8192) + (eb & 7) * 2048;
      ga = ldca_row(g_x.mod + 2 * DM, lane); sb = ldca_row(g_x.mod + 3 * DM, lane); cb = ldca_row(g_x.mod + 4 * DM, lane); gb = ldca_row(g_x.mod + 5 * DM, lane);
      wr = ldca_row(w_r, lane);
      if (moe_cta) st_tagged2(yp, 0, 0, 0);
      o_wait_full(bars, e0);
      o_wait_full(bars, ea);
      o_wait_full(bars, eb);
      wgmma_fence();
      kblock_n128<0, 0, SW64>(accA, da, db0, 1); kblock_n128<1024, 0, SW64>(accA, da, db1, 1);
      wgmma_commit();
      kblock_n128<0, 1024, SW64>(accB, da, db0, 1); kblock_n128<1024, 1024, SW64>(accB, da, db1, 1);
      wgmma_commit();
      __syncwarp();
      cluster_arrive();
      __nv_bfloat16* dst = sched.part + ((m * 8 + cw) * 8 + (ot >> 3)) * 4096;
      auto send = [&](const float (&acc)[64], int h) {
        uint32_t D[32];
        pack_tile(acc, D, 1.f, 1.f);
        #pragma unroll
        for (int i = 0; i < 8; i++) stg_v4(dst + (h * 8 + i) * 256 + ((lane ^ (h * 4 + (i >> 1))) << 3), D[4*i], D[4*i+1], D[4*i+2], D[4*i+3]);
      };
      wgmma_wait<1>();
      fence_regs(accA);
      send(accA, 0);
      o_wait_full(bars, eb);
      wgmma_wait<0>();
      fence_regs(accB);
      send(accB, 1);
      publish(x, C_PART + (m * 2 + w) * 32 + (ot >> 3));
    }
    asm volatile("setmaxnreg.dec.sync.aligned.u32 208;");
    const uint32_t sD = base + (oent(kl + 3) & 7) * 32768, sW = base + (oent(kl + 4) & 7) * 32768;
    o_wait_full(bars, oent(kl + 3)); o_wait_full(bars, oent(kl + 4));
    Row x1[2];
    #pragma unroll
    for (int r = 0; r < 2; r++) x1[r] = lds_row(sD + 16384 + (cw * 2 + r) * 1024, lane);
    uint4 wgv[4], wuv[4], wdv[4];
    #pragma unroll
    for (int r = 0; r < 4; r++) {
      const uint32_t k = (lane & 7) + ((lane >> 4) << 3), h = (lane >> 3) & 1;
      wgv[r] = ldsm_x4_t(sW + (cw * 64 + r * 16 + k) * 32 + ((h ^ ((lane >> 2) & 1)) << 4));
      wuv[r] = ldsm_x4_t(sW + 16384 + (cw * 64 + r * 16 + k) * 32 + ((h ^ ((lane >> 2) & 1)) << 4));
      wdv[r] = ldsm_x4_t(sD + cw * 2048 + k * 128 + (((r * 2 + h) ^ (lane & 7)) << 4));
    }
    const Row cb1 = one_plus(cb);
    const unsigned int tag = lds_u32(base + SM_KEY + 48);
    float u[16], ub[2] = {0.f, 0.f};
    #pragma unroll
    for (int i = 0; i < 16; i++) { u[i] = row_at(cb1, i) * row_at(wr, i); ub[0] += u[i]; ub[1] = fmaf(row_at(sb, i), row_at(wr, i), ub[1]); }
    warp_sums(ub);
    float st[6] = {0.f, 0.f, 0.f, 0.f, 0.f, 0.f};
    uint32_t key[2];
    {
      const uint32_t po = base + ((lane & 7) * 2 + (cw >> 2)) * 512 + (cw & 3) * 128;
      Row av[2][2];
      #pragma unroll
      for (int k = 0; k < 4; k++) {
        mbar_wait(bars + R_PART + 8 * k, 1);
        const uint32_t pa = po + (oent(kl + (k >> 1)) & 7) * 32768 + (k & 1) * 16384;
        #pragma unroll
        for (int r = 0; r < 2; r++) {
          const uint32_t sw = ((r * 4 + (lane >> 3)) ^ (lane & 7)) << 4;
          const uint4 lo = ldsm_x4(pa + sw), hi = ldsm_x4(pa + 8192 + sw);
          const Row v{{lo.x, lo.y, lo.z, lo.w, hi.x, hi.y, hi.z, hi.w}};
          av[r][k >> 1] = (k & 1) ? add_row(av[r][k >> 1], v) : v;
        }
      }
      #pragma unroll
      for (int r = 0; r < 2; r++) {
        x1[r] = fma_row(ga, add_row(av[r][0], av[r][1]), x1[r]);
        #pragma unroll
        for (int i = 0; i < 16; i++) { const float v = row_at(x1[r], i); st[3*r] += v; st[3*r+1] = fmaf(v, v, st[3*r+1]); st[3*r+2] = fmaf(v, u[i], st[3*r+2]); }
      }
      warp_sums(st);
      #pragma unroll
      for (int r = 0; r < 2; r++) {
        ln_stats(st[3*r], st[3*r+1]);
        const uint32_t rb = __float_as_uint(fmaf(st[3*r+1], fmaf(-st[3*r], ub[0], st[3*r+2]), ub[1]));
        key[r] = (((rb & 0x80000000u) ? ~rb : (rb | 0x80000000u)) & 0xfffff000u) | (0xfffu - (uint32_t)(row0 + r));
      }
    }
    float* s_red = reinterpret_cast<float*>(smem_raw + SM_RED);
    uint32_t* s_key = reinterpret_cast<uint32_t*>(smem_raw + SM_KEY);
    const int rb = key[1] > key[0];
    const uint32_t wbest = rb ? key[1] : key[0];
    if (lane == 0) s_key[cw] = wbest;
    bar_sync(5, 256);
    const uint32_t cbest = __reduce_max_sync(0xffffffff, s_key[lane & 7]);
    if (wbest == cbest && lane == 0) st_tagged(&g_x.keys[grp][0], cbest, tag);
    Row xb, xo;
    #pragma unroll
    for (int i = 0; i < 8; i++) { xb.v[i] = rb ? x1[1].v[i] : x1[0].v[i]; xo.v[i] = rb ? x1[0].v[i] : x1[1].v[i]; }
    const Row hb = fma_row(ln_apply(xb, rb ? st[3] : st[0], rb ? st[4] : st[1]), cb1, sb);
    if (wbest == cbest) {
      #pragma unroll
      for (int i = 0; i < 4; i++) st_tagged2(&g_x.row[grp][0][i * 64 + lane * 2], hb.v[2*i], hb.v[2*i+1], tag);
      #pragma unroll
      for (int i = 0; i < 4; i++) st_tagged2(&g_x.row[grp][1][i * 64 + lane * 2], xb.v[2*i], xb.v[2*i+1], tag);
    }
    const Row ob = fma_row(gb, hb, xb);
    if (wbest != cbest) store_row(out + (size_t)(row0 + rb) * DM, lane, ob);
    store_row(out + (size_t)(row0 + 1 - rb) * DM, lane, fma_row(gb, fma_row(ln_apply(xo, rb ? st[0] : st[3], rb ? st[1] : st[4]), cb1, sb), xo));
    mbar_wait(bars + R_KEY, 1);
    if (moe_cta) {
      float cg[4] = {0, 0, 0, 0}, cu[4] = {0, 0, 0, 0};
      #pragma unroll
      for (int r = 0; r < 4; r++) {
        const uint32_t b0 = lds_u32(base + SM_H2 + (cw * 64 + r * 16) * 2 + (lane & 3) * 4), b1 = lds_u32(base + SM_H2 + (cw * 64 + r * 16) * 2 + 16 + (lane & 3) * 4);
        mma16816(cg, wgv[r], b0, b1); mma16816(cu, wuv[r], b0, b1);
      }
      s_red[cw * 32 + (lane & 3) * 8 + (lane >> 2)] = (lane & 2) ? ((lane & 1) ? cu[2] : cu[0]) : ((lane & 1) ? cg[2] : cg[0]);
      bar_sync(5, 256);
      float g = 0.f;
      #pragma unroll
      for (int i = 0; i < 8; i++) g += s_red[i * 32 + lane];
      g = rbf(g);
      const float act = rbf(__fdividef(g, 1.f + __expf(-g))) * __shfl_down_sync(0xffffffff, g, 16);
      const uint32_t a2 = pack_bf16(act, __shfl_down_sync(0xffffffff, act, 1));
      const uint32_t b0 = __shfl_sync(0xffffffff, a2, (lane & 3) * 2), b1 = __shfl_sync(0xffffffff, a2, (lane & 3) * 2 + 8);
      float y0 = 0.f, y1 = 0.f;
      #pragma unroll
      for (int r = 0; r < 4; r++) {
        float c[4] = {0, 0, 0, 0};
        mma16816(c, wdv[r], b0, b1);
        if ((lane & 3) == r) { y0 = c[0]; y1 = c[2]; }
      }
      st_tagged2(yp, __float_as_uint(y0), __float_as_uint(y1), tag);
    }
    bar_arrive(9, 384);
    if (wbest == cbest && wbest != s_key[8]) store_row(out + (size_t)(row0 + rb) * DM, lane, ob);
    __syncwarp();
    cluster_wait();
  }
}

typedef CUresult (*EncodeFn)(CUtensorMap*, CUtensorMapDataType, cuuint32_t, void*, const cuuint64_t*, const cuuint64_t*, const cuuint32_t*,
                             const cuuint32_t*, CUtensorMapInterleave, CUtensorMapSwizzle, CUtensorMapL2promotion, CUtensorMapFloatOOBfill);

struct HostState {
  bool ready = false;
  EncodeFn encode = nullptr;
  CUtensorMap tmC, tmWq, tmWk, tmWv, tmWo, tmWg, tmWu, tmWd, tmWm;
  Sched sched;
};

void make_map(EncodeFn enc, CUtensorMap* m, const void* ptr, int rank, const cuuint64_t* dims, const cuuint64_t* strides, const cuuint32_t* box, bool wide = true) {
  const cuuint32_t es[3] = {1, 1, 1};
  enc(m, CU_TENSOR_MAP_DATA_TYPE_BFLOAT16, rank, const_cast<void*>(ptr), dims, strides, box, es, CU_TENSOR_MAP_INTERLEAVE_NONE,
      wide ? CU_TENSOR_MAP_SWIZZLE_128B : CU_TENSOR_MAP_SWIZZLE_32B, wide ? CU_TENSOR_MAP_L2_PROMOTION_L2_128B : CU_TENSOR_MAP_L2_PROMOTION_NONE, CU_TENSOR_MAP_FLOAT_OOB_FILL_NONE);
}
void make_2d(EncodeFn enc, CUtensorMap* m, const void* ptr, int rows, int cols, int box_rows) {
  const cuuint64_t dims[2] = {(cuuint64_t)cols, (cuuint64_t)rows}, strides[1] = {(cuuint64_t)cols * 2};
  const cuuint32_t box[2] = {64, (cuuint32_t)box_rows};
  make_map(enc, m, ptr, 2, dims, strides, box);
}
void make_3d(EncodeFn enc, CUtensorMap* m, const void* ptr, int rows, int chunks, size_t row_stride, size_t chunk_stride, int box_rows = 64, int box_chunks = 2) {
  const cuuint64_t dims[3] = {64, (cuuint64_t)rows, (cuuint64_t)chunks}, strides[2] = {row_stride, chunk_stride};
  const cuuint32_t box[3] = {64, (cuuint32_t)box_rows, (cuuint32_t)box_chunks};
  make_map(enc, m, ptr, 3, dims, strides, box);
}

void make_ffn(EncodeFn enc, CUtensorMap* m, const void* ptr) {
  const cuuint64_t dims[2] = {(cuuint64_t)FF, (cuuint64_t)DM}, strides[1] = {(cuuint64_t)FF * 2};
  const cuuint32_t box[2] = {16, 256};
  make_map(enc, m, ptr, 2, dims, strides, box, false);
}

#define SR 0x213312
#define SEED 12345
#define SPARE_N 3
void build_sched(Sched& s) {
  memset(&s, 0, sizeof(s));
  const int NP = NCTA / 2, korder[4] = {(KORDER >> 12) & 3, (KORDER >> 8) & 3, (KORDER >> 4) & 3, KORDER & 3};
  const int sround[4][2][3] = {{}, {{1}, {2}}, {{1, 2}, {1, 2}}, {{(SR >> 20) & 3, (SR >> 16) & 3, (SR >> 12) & 3}, {(SR >> 8) & 3, (SR >> 4) & 3, SR & 3}}};
  int jv[4][NP], used[4][8] = {};
  for (int r = 0; r < 4; r++) for (int p = 0; p < NP; p++) jv[r][p] = (r & 2) ? 7 - ((p + 4 * (r & 1)) & 7) : (p + 4 * (r & 1)) & 7;
  for (int q = 0; q < 2; q++) {
    s.pair[NP + q].nitems = SPARE_N;
    for (int i = 0; i < SPARE_N; i++) {
      const int r = sround[SPARE_N][q][i];
      s.pair[NP + q].item[i] = (uint8_t)((r * 8 + used[r][6]++) * 8 + 6);
      for (int p = 0; p < NP; p++) if (jv[r][p] == 6) { jv[r][p] = -2; break; }
    }
  }
  auto cost = [&](int p) {
    int u = 8 - ((p >> 4) < SPARE_N ? 21 : 22), z = 0, none = 0;
    for (int r = 0; r < 4; r++) { u += jv[r][p]; z += jv[r][p] == 0; none += jv[r][p] < 0; }
    return 4 * u * u + (z > 1) + 4 * (none > 1);
  };
  uint32_t rng = SEED;
  for (int it = 0; it < 2000000; it++) {
    if ((it & 255) == 0) { int t = 0; for (int p = 0; p < NP; p++) t += cost(p); if (t == 0) break; }
    rng = rng * 1664525u + 1013904223u;
    const int r = (rng >> 8) & 3, a = (rng >> 12) & 63, b = (rng >> 20) & 63, before = cost(a) + cost(b);
    int t = jv[r][a]; jv[r][a] = jv[r][b]; jv[r][b] = t;
    if (cost(a) + cost(b) > before) { jv[r][b] = jv[r][a]; jv[r][a] = t; }
  }
  int done[256];
  for (int p = 0; p < NP + 2; p++) {
    Sched::Pair& q = s.pair[p];
    if (p < NP) {
      for (int k = 0; k < 4; k++) q.khead[k] = (uint8_t)(korder[k] * 8 + (p >> 3));
      for (int r = 0; r < 4; r++) {
        if (jv[r][p] < 0) continue;
        q.item[q.nitems++] = (uint8_t)((r * 8 + used[r][jv[r][p]]++) * 8 + jv[r][p]);
      }
    }
    int t = p < NP ? 0 : -3, e = 1;
    for (int i = 0; i < q.nitems; i++) { t += (q.item[i] & 7) + 2; done[q.item[i]] = t + (i + 1 < q.nitems ? 2 : 0); e += 8 + 4 * ((q.item[i] & 7) + 1); }
    for (int k = 0; k < 3 * MAX_STEPS + 6; k++) {
      const int n = k > 0 ? k - (SPARE_N & 1) : 0, r = n % 7, f = (e + (r < 4 ? r : r - 1)) % 12;
      q.oent[k] = (uint8_t)((r == 4 ? 6 : f >= 6 ? f + 2 : f) ^ (((n / 7) & 1) << 3));
    }
  }
  for (int j = 0; j < 8; j++) {
    int order[NH], left[4];
    for (int h = 0; h < NH; h++) { int k = h; for (; k > 0 && done[order[k - 1] * 8 + j] < done[h * 8 + j]; k--) order[k] = order[k - 1]; order[k] = h; }
    for (int kq = 0; kq < 4; kq++) {
      left[kq] = SPARE_N == 0 ? 16 : kq < SPARE_N ? 20 - SPARE_N : 16 - SPARE_N;
      for (int nh = 0; nh < 2; nh++) { Sched::Pair& q = s.pair[kq * 16 + nh * 8 + j]; q.otask = (uint8_t)(kq * 16 + nh * 8 + j); q.nsteps = (uint8_t)((left[kq] + 1) / 2); q.ochunk[0][0] = 255; }
    }
    for (int n = 0, kq = 0, run = 0; n < 64; ) {
      if (left[kq] > 0 && run < 2) {
        const int pos = --left[kq] + (SPARE_N & 1);
        for (int nh = 0; nh < 2; nh++) s.pair[kq * 16 + nh * 8 + j].ochunk[pos >> 1][pos & 1] = (uint8_t)(order[n >> 1] * 2 + 1 - (n & 1));
        n++; run++;
      } else { kq = (kq + 1) & 3; run = 0; }
    }
  }
}

}

extern "C" void kernel_launch(void* const* d_in, const int* in_sizes, int n_in, void* d_out, int out_size) {
  (void)in_sizes; (void)n_in; (void)out_size;
  const __nv_bfloat16* x     = (const __nv_bfloat16*)d_in[0];
  const __nv_bfloat16* ckv   = (const __nv_bfloat16*)d_in[1];
  const __nv_bfloat16* w_q   = (const __nv_bfloat16*)d_in[2];
  const __nv_bfloat16* w_uk  = (const __nv_bfloat16*)d_in[3];
  const __nv_bfloat16* w_uv  = (const __nv_bfloat16*)d_in[4];
  const __nv_bfloat16* w_o   = (const __nv_bfloat16*)d_in[5];
  const __nv_bfloat16* w_r   = (const __nv_bfloat16*)d_in[7];
  const __nv_bfloat16* w_g   = (const __nv_bfloat16*)d_in[8];
  const __nv_bfloat16* w_u   = (const __nv_bfloat16*)d_in[9];
  const __nv_bfloat16* w_d   = (const __nv_bfloat16*)d_in[10];
  const __nv_bfloat16* cvec  = (const __nv_bfloat16*)d_in[11];
  const __nv_bfloat16* w_mod = (const __nv_bfloat16*)d_in[12];
  __nv_bfloat16* out = (__nv_bfloat16*)d_out;

  static HostState st;
  if (!st.ready) {
    void* fn = nullptr; cudaDriverEntryPointQueryResult qr;
    cudaGetDriverEntryPoint("cuTensorMapEncodeTiled", &fn, cudaEnableDefault, &qr);
    st.encode = (EncodeFn)fn;
    cudaFuncSetAttribute(k_fused, cudaFuncAttributeMaxDynamicSharedMemorySize, SMEM);
    build_sched(st.sched);
    void *p_kvc, *p_h1, *p_part;
    cudaGetSymbolAddress(&p_kvc, g_kvc); cudaGetSymbolAddress(&p_h1, g_h1); cudaGetSymbolAddress(&p_part, g_part);
    st.sched.kvc = (__nv_bfloat16*)p_kvc; st.sched.h1 = (__nv_bfloat16*)p_h1; st.sched.part = (__nv_bfloat16*)p_part;
    st.ready = true;
  }
  make_2d(st.encode, &st.tmC, ckv, SEQ, DM, 128);
  make_2d(st.encode, &st.tmWq, w_q, DM, NH * DH, 64);
  make_2d(st.encode, &st.tmWk, w_uk, DM, NH * DH, 64);
  make_2d(st.encode, &st.tmWv, w_uv, DM, NH * DH, 64);
  make_3d(st.encode, &st.tmWo, w_o, NH * DH, DM / 64, (size_t)DM * 2, 128);
  make_3d(st.encode, &st.tmWm, w_mod, DM, 6 * DM / 64, (size_t)6 * DM * 2, 128);
  make_3d(st.encode, &st.tmWd, w_d, FF, DM / 64, (size_t)DM * 2, 128, 16, 8);
  make_ffn(st.encode, &st.tmWg, w_g);
  make_ffn(st.encode, &st.tmWu, w_u);

  k_fused<<<NGRID, 384, SMEM, cudaStreamPerThread>>>(st.tmC, st.tmWq, st.tmWk, st.tmWv, st.tmWo, st.tmWg, st.tmWu, st.tmWd, st.tmWm, st.sched,
                                                     x, cvec, w_o, w_r, w_g, w_u, w_d, out);
}
```

```cpp
#include <cuda_runtime.h>
#include <cuda_bf16.h>
#include <cuda.h>
#include <stdint.h>
#include <string.h>
#include <math.h>

namespace {

constexpr int SEQ = 2048, DM = 512, NH = 32, DH = 128, FF = 1792;
constexpr int NCTA = 128, NGRID = 132;

__device__ __align__(128) __nv_bfloat16 g_kvc[192 * SEQ * 64];
__device__ __align__(128) __nv_bfloat16 g_h1[SEQ * DM];
__device__ __align__(128) __nv_bfloat16 g_part[128 * 8 * 4096];
constexpr int C_MOD = 0, C_MOD2 = 16, C_H1 = 32, C_KV = 64, C_CTX = 128, C_END = 384;
struct Exchange {
  uint2 keys[128][4];
  uint2 row[128][2][DM / 2];
  uint2 yll[FF / 16][DM];
  __nv_bfloat16 mod[6 * DM];
  unsigned int sent[128][8];
  unsigned int cnt[C_END];
  unsigned int epoch;
};
__device__ __align__(4096) Exchange g_x;


__device__ __forceinline__ uint32_t smem_u32(const void* p) { return (uint32_t)__cvta_generic_to_shared(p); }
__device__ __forceinline__ int wg_tid() { int t; asm volatile("mov.u32 %0, %%tid.x;" : "=r"(t)); return t & 127; }
__device__ __forceinline__ void mbar_arrive(uint32_t bar) { asm volatile("mbarrier.arrive.shared::cta.b64 _, [%0];" :: "r"(bar) : "memory"); }
__device__ __forceinline__ uint32_t mapa(uint32_t addr, uint32_t cta) { uint32_t r; asm("mapa.shared::cluster.u32 %0, %1, %2;" : "=r"(r) : "r"(addr), "r"(cta)); return r; }
__device__ __forceinline__ void mbar_arrive_remote_if(uint32_t cluster_addr, bool pred) {
  asm volatile("{\n.reg .pred p;\nsetp.ne.u32 p, %1, 0;\n@p mbarrier.arrive.shared::cluster.b64 _, [%0];\n}" :: "r"(cluster_addr), "r"((uint32_t)pred) : "memory");
}
__device__ __forceinline__ bool mbar_try(uint32_t bar, uint32_t parity) {
  uint32_t done;
  asm volatile("{\n.reg .pred p;\nmbarrier.try_wait.parity.shared::cta.b64 p, [%1], %2;\nselp.u32 %0, 1, 0, p;\n}" : "=r"(done) : "r"(bar), "r"(parity) : "memory");
  return done;
}
__device__ __forceinline__ bool mbar_test2(uint32_t bar, uint32_t parity) {
  uint32_t done;
  asm volatile("{\n.reg .pred p, q;\nmbarrier.test_wait.parity.shared::cta.b64 p, [%1], %2;\nmbarrier.test_wait.parity.shared::cta.b64 q, [%1 + 8], %2;\n"
               "and.pred p, p, q;\nselp.u32 %0, 1, 0, p;\n}" : "=r"(done) : "r"(bar), "r"(parity) : "memory");
  return done;
}
#define WAIT_LIM (1 << 14)
__device__ __forceinline__ void mbar_wait(uint32_t bar, uint32_t parity) {
  #pragma unroll 1
  for (int n = 0; n < WAIT_LIM; n++) { if (mbar_try(bar, parity)) break; }
}
__device__ __forceinline__ unsigned int ld_acquire(const unsigned int* p) {
  unsigned int v; asm volatile("ld.acquire.gpu.global.u32 %0, [%1];" : "=r"(v) : "l"(p) : "memory"); return v;
}
__device__ __forceinline__ unsigned int ld_relaxed(const unsigned int* p) {
  unsigned int v; asm volatile("ld.relaxed.gpu.global.u32 %0, [%1];" : "=r"(v) : "l"(p) : "memory"); return v;
}
__device__ __forceinline__ void wait_count_lazy(int idx, unsigned int target) {
  #pragma unroll 1
  for (int n = 0; n < WAIT_LIM; n++) { if (__all_sync(0xffffffff, (int)(ld_acquire(&g_x.cnt[idx]) - target) >= 0)) break; __nanosleep(100); }
}
__device__ __forceinline__ uint4 ld_tagged2(const void* p) {
  uint4 v;
  asm volatile("{\n.reg .b64 a, b;\nld.relaxed.gpu.global.v2.u64 {a, b}, [%4];\nmov.b64 {%0, %1}, a;\nmov.b64 {%2, %3}, b;\n}"
    : "=r"(v.x), "=r"(v.y), "=r"(v.z), "=r"(v.w) : "l"(p) : "memory");
  return v;
}
__device__ __forceinline__ uint2 ld_tagged(const void* p) {
  uint2 v; asm volatile("{\n.reg .b64 a;\nld.relaxed.gpu.global.u64 a, [%2];\nmov.b64 {%0, %1}, a;\n}" : "=r"(v.x), "=r"(v.y) : "l"(p) : "memory"); return v;
}
__device__ __forceinline__ void st_tagged2(void* p, uint32_t a, uint32_t b, uint32_t tag) {
  asm volatile("{\n.reg .b64 a, b;\nmov.b64 a, {%1, %3};\nmov.b64 b, {%2, %3};\nst.relaxed.gpu.global.v2.u64 [%0], {a, b};\n}" :: "l"(p), "r"(a), "r"(b), "r"(tag) : "memory");
}
__device__ __forceinline__ void st_tagged(void* p, uint32_t a, uint32_t tag) {
  asm volatile("{\n.reg .b64 a;\nmov.b64 a, {%1, %2};\nst.relaxed.gpu.global.u64 [%0], a;\n}" :: "l"(p), "r"(a), "r"(tag) : "memory");
}
__device__ __forceinline__ void stg_v4(void* p, uint32_t a, uint32_t b, uint32_t c, uint32_t d) {
  asm volatile("st.global.v4.u32 [%0], {%1, %2, %3, %4};" :: "l"(p), "r"(a), "r"(b), "r"(c), "r"(d) : "memory");
}
__device__ __forceinline__ uint4 lds_v4(uint32_t addr) {
  uint4 v; asm volatile("ld.shared.v4.u32 {%0, %1, %2, %3}, [%4];" : "=r"(v.x), "=r"(v.y), "=r"(v.z), "=r"(v.w) : "r"(addr) : "memory"); return v;
}
__device__ __forceinline__ uint32_t lds_u32(uint32_t addr) { uint32_t v; asm volatile("ld.shared.u32 %0, [%1];" : "=r"(v) : "r"(addr) : "memory"); return v; }
__device__ __forceinline__ void sts_v4(uint32_t addr, uint32_t a, uint32_t b, uint32_t c, uint32_t d) {
  asm volatile("st.shared.v4.u32 [%0], {%1, %2, %3, %4};" :: "r"(addr), "r"(a), "r"(b), "r"(c), "r"(d) : "memory");
}
#define ELECT "{\n.reg .pred p;\nelect.sync _|p, 0xffffffff;\n@p "
__device__ __forceinline__ void w_mbar_init(uint32_t bar, uint32_t cnt) { asm volatile(ELECT "mbarrier.init.shared::cta.b64 [%0], %1;\n}" :: "r"(bar), "r"(cnt) : "memory"); }
__device__ __forceinline__ void w_expect_tx(uint32_t bar, uint32_t bytes) { asm volatile(ELECT "mbarrier.arrive.expect_tx.shared::cta.b64 _, [%0], %1;\n}" :: "r"(bar), "r"(bytes) : "memory"); }
__device__ __forceinline__ void w_arrive(uint32_t bar) { asm volatile(ELECT "mbarrier.arrive.shared::cta.b64 _, [%0];\n}" :: "r"(bar) : "memory"); }
__device__ __forceinline__ void tma_load_2d(uint32_t dst, const CUtensorMap* tm, uint32_t bar, int c0, int c1) {
  asm volatile(ELECT "cp.async.bulk.tensor.2d.shared::cluster.global.mbarrier::complete_tx::bytes [%0], [%1, {%3, %4}], [%2];\n}"
    :: "r"(dst), "l"(tm), "r"(bar), "r"(c0), "r"(c1) : "memory");
}
__device__ __forceinline__ void tma_load_2d_mc(uint32_t dst, const CUtensorMap* tm, uint32_t bar, int c0, int c1) {
  asm volatile(ELECT "cp.async.bulk.tensor.2d.shared::cluster.global.mbarrier::complete_tx::bytes.multicast::cluster [%0], [%1, {%3, %4}], [%2], %5;\n}"
    :: "r"(dst), "l"(tm), "r"(bar), "r"(c0), "r"(c1), "h"((uint16_t)3) : "memory");
}
__device__ __forceinline__ void tma_load_3d(uint32_t dst, const CUtensorMap* tm, uint32_t bar, int c0, int c1, int c2) {
  asm volatile(ELECT "cp.async.bulk.tensor.3d.shared::cluster.global.mbarrier::complete_tx::bytes [%0], [%1, {%3, %4, %5}], [%2];\n}"
    :: "r"(dst), "l"(tm), "r"(bar), "r"(c0), "r"(c1), "r"(c2) : "memory");
}
__device__ __forceinline__ void tma_load_3d_mc(uint32_t dst, const CUtensorMap* tm, uint32_t bar, int c0, int c1, int c2) {
  asm volatile(ELECT "cp.async.bulk.tensor.3d.shared::cluster.global.mbarrier::complete_tx::bytes.multicast::cluster [%0], [%1, {%3, %4, %5}], [%2], %6;\n}"
    :: "r"(dst), "l"(tm), "r"(bar), "r"(c0), "r"(c1), "r"(c2), "h"((uint16_t)3) : "memory");
}
__device__ __forceinline__ void bulk_load_mc(uint32_t dst, const void* src, uint32_t bar) {
  asm volatile(ELECT "cp.async.bulk.shared::cluster.global.mbarrier::complete_tx::bytes.multicast::cluster [%0], [%1], 16384, [%2], %3;\n}"
    :: "r"(dst), "l"(src), "r"(bar), "h"((uint16_t)3) : "memory");
}
__device__ __forceinline__ void bulk_load(uint32_t dst, const void* src, uint32_t bytes, uint32_t bar) {
  asm volatile(ELECT "cp.async.bulk.shared::cluster.global.mbarrier::complete_tx::bytes [%0], [%1], %2, [%3];\n}" :: "r"(dst), "l"(src), "r"(bytes), "r"(bar) : "memory");
}
__device__ __forceinline__ void tma_prefetch_2d(const CUtensorMap* tm, int c0, int c1) {
  asm volatile(ELECT "cp.async.bulk.prefetch.tensor.2d.L2.global [%0, {%1, %2}];\n}" :: "l"(tm), "r"(c0), "r"(c1) : "memory");
}
__device__ __forceinline__ void bulk_prefetch(const void* p, uint32_t bytes) {
  asm volatile(ELECT "cp.async.bulk.prefetch.L2.global [%0], %1;\n}" :: "l"(p), "r"(bytes) : "memory");
}
__device__ __forceinline__ void red_relaxed(unsigned int* p) { asm volatile("red.relaxed.gpu.global.add.u32 [%0], 1;" :: "l"(p) : "memory"); }
__device__ __forceinline__ void red_release(int idx) { asm volatile("red.release.gpu.global.add.u32 [%0], 1;" :: "l"(&g_x.cnt[idx]) : "memory"); }
__device__ __forceinline__ void prefetch_tmap(const CUtensorMap* tm) { asm volatile("prefetch.tensormap [%0];" :: "l"(tm) : "memory"); }
__device__ __forceinline__ void bar_sync(int id, int n) { asm volatile("bar.sync %0, %1;" :: "r"(id), "r"(n) : "memory"); }
__device__ __forceinline__ void bar_arrive(int id, int n) { asm volatile("bar.arrive %0, %1;" :: "r"(id), "r"(n) : "memory"); }
__device__ __forceinline__ void fence_async_smem() { asm volatile("fence.proxy.async.shared::cta;" ::: "memory"); }
__device__ __forceinline__ void fence_async_global() { asm volatile("fence.proxy.async.global;" ::: "memory"); }
__device__ __forceinline__ void fence_mbar_init() { asm volatile("fence.mbarrier_init.release.cluster;" ::: "memory"); }
__device__ __forceinline__ void cluster_arrive() { asm volatile("barrier.cluster.arrive.relaxed.aligned;" ::: "memory"); }
__device__ __forceinline__ void cluster_wait() { asm volatile("barrier.cluster.wait.aligned;" ::: "memory"); }
__device__ __forceinline__ uint32_t cluster_ctarank() { uint32_t r; asm volatile("mov.u32 %0, %%cluster_ctarank;" : "=r"(r)); return r; }
__device__ __forceinline__ void wgmma_fence() { asm volatile("wgmma.fence.sync.aligned;" ::: "memory"); }
__device__ __forceinline__ void wgmma_commit() { asm volatile("wgmma.commit_group.sync.aligned;" ::: "memory"); }
template<int N> __device__ __forceinline__ void wgmma_wait() { asm volatile("wgmma.wait_group.sync.aligned %0;" :: "n"(N) : "memory"); }
__device__ __forceinline__ float ex2(float x) { float y; asm("ex2.approx.ftz.f32 %0, %1;" : "=f"(y) : "f"(x)); return y; }
__device__ __forceinline__ float rcp_fast(float x) { float y; asm("rcp.approx.ftz.f32 %0, %1;" : "=f"(y) : "f"(x)); return y; }
__device__ __forceinline__ uint32_t pack_bf16(float lo, float hi) { uint32_t r; asm("cvt.rn.bf16x2.f32 %0, %1, %2;" : "=r"(r) : "f"(hi), "f"(lo)); return r; }
__device__ __forceinline__ float rbf(float x) { return __uint_as_float(pack_bf16(0.f, x)); }
__device__ __forceinline__ float bf_lo(uint32_t v) { return __uint_as_float(v << 16); }
__device__ __forceinline__ float bf_hi(uint32_t v) { return __uint_as_float(v & 0xffff0000u); }
__device__ __forceinline__ uint32_t add2(uint32_t a, uint32_t b) { uint32_t r; asm("add.rn.bf16x2 %0, %1, %2;" : "=r"(r) : "r"(a), "r"(b)); return r; }
__device__ __forceinline__ uint32_t fma2(uint32_t a, uint32_t b, uint32_t c) { uint32_t r; asm("fma.rn.bf16x2 %0, %1, %2, %3;" : "=r"(r) : "r"(a), "r"(b), "r"(c)); return r; }
__device__ __forceinline__ uint4 ldsm_x4_t(uint32_t addr) {
  uint4 v; asm volatile("ldmatrix.sync.aligned.m8n8.x4.trans.shared.b16 {%0, %1, %2, %3}, [%4];" : "=r"(v.x), "=r"(v.y), "=r"(v.z), "=r"(v.w) : "r"(addr) : "memory"); return v;
}
__device__ __forceinline__ uint4 ldsm_x4(uint32_t addr) {
  uint4 v; asm volatile("ldmatrix.sync.aligned.m8n8.x4.shared.b16 {%0, %1, %2, %3}, [%4];" : "=r"(v.x), "=r"(v.y), "=r"(v.z), "=r"(v.w) : "r"(addr) : "memory"); return v;
}
__device__ __forceinline__ void mma16816(float (&c)[4], const uint4& a, uint32_t b0, uint32_t b1) {
  asm("mma.sync.aligned.m16n8k16.row.col.f32.bf16.bf16.f32 {%0, %1, %2, %3}, {%4, %5, %6, %7}, {%8, %9}, {%0, %1, %2, %3};"
    : "+f"(c[0]), "+f"(c[1]), "+f"(c[2]), "+f"(c[3]) : "r"(a.x), "r"(a.y), "r"(a.z), "r"(a.w), "r"(b0), "r"(b1));
}
template<int N> __device__ __forceinline__ void fence_regs(float (&a)[N]) {
  #pragma unroll
  for (int i = 0; i < N; i++) asm volatile("" : "+f"(a[i]) :: "memory");
}
template<int N> __device__ __forceinline__ void fence_regs_u(uint32_t (&a)[N]) {
  #pragma unroll
  for (int i = 0; i < N; i++) asm volatile("" : "+r"(a[i]) :: "memory");
}
constexpr uint32_t SW128 = 0x40000040u, SW64 = 0x80000020u;
__device__ __forceinline__ uint32_t desc_lo(uint32_t addr, uint32_t lbo) { return ((addr & 0x3FFFF) >> 4) | ((lbo >> 4) << 16); }

template<int TB, int OA, int OB, uint32_t HA, uint32_t HB> __device__ __forceinline__ void wgmma_ss_n128(float (&d)[64], uint32_t da, uint32_t db, int sd) {
  asm volatile("{\n.reg .pred p;\n.reg .b32 ta, tb;\n.reg .b64 da, db;\nsetp.ne.b32 p, %66, 0;\nadd.u32 ta, %64, %68;\nadd.u32 tb, %65, %69;\nmov.b64 da, {ta, %70};\nmov.b64 db, {tb, %71};\n"
    "wgmma.mma_async.sync.aligned.m64n128k16.f32.bf16.bf16 "
    "{%0, %1, %2, %3, %4, %5, %6, %7, %8, %9, %10, %11, %12, %13, %14, %15, %16, %17, %18, %19, %20, %21, %22, %23, %24, %25, %26, %27, %28, %29, %30, %31, %32, %33, %34, %35, %36, %37, %38, %39, %40, %41, %42, %43, %44, %45, %46, %47, %48, %49, %50, %51, %52, %53, %54, %55, %56, %57, %58, %59, %60, %61, %62, %63}, da, db, p, 1, 1, 0, %67;\n}\n"
    : "+f"(d[0]), "+f"(d[1]), "+f"(d[2]), "+f"(d[3]), "+f"(d[4]), "+f"(d[5]), "+f"(d[6]), "+f"(d[7]), "+f"(d[8]), "+f"(d[9]), "+f"(d[10]), "+f"(d[11]), "+f"(d[12]), "+f"(d[13]), "+f"(d[14]), "+f"(d[15]), "+f"(d[16]), "+f"(d[17]), "+f"(d[18]), "+f"(d[19]), "+f"(d[20]), "+f"(d[21]), "+f"(d[22]), "+f"(d[23]), "+f"(d[24]), "+f"(d[25]), "+f"(d[26]), "+f"(d[27]), "+f"(d[28]), "+f"(d[29]), "+f"(d[30]), "+f"(d[31]), "+f"(d[32]), "+f"(d[33]), "+f"(d[34]), "+f"(d[35]), "+f"(d[36]), "+f"(d[37]), "+f"(d[38]), "+f"(d[39]), "+f"(d[40]), "+f"(d[41]), "+f"(d[42]), "+f"(d[43]), "+f"(d[44]), "+f"(d[45]), "+f"(d[46]), "+f"(d[47]), "+f"(d[48]), "+f"(d[49]), "+f"(d[50]), "+f"(d[51]), "+f"(d[52]), "+f"(d[53]), "+f"(d[54]), "+f"(d[55]), "+f"(d[56]), "+f"(d[57]), "+f"(d[58]), "+f"(d[59]), "+f"(d[60]), "+f"(d[61]), "+f"(d[62]), "+f"(d[63])
    : "r"(da), "r"(db), "r"(sd), "n"(TB), "n"(OA), "n"(OB), "n"(HA), "n"(HB));
}
template<int TB, int OB, uint32_t HB> __device__ __forceinline__ void wgmma_rs_n128(float (&d)[64], uint32_t a0, uint32_t a1, uint32_t a2, uint32_t a3, uint32_t db, int sd) {
  asm volatile("{\n.reg .pred p;\n.reg .b32 tb;\n.reg .b64 db;\nsetp.ne.b32 p, %69, 0;\nadd.u32 tb, %68, %71;\nmov.b64 db, {tb, %72};\n"
    "wgmma.mma_async.sync.aligned.m64n128k16.f32.bf16.bf16 "
    "{%0, %1, %2, %3, %4, %5, %6, %7, %8, %9, %10, %11, %12, %13, %14, %15, %16, %17, %18, %19, %20, %21, %22, %23, %24, %25, %26, %27, %28, %29, %30, %31, %32, %33, %34, %35, %36, %37, %38, %39, %40, %41, %42, %43, %44, %45, %46, %47, %48, %49, %50, %51, %52, %53, %54, %55, %56, %57, %58, %59, %60, %61, %62, %63}, {%64,%65,%66,%67}, db, p, 1, 1, %70;\n}\n"
    : "+f"(d[0]), "+f"(d[1]), "+f"(d[2]), "+f"(d[3]), "+f"(d[4]), "+f"(d[5]), "+f"(d[6]), "+f"(d[7]), "+f"(d[8]), "+f"(d[9]), "+f"(d[10]), "+f"(d[11]), "+f"(d[12]), "+f"(d[13]), "+f"(d[14]), "+f"(d[15]), "+f"(d[16]), "+f"(d[17]), "+f"(d[18]), "+f"(d[19]), "+f"(d[20]), "+f"(d[21]), "+f"(d[22]), "+f"(d[23]), "+f"(d[24]), "+f"(d[25]), "+f"(d[26]), "+f"(d[27]), "+f"(d[28]), "+f"(d[29]), "+f"(d[30]), "+f"(d[31]), "+f"(d[32]), "+f"(d[33]), "+f"(d[34]), "+f"(d[35]), "+f"(d[36]), "+f"(d[37]), "+f"(d[38]), "+f"(d[39]), "+f"(d[40]), "+f"(d[41]), "+f"(d[42]), "+f"(d[43]), "+f"(d[44]), "+f"(d[45]), "+f"(d[46]), "+f"(d[47]), "+f"(d[48]), "+f"(d[49]), "+f"(d[50]), "+f"(d[51]), "+f"(d[52]), "+f"(d[53]), "+f"(d[54]), "+f"(d[55]), "+f"(d[56]), "+f"(d[57]), "+f"(d[58]), "+f"(d[59]), "+f"(d[60]), "+f"(d[61]), "+f"(d[62]), "+f"(d[63])
    : "r"(a0), "r"(a1), "r"(a2), "r"(a3), "r"(db), "r"(sd), "n"(TB), "n"(OB), "n"(HB));
}
template<int TB, int OA, int OB, uint32_t HA, uint32_t HB> __device__ __forceinline__ void wgmma_ss_n64(float (&d)[32], uint32_t da, uint32_t db, int sd) {
  asm volatile("{\n.reg .pred p;\n.reg .b32 ta, tb;\n.reg .b64 da, db;\nsetp.ne.b32 p, %34, 0;\nadd.u32 ta, %32, %36;\nadd.u32 tb, %33, %37;\nmov.b64 da, {ta, %38};\nmov.b64 db, {tb, %39};\n"
    "wgmma.mma_async.sync.aligned.m64n64k16.f32.bf16.bf16 "
    "{%0, %1, %2, %3, %4, %5, %6, %7, %8, %9, %10, %11, %12, %13, %14, %15, %16, %17, %18, %19, %20, %21, %22, %23, %24, %25, %26, %27, %28, %29, %30, %31}, da, db, p, 1, 1, 0, %35;\n}\n"
    : "+f"(d[0]), "+f"(d[1]), "+f"(d[2]), "+f"(d[3]), "+f"(d[4]), "+f"(d[5]), "+f"(d[6]), "+f"(d[7]), "+f"(d[8]), "+f"(d[9]), "+f"(d[10]), "+f"(d[11]), "+f"(d[12]), "+f"(d[13]), "+f"(d[14]), "+f"(d[15]), "+f"(d[16]), "+f"(d[17]), "+f"(d[18]), "+f"(d[19]), "+f"(d[20]), "+f"(d[21]), "+f"(d[22]), "+f"(d[23]), "+f"(d[24]), "+f"(d[25]), "+f"(d[26]), "+f"(d[27]), "+f"(d[28]), "+f"(d[29]), "+f"(d[30]), "+f"(d[31])
    : "r"(da), "r"(db), "r"(sd), "n"(TB), "n"(OA), "n"(OB), "n"(HA), "n"(HB));
}
template<int TB, int OA, int OB, uint32_t HA, uint32_t HB> __device__ __forceinline__ void wgmma_ss_n128_new(float (&d)[64], uint32_t da, uint32_t db) {
  asm volatile("{\n.reg .pred p;\n.reg .b32 ta, tb;\n.reg .b64 da, db;\nsetp.ne.b32 p, %66, 0;\nadd.u32 ta, %64, %68;\nadd.u32 tb, %65, %69;\nmov.b64 da, {ta, %70};\nmov.b64 db, {tb, %71};\n"
    "wgmma.mma_async.sync.aligned.m64n128k16.f32.bf16.bf16 "
    "{%0, %1, %2, %3, %4, %5, %6, %7, %8, %9, %10, %11, %12, %13, %14, %15, %16, %17, %18, %19, %20, %21, %22, %23, %24, %25, %26, %27, %28, %29, %30, %31, %32, %33, %34, %35, %36, %37, %38, %39, %40, %41, %42, %43, %44, %45, %46, %47, %48, %49, %50, %51, %52, %53, %54, %55, %56, %57, %58, %59, %60, %61, %62, %63}, da, db, p, 1, 1, 0, %67;\n}\n"
    : "=f"(d[0]), "=f"(d[1]), "=f"(d[2]), "=f"(d[3]), "=f"(d[4]), "=f"(d[5]), "=f"(d[6]), "=f"(d[7]), "=f"(d[8]), "=f"(d[9]), "=f"(d[10]), "=f"(d[11]), "=f"(d[12]), "=f"(d[13]), "=f"(d[14]), "=f"(d[15]), "=f"(d[16]), "=f"(d[17]), "=f"(d[18]), "=f"(d[19]), "=f"(d[20]), "=f"(d[21]), "=f"(d[22]), "=f"(d[23]), "=f"(d[24]), "=f"(d[25]), "=f"(d[26]), "=f"(d[27]), "=f"(d[28]), "=f"(d[29]), "=f"(d[30]), "=f"(d[31]), "=f"(d[32]), "=f"(d[33]), "=f"(d[34]), "=f"(d[35]), "=f"(d[36]), "=f"(d[37]), "=f"(d[38]), "=f"(d[39]), "=f"(d[40]), "=f"(d[41]), "=f"(d[42]), "=f"(d[43]), "=f"(d[44]), "=f"(d[45]), "=f"(d[46]), "=f"(d[47]), "=f"(d[48]), "=f"(d[49]), "=f"(d[50]), "=f"(d[51]), "=f"(d[52]), "=f"(d[53]), "=f"(d[54]), "=f"(d[55]), "=f"(d[56]), "=f"(d[57]), "=f"(d[58]), "=f"(d[59]), "=f"(d[60]), "=f"(d[61]), "=f"(d[62]), "=f"(d[63])
    : "r"(da), "r"(db), "n"(0), "n"(TB), "n"(OA), "n"(OB), "n"(HA), "n"(HB));
}
template<int TB, int OA, int OB, uint32_t HA, uint32_t HB> __device__ __forceinline__ void wgmma_ss_n64_new(float (&d)[32], uint32_t da, uint32_t db) {
  asm volatile("{\n.reg .pred p;\n.reg .b32 ta, tb;\n.reg .b64 da, db;\nsetp.ne.b32 p, %34, 0;\nadd.u32 ta, %32, %36;\nadd.u32 tb, %33, %37;\nmov.b64 da, {ta, %38};\nmov.b64 db, {tb, %39};\n"
    "wgmma.mma_async.sync.aligned.m64n64k16.f32.bf16.bf16 "
    "{%0, %1, %2, %3, %4, %5, %6, %7, %8, %9, %10, %11, %12, %13, %14, %15, %16, %17, %18, %19, %20, %21, %22, %23, %24, %25, %26, %27, %28, %29, %30, %31}, da, db, p, 1, 1, 0, %35;\n}\n"
    : "=f"(d[0]), "=f"(d[1]), "=f"(d[2]), "=f"(d[3]), "=f"(d[4]), "=f"(d[5]), "=f"(d[6]), "=f"(d[7]), "=f"(d[8]), "=f"(d[9]), "=f"(d[10]), "=f"(d[11]), "=f"(d[12]), "=f"(d[13]), "=f"(d[14]), "=f"(d[15]), "=f"(d[16]), "=f"(d[17]), "=f"(d[18]), "=f"(d[19]), "=f"(d[20]), "=f"(d[21]), "=f"(d[22]), "=f"(d[23]), "=f"(d[24]), "=f"(d[25]), "=f"(d[26]), "=f"(d[27]), "=f"(d[28]), "=f"(d[29]), "=f"(d[30]), "=f"(d[31])
    : "r"(da), "r"(db), "n"(0), "n"(TB), "n"(OA), "n"(OB), "n"(HA), "n"(HB));
}
template<int OA, int OB = 0, uint32_t HA = SW128> __device__ __forceinline__ void kblock_n128(float (&d)[64], uint32_t da, uint32_t db, int sd) {
  constexpr int H = HA == SW128 ? 4 : 512;
  wgmma_ss_n128<1, OA, OB, HA, SW128>(d, da, db, sd); wgmma_ss_n128<1, OA + 2, OB + 128, HA, SW128>(d, da, db, 1);
  wgmma_ss_n128<1, OA + H, OB + 256, HA, SW128>(d, da, db, 1); wgmma_ss_n128<1, OA + H + 2, OB + 384, HA, SW128>(d, da, db, 1);
}

__device__ __forceinline__ float quad_sum(float v) {
  v += __shfl_xor_sync(0xffffffff, v, 1);
  v += __shfl_xor_sync(0xffffffff, v, 2);
  return v;
}
struct Row { uint32_t v[8]; };
template<class F> __device__ __forceinline__ Row load_row(const __nv_bfloat16* p, int lane, F ld) {
  const uint4 a = ld(reinterpret_cast<const uint4*>(p) + lane), b = ld(reinterpret_cast<const uint4*>(p) + 32 + lane);
  return Row{{a.x, a.y, a.z, a.w, b.x, b.y, b.z, b.w}};
}
__device__ __forceinline__ Row ldg_row(const __nv_bfloat16* p, int lane) { return load_row(p, lane, [](const uint4* q) { return __ldg(q); }); }
__device__ __forceinline__ Row ldca_row(const __nv_bfloat16* p, int lane) { return load_row(p, lane, [](const uint4* q) { return __ldca(q); }); }
__device__ __forceinline__ Row lds_row(uint32_t addr, int lane) {
  const uint4 a = lds_v4(addr + lane * 16), b = lds_v4(addr + 512 + lane * 16);
  return Row{{a.x, a.y, a.z, a.w, b.x, b.y, b.z, b.w}};
}
__device__ __forceinline__ void store_row(__nv_bfloat16* p, int lane, const Row& r) {
  stg_v4(p + lane * 8, r.v[0], r.v[1], r.v[2], r.v[3]); stg_v4(p + 256 + lane * 8, r.v[4], r.v[5], r.v[6], r.v[7]);
}
__device__ __forceinline__ Row fma_row(const Row& a, const Row& b, const Row& c) {
  Row r;
  #pragma unroll
  for (int i = 0; i < 8; i++) r.v[i] = fma2(a.v[i], b.v[i], c.v[i]);
  return r;
}
__device__ __forceinline__ Row add_row(const Row& a, const Row& b) {
  Row r;
  #pragma unroll
  for (int i = 0; i < 8; i++) r.v[i] = add2(a.v[i], b.v[i]);
  return r;
}
__device__ __forceinline__ Row one_plus(const Row& a) {
  Row r;
  #pragma unroll
  for (int i = 0; i < 8; i++) r.v[i] = add2(a.v[i], 0x3f803f80u);
  return r;
}
__device__ __forceinline__ float row_at(const Row& x, int i) { return (i & 1) ? bf_hi(x.v[i >> 1]) : bf_lo(x.v[i >> 1]); }
template<int N> __device__ __forceinline__ void warp_sums(float (&s)[N]) {
  #pragma unroll
  for (int o = 16; o > 0; o >>= 1) {
    #pragma unroll
    for (int k = 0; k < N; k++) s[k] += __shfl_xor_sync(0xffffffff, s[k], o);
  }
}
__device__ __forceinline__ void ln_stats(float& s1, float& s2) {
  s1 *= 1.f / DM;
  asm("rsqrt.approx.ftz.f32 %0, %1;" : "=f"(s2) : "f"(fmaxf(fmaf(-s1, s1, s2 * (1.f / DM)), 0.f) + 1e-5f));
}
__device__ __forceinline__ Row ln_apply(const Row& x, float mean, float f) {
  Row n;
  const float o = -mean * f;
  #pragma unroll
  for (int i = 0; i < 8; i++) n.v[i] = pack_bf16(fmaf(bf_lo(x.v[i]), f, o), fmaf(bf_hi(x.v[i]), f, o));
  return n;
}

constexpr int SM_Q = 6 * 32768, SM_BAR = 7 * 32768, SM_MAIL = SM_BAR + 640, SM_RED = SM_MAIL + 128, SM_H2 = SM_RED + 1024, SM_KEY = SM_H2 + 1024, SMEM = SM_KEY + 128;
constexpr int B_AF = 0, B_WF = 64, B_RF = 112, B_WE = 168, B_RE = 216, B_PUB = 272, B_RDY = 496;
constexpr int R_MOD = B_RDY, R_H1 = B_RDY + 8, R_ITEM = B_RDY + 16, R_NEAR = B_RDY + 48, R_CTX = B_RDY + 64;
constexpr int R_KEY = B_AF + 8, R_PART = B_AF + 32;
constexpr int NPUB = 14;
__device__ __forceinline__ uint32_t k_addrA(int kb) { return ((0x6310u >> ((kb >> 1) * 4)) & 15u) * 32768u + (kb & 1) * 16384u; }
__device__ __forceinline__ uint32_t k_addrW(int s) { return ((0x254u >> ((s >> 1) * 4)) & 15u) * 32768u + (s & 1) * 16384u; }

#define KORDER 0x3201
constexpr int KHEAD0 = ((KORDER >> 12) & 3) * 8;
constexpr int MAX_ITEMS = 4;
constexpr int MAX_STEPS = 10;
struct Sched {
  __nv_bfloat16 *kvc, *h1, *part;
  struct Pair {
    uint8_t oent[3 * MAX_STEPS + 6];
    uint8_t khead[4];
    uint8_t nitems, item[MAX_ITEMS];
    uint8_t otask, nsteps;
    uint8_t ochunk[MAX_STEPS][2];
  } pair[NGRID / 2];
};

__device__ __forceinline__ int ring_add(int e, int n) { e += n; return e >= 12 ? e - 12 : e; }
__device__ __forceinline__ int ring_slot(int e) { return e >= 6 ? e - 6 : e; }
__device__ __forceinline__ void ring_wait_full(uint32_t bars, int e) { mbar_wait(bars + B_RF + 8 * ring_slot(e), e >= 6); }

__device__ __forceinline__ void o_wait_full(uint32_t bars, uint32_t v) { mbar_wait(bars + B_RF + 8 * (v & 7), v >> 3); }

struct Ctx {
  uint32_t base, bars;
  uint32_t rel;
  bool rel1;
  int w, nev;
  const Sched* sched;
};
__device__ __forceinline__ void slot_release(const Ctx& x, int s, bool twice) {
  mbar_arrive_remote_if(x.rel + B_RE + 8 * s, twice ? (wg_tid() & 31) == 0 : x.rel1);
}
__device__ __forceinline__ void ring_release(const Ctx& x, int e, bool twice) { slot_release(x, ring_slot(e), twice); }
__device__ __forceinline__ void publish(Ctx& x, int idx) {
  const uint32_t n = x.w * NPUB + x.nev;
  const int t = wg_tid();
  if (t == 0) asm volatile("st.shared.u32 [%0], %1;" :: "r"(x.base + SM_MAIL + 4 * n), "r"(idx) : "memory");
  __syncwarp();
  if ((t & 31) == 0) mbar_arrive(x.bars + B_PUB + 8 * n);
  x.nev++;
}

template<int KK = 0> __device__ __forceinline__ void issue_qk(float (&S)[64], uint32_t dq, uint32_t dk) {
  constexpr int off = (KK >> 1) * 512 + (KK & 1) * 2;
  if constexpr (KK == 0) wgmma_ss_n128_new<0, 0, 0, SW64, SW64>(S, dq, dk); else wgmma_ss_n128<0, off, off, SW64, SW64>(S, dq, dk, 1);
  if constexpr (KK < 7) issue_qk<KK + 1>(S, dq, dk);
}
template<int KK = 0> __device__ __forceinline__ void issue_qk_half(float (&S)[32], uint32_t dq, uint32_t dk) {
  constexpr int off = (KK >> 1) * 512 + (KK & 1) * 2;
  if constexpr (KK == 0) wgmma_ss_n64_new<0, 0, 256, SW64, SW64>(S, dq, dk); else wgmma_ss_n64<0, off, off + 256, SW64, SW64>(S, dq, dk, 1);
  if constexpr (KK < 7) issue_qk_half<KK + 1>(S, dq, dk);
}
template<int NK, int KK = 0>
__device__ __forceinline__ void issue_pv(float (&O)[64], uint32_t (&P)[32], uint32_t dv, int accumulate) {
  wgmma_rs_n128<1, (KK + 8 - NK) * 64, SW64>(O, P[4*KK], P[4*KK+1], P[4*KK+2], P[4*KK+3], dv, accumulate);
  if constexpr (KK + 1 < NK) issue_pv<NK, KK + 1>(O, P, dv, 1);
}
template<int K0, int K1>
__device__ __forceinline__ void exp_pack(const float (&S)[64], uint32_t (&D)[32], float& s0, float& s1) {
  #pragma unroll
  for (int k = K0; k < K1; k++) {
    const float e0 = ex2(S[2*k]), e1 = ex2(S[2*k+1]);
    D[k] = pack_bf16(e0, e1);
    if (k & 1) s1 += e0 + e1; else s0 += e0 + e1;
  }
}
__device__ __forceinline__ int diag_limit() { const int t = wg_tid(); return 16 * (t >> 5) + ((t & 31) >> 2) - 2 * (t & 3); }
__device__ __forceinline__ void exp_pack_diag(const float (&S)[64], uint32_t (&D)[32], int t, float& s0, float& s1) {
  #pragma unroll
  for (int k = 0; k < 16; k++) {
    const int c = 8 * (k >> 1) - 8 * (k & 1);
    const float e0 = ex2((c <= t) ? S[2*k] : -INFINITY), e1 = ex2((c + 1 <= t) ? S[2*k+1] : -INFINITY);
    D[k] = pack_bf16(e0, e1);
    if (k & 1) s1 += e0 + e1; else s0 += e0 + e1;
  }
}
constexpr float SUM_HI = 1.8446744073709552e19f;
constexpr float SUM_LO = 5.421010862427522e-20f;

__device__ __forceinline__ void classic_tile(const float (&S)[64], uint32_t (&P)[32], bool fresh, bool half, bool was_classic, volatile float* mc,
                                             float& l0, float& l1, float& s0, float& s1, float& sc0, float& sc1) {
  const int tmask = diag_limit();
  float4 t[16];
  #pragma unroll
  for (int j = 0; j < 16; j++) t[j] = make_float4(S[4*j], S[4*j+1], S[4*j+2], S[4*j+3]);
  float mx0 = -INFINITY, mx1 = -INFINITY;
  #pragma unroll 1
  for (int j = 0; j < 16; j++) {
    float4 v = t[j];
    const int lim = !fresh ? 1000 : j < 8 ? tmask - 8 * j : half ? -1000 : 1000;
    v.x = 0 <= lim ? v.x : -INFINITY; v.y = 1 <= lim ? v.y : -INFINITY; v.z = -8 <= lim ? v.z : -INFINITY; v.w = -7 <= lim ? v.w : -INFINITY;
    t[j] = v;
    mx0 = fmaxf(mx0, fmaxf(v.x, v.y)); mx1 = fmaxf(mx1, fmaxf(v.z, v.w));
  }
  mx0 = fmaxf(mx0, __shfl_xor_sync(0xffffffff, mx0, 1));
  mx1 = fmaxf(mx1, __shfl_xor_sync(0xffffffff, mx1, 1));
  mx0 = fmaxf(mx0, __shfl_xor_sync(0xffffffff, mx0, 2));
  mx1 = fmaxf(mx1, __shfl_xor_sync(0xffffffff, mx1, 2));
  const float mc0 = was_classic ? mc[0] : 0.f, mc1 = was_classic ? mc[1] : 0.f;
  const float n0 = fresh ? -mx0 : fminf(mc0, -mx0), n1 = fresh ? -mx1 : fminf(mc1, -mx1);
  sc0 = ex2(n0 - mc0); sc1 = ex2(n1 - mc1);
  mc[0] = n0; mc[1] = n1;
  s0 = 0.f; s1 = 0.f;
  #pragma unroll 1
  for (int j = 0; j < 16; j++) {
    const float4 v = t[j];
    const float e0 = ex2(v.x + n0), e1 = ex2(v.y + n0), e2 = ex2(v.z + n1), e3 = ex2(v.w + n1);
    s0 += e0 + e1; s1 += e2 + e3;
    reinterpret_cast<uint2*>(t)[j] = make_uint2(pack_bf16(e0, e1), pack_bf16(e2, e3));
  }
  #pragma unroll
  for (int j = 0; j < 8; j++) { P[4*j] = __float_as_uint(t[j].x); P[4*j+1] = __float_as_uint(t[j].y); P[4*j+2] = __float_as_uint(t[j].z); P[4*j+3] = __float_as_uint(t[j].w); }
  if (!fresh) { l0 *= sc0; l1 *= sc1; }
}
__device__ __forceinline__ void pack_tile(const float (&A)[64], uint32_t (&D)[32], float f0, float f1) {
  #pragma unroll
  for (int j = 0; j < 16; j++) {
    D[8 * (j >> 2) + (j & 3)] = pack_bf16(A[4*j] * f0, A[4*j+1] * f0);
    D[8 * (j >> 2) + 4 + (j & 3)] = pack_bf16(A[4*j+2] * f1, A[4*j+3] * f1);
  }
}
__device__ __forceinline__ int piece0(int t) { return ((t >> 5) * 16 + ((t & 31) >> 2)) * 32 + (((t ^ (t >> 3)) & 3) << 3); }
__device__ __forceinline__ void store_tile(__nv_bfloat16* p, const uint32_t (&D)[32]) {
  #pragma unroll
  for (int i = 0; i < 8; i++) stg_v4(p + (i >> 2) * (SEQ * 64) + ((i >> 1) & 1) * 4096 + (i & 1) * 256, D[4*i], D[4*i+1], D[4*i+2], D[4*i+3]);
}

enum : int { PV_ACC = 0, PV_ZERO = 1, PV_HALF = 2, PV_NONE = 3 };
struct Att {
  float l0, l1, i0, i1;
  bool classic;
  volatile float* mc;
};
__device__ __forceinline__ void store_ctx(Ctx& x, int code, const uint32_t (&D)[32]) {
  store_tile(x.sched->kvc + ((size_t)(128 + (code >> 5) * 2) * SEQ + ((code >> 1) & 15) * 128) * 64 + (code & 1) * 2048 + piece0(wg_tid()), D);
  publish(x, C_CTX + (code >> 2));
}
__device__ __forceinline__ __nv_bfloat16* kv_tile(const Ctx& x, int code) {
  return x.sched->kvc + ((size_t)(x.w * 64 + (code >> 4) * 2) * SEQ + (code & 15) * 128) * 64 + piece0(wg_tid());
}
__device__ __forceinline__ void q_proj(Ctx& x, Att& a, int& e, int& sk, int& sv, int& en, int& sn, bool isY,
                                       const uint32_t (&PA)[32], const uint32_t (&PB)[32], int vtile, bool first) {
  float S[64];
  int ek = 0, s = sk, ps = 0, ph = e >= 6, kb = 0;
  uint32_t qa = 0;
  sv = en = sn = 0;
  if (isY) bar_sync(1 + x.w, 256);
  if (first) mbar_wait(x.bars + B_RF + 8 * s, ph);
  #pragma unroll 1
  while (true) {
    #pragma unroll 1
    do {
      wgmma_fence();
      kblock_n128<0>(S, desc_lo(x.base + x.w * 8192, 16) + s * 2048, desc_lo(x.base + 16384, 8192) + s * 2048, kb != 0);
      wgmma_commit();
      if (kb == 7 && !isY) bar_arrive(1 + (x.w ^ 1), 256);
      wgmma_wait<1>();
      mbar_arrive_remote_if(x.rel + B_RE + 8 * ps, x.rel1 && kb > 0);
      ps = s;
      if (++s == 6) { s = 0; ph ^= 1; }
      if (++kb == 8) break;
      mbar_wait(x.bars + B_RF + 8 * s, ph);
    } while (kb != 4);
    asm volatile("" : "+r"(vtile));
    if (kb == 8) break;
    a.i0 = rcp_fast(quad_sum(a.l0)); a.i1 = rcp_fast(quad_sum(a.l1));
    e = ring_add(e, 8); ek = ring_add(e, isY ? 0 : 2); en = ring_add(e, isY ? 2 : 4);
    sk = ring_slot(ek); sv = ring_slot(e) + 1; sn = ring_slot(en);
    qa = x.base + SM_Q + x.w * 4096 + piece0(wg_tid()) * 2;
    if (vtile >= 0) store_tile(kv_tile(x, vtile) + 2048, PA);
  }
  if (vtile >= 0) { store_tile(kv_tile(x, vtile), PB); publish(x, C_KV + (vtile >> 4)); }
  wgmma_wait<0>();
  fence_regs(S);
  slot_release(x, ps, false);
  const bool landed = isY && mbar_test2(x.bars + B_RF + 8 * sk, e >= 6);
  #pragma unroll
  for (int i = 0; i < 8; i++) {
    const int j = 4 * (i >> 1), o = 2 * (i & 1);
    sts_v4(qa + (i >> 1) * 8192 + (i & 1) * 512,
           pack_bf16(S[4*j+o], S[4*j+o+1]), pack_bf16(S[4*j+4+o], S[4*j+5+o]), pack_bf16(S[4*j+8+o], S[4*j+9+o]), pack_bf16(S[4*j+12+o], S[4*j+13+o]));
  }
  fence_async_smem();
  if (!landed) { mbar_wait(x.bars + B_RF + 8 * sk, ek >= 6); mbar_wait(x.bars + B_RF + 8 * sv, e >= 6); }
}

template<int KIND>
__device__ __forceinline__ void slot(Ctx& x, Att& a, int& e, int& sk, int sv, int en, int sn, float (&O)[64], uint32_t (&Pn)[32], uint32_t (&Po)[32],
                                     bool more, bool isY, bool half, int pv, int pend) {
  float S[64];
  const int w = x.w;
  const uint32_t dq = desc_lo(x.base + SM_Q + w * 4096, 16), dk = desc_lo(x.base, 16) + sk * 2048, dv = desc_lo(x.base, 8192) + sv * 2048;
  bar_sync(1 + w, 256);
  if (KIND == 2) {
    wgmma_fence();
    issue_qk(S, dq, dk); wgmma_commit();
    issue_pv<8>(O, Po, dv, 1); wgmma_commit();
    bar_arrive(1 + (w ^ 1), 256);
    wgmma_wait<1>();
  } else if (KIND == 0 && half) {
    float T[32];
    wgmma_fence(); issue_qk_half(T, dq, dk); wgmma_commit();
    if (pv == PV_NONE) { wgmma_fence(); wgmma_commit(); }
    else               { wgmma_fence(); issue_pv<8>(O, Po, dv, pv == PV_ACC); wgmma_commit(); }
    bar_arrive(1 + (w ^ 1), 256);
    wgmma_wait<1>();
    fence_regs(T);
    #pragma unroll
    for (int i = 0; i < 32; i++) { S[i] = T[i]; asm volatile("" : "=f"(S[32 + i])); }
  } else {
    wgmma_fence(); issue_qk(S, dq, dk); wgmma_commit();
    if (KIND == 1 && pend >= 0) { bar_arrive(1 + (w ^ 1), 256); pack_tile(O, Pn, a.i0, a.i1); store_ctx(x, pend, Pn); }
    if (KIND == 0 && pv == PV_NONE) { wgmma_fence(); wgmma_commit(); }
    else if (pv == PV_HALF)         { wgmma_fence(); issue_pv<4>(O, Po, dv, 0); wgmma_commit(); }
    else                            { wgmma_fence(); issue_pv<8>(O, Po, dv, pv == PV_ACC); wgmma_commit(); }
    if (KIND == 0 || pend < 0) bar_arrive(1 + (w ^ 1), 256);
    wgmma_wait<1>();
  }
  fence_regs(S);
  fence_regs_u(Pn);
  slot_release(x, sk, KIND == 0 && isY);
  const bool landed = mbar_test2(x.bars + B_RF + 8 * sn, en >= 6);
  float s0 = 0.f, s1 = 0.f;
  const bool was_classic = KIND != 0 && a.classic;
  if (KIND == 0) {
    a.l0 = 0.f; a.l1 = 0.f;
    if (!half) exp_pack<16, 32>(S, Pn, s0, s1);
    else {
      #pragma unroll
      for (int i = 16; i < 32; i++) asm volatile("" : "=r"(Pn[i]));
    }
    exp_pack_diag(S, Pn, diag_limit(), s0, s1);
    uint32_t b0 = __ballot_sync(0xffffffff, s0 >= SUM_LO), b1 = __ballot_sync(0xffffffff, s1 >= SUM_LO);
    b0 |= b0 >> 1; b0 |= b0 >> 2; b1 |= b1 >> 1; b1 |= b1 >> 2;
    a.classic = __any_sync(0xffffffff, !(s0 <= SUM_HI && s1 <= SUM_HI)) || (b0 & b1 & 0x11111111u) != 0x11111111u;
  } else {
    exp_pack<0, 32>(S, Pn, s0, s1);
    a.classic = __any_sync(0xffffffff, a.classic || !(s0 <= SUM_HI && s1 <= SUM_HI));
  }
  fence_regs_u(Pn);
  if (!landed) {
    mbar_wait(x.bars + B_RF + 8 * sn, en >= 6);
    if (more) mbar_wait(x.bars + B_RF + 8 * sn + 8, en >= 6);
  }
  wgmma_wait<0>();
  fence_regs(O);
  fence_regs_u(Po);
  slot_release(x, sv, KIND == 1 && isY && pv != PV_ACC);
  if (__builtin_expect(a.classic, 0)) {
    float sc0, sc1;
    classic_tile(S, Pn, KIND == 0, half, was_classic, a.mc, a.l0, a.l1, s0, s1, sc0, sc1);
    if (KIND != 0) {
      #pragma unroll
      for (int j = 0; j < 16; j++) { O[4*j] *= sc0; O[4*j+1] *= sc0; O[4*j+2] *= sc1; O[4*j+3] *= sc1; }
    }
  }
  a.l0 += s0; a.l1 += s1;
  e = en; sk = sn;
}

__device__ __forceinline__ int attention(Ctx& x, const uint8_t* items, int nitems, int rank, uint32_t (&PA)[32], uint32_t (&PB)[32], int vtile) {
  int e = 0, sk = 0;
  float O[64];
  Att a;
  volatile float mc[2];
  a.l0 = 1.f; a.l1 = 1.f; a.i0 = 0.f; a.i1 = 0.f; a.classic = false; a.mc = mc;
  int pv = PV_NONE, cur = -1;
  #pragma unroll 1
  for (int it = 0; ; it++) {
    const bool isY = (it & 1) == x.w;
    int pend = cur;
    if (it < nitems) {
      const bool half = isY == (rank != 0);
      int sv, en, sn;
      q_proj(x, a, e, sk, sv, en, sn, isY, PA, PB, vtile, it == 0);
      vtile = -1;
      const int item = items[it];
      cur = item * 4 + (isY ? 3 - rank : rank);
      int rem = 2 * (item & 7) + (isY ? 1 : 0);
      slot<0>(x, a, e, sk, sv, en, sn, O, PA, PB, rem > 0, isY, half, pv, -1);
      pv = half ? PV_HALF : PV_ZERO;
      #pragma unroll 1
      while (rem > 0) {
        slot<1>(x, a, e, sk, sk + 1, ring_add(e, 2), sk == 4 ? 0 : sk + 2, O, PB, PA, rem > 1, isY, false, pv, pend);
        pv = PV_ACC; pend = -1;
        if (rem == 1) break;
        rem -= 2;
        slot<2>(x, a, e, sk, sk + 1, ring_add(e, 2), sk == 4 ? 0 : sk + 2, O, PA, PB, rem > 0, false, false, 0, -1);
      }
      if (isY) continue;
    } else {
      slot_release(x, 6, false);
      const uint32_t dv = desc_lo(x.base, 8192) + sk * 2048;
      bar_sync(1 + x.w, 256);
      if (pv == PV_HALF) { wgmma_fence(); issue_pv<4>(O, PB, dv, 0); wgmma_commit(); }
      else { wgmma_fence(); issue_pv<8>(O, PB, dv, pv == PV_ACC); wgmma_commit(); }
      if (isY) bar_arrive(1 + (x.w ^ 1), 256);
      a.i0 = rcp_fast(quad_sum(a.l0)); a.i1 = rcp_fast(quad_sum(a.l1));
      ring_wait_full(x.bars, e);
      wgmma_wait<0>();
      fence_regs(O);
      fence_regs_u(PB);
      slot_release(x, sk, false);
    }
    if (pend >= 0) {
      pack_tile(O, PB, a.i0, a.i1);
      if (it == nitems) return pend;
      store_ctx(x, pend, PB);
    }
    #pragma unroll
    for (int i = 0; i < 32; i++) asm volatile("mov.b32 %0, %1;" : "=r"(PB[i]) : "r"(PA[i]));
  }
}

#define LN_AT 2
#define X_AT 6
#define PERT 0
#define CTX_T 3
#define PF_AT 5
#define PF_N 4
#define PF_MOE 3
constexpr float QSCALE = 0.08838834764831845f * 1.4426950408889634f;
__device__ __forceinline__ void mod_cta(Ctx& x, const __nv_bfloat16* cvec) {
  const int t = wg_tid(), ct = x.w * 128 + t;
  #pragma unroll 1
  for (int k = 0; k < 6; k++) slot_release(x, k, false);
  const uint32_t cv = __ldg(reinterpret_cast<const uint32_t*>(cvec) + ct);
  asm volatile("st.shared.u32 [%0], %1;" :: "r"(x.base + SM_H2 + ct * 4),
               "r"(pack_bf16(__fdividef(bf_lo(cv), 1.f + __expf(-bf_lo(cv))), __fdividef(bf_hi(cv), 1.f + __expf(-bf_hi(cv))))) : "memory");
  bar_sync(5, 256);
  float acc[64];
  int e = 0;
  #pragma unroll 1
  for (int g = 0; g < 24; g++) {
    uint32_t a[8];
    #pragma unroll
    for (int i = 0; i < 8; i++) a[i] = lds_u32(x.base + SM_H2 + (g & 7) * 128 + i * 16 + (t & 3) * 4);
    ring_wait_full(x.bars, e);
    const uint32_t db = desc_lo(x.base + x.w * 16384, 8192) + ring_slot(e) * 2048;
    wgmma_fence();
    wgmma_rs_n128<1, 0, SW128>(acc, a[0], a[0], a[1], a[1], db, g & 7);
    wgmma_rs_n128<1, 128, SW128>(acc, a[2], a[2], a[3], a[3], db, 1);
    wgmma_rs_n128<1, 256, SW128>(acc, a[4], a[4], a[5], a[5], db, 1);
    wgmma_rs_n128<1, 384, SW128>(acc, a[6], a[6], a[7], a[7], db, 1);
    wgmma_commit();
    wgmma_wait<0>();
    fence_regs(acc);
    ring_release(x, e, false);
    e = ring_add(e, 1);
    if ((g & 7) == 7) {
      if (t < 4) {
        const float sc = (g == 7 && blockIdx.x < NCTA + 2) ? QSCALE : 1.f;
        uint32_t* dst = reinterpret_cast<uint32_t*>(g_x.mod + (g >> 3) * 1024 + (blockIdx.x - NCTA) * 256 + x.w * 128) + t;
        #pragma unroll
        for (int j = 0; j < 16; j++) dst[4 * j] = pack_bf16(rbf(acc[4*j]) * sc, rbf(acc[4*j+1]) * sc);
      }
      publish(x, g == 7 ? C_MOD : C_MOD2);
    }
  }
}

__global__ void __cluster_dims__(2, 1, 1) __launch_bounds__(384, 1)
k_fused(const __grid_constant__ CUtensorMap tmC, const __grid_constant__ CUtensorMap tmWq,
        const __grid_constant__ CUtensorMap tmWk, const __grid_constant__ CUtensorMap tmWv,
        const __grid_constant__ CUtensorMap tmWo, const __grid_constant__ CUtensorMap tmWg,
        const __grid_constant__ CUtensorMap tmWu, const __grid_constant__ CUtensorMap tmWd, const __grid_constant__ CUtensorMap tmWm,
        const __grid_constant__ Sched sched,
        const __nv_bfloat16* __restrict__ xin,
        const __nv_bfloat16* __restrict__ cvec, const __nv_bfloat16* __restrict__ w_o,
        const __nv_bfloat16* __restrict__ w_r, const __nv_bfloat16* __restrict__ w_gate, const __nv_bfloat16* __restrict__ w_up,
        const __nv_bfloat16* __restrict__ w_down, __nv_bfloat16* __restrict__ out) {
  extern __shared__ __align__(1024) uint8_t smem_raw[];
  const uint32_t base = smem_u32(smem_raw), bars = base + SM_BAR;
  const int warp = __shfl_sync(0xffffffff, threadIdx.x >> 5, 0), wg = warp >> 2;
  const int rank = cluster_ctarank(), p = blockIdx.x >> 1;
  const int mt = (p & 7) * 2 + rank;
  const bool spare = blockIdx.x >= NCTA;
  #pragma unroll
  for (int i = 0; i < PERT; i++) { uint32_t d; asm volatile("mov.u32 %0, %%laneid;" : "=r"(d)); (void)d; }
  {
    const int h0 = KHEAD0 + (p >> 3);
    if (warp == 11) { prefetch_tmap(&tmC); prefetch_tmap(&tmWk); }
    #pragma unroll 1
    for (int t = warp == 8 ? 0 : warp < 8 ? warp + 1 : warp == 11 ? 64 : warp; t < B_PUB / 8; t += (warp == 8 ? 64 : 10))
      w_mbar_init(bars + 8 * t, t < B_WE / 8 ? 1 : t < B_RE / 8 ? 2 : 4);
    fence_mbar_init();
    cluster_arrive();
    if (warp == 9) prefetch_tmap(&tmWv);
    if (wg == 2) bar_arrive(1, 256);
    if (warp == 8 && !spare) {
      #pragma unroll 1
      for (int kb = 0; kb < 8; kb++) {
        w_expect_tx(bars + B_AF + 8 * kb, 16384);
        tma_load_2d(base + k_addrA(kb), &tmC, bars + B_AF + 8 * kb, kb * 64, mt * 128);
        if (kb == 0) cluster_wait();
        if (kb < 6) {
          w_expect_tx(bars + B_WF + 8 * kb, 16384);
          tma_load_2d_mc(base + k_addrW(kb) + rank * 8192, &tmWk, bars + B_WF + 8 * kb, h0 * 128 + rank * 64, kb * 64);
        }
      }
    }
  }
  const Sched::Pair& sp = sched.pair[p];
  const int nitems = sp.nitems, nsteps = sp.nsteps;
  auto oent = [&](int k) -> uint32_t { return sp.oent[k]; };
  const int ot = sp.otask, m = (ot & 7) * 2 + rank, grp = m * 8 + (ot >> 3);

  if (wg == 0) {
    asm volatile("setmaxnreg.dec.sync.aligned.u32 24;");
    const int lane = threadIdx.x & 31;
    #pragma unroll 1
    for (int t = B_PUB / 8 + warp; t < 80; t += 4) w_mbar_init(bars + 8 * t, t < B_RDY / 8 ? 4 : 1);
    bar_sync(6, 128);
    bar_arrive(7, 256); bar_arrive(8, 256);
    cluster_wait();
    const unsigned int tag = ld_relaxed(&g_x.epoch) + 1;
    if (warp == 0) {
      if (!spare) {
        int s = 0, ph = 0;
        tma_prefetch_2d(&tmWv, sp.khead[0] * 128 + rank * 64, (p & 7) * 64);
        #pragma unroll 1
        for (int g = 6; g < 64; g++) {
          const int u = g >> 3, kb = g & 7;
          if (kb == 0 && u < 7) tma_prefetch_2d((u & 1) ? &tmWk : &tmWv, sp.khead[(u + 1) >> 1] * 128 + rank * 64, (p & 7) * 64);
          mbar_wait(bars + B_WE + 8 * s, ph);
          w_expect_tx(bars + B_WF + 8 * s, 16384);
          tma_load_2d_mc(base + k_addrW(s) + rank * 8192, (u & 1) ? &tmWv : &tmWk, bars + B_WF + 8 * s, sp.khead[u >> 1] * 128 + rank * 64, kb * 64);
          if (++s == 6) { s = 0; ph ^= 1; }
        }
      }
      int s = 0, ph = 0;
      auto next_entry = [&](int bytes) {
        mbar_wait(bars + B_RE + 8 * s, ph);
        w_expect_tx(bars + B_RF + 8 * s, bytes);
      };
      auto advance = [&]() { if (++s == 6) { s = 0; ph ^= 1; } };
      if (spare) {
        #pragma unroll 1
        for (int g = 0; g < 24; g++) {
          if (g == 8) mbar_wait(bars + R_MOD, 0);
          next_entry(32768);
          for (int k = 0; k < 2; k++) tma_load_3d(base + s * 32768 + k * 16384, &tmWm, bars + B_RF + 8 * s, 0, (g & 7) * 64, (g >> 3) * 16 + (blockIdx.x - NCTA) * 4 + k * 2);
          advance();
        }
      }
      mbar_wait(bars + R_H1, 0);
      fence_async_global();
      int vrow = -1;
      #pragma unroll 1
      for (int i = 0; i <= nitems; i++) {
        const int item = sp.item[i & (MAX_ITEMS - 1)], h = item >> 3, j = item & 7;
        if (i < nitems) {
          const int row0 = j * 256 + ((i & 1) ? rank : 3 - rank) * 64, row1 = j * 256 + ((i & 1) ? 3 - rank : rank) * 64;
          #pragma unroll 1
          for (int kb = 0; kb < 8; kb++) {
            next_entry(32768);
            tma_load_2d_mc(base + s * 32768 + 16384 + rank * 8192, &tmWq, bars + B_RF + 8 * s, h * 128 + rank * 64, kb * 64);
            bulk_load(base + s * 32768, sched.h1 + row0 * DM + kb * 4096, 8192, bars + B_RF + 8 * s);
            bulk_load(base + s * 32768 + 8192, sched.h1 + row1 * DM + kb * 4096, 8192, bars + B_RF + 8 * s);
            advance();
          }
          mbar_wait(bars + R_ITEM + 8 * i, 0);
          fence_async_global();
        }
        #pragma unroll 1
        for (int n = i < nitems ? 4 * j + 3 : 0; n >= 0; n--) {
          const int krow = (h * 2 + rank) * SEQ + (n >> 1) * 128;
          const int row = (n & 1) ? krow : vrow;
          if (i + 1 == nitems && n == min(4 * j + 3, 2 * PF_AT + 1)) w_arrive(bars + R_NEAR);
          next_entry(row >= 0 ? 32768 : 0);
          if (row >= 0) bulk_load_mc(base + s * 32768 + rank * 16384, sched.kvc + (size_t)row * 64, bars + B_RF + 8 * s);
          advance();
          if (!(n & 1)) vrow = krow + 64 * SEQ;
        }
      }
      if (!spare) {
      const int oc = ((ot >> 3) & 1) * 4 + rank * 2;
      auto o_next = [&](int k, int bytes) {
        const uint32_t v = oent(k); s = v & 7;
        mbar_wait(bars + B_RE + 8 * s, v >> 3);
        w_expect_tx(bars + B_RF + 8 * s, bytes);
      };
      #pragma unroll 1
      for (int i = 0; i < nsteps; i++) {
        const int c0 = sp.ochunk[i][0], c1 = sp.ochunk[i][1];
        const int pf = i - nsteps + PF_MOE;
        if (pf >= 0 && pf < 3)
          bulk_prefetch((pf == 0 ? w_gate : pf == 1 ? w_up : w_down) + (size_t)blockIdx.x * (DM * FF / NCTA), DM * FF / NCTA * 2);
        if (c0 < 64) { o_next(3 * i, 32768); tma_load_3d_mc(base + s * 32768 + rank * 16384, &tmWo, bars + B_RF + 8 * s, 0, c0 * 64, oc); }
        mbar_wait(bars + R_CTX + 8 * i, 0);
        fence_async_global();
        o_next(3 * i + 1, c0 < 64 ? 32768 : 16384);
        if (c0 < 64) bulk_load(base + s * 32768, sched.kvc + (size_t)((128 + c0) * SEQ + m * 128) * 64, 16384, bars + B_RF + 8 * s);
        bulk_load(base + s * 32768 + 16384, sched.kvc + (size_t)((128 + c1) * SEQ + m * 128) * 64, 16384, bars + B_RF + 8 * s);
        o_next(3 * i + 2, 32768);
        tma_load_3d_mc(base + s * 32768 + rank * 16384, &tmWo, bars + B_RF + 8 * s, 0, c1 * 64, oc);
      }
      const int f0 = (blockIdx.x < FF / 16 ? blockIdx.x : 0) * 16;
      o_next(3 * nsteps, 32768);
      tma_load_3d(base + s * 32768, &tmWd, bars + B_RF + 8 * s, 0, f0, 0);
      bulk_load(base + s * 32768 + 16384, xin + (size_t)grp * 16 * DM, 16384, bars + B_RF + 8 * s);
      o_next(3 * nsteps + 1, 32768);
      #pragma unroll 1
      for (int k = 0; k < 4; k++) tma_load_2d(base + s * 32768 + k * 8192, (k & 2) ? &tmWu : &tmWg, bars + B_RF + 8 * s, f0, (k & 1) * 256);
      #pragma unroll 1
      for (int k = 0; k < 4; k++) w_expect_tx(bars + R_PART + 8 * k, 16384);
      mbar_wait(bars + B_PUB + 8 * (5 + nitems), 0);
      mbar_wait(bars + B_PUB + 8 * (NPUB + 5 + nitems), 0);
      uint32_t todo = 0xff;
      #pragma unroll 1
      for (int n = 0; n < WAIT_LIM && todo; n++) {
        uint32_t now = __ballot_sync(0xffffffff, ld_acquire(&g_x.sent[grp][lane & 7]) == tag) & todo;
        todo &= ~now;
        if (now) fence_async_global();
        #pragma unroll 1
        for (; now; now &= now - 1) {
          const int q = __ffs(now) - 1;
          bulk_load(base + (oent(3 * nsteps - 3 + (q >> 2)) & 7) * 32768 + (q & 3) * 8192, sched.part + (grp * 8 + q) * 4096, 8192, bars + R_PART + 8 * (q >> 1));
        }
      }
      }
    } else if (warp < 3) {
      const int w = warp - 1, n1 = w * NPUB + (spare ? 3 : 5) + nitems;
      #pragma unroll 1
      for (int n = w * NPUB; n < n1; n++) {
        #pragma unroll 1
        for (int k = 0; k < 8 * WAIT_LIM; k++) { if (mbar_try(bars + B_PUB + 8 * n, 0)) break; }
        const uint32_t idx = lds_u32(base + SM_MAIL + 4 * n);
        fence_async_global();
        if (lane == 0 && idx < (unsigned)C_END) red_release(idx);
        __syncwarp();
      }
    } else {
      *reinterpret_cast<volatile uint32_t*>(smem_raw + SM_KEY + 48) = tag;
      if (!spare) { mbar_wait(bars + B_AF + 8 * X_AT, 0); bulk_prefetch(xin + (size_t)blockIdx.x * 16 * DM, 16 * DM * 2); }
      #pragma unroll 1
      for (int n = 0; n < 8 + nsteps; n++) {
        if (n == 2 + nitems) n = 7;
        int idx = n == 0 ? C_MOD : n == 1 ? C_H1 : C_MOD2, cnt = n == 0 ? 8 : n == 1 ? 256 : 16;
        if (n == 2) tma_prefetch_2d(&tmWq, (sp.item[0] >> 3) * 128 + rank * 64, (sp.item[0] & 7) * 64);
        if (n >= 2 && n < 7) { idx = C_KV + (sp.item[n - 2] >> 3); cnt = 32; }
        if (n >= 8) { const int c0 = sp.ochunk[n - 8][0], c1 = sp.ochunk[n - 8][1]; idx = C_CTX + (((lane & 1) && c0 < 64 ? c0 : c1) >> 1) * 8 + (ot & 7); cnt = 4; }
        wait_count_lazy(idx, cnt * tag);
        w_arrive(bars + B_RDY + 8 * n);
        if (n == 8 + PF_N - 1) {
          #pragma unroll 1
          for (int k = 0; k < 8 * WAIT_LIM; k++) { if (mbar_try(bars + R_NEAR, 0)) break; }
          bulk_prefetch(w_o + (size_t)blockIdx.x * (NH * DH * DM / NCTA), NH * DH * DM / NCTA * 2);
          #pragma unroll 1
          for (int k = 0; k < PF_N; k++) {
            const int cc = sp.ochunk[k][(ot >> 3) & 1];
            if (cc < 64) bulk_prefetch(sched.kvc + ((size_t)(128 + cc) * SEQ + m * 128) * 64, 16384);
          }
        }
      }
    }
    __syncwarp();
    cluster_arrive();
    if (!spare) {
      bar_sync(6, 128);
      asm volatile("setmaxnreg.inc.sync.aligned.u32 88;");
      const int pos = blockIdx.x * 4 + (lane & 1) * 2, col = (blockIdx.x >> 2) * 16 + (blockIdx.x & 3) * 2 + (lane & 1) * 8, src = threadIdx.x >> 1;
      uint32_t gbest = 0, hh = 0, gbf = 0;
      uint2 xx = make_uint2(0, 0);
      uint4 ya = make_uint4(0, 0, 0, 0), yb = make_uint4(0, tag, 0, tag);
      auto poll_y = [&]() {
        if (ya.y != tag || ya.w != tag) ya = ld_tagged2(&g_x.yll[src][pos]);
        if (yb.y != tag || yb.w != tag) yb = ld_tagged2(&g_x.yll[src + 64][pos]);
        return __all_sync(0xffffffff, ya.y == tag && ya.w == tag && yb.y == tag && yb.w == tag);
      };
      ya.y = tag - 1; if (src + 64 < FF / 16) yb.y = tag - 1;
      if (warp == 3) {
        gbf = __ldcg(reinterpret_cast<const uint32_t*>(g_x.mod + 5 * DM + col));
        uint32_t have = 0;
        uint2 k[4];
        #pragma unroll
        for (int i = 0; i < 4; i++) k[i] = make_uint2(0, tag - 1);
        #pragma unroll 1
        for (int n = 0; n < WAIT_LIM; n++) {
          #pragma unroll
          for (int i = 0; i < 4; i++) if (k[i].y != tag) k[i] = ld_tagged(&g_x.keys[i * 32 + lane][0]);
          if (gbest != have) {
            const int g = ((0xffffu - gbest) >> 4) & 127;
            uint4 hv[4];
            #pragma unroll
            for (int i = 0; i < 4; i++) hv[i] = ld_tagged2(&g_x.row[g][0][i * 64 + lane * 2]);
            xx = ld_tagged(&g_x.row[g][1][(col >> 8) * 128 + ((col >> 2) & 1) * 64 + ((col >> 3) & 31) * 2 + ((col >> 1) & 1)]);
            bool ok = xx.y == tag;
            #pragma unroll
            for (int i = 0; i < 4; i++) { ok = ok && hv[i].y == tag && hv[i].w == tag; reinterpret_cast<uint2*>(smem_raw + SM_H2)[(i >> 1) * 64 + lane * 2 + (i & 1)] = make_uint2(hv[i].x, hv[i].z); }
            if (lane == 0) *reinterpret_cast<uint32_t*>(smem_raw + SM_KEY + 32) = gbest;
            have = __all_sync(0xffffffff, ok) ? gbest : 0;
          }
          bool all = true;
          #pragma unroll
          for (int i = 0; i < 4; i++) { all = all && k[i].y == tag; gbest = max(gbest, k[i].y == tag ? k[i].x : 0u); }
          gbest = __reduce_max_sync(0xffffffff, gbest);
          if (__all_sync(0xffffffff, all) && gbest == have) break;
        }
        __syncwarp();
        w_arrive(bars + R_KEY);
        if (blockIdx.x == 0 && lane == 0) g_x.epoch = tag;
        hh = lds_u32(base + SM_H2 + col * 2);
      }
      const float rsel = rbf(__uint_as_float((((gbest & 0x80000000u) ? gbest & 0x7fffffffu : ~gbest) & 0xfffff000u) | 0x800u));
      const float rs = rbf(__fdividef(1.f, 1.f + __expf(-rsel)));
      bar_sync(9, 384);
      #pragma unroll 1
      for (int n = 0; n < WAIT_LIM; n++) { if (poll_y()) break; }
      float y0 = __uint_as_float(ya.x) + __uint_as_float(yb.x), y1 = __uint_as_float(ya.z) + __uint_as_float(yb.z);
      #pragma unroll
      for (int o = 2; o < 32; o <<= 1) { y0 += __shfl_xor_sync(0xffffffff, y0, o); y1 += __shfl_xor_sync(0xffffffff, y1, o); }
      float2* s_y = reinterpret_cast<float2*>(smem_raw + SM_KEY + 64);
      if (lane < 2) s_y[warp * 2 + lane] = make_float2(y0, y1);
      bar_sync(6, 128);
      if (warp == 3 && lane < 2) {
        y0 = 0.f; y1 = 0.f;
        #pragma unroll
        for (int i = 0; i < 4; i++) { y0 += reinterpret_cast<const float*>(s_y)[i * 4 + lane]; y1 += reinterpret_cast<const float*>(s_y)[i * 4 + 2 + lane]; }
        const float o0 = bf_lo(xx.x) + rbf(bf_lo(gbf) * rbf(bf_lo(hh) + rbf(rbf(y0) * rs)));
        const float o1 = bf_hi(xx.x) + rbf(bf_hi(gbf) * rbf(bf_hi(hh) + rbf(rbf(y1) * rs)));
        *reinterpret_cast<uint32_t*>(out + (size_t)((0xffffu - gbest) & (SEQ - 1)) * DM + col) = pack_bf16(o0, o1);
      }
    }
    __syncwarp();
    cluster_wait();
  } else {
    asm volatile("setmaxnreg.inc.sync.aligned.u32 240;");
    Ctx x;
    x.w = wg - 1; x.base = base; x.bars = bars; x.nev = 0; x.sched = &sched;
    const int w = x.w, warp4 = warp & 3;
    x.rel = mapa(bars, (warp4 & 1) ^ 1);
    x.rel1 = (threadIdx.x & 127) == 32 || (threadIdx.x & 127) == 64;
    if (warp != 8 || spare) cluster_wait();
    if (w == 1 || spare) bar_sync(7 + w, 256);
    uint32_t PA[32], PB[32];
    int vtile = -1;
    if (spare) {
      mod_cta(x, cvec);
    } else {
      const int lane = wg_tid() & 31;
      Row xn[2];
      float acc0[64], acc1[64];
      int s = 2 * w, ph = w;
      #pragma unroll 1
      for (int u = w; u < 8; u += 2) {
        bar_sync(1 + w, 256);
        int ps = 0;
        #pragma unroll 1
        for (int kb = 0; kb < 8; kb++) {
          if (u < 2) mbar_wait(bars + B_AF + 8 * kb, 0);
          mbar_wait(bars + B_WF + 8 * s, ph);
          const uint32_t da = desc_lo(base + k_addrA(kb), 16), dw = desc_lo(base + k_addrW(s), 8192);
          wgmma_fence();
          kblock_n128<0>(acc0, da, dw, kb != 0);
          kblock_n128<512>(acc1, da, dw, kb != 0);
          wgmma_commit();
          if (kb == 7) bar_arrive(1 + (w ^ 1), 256);
          if (kb > 0) {
            wgmma_wait<1>();
            mbar_arrive_remote_if(x.rel + B_WE + 8 * ps, x.rel1);
            if (u == 7 && !(kb & 1)) {
              ring_release(x, kb == 2 ? 0 : kb - 3, false);
              if (kb > 2) ring_release(x, kb - 2, false);
            }
          }
          ps = s;
          if (++s == 6) { s = 0; ph ^= 1; }
        }
        Row t[2];
        const int lrow = blockIdx.x * 16 + w * 8 + warp4 * 2;
        if (u == w) { t[0] = ldg_row(xin + (size_t)lrow * DM, lane); t[1] = ldg_row(xin + (size_t)(lrow + 1) * DM, lane); }
        if (u == LN_AT || u == LN_AT + 1) {
          mbar_wait(bars + R_MOD, 0);
          t[0] = ldca_row(g_x.mod, lane); t[1] = ldca_row(g_x.mod + DM, lane);
        }
        wgmma_wait<0>();
        fence_regs(acc0); fence_regs(acc1);
        mbar_arrive_remote_if(x.rel + B_WE + 8 * ps, x.rel1);
        if (u == 6) { for (int k = 0; k < 5; k++) ring_release(x, k, false); }
        if (u >= 6) ring_release(x, 5, false);
        if (u == 7) {
          pack_tile(acc0, PA, 1.f, 1.f); pack_tile(acc1, PB, 1.f, 1.f);
          vtile = sp.khead[3] * 16 + mt;
          break;
        }
        s += 2; ph ^= 1; if (s >= 6) { s -= 6; ph ^= 1; }
        if (u == 0) bar_sync(7, 256);
        if (u == w) {
          float st[4] = {0.f, 0.f, 0.f, 0.f};
          #pragma unroll
          for (int i = 0; i < 32; i++) { const float v = row_at(t[i >> 4], i & 15); st[(i >> 4) * 2] += v; st[(i >> 4) * 2 + 1] = fmaf(v, v, st[(i >> 4) * 2 + 1]); }
          warp_sums(st);
          #pragma unroll
          for (int r = 0; r < 2; r++) { ln_stats(st[2*r], st[2*r+1]); xn[r] = ln_apply(t[r], st[2*r], st[2*r+1] * QSCALE); }
        }
        if ((u == LN_AT || u == LN_AT + 1)) {
          #pragma unroll
          for (int r = 0; r < 2; r++) {
            const Row hr = fma_row(xn[r], one_plus(t[1]), t[0]);
            __nv_bfloat16* hp = sched.h1 + (lrow & ~63) * DM + (lane >> 3) * 4096 + ((lrow + r) & 63) * 64 + (((lane ^ (lrow + r)) & 7) << 3);
            stg_v4(hp, hr.v[0], hr.v[1], hr.v[2], hr.v[3]); stg_v4(hp + 4 * 4096, hr.v[4], hr.v[5], hr.v[6], hr.v[7]);
          }
        }
        const int tile = sp.khead[u >> 1] * 16 + mt;
        __nv_bfloat16* dst = kv_tile(x, tile);
        uint32_t D[32];
        pack_tile(acc0, D, 1.f, 1.f); store_tile(dst + 2048, D);
        pack_tile(acc1, D, 1.f, 1.f); store_tile(dst, D);
        if (u == LN_AT || u == LN_AT + 1) publish(x, C_H1);
        publish(x, C_KV + (tile >> 4));
      }
    }
    const int last = attention(x, sp.item, nitems, rank, PA, PB, vtile);
    const int lane = wg_tid() & 31, cw = w * 4 + warp4;
    const int row0 = grp * 16 + cw * 2;
    const bool moe_cta = blockIdx.x < FF / 16;
    if (spare) { store_ctx(x, last, PB); __syncwarp(); cluster_arrive(); cluster_wait(); return; }
    const int kl = 3 * nsteps - 3;
    uint2* const yp = &g_x.yll[blockIdx.x][cw * 64 + (lane & 3) * 16 + (lane >> 2) * 2];
    Row ga, sb, cb, gb, wr;
    unsigned int tag;
    {
      float accA[64], accB[64];
      const int t0 = oent(0) == oent(1);
      uint32_t pa = 0, pb = 0;
      #pragma unroll 1
      for (int t = t0; t < 2 * nsteps - 2; t++) {
        const uint32_t eb = oent(3 * (t >> 1) + 2 * (t & 1)), ea = oent(3 * (t >> 1) + 1);
        o_wait_full(bars, eb);
        o_wait_full(bars, ea);
        const uint32_t da = desc_lo(base + w * 4096, 16) + (ea & 7) * 2048 + (t & 1) * 1024, db = desc_lo(base, 8192) + (eb & 7) * 2048;
        wgmma_fence();
        kblock_n128<0, 0, SW64>(accA, da, db, t != t0); kblock_n128<0, 1024, SW64>(accB, da, db, t != t0);
        wgmma_commit();
        if (t == CTX_T) store_ctx(x, last, PB);
        if (t > t0) { wgmma_wait<1>(); slot_release(x, pb, false); if (!(t & 1)) slot_release(x, pa, false); }
        pa = ea & 7; pb = eb & 7;
      }
      const uint32_t e0 = oent(kl), ea = oent(kl + 1), eb = oent(kl + 2);
      const uint32_t da = desc_lo(base + w * 4096, 16) + (ea & 7) * 2048;
      const uint32_t db0 = desc_lo(base, 8192) + (e0 & 7) * 2048, db1 = desc_lo(base, 8192) + (eb & 7) * 2048;
      ga = ldca_row(g_x.mod + 2 * DM, lane); sb = ldca_row(g_x.mod + 3 * DM, lane); cb = ldca_row(g_x.mod + 4 * DM, lane); gb = ldca_row(g_x.mod + 5 * DM, lane);
      wr = ldca_row(w_r, lane);
      tag = lds_u32(base + SM_KEY + 48);
      if (moe_cta) st_tagged2(yp, 0, 0, 0);
      o_wait_full(bars, e0);
      o_wait_full(bars, ea);
      o_wait_full(bars, eb);
      wgmma_fence();
      kblock_n128<0, 0, SW64>(accA, da, db0, 1); kblock_n128<1024, 0, SW64>(accA, da, db1, 1);
      wgmma_commit();
      kblock_n128<0, 1024, SW64>(accB, da, db0, 1); kblock_n128<1024, 1024, SW64>(accB, da, db1, 1);
      wgmma_commit();
      __syncwarp();
      cluster_arrive();
      __nv_bfloat16* dst = sched.part + ((m * 8 + cw) * 8 + (ot >> 3)) * 4096;
      const uint32_t even = ~lane & 1;
      auto send = [&](const float (&acc)[64], int h) {
        uint32_t D[32];
        pack_tile(acc, D, 1.f, 1.f);
        #pragma unroll
        for (int i = 0; i < 8; i++) stg_v4(dst + (h * 8 + i) * 256 + ((lane ^ (h * 4 + (i >> 1))) << 3), (D[4*i] & ~even) | (tag & even), D[4*i+1], D[4*i+2], D[4*i+3]);
      };
      wgmma_wait<1>();
      fence_regs(accA);
      send(accA, 0);
      o_wait_full(bars, eb);
      wgmma_wait<0>();
      fence_regs(accB);
      send(accB, 1);
      __syncwarp();
      if (lane == 0) red_relaxed(&g_x.sent[m * 8 + cw][ot >> 3]);
      publish(x, 0);
    }
    asm volatile("setmaxnreg.dec.sync.aligned.u32 208;");
    const uint32_t sD = base + (oent(kl + 3) & 7) * 32768, sW = base + (oent(kl + 4) & 7) * 32768;
    o_wait_full(bars, oent(kl + 3)); o_wait_full(bars, oent(kl + 4));
    Row x1[2];
    #pragma unroll
    for (int r = 0; r < 2; r++) x1[r] = lds_row(sD + 16384 + (cw * 2 + r) * 1024, lane);
    uint4 wgv[4], wuv[4], wdv[4];
    #pragma unroll
    for (int r = 0; r < 4; r++) {
      const uint32_t k = (lane & 7) + ((lane >> 4) << 3), h = (lane >> 3) & 1;
      wgv[r] = ldsm_x4_t(sW + (cw * 64 + r * 16 + k) * 32 + ((h ^ ((lane >> 2) & 1)) << 4));
      wuv[r] = ldsm_x4_t(sW + 16384 + (cw * 64 + r * 16 + k) * 32 + ((h ^ ((lane >> 2) & 1)) << 4));
      wdv[r] = ldsm_x4_t(sD + cw * 2048 + k * 128 + (((r * 2 + h) ^ (lane & 7)) << 4));
    }
    const Row cb1 = one_plus(cb);
    float u[16], ub[2] = {0.f, 0.f};
    #pragma unroll
    for (int i = 0; i < 16; i++) { u[i] = row_at(cb1, i) * row_at(wr, i); ub[0] += u[i]; ub[1] = fmaf(row_at(sb, i), row_at(wr, i), ub[1]); }
    warp_sums(ub);
    float st[6] = {0.f, 0.f, 0.f, 0.f, 0.f, 0.f};
    uint32_t key[2];
    {
      const uint32_t po = base + ((lane & 7) * 2 + (cw >> 2)) * 512 + (cw & 3) * 128;
      const uint32_t par = (lane & 3) == 0 ? tag & 1 : 0;
      Row av[2][2];
      #pragma unroll 1
      for (int n = 0; n < WAIT_LIM; n++) {
        uint32_t late = 0;
        #pragma unroll
        for (int k = 0; k < 4; k++) {
          mbar_wait(bars + R_PART + 8 * k, 1);
          late = (late & 7) * 2;
          uint32_t odd = 0;
          const uint32_t pa = po + (oent(kl + (k >> 1)) & 7) * 32768 + (k & 1) * 16384;
          #pragma unroll
          for (int r = 0; r < 2; r++) {
            const uint32_t sw = ((r * 4 + (lane >> 3)) ^ (lane & 7)) << 4;
            const uint4 lo = ldsm_x4(pa + sw), hi = ldsm_x4(pa + 8192 + sw);
            const Row v{{lo.x ^ par, lo.y, lo.z ^ par, lo.w, hi.x ^ par, hi.y, hi.z ^ par, hi.w}};
            odd |= v.v[0] | v.v[2] | v.v[4] | v.v[6];
            av[r][k >> 1] = (k & 1) ? add_row(av[r][k >> 1], v) : v;
          }
          late |= odd & 1;
        }
        late = __reduce_or_sync(0xffffffff, (lane & 3) == 0 ? late : 0);
        if (!late) break;
        #pragma unroll 1
        for (; late; late &= late - 1) {
          const int k = 4 - __ffs(late);
          const uint32_t off = (k & 1) * 16384 + ((lane >> 3) * 2 + (cw >> 2)) * 512 + (cw & 3) * 128 + (lane & 7) * 16;
          uint4 v[4];
          #pragma unroll
          for (int i = 0; i < 4; i++) v[i] = ld_tagged2(reinterpret_cast<const uint8_t*>(sched.part + (grp * 8 + (k >> 1) * 4) * 4096) + off + i * 4096);
          #pragma unroll
          for (int i = 0; i < 4; i++) sts_v4(base + (oent(kl + (k >> 1)) & 7) * 32768 + off + i * 4096, v[i].x, v[i].y, v[i].z, v[i].w);
        }
        __syncwarp();
      }
      #pragma unroll
      for (int r = 0; r < 2; r++) {
        x1[r] = fma_row(ga, add_row(av[r][0], av[r][1]), x1[r]);
        #pragma unroll
        for (int i = 0; i < 16; i++) { const float v = row_at(x1[r], i); st[3*r] += v; st[3*r+1] = fmaf(v, v, st[3*r+1]); st[3*r+2] = fmaf(v, u[i], st[3*r+2]); }
      }
      warp_sums(st);
      #pragma unroll
      for (int r = 0; r < 2; r++) {
        ln_stats(st[3*r], st[3*r+1]);
        const uint32_t rb = __float_as_uint(fmaf(st[3*r+1], fmaf(-st[3*r], ub[0], st[3*r+2]), ub[1]));
        key[r] = (((rb & 0x80000000u) ? ~rb : (rb | 0x80000000u)) & 0xfffff000u) | (0xfffu - (uint32_t)(row0 + r));
      }
    }
    float* s_red = reinterpret_cast<float*>(smem_raw + SM_RED);
    uint32_t* s_key = reinterpret_cast<uint32_t*>(smem_raw + SM_KEY);
    const int rb = key[1] > key[0];
    const uint32_t wbest = rb ? key[1] : key[0];
    if (lane == 0) s_key[cw] = wbest;
    bar_sync(5, 256);
    const uint32_t cbest = __reduce_max_sync(0xffffffff, s_key[lane & 7]);
    if (wbest == cbest && lane == 0) st_tagged(&g_x.keys[grp][0], cbest, tag);
    Row xb, xo;
    #pragma unroll
    for (int i = 0; i < 8; i++) { xb.v[i] = rb ? x1[1].v[i] : x1[0].v[i]; xo.v[i] = rb ? x1[0].v[i] : x1[1].v[i]; }
    const Row hb = fma_row(ln_apply(xb, rb ? st[3] : st[0], rb ? st[4] : st[1]), cb1, sb);
    if (wbest == cbest) {
      #pragma unroll
      for (int i = 0; i < 4; i++) st_tagged2(&g_x.row[grp][0][i * 64 + lane * 2], hb.v[2*i], hb.v[2*i+1], tag);
      #pragma unroll
      for (int i = 0; i < 4; i++) st_tagged2(&g_x.row[grp][1][i * 64 + lane * 2], xb.v[2*i], xb.v[2*i+1], tag);
    }
    const Row ob = fma_row(gb, hb, xb);
    if (wbest != cbest) store_row(out + (size_t)(row0 + rb) * DM, lane, ob);
    store_row(out + (size_t)(row0 + 1 - rb) * DM, lane, fma_row(gb, fma_row(ln_apply(xo, rb ? st[0] : st[3], rb ? st[1] : st[4]), cb1, sb), xo));
    mbar_wait(bars + R_KEY, 1);
    if (moe_cta) {
      float cg[4] = {0, 0, 0, 0}, cu[4] = {0, 0, 0, 0};
      #pragma unroll
      for (int r = 0; r < 4; r++) {
        const uint32_t b0 = lds_u32(base + SM_H2 + (cw * 64 + r * 16) * 2 + (lane & 3) * 4), b1 = lds_u32(base + SM_H2 + (cw * 64 + r * 16) * 2 + 16 + (lane & 3) * 4);
        mma16816(cg, wgv[r], b0, b1); mma16816(cu, wuv[r], b0, b1);
      }
      s_red[cw * 32 + (lane & 3) * 8 + (lane >> 2)] = (lane & 2) ? ((lane & 1) ? cu[2] : cu[0]) : ((lane & 1) ? cg[2] : cg[0]);
      bar_sync(5, 256);
      float g = 0.f;
      #pragma unroll
      for (int i = 0; i < 8; i++) g += s_red[i * 32 + lane];
      g = rbf(g);
      const float act = rbf(__fdividef(g, 1.f + __expf(-g))) * __shfl_down_sync(0xffffffff, g, 16);
      const uint32_t a2 = pack_bf16(act, __shfl_down_sync(0xffffffff, act, 1));
      const uint32_t b0 = __shfl_sync(0xffffffff, a2, (lane & 3) * 2), b1 = __shfl_sync(0xffffffff, a2, (lane & 3) * 2 + 8);
      float y0 = 0.f, y1 = 0.f;
      #pragma unroll
      for (int r = 0; r < 4; r++) {
        float c[4] = {0, 0, 0, 0};
        mma16816(c, wdv[r], b0, b1);
        if ((lane & 3) == r) { y0 = c[0]; y1 = c[2]; }
      }
      st_tagged2(yp, __float_as_uint(y0), __float_as_uint(y1), tag);
    }
    bar_arrive(9, 384);
    if (wbest == cbest && wbest != s_key[8]) store_row(out + (size_t)(row0 + rb) * DM, lane, ob);
    __syncwarp();
    cluster_wait();
  }
}

typedef CUresult (*EncodeFn)(CUtensorMap*, CUtensorMapDataType, cuuint32_t, void*, const cuuint64_t*, const cuuint64_t*, const cuuint32_t*,
                             const cuuint32_t*, CUtensorMapInterleave, CUtensorMapSwizzle, CUtensorMapL2promotion, CUtensorMapFloatOOBfill);

struct HostState {
  bool ready = false;
  EncodeFn encode = nullptr;
  CUtensorMap tmC, tmWq, tmWk, tmWv, tmWo, tmWg, tmWu, tmWd, tmWm;
  Sched sched;
};

void make_map(EncodeFn enc, CUtensorMap* m, const void* ptr, int rank, const cuuint64_t* dims, const cuuint64_t* strides, const cuuint32_t* box, bool wide = true) {
  const cuuint32_t es[3] = {1, 1, 1};
  enc(m, CU_TENSOR_MAP_DATA_TYPE_BFLOAT16, rank, const_cast<void*>(ptr), dims, strides, box, es, CU_TENSOR_MAP_INTERLEAVE_NONE,
      wide ? CU_TENSOR_MAP_SWIZZLE_128B : CU_TENSOR_MAP_SWIZZLE_32B, wide ? CU_TENSOR_MAP_L2_PROMOTION_L2_128B : CU_TENSOR_MAP_L2_PROMOTION_NONE, CU_TENSOR_MAP_FLOAT_OOB_FILL_NONE);
}
void make_2d(EncodeFn enc, CUtensorMap* m, const void* ptr, int rows, int cols, int box_rows) {
  const cuuint64_t dims[2] = {(cuuint64_t)cols, (cuuint64_t)rows}, strides[1] = {(cuuint64_t)cols * 2};
  const cuuint32_t box[2] = {64, (cuuint32_t)box_rows};
  make_map(enc, m, ptr, 2, dims, strides, box);
}
void make_3d(EncodeFn enc, CUtensorMap* m, const void* ptr, int rows, int chunks, size_t row_stride, size_t chunk_stride, int box_rows = 64, int box_chunks = 2) {
  const cuuint64_t dims[3] = {64, (cuuint64_t)rows, (cuuint64_t)chunks}, strides[2] = {row_stride, chunk_stride};
  const cuuint32_t box[3] = {64, (cuuint32_t)box_rows, (cuuint32_t)box_chunks};
  make_map(enc, m, ptr, 3, dims, strides, box);
}

void make_ffn(EncodeFn enc, CUtensorMap* m, const void* ptr) {
  const cuuint64_t dims[2] = {(cuuint64_t)FF, (cuuint64_t)DM}, strides[1] = {(cuuint64_t)FF * 2};
  const cuuint32_t box[2] = {16, 256};
  make_map(enc, m, ptr, 2, dims, strides, box, false);
}

#define SR 0x213312
#define SEED 12345
#define SPARE_N 3
void build_sched(Sched& s) {
  memset(&s, 0, sizeof(s));
  const int NP = NCTA / 2, korder[4] = {(KORDER >> 12) & 3, (KORDER >> 8) & 3, (KORDER >> 4) & 3, KORDER & 3};
  const int sround[4][2][3] = {{}, {{1}, {2}}, {{1, 2}, {1, 2}}, {{(SR >> 20) & 3, (SR >> 16) & 3, (SR >> 12) & 3}, {(SR >> 8) & 3, (SR >> 4) & 3, SR & 3}}};
  int jv[4][NP], used[4][8] = {};
  for (int r = 0; r < 4; r++) for (int p = 0; p < NP; p++) jv[r][p] = (r & 2) ? 7 - ((p + 4 * (r & 1)) & 7) : (p + 4 * (r & 1)) & 7;
  for (int q = 0; q < 2; q++) {
    s.pair[NP + q].nitems = SPARE_N;
    for (int i = 0; i < SPARE_N; i++) {
      const int r = sround[SPARE_N][q][i];
      s.pair[NP + q].item[i] = (uint8_t)((r * 8 + used[r][6]++) * 8 + 6);
      for (int p = 0; p < NP; p++) if (jv[r][p] == 6) { jv[r][p] = -2; break; }
    }
  }
  auto cost = [&](int p) {
    int u = 8 - ((p >> 4) < SPARE_N ? 21 : 22), z = 0, none = 0;
    for (int r = 0; r < 4; r++) { u += jv[r][p]; z += jv[r][p] == 0; none += jv[r][p] < 0; }
    return 4 * u * u + (z > 1) + 4 * (none > 1);
  };
  uint32_t rng = SEED;
  for (int it = 0; it < 2000000; it++) {
    if ((it & 255) == 0) { int t = 0; for (int p = 0; p < NP; p++) t += cost(p); if (t == 0) break; }
    rng = rng * 1664525u + 1013904223u;
    const int r = (rng >> 8) & 3, a = (rng >> 12) & 63, b = (rng >> 20) & 63, before = cost(a) + cost(b);
    int t = jv[r][a]; jv[r][a] = jv[r][b]; jv[r][b] = t;
    if (cost(a) + cost(b) > before) { jv[r][b] = jv[r][a]; jv[r][a] = t; }
  }
  int done[256];
  for (int p = 0; p < NP + 2; p++) {
    Sched::Pair& q = s.pair[p];
    if (p < NP) {
      for (int k = 0; k < 4; k++) q.khead[k] = (uint8_t)(korder[k] * 8 + (p >> 3));
      for (int r = 0; r < 4; r++) {
        if (jv[r][p] < 0) continue;
        q.item[q.nitems++] = (uint8_t)((r * 8 + used[r][jv[r][p]]++) * 8 + jv[r][p]);
      }
    }
    int t = p < NP ? 0 : -3, e = 1;
    for (int i = 0; i < q.nitems; i++) { t += (q.item[i] & 7) + 2; done[q.item[i]] = t + (i + 1 < q.nitems ? 2 : 0); e += 8 + 4 * ((q.item[i] & 7) + 1); }
    for (int k = 0; k < 3 * MAX_STEPS + 6; k++) {
      const int n = k > 0 ? k - (SPARE_N & 1) : 0, r = n % 7, f = (e + (r < 4 ? r : r - 1)) % 12;
      q.oent[k] = (uint8_t)((r == 4 ? 6 : f >= 6 ? f + 2 : f) ^ (((n / 7) & 1) << 3));
    }
  }
  for (int j = 0; j < 8; j++) {
    int order[NH], left[4];
    for (int h = 0; h < NH; h++) { int k = h; for (; k > 0 && done[order[k - 1] * 8 + j] < done[h * 8 + j]; k--) order[k] = order[k - 1]; order[k] = h; }
    for (int kq = 0; kq < 4; kq++) {
      left[kq] = SPARE_N == 0 ? 16 : kq < SPARE_N ? 20 - SPARE_N : 16 - SPARE_N;
      for (int nh = 0; nh < 2; nh++) { Sched::Pair& q = s.pair[kq * 16 + nh * 8 + j]; q.otask = (uint8_t)(kq * 16 + nh * 8 + j); q.nsteps = (uint8_t)((left[kq] + 1) / 2); q.ochunk[0][0] = 255; }
    }
    for (int n = 0, kq = 0, run = 0; n < 64; ) {
      if (left[kq] > 0 && run < 2) {
        const int pos = --left[kq] + (SPARE_N & 1);
        for (int nh = 0; nh < 2; nh++) s.pair[kq * 16 + nh * 8 + j].ochunk[pos >> 1][pos & 1] = (uint8_t)(order[n >> 1] * 2 + 1 - (n & 1));
        n++; run++;
      } else { kq = (kq + 1) & 3; run = 0; }
    }
  }
}

}

extern "C" void kernel_launch(void* const* d_in, const int* in_sizes, int n_in, void* d_out, int out_size) {
  (void)in_sizes; (void)n_in; (void)out_size;
  const __nv_bfloat16* x     = (const __nv_bfloat16*)d_in[0];
  const __nv_bfloat16* ckv   = (const __nv_bfloat16*)d_in[1];
  const __nv_bfloat16* w_q   = (const __nv_bfloat16*)d_in[2];
  const __nv_bfloat16* w_uk  = (const __nv_bfloat16*)d_in[3];
  const __nv_bfloat16* w_uv  = (const __nv_bfloat16*)d_in[4];
  const __nv_bfloat16* w_o   = (const __nv_bfloat16*)d_in[5];
  const __nv_bfloat16* w_r   = (const __nv_bfloat16*)d_in[7];
  const __nv_bfloat16* w_g   = (const __nv_bfloat16*)d_in[8];
  const __nv_bfloat16* w_u   = (const __nv_bfloat16*)d_in[9];
  const __nv_bfloat16* w_d   = (const __nv_bfloat16*)d_in[10];
  const __nv_bfloat16* cvec  = (const __nv_bfloat16*)d_in[11];
  const __nv_bfloat16* w_mod = (const __nv_bfloat16*)d_in[12];
  __nv_bfloat16* out = (__nv_bfloat16*)d_out;

  static HostState st;
  if (!st.ready) {
    void* fn = nullptr; cudaDriverEntryPointQueryResult qr;
    cudaGetDriverEntryPoint("cuTensorMapEncodeTiled", &fn, cudaEnableDefault, &qr);
    st.encode = (EncodeFn)fn;
    cudaFuncSetAttribute(k_fused, cudaFuncAttributeMaxDynamicSharedMemorySize, SMEM);
    build_sched(st.sched);
    void *p_kvc, *p_h1, *p_part;
    cudaGetSymbolAddress(&p_kvc, g_kvc); cudaGetSymbolAddress(&p_h1, g_h1); cudaGetSymbolAddress(&p_part, g_part);
    st.sched.kvc = (__nv_bfloat16*)p_kvc; st.sched.h1 = (__nv_bfloat16*)p_h1; st.sched.part = (__nv_bfloat16*)p_part;
    st.ready = true;
  }
  make_2d(st.encode, &st.tmC, ckv, SEQ, DM, 128);
  make_2d(st.encode, &st.tmWq, w_q, DM, NH * DH, 64);
  make_2d(st.encode, &st.tmWk, w_uk, DM, NH * DH, 64);
  make_2d(st.encode, &st.tmWv, w_uv, DM, NH * DH, 64);
  make_3d(st.encode, &st.tmWo, w_o, NH * DH, DM / 64, (size_t)DM * 2, 128);
  make_3d(st.encode, &st.tmWm, w_mod, DM, 6 * DM / 64, (size_t)6 * DM * 2, 128);
  make_3d(st.encode, &st.tmWd, w_d, FF, DM / 64, (size_t)DM * 2, 128, 16, 8);
  make_ffn(st.encode, &st.tmWg, w_g);
  make_ffn(st.encode, &st.tmWu, w_u);

  k_fused<<<NGRID, 384, SMEM, cudaStreamPerThread>>>(st.tmC, st.tmWq, st.tmWk, st.tmWv, st.tmWo, st.tmWg, st.tmWu, st.tmWd, st.tmWm, st.sched,
                                                     x, cvec, w_o, w_r, w_g, w_u, w_d, out);
}
```

```cpp
#include <cuda_runtime.h>
#include <cuda_bf16.h>
#include <cuda.h>
#include <stdint.h>
#include <string.h>
#include <math.h>

namespace {

constexpr int SEQ = 2048, DM = 512, NH = 32, DH = 128, FF = 1792;
constexpr int NCTA = 128, NGRID = 132;

__device__ __align__(128) __nv_bfloat16 g_kvc[192 * SEQ * 64];
__device__ __align__(128) __nv_bfloat16 g_h1[SEQ * DM];
__device__ __align__(128) __nv_bfloat16 g_part[128 * 8 * 4096];
constexpr int C_MOD = 0, C_MOD2 = 16, C_H1 = 32, C_KV = 64, C_CTX = 128, C_END = 384;
struct Exchange {
  uint2 keys[128][4];
  uint2 row[128][2][DM / 2];
  uint2 yll[FF / 16][DM];
  __nv_bfloat16 mod[6 * DM];
  unsigned int sent[128][32];
  unsigned int cnt[C_END];
  unsigned int epoch;
};
__device__ __align__(4096) Exchange g_x;


__device__ __forceinline__ uint32_t smem_u32(const void* p) { return (uint32_t)__cvta_generic_to_shared(p); }
__device__ __forceinline__ int wg_tid() { int t; asm volatile("mov.u32 %0, %%tid.x;" : "=r"(t)); return t & 127; }
__device__ __forceinline__ void mbar_arrive(uint32_t bar) { asm volatile("mbarrier.arrive.shared::cta.b64 _, [%0];" :: "r"(bar) : "memory"); }
__device__ __forceinline__ uint32_t mapa(uint32_t addr, uint32_t cta) { uint32_t r; asm("mapa.shared::cluster.u32 %0, %1, %2;" : "=r"(r) : "r"(addr), "r"(cta)); return r; }
__device__ __forceinline__ void mbar_arrive_remote_if(uint32_t cluster_addr, bool pred) {
  asm volatile("{\n.reg .pred p;\nsetp.ne.u32 p, %1, 0;\n@p mbarrier.arrive.shared::cluster.b64 _, [%0];\n}" :: "r"(cluster_addr), "r"((uint32_t)pred) : "memory");
}
__device__ __forceinline__ bool mbar_try(uint32_t bar, uint32_t parity) {
  uint32_t done;
  asm volatile("{\n.reg .pred p;\nmbarrier.try_wait.parity.shared::cta.b64 p, [%1], %2;\nselp.u32 %0, 1, 0, p;\n}" : "=r"(done) : "r"(bar), "r"(parity) : "memory");
  return done;
}
__device__ __forceinline__ bool mbar_test2(uint32_t bar, uint32_t parity) {
  uint32_t done;
  asm volatile("{\n.reg .pred p, q;\nmbarrier.test_wait.parity.shared::cta.b64 p, [%1], %2;\nmbarrier.test_wait.parity.shared::cta.b64 q, [%1 + 8], %2;\n"
               "and.pred p, p, q;\nselp.u32 %0, 1, 0, p;\n}" : "=r"(done) : "r"(bar), "r"(parity) : "memory");
  return done;
}
#define WAIT_LIM (1 << 14)
__device__ __forceinline__ void mbar_wait(uint32_t bar, uint32_t parity) {
  #pragma unroll 1
  for (int n = 0; n < WAIT_LIM; n++) { if (mbar_try(bar, parity)) break; }
}
__device__ __forceinline__ unsigned int ld_acquire(const unsigned int* p) {
  unsigned int v; asm volatile("ld.acquire.gpu.global.u32 %0, [%1];" : "=r"(v) : "l"(p) : "memory"); return v;
}
__device__ __forceinline__ unsigned int ld_relaxed(const unsigned int* p) {
  unsigned int v; asm volatile("ld.relaxed.gpu.global.u32 %0, [%1];" : "=r"(v) : "l"(p) : "memory"); return v;
}
__device__ __forceinline__ void wait_count_lazy(int idx, unsigned int target) {
  #pragma unroll 1
  for (int n = 0; n < WAIT_LIM; n++) { if (__all_sync(0xffffffff, (int)(ld_acquire(&g_x.cnt[idx]) - target) >= 0)) break; __nanosleep(100); }
}
__device__ __forceinline__ uint4 ld_tagged2(const void* p) {
  uint4 v;
  asm volatile("{\n.reg .b64 a, b;\nld.relaxed.gpu.global.v2.u64 {a, b}, [%4];\nmov.b64 {%0, %1}, a;\nmov.b64 {%2, %3}, b;\n}"
    : "=r"(v.x), "=r"(v.y), "=r"(v.z), "=r"(v.w) : "l"(p) : "memory");
  return v;
}
__device__ __forceinline__ uint2 ld_tagged(const void* p) {
  uint2 v; asm volatile("{\n.reg .b64 a;\nld.relaxed.gpu.global.u64 a, [%2];\nmov.b64 {%0, %1}, a;\n}" : "=r"(v.x), "=r"(v.y) : "l"(p) : "memory"); return v;
}
__device__ __forceinline__ void st_tagged2(void* p, uint32_t a, uint32_t b, uint32_t tag) {
  asm volatile("{\n.reg .b64 a, b;\nmov.b64 a, {%1, %3};\nmov.b64 b, {%2, %3};\nst.relaxed.gpu.global.v2.u64 [%0], {a, b};\n}" :: "l"(p), "r"(a), "r"(b), "r"(tag) : "memory");
}
__device__ __forceinline__ void st_tagged(void* p, uint32_t a, uint32_t tag) {
  asm volatile("{\n.reg .b64 a;\nmov.b64 a, {%1, %2};\nst.relaxed.gpu.global.u64 [%0], a;\n}" :: "l"(p), "r"(a), "r"(tag) : "memory");
}
__device__ __forceinline__ void stg_v4(void* p, uint32_t a, uint32_t b, uint32_t c, uint32_t d) {
  asm volatile("st.global.v4.u32 [%0], {%1, %2, %3, %4};" :: "l"(p), "r"(a), "r"(b), "r"(c), "r"(d) : "memory");
}
__device__ __forceinline__ uint4 lds_v4(uint32_t addr) {
  uint4 v; asm volatile("ld.shared.v4.u32 {%0, %1, %2, %3}, [%4];" : "=r"(v.x), "=r"(v.y), "=r"(v.z), "=r"(v.w) : "r"(addr) : "memory"); return v;
}
__device__ __forceinline__ uint32_t lds_u32(uint32_t addr) { uint32_t v; asm volatile("ld.shared.u32 %0, [%1];" : "=r"(v) : "r"(addr) : "memory"); return v; }
__device__ __forceinline__ void sts_v4(uint32_t addr, uint32_t a, uint32_t b, uint32_t c, uint32_t d) {
  asm volatile("st.shared.v4.u32 [%0], {%1, %2, %3, %4};" :: "r"(addr), "r"(a), "r"(b), "r"(c), "r"(d) : "memory");
}
#define ELECT "{\n.reg .pred p;\nelect.sync _|p, 0xffffffff;\n@p "
__device__ __forceinline__ void w_mbar_init(uint32_t bar, uint32_t cnt) { asm volatile(ELECT "mbarrier.init.shared::cta.b64 [%0], %1;\n}" :: "r"(bar), "r"(cnt) : "memory"); }
__device__ __forceinline__ void w_expect_tx(uint32_t bar, uint32_t bytes) { asm volatile(ELECT "mbarrier.arrive.expect_tx.shared::cta.b64 _, [%0], %1;\n}" :: "r"(bar), "r"(bytes) : "memory"); }
__device__ __forceinline__ void w_arrive(uint32_t bar) { asm volatile(ELECT "mbarrier.arrive.shared::cta.b64 _, [%0];\n}" :: "r"(bar) : "memory"); }
__device__ __forceinline__ void tma_load_2d(uint32_t dst, const CUtensorMap* tm, uint32_t bar, int c0, int c1) {
  asm volatile(ELECT "cp.async.bulk.tensor.2d.shared::cluster.global.mbarrier::complete_tx::bytes [%0], [%1, {%3, %4}], [%2];\n}"
    :: "r"(dst), "l"(tm), "r"(bar), "r"(c0), "r"(c1) : "memory");
}
__device__ __forceinline__ void tma_load_2d_mc(uint32_t dst, const CUtensorMap* tm, uint32_t bar, int c0, int c1) {
  asm volatile(ELECT "cp.async.bulk.tensor.2d.shared::cluster.global.mbarrier::complete_tx::bytes.multicast::cluster [%0], [%1, {%3, %4}], [%2], %5;\n}"
    :: "r"(dst), "l"(tm), "r"(bar), "r"(c0), "r"(c1), "h"((uint16_t)3) : "memory");
}
__device__ __forceinline__ void tma_load_3d(uint32_t dst, const CUtensorMap* tm, uint32_t bar, int c0, int c1, int c2) {
  asm volatile(ELECT "cp.async.bulk.tensor.3d.shared::cluster.global.mbarrier::complete_tx::bytes [%0], [%1, {%3, %4, %5}], [%2];\n}"
    :: "r"(dst), "l"(tm), "r"(bar), "r"(c0), "r"(c1), "r"(c2) : "memory");
}
__device__ __forceinline__ void tma_load_3d_mc(uint32_t dst, const CUtensorMap* tm, uint32_t bar, int c0, int c1, int c2) {
  asm volatile(ELECT "cp.async.bulk.tensor.3d.shared::cluster.global.mbarrier::complete_tx::bytes.multicast::cluster [%0], [%1, {%3, %4, %5}], [%2], %6;\n}"
    :: "r"(dst), "l"(tm), "r"(bar), "r"(c0), "r"(c1), "r"(c2), "h"((uint16_t)3) : "memory");
}
__device__ __forceinline__ void bulk_load_mc(uint32_t dst, const void* src, uint32_t bar) {
  asm volatile(ELECT "cp.async.bulk.shared::cluster.global.mbarrier::complete_tx::bytes.multicast::cluster [%0], [%1], 16384, [%2], %3;\n}"
    :: "r"(dst), "l"(src), "r"(bar), "h"((uint16_t)3) : "memory");
}
__device__ __forceinline__ void bulk_load(uint32_t dst, const void* src, uint32_t bytes, uint32_t bar) {
  asm volatile(ELECT "cp.async.bulk.shared::cluster.global.mbarrier::complete_tx::bytes [%0], [%1], %2, [%3];\n}" :: "r"(dst), "l"(src), "r"(bytes), "r"(bar) : "memory");
}
__device__ __forceinline__ void tma_prefetch_2d(const CUtensorMap* tm, int c0, int c1) {
  asm volatile(ELECT "cp.async.bulk.prefetch.tensor.2d.L2.global [%0, {%1, %2}];\n}" :: "l"(tm), "r"(c0), "r"(c1) : "memory");
}
__device__ __forceinline__ void bulk_prefetch(const void* p, uint32_t bytes) {
  asm volatile(ELECT "cp.async.bulk.prefetch.L2.global [%0], %1;\n}" :: "l"(p), "r"(bytes) : "memory");
}
__device__ __forceinline__ void red_relaxed(unsigned int* p) { asm volatile("red.relaxed.gpu.global.add.u32 [%0], 1;" :: "l"(p) : "memory"); }
__device__ __forceinline__ void red_release(int idx) { asm volatile("red.release.gpu.global.add.u32 [%0], 1;" :: "l"(&g_x.cnt[idx]) : "memory"); }
__device__ __forceinline__ void prefetch_tmap(const CUtensorMap* tm) { asm volatile("prefetch.tensormap [%0];" :: "l"(tm) : "memory"); }
__device__ __forceinline__ void bar_sync(int id, int n) { asm volatile("bar.sync %0, %1;" :: "r"(id), "r"(n) : "memory"); }
__device__ __forceinline__ void bar_arrive(int id, int n) { asm volatile("bar.arrive %0, %1;" :: "r"(id), "r"(n) : "memory"); }
__device__ __forceinline__ void fence_async_smem() { asm volatile("fence.proxy.async.shared::cta;" ::: "memory"); }
__device__ __forceinline__ void fence_async_global() { asm volatile("fence.proxy.async.global;" ::: "memory"); }
__device__ __forceinline__ void fence_mbar_init() { asm volatile("fence.mbarrier_init.release.cluster;" ::: "memory"); }
__device__ __forceinline__ void cluster_arrive() { asm volatile("barrier.cluster.arrive.relaxed.aligned;" ::: "memory"); }
__device__ __forceinline__ void cluster_wait() { asm volatile("barrier.cluster.wait.aligned;" ::: "memory"); }
__device__ __forceinline__ uint32_t cluster_ctarank() { uint32_t r; asm volatile("mov.u32 %0, %%cluster_ctarank;" : "=r"(r)); return r; }
__device__ __forceinline__ void wgmma_fence() { asm volatile("wgmma.fence.sync.aligned;" ::: "memory"); }
__device__ __forceinline__ void wgmma_commit() { asm volatile("wgmma.commit_group.sync.aligned;" ::: "memory"); }
template<int N> __device__ __forceinline__ void wgmma_wait() { asm volatile("wgmma.wait_group.sync.aligned %0;" :: "n"(N) : "memory"); }
__device__ __forceinline__ float ex2(float x) { float y; asm("ex2.approx.ftz.f32 %0, %1;" : "=f"(y) : "f"(x)); return y; }
__device__ __forceinline__ float rcp_fast(float x) { float y; asm("rcp.approx.ftz.f32 %0, %1;" : "=f"(y) : "f"(x)); return y; }
__device__ __forceinline__ uint32_t pack_bf16(float lo, float hi) { uint32_t r; asm("cvt.rn.bf16x2.f32 %0, %1, %2;" : "=r"(r) : "f"(hi), "f"(lo)); return r; }
__device__ __forceinline__ float rbf(float x) { return __uint_as_float(pack_bf16(0.f, x)); }
__device__ __forceinline__ float bf_lo(uint32_t v) { return __uint_as_float(v << 16); }
__device__ __forceinline__ float bf_hi(uint32_t v) { return __uint_as_float(v & 0xffff0000u); }
__device__ __forceinline__ uint32_t add2(uint32_t a, uint32_t b) { uint32_t r; asm("add.rn.bf16x2 %0, %1, %2;" : "=r"(r) : "r"(a), "r"(b)); return r; }
__device__ __forceinline__ uint32_t fma2(uint32_t a, uint32_t b, uint32_t c) { uint32_t r; asm("fma.rn.bf16x2 %0, %1, %2, %3;" : "=r"(r) : "r"(a), "r"(b), "r"(c)); return r; }
__device__ __forceinline__ uint4 ldsm_x4_t(uint32_t addr) {
  uint4 v; asm volatile("ldmatrix.sync.aligned.m8n8.x4.trans.shared.b16 {%0, %1, %2, %3}, [%4];" : "=r"(v.x), "=r"(v.y), "=r"(v.z), "=r"(v.w) : "r"(addr) : "memory"); return v;
}
__device__ __forceinline__ uint4 ldsm_x4(uint32_t addr) {
  uint4 v; asm volatile("ldmatrix.sync.aligned.m8n8.x4.shared.b16 {%0, %1, %2, %3}, [%4];" : "=r"(v.x), "=r"(v.y), "=r"(v.z), "=r"(v.w) : "r"(addr) : "memory"); return v;
}
__device__ __forceinline__ void mma16816(float (&c)[4], const uint4& a, uint32_t b0, uint32_t b1) {
  asm("mma.sync.aligned.m16n8k16.row.col.f32.bf16.bf16.f32 {%0, %1, %2, %3}, {%4, %5, %6, %7}, {%8, %9}, {%0, %1, %2, %3};"
    : "+f"(c[0]), "+f"(c[1]), "+f"(c[2]), "+f"(c[3]) : "r"(a.x), "r"(a.y), "r"(a.z), "r"(a.w), "r"(b0), "r"(b1));
}
template<int N> __device__ __forceinline__ void fence_regs(float (&a)[N]) {
  #pragma unroll
  for (int i = 0; i < N; i++) asm volatile("" : "+f"(a[i]) :: "memory");
}
template<int N> __device__ __forceinline__ void fence_regs_u(uint32_t (&a)[N]) {
  #pragma unroll
  for (int i = 0; i < N; i++) asm volatile("" : "+r"(a[i]) :: "memory");
}
constexpr uint32_t SW128 = 0x40000040u, SW64 = 0x80000020u;
__device__ __forceinline__ uint32_t desc_lo(uint32_t addr, uint32_t lbo) { return ((addr & 0x3FFFF) >> 4) | ((lbo >> 4) << 16); }

template<int TB, int OA, int OB, uint32_t HA, uint32_t HB> __device__ __forceinline__ void wgmma_ss_n128(float (&d)[64], uint32_t da, uint32_t db, int sd) {
  asm volatile("{\n.reg .pred p;\n.reg .b32 ta, tb;\n.reg .b64 da, db;\nsetp.ne.b32 p, %66, 0;\nadd.u32 ta, %64, %68;\nadd.u32 tb, %65, %69;\nmov.b64 da, {ta, %70};\nmov.b64 db, {tb, %71};\n"
    "wgmma.mma_async.sync.aligned.m64n128k16.f32.bf16.bf16 "
    "{%0, %1, %2, %3, %4, %5, %6, %7, %8, %9, %10, %11, %12, %13, %14, %15, %16, %17, %18, %19, %20, %21, %22, %23, %24, %25, %26, %27, %28, %29, %30, %31, %32, %33, %34, %35, %36, %37, %38, %39, %40, %41, %42, %43, %44, %45, %46, %47, %48, %49, %50, %51, %52, %53, %54, %55, %56, %57, %58, %59, %60, %61, %62, %63}, da, db, p, 1, 1, 0, %67;\n}\n"
    : "+f"(d[0]), "+f"(d[1]), "+f"(d[2]), "+f"(d[3]), "+f"(d[4]), "+f"(d[5]), "+f"(d[6]), "+f"(d[7]), "+f"(d[8]), "+f"(d[9]), "+f"(d[10]), "+f"(d[11]), "+f"(d[12]), "+f"(d[13]), "+f"(d[14]), "+f"(d[15]), "+f"(d[16]), "+f"(d[17]), "+f"(d[18]), "+f"(d[19]), "+f"(d[20]), "+f"(d[21]), "+f"(d[22]), "+f"(d[23]), "+f"(d[24]), "+f"(d[25]), "+f"(d[26]), "+f"(d[27]), "+f"(d[28]), "+f"(d[29]), "+f"(d[30]), "+f"(d[31]), "+f"(d[32]), "+f"(d[33]), "+f"(d[34]), "+f"(d[35]), "+f"(d[36]), "+f"(d[37]), "+f"(d[38]), "+f"(d[39]), "+f"(d[40]), "+f"(d[41]), "+f"(d[42]), "+f"(d[43]), "+f"(d[44]), "+f"(d[45]), "+f"(d[46]), "+f"(d[47]), "+f"(d[48]), "+f"(d[49]), "+f"(d[50]), "+f"(d[51]), "+f"(d[52]), "+f"(d[53]), "+f"(d[54]), "+f"(d[55]), "+f"(d[56]), "+f"(d[57]), "+f"(d[58]), "+f"(d[59]), "+f"(d[60]), "+f"(d[61]), "+f"(d[62]), "+f"(d[63])
    : "r"(da), "r"(db), "r"(sd), "n"(TB), "n"(OA), "n"(OB), "n"(HA), "n"(HB));
}
template<int TB, int OB, uint32_t HB> __device__ __forceinline__ void wgmma_rs_n128(float (&d)[64], uint32_t a0, uint32_t a1, uint32_t a2, uint32_t a3, uint32_t db, int sd) {
  asm volatile("{\n.reg .pred p;\n.reg .b32 tb;\n.reg .b64 db;\nsetp.ne.b32 p, %69, 0;\nadd.u32 tb, %68, %71;\nmov.b64 db, {tb, %72};\n"
    "wgmma.mma_async.sync.aligned.m64n128k16.f32.bf16.bf16 "
    "{%0, %1, %2, %3, %4, %5, %6, %7, %8, %9, %10, %11, %12, %13, %14, %15, %16, %17, %18, %19, %20, %21, %22, %23, %24, %25, %26, %27, %28, %29, %30, %31, %32, %33, %34, %35, %36, %37, %38, %39, %40, %41, %42, %43, %44, %45, %46, %47, %48, %49, %50, %51, %52, %53, %54, %55, %56, %57, %58, %59, %60, %61, %62, %63}, {%64,%65,%66,%67}, db, p, 1, 1, %70;\n}\n"
    : "+f"(d[0]), "+f"(d[1]), "+f"(d[2]), "+f"(d[3]), "+f"(d[4]), "+f"(d[5]), "+f"(d[6]), "+f"(d[7]), "+f"(d[8]), "+f"(d[9]), "+f"(d[10]), "+f"(d[11]), "+f"(d[12]), "+f"(d[13]), "+f"(d[14]), "+f"(d[15]), "+f"(d[16]), "+f"(d[17]), "+f"(d[18]), "+f"(d[19]), "+f"(d[20]), "+f"(d[21]), "+f"(d[22]), "+f"(d[23]), "+f"(d[24]), "+f"(d[25]), "+f"(d[26]), "+f"(d[27]), "+f"(d[28]), "+f"(d[29]), "+f"(d[30]), "+f"(d[31]), "+f"(d[32]), "+f"(d[33]), "+f"(d[34]), "+f"(d[35]), "+f"(d[36]), "+f"(d[37]), "+f"(d[38]), "+f"(d[39]), "+f"(d[40]), "+f"(d[41]), "+f"(d[42]), "+f"(d[43]), "+f"(d[44]), "+f"(d[45]), "+f"(d[46]), "+f"(d[47]), "+f"(d[48]), "+f"(d[49]), "+f"(d[50]), "+f"(d[51]), "+f"(d[52]), "+f"(d[53]), "+f"(d[54]), "+f"(d[55]), "+f"(d[56]), "+f"(d[57]), "+f"(d[58]), "+f"(d[59]), "+f"(d[60]), "+f"(d[61]), "+f"(d[62]), "+f"(d[63])
    : "r"(a0), "r"(a1), "r"(a2), "r"(a3), "r"(db), "r"(sd), "n"(TB), "n"(OB), "n"(HB));
}
template<int TB, int OA, int OB, uint32_t HA, uint32_t HB> __device__ __forceinline__ void wgmma_ss_n64(float (&d)[32], uint32_t da, uint32_t db, int sd) {
  asm volatile("{\n.reg .pred p;\n.reg .b32 ta, tb;\n.reg .b64 da, db;\nsetp.ne.b32 p, %34, 0;\nadd.u32 ta, %32, %36;\nadd.u32 tb, %33, %37;\nmov.b64 da, {ta, %38};\nmov.b64 db, {tb, %39};\n"
    "wgmma.mma_async.sync.aligned.m64n64k16.f32.bf16.bf16 "
    "{%0, %1, %2, %3, %4, %5, %6, %7, %8, %9, %10, %11, %12, %13, %14, %15, %16, %17, %18, %19, %20, %21, %22, %23, %24, %25, %26, %27, %28, %29, %30, %31}, da, db, p, 1, 1, 0, %35;\n}\n"
    : "+f"(d[0]), "+f"(d[1]), "+f"(d[2]), "+f"(d[3]), "+f"(d[4]), "+f"(d[5]), "+f"(d[6]), "+f"(d[7]), "+f"(d[8]), "+f"(d[9]), "+f"(d[10]), "+f"(d[11]), "+f"(d[12]), "+f"(d[13]), "+f"(d[14]), "+f"(d[15]), "+f"(d[16]), "+f"(d[17]), "+f"(d[18]), "+f"(d[19]), "+f"(d[20]), "+f"(d[21]), "+f"(d[22]), "+f"(d[23]), "+f"(d[24]), "+f"(d[25]), "+f"(d[26]), "+f"(d[27]), "+f"(d[28]), "+f"(d[29]), "+f"(d[30]), "+f"(d[31])
    : "r"(da), "r"(db), "r"(sd), "n"(TB), "n"(OA), "n"(OB), "n"(HA), "n"(HB));
}
template<int TB, int OA, int OB, uint32_t HA, uint32_t HB> __device__ __forceinline__ void wgmma_ss_n128_new(float (&d)[64], uint32_t da, uint32_t db) {
  asm volatile("{\n.reg .pred p;\n.reg .b32 ta, tb;\n.reg .b64 da, db;\nsetp.ne.b32 p, %66, 0;\nadd.u32 ta, %64, %68;\nadd.u32 tb, %65, %69;\nmov.b64 da, {ta, %70};\nmov.b64 db, {tb, %71};\n"
    "wgmma.mma_async.sync.aligned.m64n128k16.f32.bf16.bf16 "
    "{%0, %1, %2, %3, %4, %5, %6, %7, %8, %9, %10, %11, %12, %13, %14, %15, %16, %17, %18, %19, %20, %21, %22, %23, %24, %25, %26, %27, %28, %29, %30, %31, %32, %33, %34, %35, %36, %37, %38, %39, %40, %41, %42, %43, %44, %45, %46, %47, %48, %49, %50, %51, %52, %53, %54, %55, %56, %57, %58, %59, %60, %61, %62, %63}, da, db, p, 1, 1, 0, %67;\n}\n"
    : "=f"(d[0]), "=f"(d[1]), "=f"(d[2]), "=f"(d[3]), "=f"(d[4]), "=f"(d[5]), "=f"(d[6]), "=f"(d[7]), "=f"(d[8]), "=f"(d[9]), "=f"(d[10]), "=f"(d[11]), "=f"(d[12]), "=f"(d[13]), "=f"(d[14]), "=f"(d[15]), "=f"(d[16]), "=f"(d[17]), "=f"(d[18]), "=f"(d[19]), "=f"(d[20]), "=f"(d[21]), "=f"(d[22]), "=f"(d[23]), "=f"(d[24]), "=f"(d[25]), "=f"(d[26]), "=f"(d[27]), "=f"(d[28]), "=f"(d[29]), "=f"(d[30]), "=f"(d[31]), "=f"(d[32]), "=f"(d[33]), "=f"(d[34]), "=f"(d[35]), "=f"(d[36]), "=f"(d[37]), "=f"(d[38]), "=f"(d[39]), "=f"(d[40]), "=f"(d[41]), "=f"(d[42]), "=f"(d[43]), "=f"(d[44]), "=f"(d[45]), "=f"(d[46]), "=f"(d[47]), "=f"(d[48]), "=f"(d[49]), "=f"(d[50]), "=f"(d[51]), "=f"(d[52]), "=f"(d[53]), "=f"(d[54]), "=f"(d[55]), "=f"(d[56]), "=f"(d[57]), "=f"(d[58]), "=f"(d[59]), "=f"(d[60]), "=f"(d[61]), "=f"(d[62]), "=f"(d[63])
    : "r"(da), "r"(db), "n"(0), "n"(TB), "n"(OA), "n"(OB), "n"(HA), "n"(HB));
}
template<int TB, int OA, int OB, uint32_t HA, uint32_t HB> __device__ __forceinline__ void wgmma_ss_n64_new(float (&d)[32], uint32_t da, uint32_t db) {
  asm volatile("{\n.reg .pred p;\n.reg .b32 ta, tb;\n.reg .b64 da, db;\nsetp.ne.b32 p, %34, 0;\nadd.u32 ta, %32, %36;\nadd.u32 tb, %33, %37;\nmov.b64 da, {ta, %38};\nmov.b64 db, {tb, %39};\n"
    "wgmma.mma_async.sync.aligned.m64n64k16.f32.bf16.bf16 "
    "{%0, %1, %2, %3, %4, %5, %6, %7, %8, %9, %10, %11, %12, %13, %14, %15, %16, %17, %18, %19, %20, %21, %22, %23, %24, %25, %26, %27, %28, %29, %30, %31}, da, db, p, 1, 1, 0, %35;\n}\n"
    : "=f"(d[0]), "=f"(d[1]), "=f"(d[2]), "=f"(d[3]), "=f"(d[4]), "=f"(d[5]), "=f"(d[6]), "=f"(d[7]), "=f"(d[8]), "=f"(d[9]), "=f"(d[10]), "=f"(d[11]), "=f"(d[12]), "=f"(d[13]), "=f"(d[14]), "=f"(d[15]), "=f"(d[16]), "=f"(d[17]), "=f"(d[18]), "=f"(d[19]), "=f"(d[20]), "=f"(d[21]), "=f"(d[22]), "=f"(d[23]), "=f"(d[24]), "=f"(d[25]), "=f"(d[26]), "=f"(d[27]), "=f"(d[28]), "=f"(d[29]), "=f"(d[30]), "=f"(d[31])
    : "r"(da), "r"(db), "n"(0), "n"(TB), "n"(OA), "n"(OB), "n"(HA), "n"(HB));
}
template<int OA, int OB = 0, uint32_t HA = SW128> __device__ __forceinline__ void kblock_n128(float (&d)[64], uint32_t da, uint32_t db, int sd) {
  constexpr int H = HA == SW128 ? 4 : 512;
  wgmma_ss_n128<1, OA, OB, HA, SW128>(d, da, db, sd); wgmma_ss_n128<1, OA + 2, OB + 128, HA, SW128>(d, da, db, 1);
  wgmma_ss_n128<1, OA + H, OB + 256, HA, SW128>(d, da, db, 1); wgmma_ss_n128<1, OA + H + 2, OB + 384, HA, SW128>(d, da, db, 1);
}

__device__ __forceinline__ float quad_sum(float v) {
  v += __shfl_xor_sync(0xffffffff, v, 1);
  v += __shfl_xor_sync(0xffffffff, v, 2);
  return v;
}
struct Row { uint32_t v[8]; };
template<class F> __device__ __forceinline__ Row load_row(const __nv_bfloat16* p, int lane, F ld) {
  const uint4 a = ld(reinterpret_cast<const uint4*>(p) + lane), b = ld(reinterpret_cast<const uint4*>(p) + 32 + lane);
  return Row{{a.x, a.y, a.z, a.w, b.x, b.y, b.z, b.w}};
}
__device__ __forceinline__ Row ldg_row(const __nv_bfloat16* p, int lane) { return load_row(p, lane, [](const uint4* q) { return __ldg(q); }); }
__device__ __forceinline__ Row ldca_row(const __nv_bfloat16* p, int lane) { return load_row(p, lane, [](const uint4* q) { return __ldca(q); }); }
__device__ __forceinline__ Row lds_row(uint32_t addr, int lane) {
  const uint4 a = lds_v4(addr + lane * 16), b = lds_v4(addr + 512 + lane * 16);
  return Row{{a.x, a.y, a.z, a.w, b.x, b.y, b.z, b.w}};
}
__device__ __forceinline__ void store_row(__nv_bfloat16* p, int lane, const Row& r) {
  stg_v4(p + lane * 8, r.v[0], r.v[1], r.v[2], r.v[3]); stg_v4(p + 256 + lane * 8, r.v[4], r.v[5], r.v[6], r.v[7]);
}
__device__ __forceinline__ Row fma_row(const Row& a, const Row& b, const Row& c) {
  Row r;
  #pragma unroll
  for (int i = 0; i < 8; i++) r.v[i] = fma2(a.v[i], b.v[i], c.v[i]);
  return r;
}
__device__ __forceinline__ Row add_row(const Row& a, const Row& b) {
  Row r;
  #pragma unroll
  for (int i = 0; i < 8; i++) r.v[i] = add2(a.v[i], b.v[i]);
  return r;
}
__device__ __forceinline__ Row one_plus(const Row& a) {
  Row r;
  #pragma unroll
  for (int i = 0; i < 8; i++) r.v[i] = add2(a.v[i], 0x3f803f80u);
  return r;
}
__device__ __forceinline__ float row_at(const Row& x, int i) { return (i & 1) ? bf_hi(x.v[i >> 1]) : bf_lo(x.v[i >> 1]); }
template<int N> __device__ __forceinline__ void warp_sums(float (&s)[N]) {
  #pragma unroll
  for (int o = 16; o > 0; o >>= 1) {
    #pragma unroll
    for (int k = 0; k < N; k++) s[k] += __shfl_xor_sync(0xffffffff, s[k], o);
  }
}
__device__ __forceinline__ void ln_stats(float& s1, float& s2) {
  s1 *= 1.f / DM;
  asm("rsqrt.approx.ftz.f32 %0, %1;" : "=f"(s2) : "f"(fmaxf(fmaf(-s1, s1, s2 * (1.f / DM)), 0.f) + 1e-5f));
}
__device__ __forceinline__ Row ln_apply(const Row& x, float mean, float f) {
  Row n;
  const float o = -mean * f;
  #pragma unroll
  for (int i = 0; i < 8; i++) n.v[i] = pack_bf16(fmaf(bf_lo(x.v[i]), f, o), fmaf(bf_hi(x.v[i]), f, o));
  return n;
}

constexpr int SM_Q = 6 * 32768, SM_BAR = 7 * 32768, SM_MAIL = SM_BAR + 640, SM_RED = SM_MAIL + 128, SM_H2 = SM_RED + 1024, SM_KEY = SM_H2 + 1024, SMEM = SM_KEY + 128;
constexpr int B_AF = 0, B_WF = 64, B_RF = 112, B_WE = 168, B_RE = 216, B_PUB = 272, B_RDY = 496;
constexpr int R_MOD = B_RDY, R_H1 = B_RDY + 8, R_ITEM = B_RDY + 16, R_NEAR = B_RDY + 48, R_CTX = B_RDY + 64;
constexpr int R_KEY = B_AF + 8, R_PART = B_AF + 32;
constexpr int NPUB = 14;
__device__ __forceinline__ uint32_t k_addrA(int kb) { return ((0x6310u >> ((kb >> 1) * 4)) & 15u) * 32768u + (kb & 1) * 16384u; }
__device__ __forceinline__ uint32_t k_addrW(int s) { return ((0x254u >> ((s >> 1) * 4)) & 15u) * 32768u + (s & 1) * 16384u; }

#define KORDER 0x3201
constexpr int KHEAD0 = ((KORDER >> 12) & 3) * 8;
constexpr int MAX_ITEMS = 4;
constexpr int MAX_STEPS = 10;
struct Sched {
  __nv_bfloat16 *kvc, *h1, *part;
  struct Pair {
    uint8_t oent[3 * MAX_STEPS + 6];
    uint8_t khead[4];
    uint8_t nitems, item[MAX_ITEMS];
    uint8_t otask, nsteps;
    uint8_t ochunk[MAX_STEPS][2];
  } pair[NGRID / 2];
};

__device__ __forceinline__ int ring_add(int e, int n) { e += n; return e >= 12 ? e - 12 : e; }
__device__ __forceinline__ int ring_slot(int e) { return e >= 6 ? e - 6 : e; }
__device__ __forceinline__ void ring_wait_full(uint32_t bars, int e) { mbar_wait(bars + B_RF + 8 * ring_slot(e), e >= 6); }

__device__ __forceinline__ void o_wait_full(uint32_t bars, uint32_t v) { mbar_wait(bars + B_RF + 8 * (v & 7), v >> 3); }

struct Ctx {
  uint32_t base, bars;
  uint32_t rel;
  bool rel1;
  int w, nev;
  const Sched* sched;
};
__device__ __forceinline__ void slot_release(const Ctx& x, int s, bool twice) {
  mbar_arrive_remote_if(x.rel + B_RE + 8 * s, twice ? (wg_tid() & 31) == 0 : x.rel1);
}
__device__ __forceinline__ void ring_release(const Ctx& x, int e, bool twice) { slot_release(x, ring_slot(e), twice); }
__device__ __forceinline__ void publish(Ctx& x, int idx) {
  const uint32_t n = x.w * NPUB + x.nev;
  const int t = wg_tid();
  if (t == 0) asm volatile("st.shared.u32 [%0], %1;" :: "r"(x.base + SM_MAIL + 4 * n), "r"(idx) : "memory");
  __syncwarp();
  if ((t & 31) == 0) mbar_arrive(x.bars + B_PUB + 8 * n);
  x.nev++;
}

template<int KK = 0> __device__ __forceinline__ void issue_qk(float (&S)[64], uint32_t dq, uint32_t dk) {
  constexpr int off = (KK >> 1) * 512 + (KK & 1) * 2;
  if constexpr (KK == 0) wgmma_ss_n128_new<0, 0, 0, SW64, SW64>(S, dq, dk); else wgmma_ss_n128<0, off, off, SW64, SW64>(S, dq, dk, 1);
  if constexpr (KK < 7) issue_qk<KK + 1>(S, dq, dk);
}
template<int KK = 0> __device__ __forceinline__ void issue_qk_half(float (&S)[32], uint32_t dq, uint32_t dk) {
  constexpr int off = (KK >> 1) * 512 + (KK & 1) * 2;
  if constexpr (KK == 0) wgmma_ss_n64_new<0, 0, 256, SW64, SW64>(S, dq, dk); else wgmma_ss_n64<0, off, off + 256, SW64, SW64>(S, dq, dk, 1);
  if constexpr (KK < 7) issue_qk_half<KK + 1>(S, dq, dk);
}
template<int NK, int KK = 0>
__device__ __forceinline__ void issue_pv(float (&O)[64], uint32_t (&P)[32], uint32_t dv, int accumulate) {
  wgmma_rs_n128<1, (KK + 8 - NK) * 64, SW64>(O, P[4*KK], P[4*KK+1], P[4*KK+2], P[4*KK+3], dv, accumulate);
  if constexpr (KK + 1 < NK) issue_pv<NK, KK + 1>(O, P, dv, 1);
}
template<int K0, int K1>
__device__ __forceinline__ void exp_pack(const float (&S)[64], uint32_t (&D)[32], float& s0, float& s1) {
  #pragma unroll
  for (int k = K0; k < K1; k++) {
    const float e0 = ex2(S[2*k]), e1 = ex2(S[2*k+1]);
    D[k] = pack_bf16(e0, e1);
    if (k & 1) s1 += e0 + e1; else s0 += e0 + e1;
  }
}
__device__ __forceinline__ int diag_limit() { const int t = wg_tid(); return 16 * (t >> 5) + ((t & 31) >> 2) - 2 * (t & 3); }
__device__ __forceinline__ void exp_pack_diag(const float (&S)[64], uint32_t (&D)[32], int t, float& s0, float& s1) {
  #pragma unroll
  for (int k = 0; k < 16; k++) {
    const int c = 8 * (k >> 1) - 8 * (k & 1);
    const float e0 = ex2((c <= t) ? S[2*k] : -INFINITY), e1 = ex2((c + 1 <= t) ? S[2*k+1] : -INFINITY);
    D[k] = pack_bf16(e0, e1);
    if (k & 1) s1 += e0 + e1; else s0 += e0 + e1;
  }
}
constexpr float SUM_HI = 1.8446744073709552e19f;
constexpr float SUM_LO = 5.421010862427522e-20f;

__device__ __forceinline__ void classic_tile(const float (&S)[64], uint32_t (&P)[32], bool fresh, bool half, bool was_classic, volatile float* mc,
                                             float& l0, float& l1, float& s0, float& s1, float& sc0, float& sc1) {
  const int tmask = diag_limit();
  float4 t[16];
  #pragma unroll
  for (int j = 0; j < 16; j++) t[j] = make_float4(S[4*j], S[4*j+1], S[4*j+2], S[4*j+3]);
  float mx0 = -INFINITY, mx1 = -INFINITY;
  #pragma unroll 1
  for (int j = 0; j < 16; j++) {
    float4 v = t[j];
    const int lim = !fresh ? 1000 : j < 8 ? tmask - 8 * j : half ? -1000 : 1000;
    v.x = 0 <= lim ? v.x : -INFINITY; v.y = 1 <= lim ? v.y : -INFINITY; v.z = -8 <= lim ? v.z : -INFINITY; v.w = -7 <= lim ? v.w : -INFINITY;
    t[j] = v;
    mx0 = fmaxf(mx0, fmaxf(v.x, v.y)); mx1 = fmaxf(mx1, fmaxf(v.z, v.w));
  }
  mx0 = fmaxf(mx0, __shfl_xor_sync(0xffffffff, mx0, 1));
  mx1 = fmaxf(mx1, __shfl_xor_sync(0xffffffff, mx1, 1));
  mx0 = fmaxf(mx0, __shfl_xor_sync(0xffffffff, mx0, 2));
  mx1 = fmaxf(mx1, __shfl_xor_sync(0xffffffff, mx1, 2));
  const float mc0 = was_classic ? mc[0] : 0.f, mc1 = was_classic ? mc[1] : 0.f;
  const float n0 = fresh ? -mx0 : fminf(mc0, -mx0), n1 = fresh ? -mx1 : fminf(mc1, -mx1);
  sc0 = ex2(n0 - mc0); sc1 = ex2(n1 - mc1);
  mc[0] = n0; mc[1] = n1;
  s0 = 0.f; s1 = 0.f;
  #pragma unroll 1
  for (int j = 0; j < 16; j++) {
    const float4 v = t[j];
    const float e0 = ex2(v.x + n0), e1 = ex2(v.y + n0), e2 = ex2(v.z + n1), e3 = ex2(v.w + n1);
    s0 += e0 + e1; s1 += e2 + e3;
    reinterpret_cast<uint2*>(t)[j] = make_uint2(pack_bf16(e0, e1), pack_bf16(e2, e3));
  }
  #pragma unroll
  for (int j = 0; j < 8; j++) { P[4*j] = __float_as_uint(t[j].x); P[4*j+1] = __float_as_uint(t[j].y); P[4*j+2] = __float_as_uint(t[j].z); P[4*j+3] = __float_as_uint(t[j].w); }
  if (!fresh) { l0 *= sc0; l1 *= sc1; }
}
__device__ __forceinline__ void pack_tile(const float (&A)[64], uint32_t (&D)[32], float f0, float f1) {
  #pragma unroll
  for (int j = 0; j < 16; j++) {
    D[8 * (j >> 2) + (j & 3)] = pack_bf16(A[4*j] * f0, A[4*j+1] * f0);
    D[8 * (j >> 2) + 4 + (j & 3)] = pack_bf16(A[4*j+2] * f1, A[4*j+3] * f1);
  }
}
__device__ __forceinline__ int piece0(int t) { return ((t >> 5) * 16 + ((t & 31) >> 2)) * 32 + (((t ^ (t >> 3)) & 3) << 3); }
__device__ __forceinline__ void store_tile(__nv_bfloat16* p, const uint32_t (&D)[32]) {
  #pragma unroll
  for (int i = 0; i < 8; i++) stg_v4(p + (i >> 2) * (SEQ * 64) + ((i >> 1) & 1) * 4096 + (i & 1) * 256, D[4*i], D[4*i+1], D[4*i+2], D[4*i+3]);
}

enum : int { PV_ACC = 0, PV_ZERO = 1, PV_HALF = 2, PV_NONE = 3 };
struct Att {
  float l0, l1, i0, i1;
  bool classic;
  volatile float* mc;
};
__device__ __forceinline__ void store_ctx(Ctx& x, int code, const uint32_t (&D)[32]) {
  store_tile(x.sched->kvc + ((size_t)(128 + (code >> 5) * 2) * SEQ + ((code >> 1) & 15) * 128) * 64 + (code & 1) * 2048 + piece0(wg_tid()), D);
  publish(x, C_CTX + (code >> 2));
}
__device__ __forceinline__ __nv_bfloat16* kv_tile(const Ctx& x, int code) {
  return x.sched->kvc + ((size_t)(x.w * 64 + (code >> 4) * 2) * SEQ + (code & 15) * 128) * 64 + piece0(wg_tid());
}
__device__ __forceinline__ void q_proj(Ctx& x, Att& a, int& e, int& sk, int& sv, int& en, int& sn, bool isY,
                                       const uint32_t (&PA)[32], const uint32_t (&PB)[32], int vtile, bool first) {
  float S[64];
  int ek = 0, s = sk, ps = 0, ph = e >= 6, kb = 0;
  uint32_t qa = 0;
  sv = en = sn = 0;
  if (isY) bar_sync(1 + x.w, 256);
  if (first) mbar_wait(x.bars + B_RF + 8 * s, ph);
  #pragma unroll 1
  while (true) {
    #pragma unroll 1
    do {
      wgmma_fence();
      kblock_n128<0>(S, desc_lo(x.base + x.w * 8192, 16) + s * 2048, desc_lo(x.base + 16384, 8192) + s * 2048, kb != 0);
      wgmma_commit();
      if (kb == 7 && !isY) bar_arrive(1 + (x.w ^ 1), 256);
      wgmma_wait<1>();
      mbar_arrive_remote_if(x.rel + B_RE + 8 * ps, x.rel1 && kb > 0);
      ps = s;
      if (++s == 6) { s = 0; ph ^= 1; }
      if (++kb == 8) break;
      mbar_wait(x.bars + B_RF + 8 * s, ph);
    } while (kb != 4);
    asm volatile("" : "+r"(vtile));
    if (kb == 8) break;
    a.i0 = rcp_fast(quad_sum(a.l0)); a.i1 = rcp_fast(quad_sum(a.l1));
    e = ring_add(e, 8); ek = ring_add(e, isY ? 0 : 2); en = ring_add(e, isY ? 2 : 4);
    sk = ring_slot(ek); sv = ring_slot(e) + 1; sn = ring_slot(en);
    qa = x.base + SM_Q + x.w * 4096 + piece0(wg_tid()) * 2;
    if (vtile >= 0) store_tile(kv_tile(x, vtile) + 2048, PA);
  }
  if (vtile >= 0) { store_tile(kv_tile(x, vtile), PB); publish(x, C_KV + (vtile >> 4)); }
  wgmma_wait<0>();
  fence_regs(S);
  slot_release(x, ps, false);
  const bool landed = isY && mbar_test2(x.bars + B_RF + 8 * sk, e >= 6);
  #pragma unroll
  for (int i = 0; i < 8; i++) {
    const int j = 4 * (i >> 1), o = 2 * (i & 1);
    sts_v4(qa + (i >> 1) * 8192 + (i & 1) * 512,
           pack_bf16(S[4*j+o], S[4*j+o+1]), pack_bf16(S[4*j+4+o], S[4*j+5+o]), pack_bf16(S[4*j+8+o], S[4*j+9+o]), pack_bf16(S[4*j+12+o], S[4*j+13+o]));
  }
  fence_async_smem();
  if (!landed) { mbar_wait(x.bars + B_RF + 8 * sk, ek >= 6); mbar_wait(x.bars + B_RF + 8 * sv, e >= 6); }
}

template<int KIND>
__device__ __forceinline__ void slot(Ctx& x, Att& a, int& e, int& sk, int sv, int en, int sn, float (&O)[64], uint32_t (&Pn)[32], uint32_t (&Po)[32],
                                     bool more, bool isY, bool half, int pv, int pend) {
  float S[64];
  const int w = x.w;
  const uint32_t dq = desc_lo(x.base + SM_Q + w * 4096, 16), dk = desc_lo(x.base, 16) + sk * 2048, dv = desc_lo(x.base, 8192) + sv * 2048;
  bar_sync(1 + w, 256);
  if (KIND == 2) {
    wgmma_fence();
    issue_qk(S, dq, dk); wgmma_commit();
    issue_pv<8>(O, Po, dv, 1); wgmma_commit();
    bar_arrive(1 + (w ^ 1), 256);
    wgmma_wait<1>();
  } else if (KIND == 0 && half) {
    float T[32];
    wgmma_fence(); issue_qk_half(T, dq, dk); wgmma_commit();
    if (pv == PV_NONE) { wgmma_fence(); wgmma_commit(); }
    else               { wgmma_fence(); issue_pv<8>(O, Po, dv, pv == PV_ACC); wgmma_commit(); }
    bar_arrive(1 + (w ^ 1), 256);
    wgmma_wait<1>();
    fence_regs(T);
    #pragma unroll
    for (int i = 0; i < 32; i++) { S[i] = T[i]; asm volatile("" : "=f"(S[32 + i])); }
  } else {
    wgmma_fence(); issue_qk(S, dq, dk); wgmma_commit();
    if (KIND == 1 && pend >= 0) { bar_arrive(1 + (w ^ 1), 256); pack_tile(O, Pn, a.i0, a.i1); store_ctx(x, pend, Pn); }
    if (KIND == 0 && pv == PV_NONE) { wgmma_fence(); wgmma_commit(); }
    else if (pv == PV_HALF)         { wgmma_fence(); issue_pv<4>(O, Po, dv, 0); wgmma_commit(); }
    else                            { wgmma_fence(); issue_pv<8>(O, Po, dv, pv == PV_ACC); wgmma_commit(); }
    if (KIND == 0 || pend < 0) bar_arrive(1 + (w ^ 1), 256);
    wgmma_wait<1>();
  }
  fence_regs(S);
  fence_regs_u(Pn);
  slot_release(x, sk, KIND == 0 && isY);
  const bool landed = mbar_test2(x.bars + B_RF + 8 * sn, en >= 6);
  float s0 = 0.f, s1 = 0.f;
  const bool was_classic = KIND != 0 && a.classic;
  if (KIND == 0) {
    a.l0 = 0.f; a.l1 = 0.f;
    if (!half) exp_pack<16, 32>(S, Pn, s0, s1);
    else {
      #pragma unroll
      for (int i = 16; i < 32; i++) asm volatile("" : "=r"(Pn[i]));
    }
    exp_pack_diag(S, Pn, diag_limit(), s0, s1);
    uint32_t b0 = __ballot_sync(0xffffffff, s0 >= SUM_LO), b1 = __ballot_sync(0xffffffff, s1 >= SUM_LO);
    b0 |= b0 >> 1; b0 |= b0 >> 2; b1 |= b1 >> 1; b1 |= b1 >> 2;
    a.classic = __any_sync(0xffffffff, !(s0 <= SUM_HI && s1 <= SUM_HI)) || (b0 & b1 & 0x11111111u) != 0x11111111u;
  } else {
    exp_pack<0, 32>(S, Pn, s0, s1);
    a.classic = __any_sync(0xffffffff, a.classic || !(s0 <= SUM_HI && s1 <= SUM_HI));
  }
  fence_regs_u(Pn);
  if (!landed) {
    mbar_wait(x.bars + B_RF + 8 * sn, en >= 6);
    if (more) mbar_wait(x.bars + B_RF + 8 * sn + 8, en >= 6);
  }
  wgmma_wait<0>();
  fence_regs(O);
  fence_regs_u(Po);
  slot_release(x, sv, KIND == 1 && isY && pv != PV_ACC);
  if (__builtin_expect(a.classic, 0)) {
    float sc0, sc1;
    classic_tile(S, Pn, KIND == 0, half, was_classic, a.mc, a.l0, a.l1, s0, s1, sc0, sc1);
    if (KIND != 0) {
      #pragma unroll
      for (int j = 0; j < 16; j++) { O[4*j] *= sc0; O[4*j+1] *= sc0; O[4*j+2] *= sc1; O[4*j+3] *= sc1; }
    }
  }
  a.l0 += s0; a.l1 += s1;
  e = en; sk = sn;
}

__device__ __forceinline__ int attention(Ctx& x, const uint8_t* items, int nitems, int rank, uint32_t (&PA)[32], uint32_t (&PB)[32], int vtile) {
  int e = 0, sk = 0;
  float O[64];
  Att a;
  volatile float mc[2];
  a.l0 = 1.f; a.l1 = 1.f; a.i0 = 0.f; a.i1 = 0.f; a.classic = false; a.mc = mc;
  int pv = PV_NONE, cur = -1;
  #pragma unroll 1
  for (int it = 0; ; it++) {
    const bool isY = (it & 1) == x.w;
    int pend = cur;
    if (it < nitems) {
      const bool half = isY == (rank != 0);
      int sv, en, sn;
      q_proj(x, a, e, sk, sv, en, sn, isY, PA, PB, vtile, it == 0);
      vtile = -1;
      const int item = items[it];
      cur = item * 4 + (isY ? 3 - rank : rank);
      int rem = 2 * (item & 7) + (isY ? 1 : 0);
      slot<0>(x, a, e, sk, sv, en, sn, O, PA, PB, rem > 0, isY, half, pv, -1);
      pv = half ? PV_HALF : PV_ZERO;
      #pragma unroll 1
      while (rem > 0) {
        slot<1>(x, a, e, sk, sk + 1, ring_add(e, 2), sk == 4 ? 0 : sk + 2, O, PB, PA, rem > 1, isY, false, pv, pend);
        pv = PV_ACC; pend = -1;
        if (rem == 1) break;
        rem -= 2;
        slot<2>(x, a, e, sk, sk + 1, ring_add(e, 2), sk == 4 ? 0 : sk + 2, O, PA, PB, rem > 0, false, false, 0, -1);
      }
      if (isY) continue;
    } else {
      slot_release(x, 6, false);
      const uint32_t dv = desc_lo(x.base, 8192) + sk * 2048;
      bar_sync(1 + x.w, 256);
      if (pv == PV_HALF) { wgmma_fence(); issue_pv<4>(O, PB, dv, 0); wgmma_commit(); }
      else { wgmma_fence(); issue_pv<8>(O, PB, dv, pv == PV_ACC); wgmma_commit(); }
      if (isY) bar_arrive(1 + (x.w ^ 1), 256);
      a.i0 = rcp_fast(quad_sum(a.l0)); a.i1 = rcp_fast(quad_sum(a.l1));
      ring_wait_full(x.bars, e);
      wgmma_wait<0>();
      fence_regs(O);
      fence_regs_u(PB);
      slot_release(x, sk, false);
    }
    if (pend >= 0) {
      pack_tile(O, PB, a.i0, a.i1);
      if (it == nitems) return pend;
      store_ctx(x, pend, PB);
    }
    #pragma unroll
    for (int i = 0; i < 32; i++) asm volatile("mov.b32 %0, %1;" : "=r"(PB[i]) : "r"(PA[i]));
  }
}

#define LN_AT 2
#define X_AT 6
#define PERT 0
#define CTX_T 3
#define PF_AT 5
#define PF_N 4
#define PF_MOE 3
constexpr float QSCALE = 0.08838834764831845f * 1.4426950408889634f;
__device__ __forceinline__ void mod_cta(Ctx& x, const __nv_bfloat16* cvec) {
  const int t = wg_tid(), ct = x.w * 128 + t;
  #pragma unroll 1
  for (int k = 0; k < 6; k++) slot_release(x, k, false);
  const uint32_t cv = __ldg(reinterpret_cast<const uint32_t*>(cvec) + ct);
  asm volatile("st.shared.u32 [%0], %1;" :: "r"(x.base + SM_H2 + ct * 4),
               "r"(pack_bf16(__fdividef(bf_lo(cv), 1.f + __expf(-bf_lo(cv))), __fdividef(bf_hi(cv), 1.f + __expf(-bf_hi(cv))))) : "memory");
  bar_sync(5, 256);
  float acc[64];
  int e = 0;
  #pragma unroll 1
  for (int g = 0; g < 24; g++) {
    uint32_t a[8];
    #pragma unroll
    for (int i = 0; i < 8; i++) a[i] = lds_u32(x.base + SM_H2 + (g & 7) * 128 + i * 16 + (t & 3) * 4);
    ring_wait_full(x.bars, e);
    const uint32_t db = desc_lo(x.base + x.w * 16384, 8192) + ring_slot(e) * 2048;
    wgmma_fence();
    wgmma_rs_n128<1, 0, SW128>(acc, a[0], a[0], a[1], a[1], db, g & 7);
    wgmma_rs_n128<1, 128, SW128>(acc, a[2], a[2], a[3], a[3], db, 1);
    wgmma_rs_n128<1, 256, SW128>(acc, a[4], a[4], a[5], a[5], db, 1);
    wgmma_rs_n128<1, 384, SW128>(acc, a[6], a[6], a[7], a[7], db, 1);
    wgmma_commit();
    wgmma_wait<0>();
    fence_regs(acc);
    ring_release(x, e, false);
    e = ring_add(e, 1);
    if ((g & 7) == 7) {
      float v[2][8];
      #pragma unroll
      for (int c = 0; c < 2; c++) {
        #pragma unroll
        for (int j = 0; j < 8; j++) v[c][j] = (t & 32) ? acc[4 * (j + 8) + c] : acc[4 * j + c];
        #pragma unroll
        for (int h = 4; h > 0; h >>= 1)
          #pragma unroll
          for (int j = 0; j < h; j++) v[c][j] = (t & (4 * h)) ? v[c][j + h] : v[c][j];
      }
      const float sc = (g == 7 && blockIdx.x < NCTA + 2) ? QSCALE : 1.f;
      if (t < 64) reinterpret_cast<uint32_t*>(g_x.mod + (g >> 3) * 1024 + (blockIdx.x - NCTA) * 256 + x.w * 128)[t] = pack_bf16(rbf(v[0][0]) * sc, rbf(v[1][0]) * sc);
      publish(x, g == 7 ? C_MOD : C_MOD2);
    }
  }
}

__global__ void __cluster_dims__(2, 1, 1) __launch_bounds__(384, 1)
k_fused(const __grid_constant__ CUtensorMap tmC, const __grid_constant__ CUtensorMap tmWq,
        const __grid_constant__ CUtensorMap tmWk, const __grid_constant__ CUtensorMap tmWv,
        const __grid_constant__ CUtensorMap tmWo, const __grid_constant__ CUtensorMap tmWg,
        const __grid_constant__ CUtensorMap tmWu, const __grid_constant__ CUtensorMap tmWd, const __grid_constant__ CUtensorMap tmWm,
        const __grid_constant__ Sched sched,
        const __nv_bfloat16* __restrict__ xin,
        const __nv_bfloat16* __restrict__ cvec, const __nv_bfloat16* __restrict__ w_o,
        const __nv_bfloat16* __restrict__ w_r, const __nv_bfloat16* __restrict__ w_gate, const __nv_bfloat16* __restrict__ w_up,
        const __nv_bfloat16* __restrict__ w_down, __nv_bfloat16* __restrict__ out) {
  extern __shared__ __align__(1024) uint8_t smem_raw[];
  const uint32_t base = smem_u32(smem_raw), bars = base + SM_BAR;
  const int warp = __shfl_sync(0xffffffff, threadIdx.x >> 5, 0), wg = warp >> 2;
  const int rank = cluster_ctarank(), p = blockIdx.x >> 1;
  const int mt = (p & 7) * 2 + rank;
  const bool spare = blockIdx.x >= NCTA;
  #pragma unroll
  for (int i = 0; i < PERT; i++) { uint32_t d; asm volatile("mov.u32 %0, %%laneid;" : "=r"(d)); (void)d; }
  {
    const int h0 = KHEAD0 + (p >> 3);
    if (warp == 11) { prefetch_tmap(&tmC); prefetch_tmap(&tmWk); }
    #pragma unroll 1
    for (int t = warp == 8 ? 0 : warp < 8 ? warp + 1 : warp == 11 ? 64 : warp; t < B_PUB / 8; t += (warp == 8 ? 64 : 10))
      w_mbar_init(bars + 8 * t, t < B_WE / 8 ? 1 : t < B_RE / 8 ? 2 : 4);
    fence_mbar_init();
    cluster_arrive();
    if (warp == 9) prefetch_tmap(&tmWv);
    if (wg == 2) bar_arrive(1, 256);
    if (warp == 8 && !spare) {
      #pragma unroll 1
      for (int kb = 0; kb < 8; kb++) {
        w_expect_tx(bars + B_AF + 8 * kb, 16384);
        tma_load_2d(base + k_addrA(kb), &tmC, bars + B_AF + 8 * kb, kb * 64, mt * 128);
        if (kb == 0) cluster_wait();
        if (kb < 6) {
          w_expect_tx(bars + B_WF + 8 * kb, 16384);
          tma_load_2d_mc(base + k_addrW(kb) + rank * 8192, &tmWk, bars + B_WF + 8 * kb, h0 * 128 + rank * 64, kb * 64);
        }
      }
    }
  }
  const Sched::Pair& sp = sched.pair[p];
  const int nitems = sp.nitems, nsteps = sp.nsteps;
  auto oent = [&](int k) -> uint32_t { return sp.oent[k]; };
  const int ot = sp.otask, m = (ot & 7) * 2 + rank, grp = m * 8 + (ot >> 3);

  if (wg == 0) {
    asm volatile("setmaxnreg.dec.sync.aligned.u32 24;");
    const int lane = threadIdx.x & 31;
    #pragma unroll 1
    for (int t = B_PUB / 8 + warp; t < 80; t += 4) w_mbar_init(bars + 8 * t, t < B_RDY / 8 ? 4 : 1);
    bar_sync(6, 128);
    bar_arrive(7, 256); bar_arrive(8, 256);
    cluster_wait();
    const unsigned int tag = ld_relaxed(&g_x.epoch) + 1;
    if (warp == 0) {
      if (!spare) {
        int s = 0, ph = 0;
        tma_prefetch_2d(&tmWv, sp.khead[0] * 128 + rank * 64, (p & 7) * 64);
        #pragma unroll 1
        for (int g = 6; g < 64; g++) {
          const int u = g >> 3, kb = g & 7;
          if (kb == 0 && u < 7) tma_prefetch_2d((u & 1) ? &tmWk : &tmWv, sp.khead[(u + 1) >> 1] * 128 + rank * 64, (p & 7) * 64);
          mbar_wait(bars + B_WE + 8 * s, ph);
          w_expect_tx(bars + B_WF + 8 * s, 16384);
          tma_load_2d_mc(base + k_addrW(s) + rank * 8192, (u & 1) ? &tmWv : &tmWk, bars + B_WF + 8 * s, sp.khead[u >> 1] * 128 + rank * 64, kb * 64);
          if (++s == 6) { s = 0; ph ^= 1; }
        }
      }
      int s = 0, ph = 0;
      auto next_entry = [&](int bytes) {
        mbar_wait(bars + B_RE + 8 * s, ph);
        w_expect_tx(bars + B_RF + 8 * s, bytes);
      };
      auto advance = [&]() { if (++s == 6) { s = 0; ph ^= 1; } };
      if (spare) {
        #pragma unroll 1
        for (int g = 0; g < 24; g++) {
          if (g == 8) mbar_wait(bars + R_MOD, 0);
          next_entry(32768);
          for (int k = 0; k < 2; k++) tma_load_3d(base + s * 32768 + k * 16384, &tmWm, bars + B_RF + 8 * s, 0, (g & 7) * 64, (g >> 3) * 16 + (blockIdx.x - NCTA) * 4 + k * 2);
          advance();
        }
      }
      mbar_wait(bars + R_H1, 0);
      fence_async_global();
      int vrow = -1;
      #pragma unroll 1
      for (int i = 0; i <= nitems; i++) {
        const int item = sp.item[i & (MAX_ITEMS - 1)], h = item >> 3, j = item & 7;
        if (i < nitems) {
          const int row0 = j * 256 + ((i & 1) ? rank : 3 - rank) * 64, row1 = j * 256 + ((i & 1) ? 3 - rank : rank) * 64;
          #pragma unroll 1
          for (int kb = 0; kb < 8; kb++) {
            next_entry(32768);
            tma_load_2d_mc(base + s * 32768 + 16384 + rank * 8192, &tmWq, bars + B_RF + 8 * s, h * 128 + rank * 64, kb * 64);
            bulk_load(base + s * 32768, sched.h1 + row0 * DM + kb * 4096, 8192, bars + B_RF + 8 * s);
            bulk_load(base + s * 32768 + 8192, sched.h1 + row1 * DM + kb * 4096, 8192, bars + B_RF + 8 * s);
            advance();
          }
          mbar_wait(bars + R_ITEM + 8 * i, 0);
          fence_async_global();
        }
        #pragma unroll 1
        for (int n = i < nitems ? 4 * j + 3 : 0; n >= 0; n--) {
          const int krow = (h * 2 + rank) * SEQ + (n >> 1) * 128;
          const int row = (n & 1) ? krow : vrow;
          if (i + 1 == nitems && n == min(4 * j + 3, 2 * PF_AT + 1)) w_arrive(bars + R_NEAR);
          next_entry(row >= 0 ? 32768 : 0);
          if (row >= 0) bulk_load_mc(base + s * 32768 + rank * 16384, sched.kvc + (size_t)row * 64, bars + B_RF + 8 * s);
          advance();
          if (!(n & 1)) vrow = krow + 64 * SEQ;
        }
      }
      if (!spare) {
      const int oc = ((ot >> 3) & 1) * 4 + rank * 2;
      auto o_next = [&](int k, int bytes) {
        const uint32_t v = oent(k); s = v & 7;
        mbar_wait(bars + B_RE + 8 * s, v >> 3);
        w_expect_tx(bars + B_RF + 8 * s, bytes);
      };
      #pragma unroll 1
      for (int i = 0; i < nsteps; i++) {
        const int c0 = sp.ochunk[i][0], c1 = sp.ochunk[i][1];
        const int pf = i - nsteps + PF_MOE;
        if (pf >= 0 && pf < 3)
          bulk_prefetch((pf == 0 ? w_gate : pf == 1 ? w_up : w_down) + (size_t)blockIdx.x * (DM * FF / NCTA), DM * FF / NCTA * 2);
        if (c0 < 64) { o_next(3 * i, 32768); tma_load_3d_mc(base + s * 32768 + rank * 16384, &tmWo, bars + B_RF + 8 * s, 0, c0 * 64, oc); }
        mbar_wait(bars + R_CTX + 8 * i, 0);
        fence_async_global();
        o_next(3 * i + 1, c0 < 64 ? 32768 : 16384);
        if (c0 < 64) bulk_load(base + s * 32768, sched.kvc + (size_t)((128 + c0) * SEQ + m * 128) * 64, 16384, bars + B_RF + 8 * s);
        bulk_load(base + s * 32768 + 16384, sched.kvc + (size_t)((128 + c1) * SEQ + m * 128) * 64, 16384, bars + B_RF + 8 * s);
        o_next(3 * i + 2, 32768);
        tma_load_3d_mc(base + s * 32768 + rank * 16384, &tmWo, bars + B_RF + 8 * s, 0, c1 * 64, oc);
      }
      const int f0 = (blockIdx.x < FF / 16 ? blockIdx.x : 0) * 16;
      o_next(3 * nsteps, 32768);
      tma_load_3d(base + s * 32768, &tmWd, bars + B_RF + 8 * s, 0, f0, 0);
      bulk_load(base + s * 32768 + 16384, xin + (size_t)grp * 16 * DM, 16384, bars + B_RF + 8 * s);
      o_next(3 * nsteps + 1, 32768);
      #pragma unroll 1
      for (int k = 0; k < 4; k++) tma_load_2d(base + s * 32768 + k * 8192, (k & 2) ? &tmWu : &tmWg, bars + B_RF + 8 * s, f0, (k & 1) * 256);
      #pragma unroll 1
      for (int k = 0; k < 4; k++) w_expect_tx(bars + R_PART + 8 * k, 16384);
      #pragma unroll 1
      for (int k = 2; k < 4; k++) mbar_wait(bars + B_RE + 8 * (oent(3 * nsteps + k) & 7), oent(3 * nsteps + k) >> 3);
      uint32_t todo = 0xff;
      #pragma unroll 1
      for (int n = 0; n < WAIT_LIM && todo; n++) {
        uint32_t now = __ballot_sync(0xffffffff, ld_acquire(&g_x.sent[grp][lane & 7]) == tag) & todo;
        todo &= ~now;
        if (now) fence_async_global();
        #pragma unroll 1
        for (; now; now &= now - 1) {
          const int q = __ffs(now) - 1;
          bulk_load(base + (oent(3 * nsteps + 2 + (q >> 2)) & 7) * 32768 + (q & 3) * 8192, sched.part + (grp * 8 + q) * 4096, 8192, bars + R_PART + 8 * (q >> 1));
        }
      }
      }
    } else if (warp < 3) {
      const int w = warp - 1, n1 = w * NPUB + (spare ? 3 : 5) + nitems;
      #pragma unroll 1
      for (int n = w * NPUB; n < n1; n++) {
        #pragma unroll 1
        for (int k = 0; k < 8 * WAIT_LIM; k++) { if (mbar_try(bars + B_PUB + 8 * n, 0)) break; }
        const uint32_t idx = lds_u32(base + SM_MAIL + 4 * n);
        fence_async_global();
        if (lane == 0 && idx < (unsigned)C_END) red_release(idx);
        __syncwarp();
      }
    } else {
      *reinterpret_cast<volatile uint32_t*>(smem_raw + SM_KEY + 48) = tag;
      if (!spare) { mbar_wait(bars + B_AF + 8 * X_AT, 0); bulk_prefetch(xin + (size_t)blockIdx.x * 16 * DM, 16 * DM * 2); }
      #pragma unroll 1
      for (int n = 0; n < 8 + nsteps; n++) {
        if (n == 2 + nitems) n = 7;
        int idx = n == 0 ? C_MOD : n == 1 ? C_H1 : C_MOD2, cnt = n == 0 ? 8 : n == 1 ? 256 : 16;
        if (n == 2) tma_prefetch_2d(&tmWq, (sp.item[0] >> 3) * 128 + rank * 64, (sp.item[0] & 7) * 64);
        if (n >= 2 && n < 7) { idx = C_KV + (sp.item[n - 2] >> 3); cnt = 32; }
        if (n >= 8) { const int c0 = sp.ochunk[n - 8][0], c1 = sp.ochunk[n - 8][1]; idx = C_CTX + (((lane & 1) && c0 < 64 ? c0 : c1) >> 1) * 8 + (ot & 7); cnt = 4; }
        wait_count_lazy(idx, cnt * tag);
        w_arrive(bars + B_RDY + 8 * n);
        if (n == 8 + PF_N - 1) {
          #pragma unroll 1
          for (int k = 0; k < 8 * WAIT_LIM; k++) { if (mbar_try(bars + R_NEAR, 0)) break; }
          bulk_prefetch(w_o + (size_t)blockIdx.x * (NH * DH * DM / NCTA), NH * DH * DM / NCTA * 2);
          #pragma unroll 1
          for (int k = 0; k < PF_N; k++) {
            const int cc = sp.ochunk[k][(ot >> 3) & 1];
            if (cc < 64) bulk_prefetch(sched.kvc + ((size_t)(128 + cc) * SEQ + m * 128) * 64, 16384);
          }
        }
      }
    }
    __syncwarp();
    cluster_arrive();
    if (!spare) {
      bar_sync(6, 128);
      asm volatile("setmaxnreg.inc.sync.aligned.u32 88;");
      const int pos = blockIdx.x * 4 + (lane & 1) * 2, col = (blockIdx.x >> 2) * 16 + (blockIdx.x & 3) * 2 + (lane & 1) * 8, src = threadIdx.x >> 1;
      uint32_t gbest = 0, hh = 0, gbf = 0;
      uint2 xx = make_uint2(0, 0);
      uint4 ya = make_uint4(0, 0, 0, 0), yb = make_uint4(0, tag, 0, tag);
      auto poll_y = [&]() {
        if (ya.y != tag || ya.w != tag) ya = ld_tagged2(&g_x.yll[src][pos]);
        if (yb.y != tag || yb.w != tag) yb = ld_tagged2(&g_x.yll[src + 64][pos]);
        return __all_sync(0xffffffff, ya.y == tag && ya.w == tag && yb.y == tag && yb.w == tag);
      };
      ya.y = tag - 1; if (src + 64 < FF / 16) yb.y = tag - 1;
      if (warp == 3) {
        gbf = __ldcg(reinterpret_cast<const uint32_t*>(g_x.mod + 5 * DM + col));
        uint32_t have = 0;
        uint2 k[4];
        #pragma unroll
        for (int i = 0; i < 4; i++) k[i] = make_uint2(0, tag - 1);
        #pragma unroll 1
        for (int n = 0; n < WAIT_LIM; n++) {
          #pragma unroll
          for (int i = 0; i < 4; i++) if (k[i].y != tag) k[i] = ld_tagged(&g_x.keys[i * 32 + lane][0]);
          if (gbest != have) {
            const int g = ((0xffffu - gbest) >> 4) & 127;
            uint4 hv[4];
            #pragma unroll
            for (int i = 0; i < 4; i++) hv[i] = ld_tagged2(&g_x.row[g][0][i * 64 + lane * 2]);
            xx = ld_tagged(&g_x.row[g][1][(col >> 8) * 128 + ((col >> 2) & 1) * 64 + ((col >> 3) & 31) * 2 + ((col >> 1) & 1)]);
            bool ok = xx.y == tag;
            #pragma unroll
            for (int i = 0; i < 4; i++) { ok = ok && hv[i].y == tag && hv[i].w == tag; reinterpret_cast<uint2*>(smem_raw + SM_H2)[(i >> 1) * 64 + lane * 2 + (i & 1)] = make_uint2(hv[i].x, hv[i].z); }
            if (lane == 0) *reinterpret_cast<uint32_t*>(smem_raw + SM_KEY + 32) = gbest;
            have = __all_sync(0xffffffff, ok) ? gbest : 0;
          }
          bool all = true;
          #pragma unroll
          for (int i = 0; i < 4; i++) { all = all && k[i].y == tag; gbest = max(gbest, k[i].y == tag ? k[i].x : 0u); }
          gbest = __reduce_max_sync(0xffffffff, gbest);
          if (__all_sync(0xffffffff, all) && gbest == have) break;
        }
        __syncwarp();
        w_arrive(bars + R_KEY);
        if (blockIdx.x == 0 && lane == 0) g_x.epoch = tag;
        hh = lds_u32(base + SM_H2 + col * 2);
      }
      const float rsel = rbf(__uint_as_float((((gbest & 0x80000000u) ? gbest & 0x7fffffffu : ~gbest) & 0xfffff000u) | 0x800u));
      const float rs = rbf(__fdividef(1.f, 1.f + __expf(-rsel)));
      bar_sync(9, 384);
      #pragma unroll 1
      for (int n = 0; n < WAIT_LIM; n++) { if (poll_y()) break; }
      float y0 = __uint_as_float(ya.x) + __uint_as_float(yb.x), y1 = __uint_as_float(ya.z) + __uint_as_float(yb.z);
      #pragma unroll
      for (int o = 2; o < 32; o <<= 1) { y0 += __shfl_xor_sync(0xffffffff, y0, o); y1 += __shfl_xor_sync(0xffffffff, y1, o); }
      float2* s_y = reinterpret_cast<float2*>(smem_raw + SM_KEY + 64);
      if (lane < 2) s_y[warp * 2 + lane] = make_float2(y0, y1);
      bar_sync(6, 128);
      if (warp == 3 && lane < 2) {
        y0 = 0.f; y1 = 0.f;
        #pragma unroll
        for (int i = 0; i < 4; i++) { y0 += reinterpret_cast<const float*>(s_y)[i * 4 + lane]; y1 += reinterpret_cast<const float*>(s_y)[i * 4 + 2 + lane]; }
        const float o0 = bf_lo(xx.x) + rbf(bf_lo(gbf) * rbf(bf_lo(hh) + rbf(rbf(y0) * rs)));
        const float o1 = bf_hi(xx.x) + rbf(bf_hi(gbf) * rbf(bf_hi(hh) + rbf(rbf(y1) * rs)));
        *reinterpret_cast<uint32_t*>(out + (size_t)((0xffffu - gbest) & (SEQ - 1)) * DM + col) = pack_bf16(o0, o1);
      }
    }
    __syncwarp();
    cluster_wait();
  } else {
    asm volatile("setmaxnreg.inc.sync.aligned.u32 240;");
    Ctx x;
    x.w = wg - 1; x.base = base; x.bars = bars; x.nev = 0; x.sched = &sched;
    const int w = x.w, warp4 = warp & 3;
    x.rel = mapa(bars, (warp4 & 1) ^ 1);
    x.rel1 = (threadIdx.x & 127) == 32 || (threadIdx.x & 127) == 64;
    if (warp != 8 || spare) cluster_wait();
    if (w == 1 || spare) bar_sync(7 + w, 256);
    uint32_t PA[32], PB[32];
    int vtile = -1;
    if (spare) {
      mod_cta(x, cvec);
    } else {
      const int lane = wg_tid() & 31;
      Row xn[2];
      float acc0[64], acc1[64];
      int s = 2 * w, ph = w;
      #pragma unroll 1
      for (int u = w; u < 8; u += 2) {
        bar_sync(1 + w, 256);
        int ps = 0;
        #pragma unroll 1
        for (int kb = 0; kb < 8; kb++) {
          if (u < 2) mbar_wait(bars + B_AF + 8 * kb, 0);
          mbar_wait(bars + B_WF + 8 * s, ph);
          const uint32_t da = desc_lo(base + k_addrA(kb), 16), dw = desc_lo(base + k_addrW(s), 8192);
          wgmma_fence();
          kblock_n128<0>(acc0, da, dw, kb != 0);
          kblock_n128<512>(acc1, da, dw, kb != 0);
          wgmma_commit();
          if (kb == 7) bar_arrive(1 + (w ^ 1), 256);
          if (kb > 0) {
            wgmma_wait<1>();
            mbar_arrive_remote_if(x.rel + B_WE + 8 * ps, x.rel1);
            if (u == 7 && !(kb & 1)) {
              ring_release(x, kb == 2 ? 0 : kb - 3, false);
              if (kb > 2) ring_release(x, kb - 2, false);
            }
          }
          ps = s;
          if (++s == 6) { s = 0; ph ^= 1; }
        }
        Row t[2];
        const int lrow = blockIdx.x * 16 + w * 8 + warp4 * 2;
        if (u == w) { t[0] = ldg_row(xin + (size_t)lrow * DM, lane); t[1] = ldg_row(xin + (size_t)(lrow + 1) * DM, lane); }
        if (u == LN_AT || u == LN_AT + 1) {
          mbar_wait(bars + R_MOD, 0);
          t[0] = ldca_row(g_x.mod, lane); t[1] = ldca_row(g_x.mod + DM, lane);
        }
        wgmma_wait<0>();
        fence_regs(acc0); fence_regs(acc1);
        mbar_arrive_remote_if(x.rel + B_WE + 8 * ps, x.rel1);
        if (u == 6) { for (int k = 0; k < 5; k++) ring_release(x, k, false); }
        if (u >= 6) ring_release(x, 5, false);
        if (u == 7) {
          pack_tile(acc0, PA, 1.f, 1.f); pack_tile(acc1, PB, 1.f, 1.f);
          vtile = sp.khead[3] * 16 + mt;
          break;
        }
        s += 2; ph ^= 1; if (s >= 6) { s -= 6; ph ^= 1; }
        if (u == 0) bar_sync(7, 256);
        if (u == w) {
          float st[4] = {0.f, 0.f, 0.f, 0.f};
          #pragma unroll
          for (int i = 0; i < 32; i++) { const float v = row_at(t[i >> 4], i & 15); st[(i >> 4) * 2] += v; st[(i >> 4) * 2 + 1] = fmaf(v, v, st[(i >> 4) * 2 + 1]); }
          warp_sums(st);
          #pragma unroll
          for (int r = 0; r < 2; r++) { ln_stats(st[2*r], st[2*r+1]); xn[r] = ln_apply(t[r], st[2*r], st[2*r+1] * QSCALE); }
        }
        if ((u == LN_AT || u == LN_AT + 1)) {
          #pragma unroll
          for (int r = 0; r < 2; r++) {
            const Row hr = fma_row(xn[r], one_plus(t[1]), t[0]);
            __nv_bfloat16* hp = sched.h1 + (lrow & ~63) * DM + (lane >> 3) * 4096 + ((lrow + r) & 63) * 64 + (((lane ^ (lrow + r)) & 7) << 3);
            stg_v4(hp, hr.v[0], hr.v[1], hr.v[2], hr.v[3]); stg_v4(hp + 4 * 4096, hr.v[4], hr.v[5], hr.v[6], hr.v[7]);
          }
        }
        const int tile = sp.khead[u >> 1] * 16 + mt;
        __nv_bfloat16* dst = kv_tile(x, tile);
        uint32_t D[32];
        pack_tile(acc0, D, 1.f, 1.f); store_tile(dst + 2048, D);
        pack_tile(acc1, D, 1.f, 1.f); store_tile(dst, D);
        if (u == LN_AT || u == LN_AT + 1) publish(x, C_H1);
        publish(x, C_KV + (tile >> 4));
      }
    }
    const int last = attention(x, sp.item, nitems, rank, PA, PB, vtile);
    const int lane = wg_tid() & 31, cw = w * 4 + warp4;
    const int row0 = grp * 16 + cw * 2;
    const bool moe_cta = blockIdx.x < FF / 16;
    if (spare) { store_ctx(x, last, PB); __syncwarp(); cluster_arrive(); cluster_wait(); return; }
    const int kl = 3 * nsteps - 3;
    uint2* const yp = &g_x.yll[blockIdx.x][cw * 64 + (lane & 3) * 16 + (lane >> 2) * 2];
    Row ga, sb, cb, gb, wr;
    unsigned int tag;
    {
      float accA[64], accB[64];
      const int t0 = oent(0) == oent(1);
      uint32_t pa = 0, pb = 0;
      #pragma unroll 1
      for (int t = t0; t < 2 * nsteps - 2; t++) {
        const uint32_t eb = oent(3 * (t >> 1) + 2 * (t & 1)), ea = oent(3 * (t >> 1) + 1);
        o_wait_full(bars, eb);
        o_wait_full(bars, ea);
        const uint32_t da = desc_lo(base + w * 4096, 16) + (ea & 7) * 2048 + (t & 1) * 1024, db = desc_lo(base, 8192) + (eb & 7) * 2048;
        wgmma_fence();
        kblock_n128<0, 0, SW64>(accA, da, db, t != t0); kblock_n128<0, 1024, SW64>(accB, da, db, t != t0);
        wgmma_commit();
        if (t == CTX_T) store_ctx(x, last, PB);
        if (t > t0) { wgmma_wait<1>(); slot_release(x, pb, false); if (!(t & 1)) slot_release(x, pa, false); }
        pa = ea & 7; pb = eb & 7;
      }
      const uint32_t e0 = oent(kl), ea = oent(kl + 1), eb = oent(kl + 2);
      const uint32_t da = desc_lo(base + w * 4096, 16) + (ea & 7) * 2048;
      const uint32_t db0 = desc_lo(base, 8192) + (e0 & 7) * 2048, db1 = desc_lo(base, 8192) + (eb & 7) * 2048;
      ga = ldca_row(g_x.mod + 2 * DM, lane); sb = ldca_row(g_x.mod + 3 * DM, lane); cb = ldca_row(g_x.mod + 4 * DM, lane); gb = ldca_row(g_x.mod + 5 * DM, lane);
      wr = ldca_row(w_r, lane);
      tag = lds_u32(base + SM_KEY + 48);
      if (moe_cta) st_tagged2(yp, 0, 0, 0);
      const bool lead = (nitems & 1) == w;
      o_wait_full(bars, e0);
      o_wait_full(bars, ea);
      o_wait_full(bars, eb);
      if (!lead) bar_sync(1, 256);
      wgmma_fence();
      kblock_n128<0, 0, SW64>(accA, da, db0, 1); kblock_n128<1024, 0, SW64>(accA, da, db1, 1);
      wgmma_commit();
      kblock_n128<0, 1024, SW64>(accB, da, db0, 1); kblock_n128<1024, 1024, SW64>(accB, da, db1, 1);
      wgmma_commit();
      if (lead) bar_arrive(1, 256);
      wgmma_wait<2>();
      slot_release(x, pa, false); slot_release(x, pb, false);
      __syncwarp();
      cluster_arrive();
      const uintptr_t dst = reinterpret_cast<uintptr_t>(sched.part + ((m * 8 + cw) * 8 + (ot >> 3)) * 4096 + lane * 8);
      const uint32_t even = ~lane & 1;
      auto send = [&](const float (&acc)[64], int h) {
        uint32_t D[32];
        pack_tile(acc, D, 1.f, 1.f);
        #pragma unroll
        for (int i = 0; i < 8; i++) stg_v4(reinterpret_cast<uint8_t*>(dst ^ ((h * 4 + (i >> 1)) << 4)) + (h * 8 + i) * 512, (D[4*i] & ~even) | (tag & even), D[4*i+1], D[4*i+2], D[4*i+3]);
      };
      wgmma_wait<1>();
      fence_regs(accA);
      send(accA, 0);
      o_wait_full(bars, eb);
      wgmma_wait<0>();
      fence_regs(accB);
      send(accB, 1);
      __syncwarp();
      if (lane == 0) red_relaxed(&g_x.sent[m * 8 + cw][ot >> 3]);
    }
    asm volatile("setmaxnreg.dec.sync.aligned.u32 208;");
    const uint32_t sD = base + (oent(kl + 3) & 7) * 32768, sW = base + (oent(kl + 4) & 7) * 32768;
    o_wait_full(bars, oent(kl + 3)); o_wait_full(bars, oent(kl + 4));
    Row x1[2];
    #pragma unroll
    for (int r = 0; r < 2; r++) x1[r] = lds_row(sD + 16384 + (cw * 2 + r) * 1024, lane);
    uint4 wgv[4], wuv[4], wdv[4];
    #pragma unroll
    for (int r = 0; r < 4; r++) {
      const uint32_t k = (lane & 7) + ((lane >> 4) << 3), h = (lane >> 3) & 1;
      wgv[r] = ldsm_x4_t(sW + (cw * 64 + r * 16 + k) * 32 + ((h ^ ((lane >> 2) & 1)) << 4));
      wuv[r] = ldsm_x4_t(sW + 16384 + (cw * 64 + r * 16 + k) * 32 + ((h ^ ((lane >> 2) & 1)) << 4));
      wdv[r] = ldsm_x4_t(sD + cw * 2048 + k * 128 + (((r * 2 + h) ^ (lane & 7)) << 4));
    }
    const Row cb1 = one_plus(cb);
    float u[16], ub[2] = {0.f, 0.f};
    #pragma unroll
    for (int i = 0; i < 16; i++) { u[i] = row_at(cb1, i) * row_at(wr, i); ub[0] += u[i]; ub[1] = fmaf(row_at(sb, i), row_at(wr, i), ub[1]); }
    warp_sums(ub);
    float st[6] = {0.f, 0.f, 0.f, 0.f, 0.f, 0.f};
    uint32_t key[2];
    {
      const uint32_t po = base + ((lane & 7) * 2 + (cw >> 2)) * 512 + (cw & 3) * 128;
      const uint32_t par = (lane & 3) == 0 ? tag & 1 : 0;
      Row av[2][2];
      #pragma unroll 1
      for (int n = 0; n < WAIT_LIM; n++) {
        uint32_t late = 0;
        #pragma unroll
        for (int k = 0; k < 4; k++) {
          mbar_wait(bars + R_PART + 8 * k, 1);
          late = (late & 7) * 2;
          uint32_t odd = 0;
          const uint32_t pa = po + (oent(kl + 5 + (k >> 1)) & 7) * 32768 + (k & 1) * 16384;
          #pragma unroll
          for (int r = 0; r < 2; r++) {
            const uint32_t sw = ((r * 4 + (lane >> 3)) ^ (lane & 7)) << 4;
            const uint4 lo = ldsm_x4(pa + sw), hi = ldsm_x4(pa + 8192 + sw);
            const Row v{{lo.x ^ par, lo.y, lo.z ^ par, lo.w, hi.x ^ par, hi.y, hi.z ^ par, hi.w}};
            odd |= v.v[0] | v.v[2] | v.v[4] | v.v[6];
            av[r][k >> 1] = (k & 1) ? add_row(av[r][k >> 1], v) : v;
          }
          late |= odd & 1;
        }
        late = __reduce_or_sync(0xffffffff, (lane & 3) == 0 ? late : 0);
        if (!late) break;
        #pragma unroll 1
        for (; late; late &= late - 1) {
          const int k = 4 - __ffs(late);
          const uint32_t off = (k & 1) * 16384 + ((lane >> 3) * 2 + (cw >> 2)) * 512 + (cw & 3) * 128 + (lane & 7) * 16;
          uint4 v[4];
          #pragma unroll
          for (int i = 0; i < 4; i++) v[i] = ld_tagged2(reinterpret_cast<const uint8_t*>(sched.part + (grp * 8 + (k >> 1) * 4) * 4096) + off + i * 4096);
          #pragma unroll
          for (int i = 0; i < 4; i++) sts_v4(base + (oent(kl + 5 + (k >> 1)) & 7) * 32768 + off + i * 4096, v[i].x, v[i].y, v[i].z, v[i].w);
        }
        __syncwarp();
      }
      #pragma unroll
      for (int r = 0; r < 2; r++) {
        x1[r] = fma_row(ga, add_row(av[r][0], av[r][1]), x1[r]);
        #pragma unroll
        for (int i = 0; i < 16; i++) { const float v = row_at(x1[r], i); st[3*r] += v; st[3*r+1] = fmaf(v, v, st[3*r+1]); st[3*r+2] = fmaf(v, u[i], st[3*r+2]); }
      }
      warp_sums(st);
      #pragma unroll
      for (int r = 0; r < 2; r++) {
        ln_stats(st[3*r], st[3*r+1]);
        const uint32_t rb = __float_as_uint(fmaf(st[3*r+1], fmaf(-st[3*r], ub[0], st[3*r+2]), ub[1]));
        key[r] = (((rb & 0x80000000u) ? ~rb : (rb | 0x80000000u)) & 0xfffff000u) | (0xfffu - (uint32_t)(row0 + r));
      }
    }
    float* s_red = reinterpret_cast<float*>(smem_raw + SM_RED);
    uint32_t* s_key = reinterpret_cast<uint32_t*>(smem_raw + SM_KEY);
    const int rb = key[1] > key[0];
    const uint32_t wbest = rb ? key[1] : key[0];
    if (lane == 0) s_key[cw] = wbest;
    bar_sync(5, 256);
    const uint32_t cbest = __reduce_max_sync(0xffffffff, s_key[lane & 7]);
    if (wbest == cbest && lane == 0) st_tagged(&g_x.keys[grp][0], cbest, tag);
    Row xb, xo;
    #pragma unroll
    for (int i = 0; i < 8; i++) { xb.v[i] = rb ? x1[1].v[i] : x1[0].v[i]; xo.v[i] = rb ? x1[0].v[i] : x1[1].v[i]; }
    const Row hb = fma_row(ln_apply(xb, rb ? st[3] : st[0], rb ? st[4] : st[1]), cb1, sb);
    if (wbest == cbest) {
      #pragma unroll
      for (int i = 0; i < 4; i++) st_tagged2(&g_x.row[grp][0][i * 64 + lane * 2], hb.v[2*i], hb.v[2*i+1], tag);
      #pragma unroll
      for (int i = 0; i < 4; i++) st_tagged2(&g_x.row[grp][1][i * 64 + lane * 2], xb.v[2*i], xb.v[2*i+1], tag);
    }
    const Row ob = fma_row(gb, hb, xb);
    if (wbest != cbest) store_row(out + (size_t)(row0 + rb) * DM, lane, ob);
    store_row(out + (size_t)(row0 + 1 - rb) * DM, lane, fma_row(gb, fma_row(ln_apply(xo, rb ? st[0] : st[3], rb ? st[1] : st[4]), cb1, sb), xo));
    mbar_wait(bars + R_KEY, 1);
    if (moe_cta) {
      float cg[4] = {0, 0, 0, 0}, cu[4] = {0, 0, 0, 0};
      #pragma unroll
      for (int r = 0; r < 4; r++) {
        const uint32_t b0 = lds_u32(base + SM_H2 + (cw * 64 + r * 16) * 2 + (lane & 3) * 4), b1 = lds_u32(base + SM_H2 + (cw * 64 + r * 16) * 2 + 16 + (lane & 3) * 4);
        mma16816(cg, wgv[r], b0, b1); mma16816(cu, wuv[r], b0, b1);
      }
      s_red[cw * 32 + (lane & 3) * 8 + (lane >> 2)] = (lane & 2) ? ((lane & 1) ? cu[2] : cu[0]) : ((lane & 1) ? cg[2] : cg[0]);
      bar_sync(5, 256);
      float g = 0.f;
      #pragma unroll
      for (int i = 0; i < 8; i++) g += s_red[i * 32 + lane];
      g = rbf(g);
      const float act = rbf(__fdividef(g, 1.f + __expf(-g))) * __shfl_down_sync(0xffffffff, g, 16);
      const uint32_t a2 = pack_bf16(act, __shfl_down_sync(0xffffffff, act, 1));
      const uint32_t b0 = __shfl_sync(0xffffffff, a2, (lane & 3) * 2), b1 = __shfl_sync(0xffffffff, a2, (lane & 3) * 2 + 8);
      float y0 = 0.f, y1 = 0.f;
      #pragma unroll
      for (int r = 0; r < 4; r++) {
        float c[4] = {0, 0, 0, 0};
        mma16816(c, wdv[r], b0, b1);
        if ((lane & 3) == r) { y0 = c[0]; y1 = c[2]; }
      }
      st_tagged2(yp, __float_as_uint(y0), __float_as_uint(y1), tag);
    }
    bar_arrive(9, 384);
    if (wbest == cbest && wbest != s_key[8]) store_row(out + (size_t)(row0 + rb) * DM, lane, ob);
    __syncwarp();
    cluster_wait();
  }
}

typedef CUresult (*EncodeFn)(CUtensorMap*, CUtensorMapDataType, cuuint32_t, void*, const cuuint64_t*, const cuuint64_t*, const cuuint32_t*,
                             const cuuint32_t*, CUtensorMapInterleave, CUtensorMapSwizzle, CUtensorMapL2promotion, CUtensorMapFloatOOBfill);

struct HostState {
  bool ready = false;
  EncodeFn encode = nullptr;
  CUtensorMap tmC, tmWq, tmWk, tmWv, tmWo, tmWg, tmWu, tmWd, tmWm;
  Sched sched;
};

void make_map(EncodeFn enc, CUtensorMap* m, const void* ptr, int rank, const cuuint64_t* dims, const cuuint64_t* strides, const cuuint32_t* box, bool wide = true) {
  const cuuint32_t es[3] = {1, 1, 1};
  enc(m, CU_TENSOR_MAP_DATA_TYPE_BFLOAT16, rank, const_cast<void*>(ptr), dims, strides, box, es, CU_TENSOR_MAP_INTERLEAVE_NONE,
      wide ? CU_TENSOR_MAP_SWIZZLE_128B : CU_TENSOR_MAP_SWIZZLE_32B, wide ? CU_TENSOR_MAP_L2_PROMOTION_L2_128B : CU_TENSOR_MAP_L2_PROMOTION_NONE, CU_TENSOR_MAP_FLOAT_OOB_FILL_NONE);
}
void make_2d(EncodeFn enc, CUtensorMap* m, const void* ptr, int rows, int cols, int box_rows) {
  const cuuint64_t dims[2] = {(cuuint64_t)cols, (cuuint64_t)rows}, strides[1] = {(cuuint64_t)cols * 2};
  const cuuint32_t box[2] = {64, (cuuint32_t)box_rows};
  make_map(enc, m, ptr, 2, dims, strides, box);
}
void make_3d(EncodeFn enc, CUtensorMap* m, const void* ptr, int rows, int chunks, size_t row_stride, size_t chunk_stride, int box_rows = 64, int box_chunks = 2) {
  const cuuint64_t dims[3] = {64, (cuuint64_t)rows, (cuuint64_t)chunks}, strides[2] = {row_stride, chunk_stride};
  const cuuint32_t box[3] = {64, (cuuint32_t)box_rows, (cuuint32_t)box_chunks};
  make_map(enc, m, ptr, 3, dims, strides, box);
}

void make_ffn(EncodeFn enc, CUtensorMap* m, const void* ptr) {
  const cuuint64_t dims[2] = {(cuuint64_t)FF, (cuuint64_t)DM}, strides[1] = {(cuuint64_t)FF * 2};
  const cuuint32_t box[2] = {16, 256};
  make_map(enc, m, ptr, 2, dims, strides, box, false);
}

#define SR 0x213312
#define SEED 12345
#define SPARE_N 3
void build_sched(Sched& s) {
  memset(&s, 0, sizeof(s));
  const int NP = NCTA / 2, korder[4] = {(KORDER >> 12) & 3, (KORDER >> 8) & 3, (KORDER >> 4) & 3, KORDER & 3};
  const int sround[4][2][3] = {{}, {{1}, {2}}, {{1, 2}, {1, 2}}, {{(SR >> 20) & 3, (SR >> 16) & 3, (SR >> 12) & 3}, {(SR >> 8) & 3, (SR >> 4) & 3, SR & 3}}};
  int jv[4][NP], used[4][8] = {};
  for (int r = 0; r < 4; r++) for (int p = 0; p < NP; p++) jv[r][p] = (r & 2) ? 7 - ((p + 4 * (r & 1)) & 7) : (p + 4 * (r & 1)) & 7;
  for (int q = 0; q < 2; q++) {
    s.pair[NP + q].nitems = SPARE_N;
    for (int i = 0; i < SPARE_N; i++) {
      const int r = sround[SPARE_N][q][i];
      s.pair[NP + q].item[i] = (uint8_t)((r * 8 + used[r][6]++) * 8 + 6);
      for (int p = 0; p < NP; p++) if (jv[r][p] == 6) { jv[r][p] = -2; break; }
    }
  }
  auto cost = [&](int p) {
    int u = 8 - ((p >> 4) < SPARE_N ? 21 : 22), z = 0, none = 0;
    for (int r = 0; r < 4; r++) { u += jv[r][p]; z += jv[r][p] == 0; none += jv[r][p] < 0; }
    return 4 * u * u + (z > 1) + 4 * (none > 1);
  };
  uint32_t rng = SEED;
  for (int it = 0; it < 2000000; it++) {
    if ((it & 255) == 0) { int t = 0; for (int p = 0; p < NP; p++) t += cost(p); if (t == 0) break; }
    rng = rng * 1664525u + 1013904223u;
    const int r = (rng >> 8) & 3, a = (rng >> 12) & 63, b = (rng >> 20) & 63, before = cost(a) + cost(b);
    int t = jv[r][a]; jv[r][a] = jv[r][b]; jv[r][b] = t;
    if (cost(a) + cost(b) > before) { jv[r][b] = jv[r][a]; jv[r][a] = t; }
  }
  int done[256];
  for (int p = 0; p < NP + 2; p++) {
    Sched::Pair& q = s.pair[p];
    if (p < NP) {
      for (int k = 0; k < 4; k++) q.khead[k] = (uint8_t)(korder[k] * 8 + (p >> 3));
      for (int r = 0; r < 4; r++) {
        if (jv[r][p] < 0) continue;
        q.item[q.nitems++] = (uint8_t)((r * 8 + used[r][jv[r][p]]++) * 8 + jv[r][p]);
      }
    }
    int t = p < NP ? 0 : -3, e = 1;
    for (int i = 0; i < q.nitems; i++) { t += (q.item[i] & 7) + 2; done[q.item[i]] = t + (i + 1 < q.nitems ? 2 : 0); e += 8 + 4 * ((q.item[i] & 7) + 1); }
    for (int k = 0; k < 3 * MAX_STEPS + 6; k++) {
      const int n = k > 0 ? k - (SPARE_N & 1) : 0, r = n % 7, f = (e + (r < 4 ? r : r - 1)) % 12;
      q.oent[k] = (uint8_t)((r == 4 ? 6 : f >= 6 ? f + 2 : f) ^ (((n / 7) & 1) << 3));
    }
  }
  for (int j = 0; j < 8; j++) {
    int order[NH], left[4];
    for (int h = 0; h < NH; h++) { int k = h; for (; k > 0 && done[order[k - 1] * 8 + j] < done[h * 8 + j]; k--) order[k] = order[k - 1]; order[k] = h; }
    for (int kq = 0; kq < 4; kq++) {
      left[kq] = SPARE_N == 0 ? 16 : kq < SPARE_N ? 20 - SPARE_N : 16 - SPARE_N;
      for (int nh = 0; nh < 2; nh++) { Sched::Pair& q = s.pair[kq * 16 + nh * 8 + j]; q.otask = (uint8_t)(kq * 16 + nh * 8 + j); q.nsteps = (uint8_t)((left[kq] + 1) / 2); q.ochunk[0][0] = 255; }
    }
    for (int n = 0, kq = 0, run = 0; n < 64; ) {
      if (left[kq] > 0 && run < 2) {
        const int pos = --left[kq] + (SPARE_N & 1);
        for (int nh = 0; nh < 2; nh++) s.pair[kq * 16 + nh * 8 + j].ochunk[pos >> 1][pos & 1] = (uint8_t)(order[n >> 1] * 2 + 1 - (n & 1));
        n++; run++;
      } else { kq = (kq + 1) & 3; run = 0; }
    }
  }
}

}

extern "C" void kernel_launch(void* const* d_in, const int* in_sizes, int n_in, void* d_out, int out_size) {
  (void)in_sizes; (void)n_in; (void)out_size;
  const __nv_bfloat16* x     = (const __nv_bfloat16*)d_in[0];
  const __nv_bfloat16* ckv   = (const __nv_bfloat16*)d_in[1];
  const __nv_bfloat16* w_q   = (const __nv_bfloat16*)d_in[2];
  const __nv_bfloat16* w_uk  = (const __nv_bfloat16*)d_in[3];
  const __nv_bfloat16* w_uv  = (const __nv_bfloat16*)d_in[4];
  const __nv_bfloat16* w_o   = (const __nv_bfloat16*)d_in[5];
  const __nv_bfloat16* w_r   = (const __nv_bfloat16*)d_in[7];
  const __nv_bfloat16* w_g   = (const __nv_bfloat16*)d_in[8];
  const __nv_bfloat16* w_u   = (const __nv_bfloat16*)d_in[9];
  const __nv_bfloat16* w_d   = (const __nv_bfloat16*)d_in[10];
  const __nv_bfloat16* cvec  = (const __nv_bfloat16*)d_in[11];
  const __nv_bfloat16* w_mod = (const __nv_bfloat16*)d_in[12];
  __nv_bfloat16* out = (__nv_bfloat16*)d_out;

  static HostState st;
  if (!st.ready) {
    void* fn = nullptr; cudaDriverEntryPointQueryResult qr;
    cudaGetDriverEntryPoint("cuTensorMapEncodeTiled", &fn, cudaEnableDefault, &qr);
    st.encode = (EncodeFn)fn;
    cudaFuncSetAttribute(k_fused, cudaFuncAttributeMaxDynamicSharedMemorySize, SMEM);
    build_sched(st.sched);
    void *p_kvc, *p_h1, *p_part;
    cudaGetSymbolAddress(&p_kvc, g_kvc); cudaGetSymbolAddress(&p_h1, g_h1); cudaGetSymbolAddress(&p_part, g_part);
    st.sched.kvc = (__nv_bfloat16*)p_kvc; st.sched.h1 = (__nv_bfloat16*)p_h1; st.sched.part = (__nv_bfloat16*)p_part;
    st.ready = true;
  }
  make_2d(st.encode, &st.tmC, ckv, SEQ, DM, 128);
  make_2d(st.encode, &st.tmWq, w_q, DM, NH * DH, 64);
  make_2d(st.encode, &st.tmWk, w_uk, DM, NH * DH, 64);
  make_2d(st.encode, &st.tmWv, w_uv, DM, NH * DH, 64);
  make_3d(st.encode, &st.tmWo, w_o, NH * DH, DM / 64, (size_t)DM * 2, 128);
  make_3d(st.encode, &st.tmWm, w_mod, DM, 6 * DM / 64, (size_t)6 * DM * 2, 128);
  make_3d(st.encode, &st.tmWd, w_d, FF, DM / 64, (size_t)DM * 2, 128, 16, 8);
  make_ffn(st.encode, &st.tmWg, w_g);
  make_ffn(st.encode, &st.tmWu, w_u);

  k_fused<<<NGRID, 384, SMEM, cudaStreamPerThread>>>(st.tmC, st.tmWq, st.tmWk, st.tmWv, st.tmWo, st.tmWg, st.tmWu, st.tmWd, st.tmWm, st.sched,
                                                     x, cvec, w_o, w_r, w_g, w_u, w_d, out);
}
```

```cpp
#include <cuda_runtime.h>
#include <cuda_bf16.h>
#include <cuda.h>
#include <stdint.h>
#include <string.h>
#include <math.h>

namespace {

constexpr int SEQ = 2048, DM = 512, NH = 32, DH = 128, FF = 1792;
constexpr int NCTA = 128, NGRID = 132;

__device__ __align__(128) __nv_bfloat16 g_kvc[192 * SEQ * 64];
__device__ __align__(128) __nv_bfloat16 g_h1[SEQ * DM];
__device__ __align__(128) __nv_bfloat16 g_part[128 * 8 * 4096];
constexpr int C_MOD = 0, C_MOD2 = 16, C_H1 = 32, C_KV = 64, C_CTX = 128, C_END = 384;
struct Exchange {
  uint2 keys[128][4];
  uint2 row[128][2][DM / 2];
  uint2 yll[FF / 16][DM];
  __nv_bfloat16 mod[6 * DM];
  unsigned int sent[128][32];
  unsigned int cnt[C_END];
  unsigned int epoch;
};
__device__ __align__(4096) Exchange g_x;


__device__ __forceinline__ uint32_t smem_u32(const void* p) { return (uint32_t)__cvta_generic_to_shared(p); }
__device__ __forceinline__ int wg_tid() { int t; asm volatile("mov.u32 %0, %%tid.x;" : "=r"(t)); return t & 127; }
__device__ __forceinline__ void mbar_arrive(uint32_t bar) { asm volatile("mbarrier.arrive.shared::cta.b64 _, [%0];" :: "r"(bar) : "memory"); }
__device__ __forceinline__ uint32_t mapa(uint32_t addr, uint32_t cta) { uint32_t r; asm("mapa.shared::cluster.u32 %0, %1, %2;" : "=r"(r) : "r"(addr), "r"(cta)); return r; }
__device__ __forceinline__ void mbar_arrive_remote_if(uint32_t cluster_addr, bool pred) {
  asm volatile("{\n.reg .pred p;\nsetp.ne.u32 p, %1, 0;\n@p mbarrier.arrive.shared::cluster.b64 _, [%0];\n}" :: "r"(cluster_addr), "r"((uint32_t)pred) : "memory");
}
__device__ __forceinline__ bool mbar_try(uint32_t bar, uint32_t parity) {
  uint32_t done;
  asm volatile("{\n.reg .pred p;\nmbarrier.try_wait.parity.shared::cta.b64 p, [%1], %2;\nselp.u32 %0, 1, 0, p;\n}" : "=r"(done) : "r"(bar), "r"(parity) : "memory");
  return done;
}
__device__ __forceinline__ bool mbar_test2(uint32_t bar, uint32_t parity) {
  uint32_t done;
  asm volatile("{\n.reg .pred p, q;\nmbarrier.test_wait.parity.shared::cta.b64 p, [%1], %2;\nmbarrier.test_wait.parity.shared::cta.b64 q, [%1 + 8], %2;\n"
               "and.pred p, p, q;\nselp.u32 %0, 1, 0, p;\n}" : "=r"(done) : "r"(bar), "r"(parity) : "memory");
  return done;
}
#define WAIT_LIM (1 << 14)
__device__ __forceinline__ void mbar_wait(uint32_t bar, uint32_t parity) {
  #pragma unroll 1
  for (int n = 0; n < WAIT_LIM; n++) { if (mbar_try(bar, parity)) break; }
}
__device__ __forceinline__ unsigned int ld_acquire(const unsigned int* p) {
  unsigned int v; asm volatile("ld.acquire.gpu.global.u32 %0, [%1];" : "=r"(v) : "l"(p) : "memory"); return v;
}
__device__ __forceinline__ unsigned int ld_relaxed(const unsigned int* p) {
  unsigned int v; asm volatile("ld.relaxed.gpu.global.u32 %0, [%1];" : "=r"(v) : "l"(p) : "memory"); return v;
}
__device__ __forceinline__ void wait_count_lazy(int idx, unsigned int target) {
  #pragma unroll 1
  for (int n = 0; n < WAIT_LIM; n++) { if (__all_sync(0xffffffff, (int)(ld_acquire(&g_x.cnt[idx]) - target) >= 0)) break; __nanosleep(100); }
}
__device__ __forceinline__ uint4 ld_tagged2(const void* p) {
  uint4 v;
  asm volatile("{\n.reg .b64 a, b;\nld.relaxed.gpu.global.v2.u64 {a, b}, [%4];\nmov.b64 {%0, %1}, a;\nmov.b64 {%2, %3}, b;\n}"
    : "=r"(v.x), "=r"(v.y), "=r"(v.z), "=r"(v.w) : "l"(p) : "memory");
  return v;
}
__device__ __forceinline__ uint2 ld_tagged(const void* p) {
  uint2 v; asm volatile("{\n.reg .b64 a;\nld.relaxed.gpu.global.u64 a, [%2];\nmov.b64 {%0, %1}, a;\n}" : "=r"(v.x), "=r"(v.y) : "l"(p) : "memory"); return v;
}
__device__ __forceinline__ void st_tagged2(void* p, uint32_t a, uint32_t b, uint32_t tag) {
  asm volatile("{\n.reg .b64 a, b;\nmov.b64 a, {%1, %3};\nmov.b64 b, {%2, %3};\nst.relaxed.gpu.global.v2.u64 [%0], {a, b};\n}" :: "l"(p), "r"(a), "r"(b), "r"(tag) : "memory");
}
__device__ __forceinline__ void st_tagged(void* p, uint32_t a, uint32_t tag) {
  asm volatile("{\n.reg .b64 a;\nmov.b64 a, {%1, %2};\nst.relaxed.gpu.global.u64 [%0], a;\n}" :: "l"(p), "r"(a), "r"(tag) : "memory");
}
__device__ __forceinline__ void stg_v4(void* p, uint32_t a, uint32_t b, uint32_t c, uint32_t d) {
  asm volatile("st.global.v4.u32 [%0], {%1, %2, %3, %4};" :: "l"(p), "r"(a), "r"(b), "r"(c), "r"(d) : "memory");
}
__device__ __forceinline__ uint4 lds_v4(uint32_t addr) {
  uint4 v; asm volatile("ld.shared.v4.u32 {%0, %1, %2, %3}, [%4];" : "=r"(v.x), "=r"(v.y), "=r"(v.z), "=r"(v.w) : "r"(addr) : "memory"); return v;
}
__device__ __forceinline__ uint32_t lds_u32(uint32_t addr) { uint32_t v; asm volatile("ld.shared.u32 %0, [%1];" : "=r"(v) : "r"(addr) : "memory"); return v; }
__device__ __forceinline__ void sts_v4(uint32_t addr, uint32_t a, uint32_t b, uint32_t c, uint32_t d) {
  asm volatile("st.shared.v4.u32 [%0], {%1, %2, %3, %4};" :: "r"(addr), "r"(a), "r"(b), "r"(c), "r"(d) : "memory");
}
#define ELECT "{\n.reg .pred p;\nelect.sync _|p, 0xffffffff;\n@p "
__device__ __forceinline__ void w_mbar_init(uint32_t bar, uint32_t cnt) { asm volatile(ELECT "mbarrier.init.shared::cta.b64 [%0], %1;\n}" :: "r"(bar), "r"(cnt) : "memory"); }
__device__ __forceinline__ void w_expect_tx(uint32_t bar, uint32_t bytes) { asm volatile(ELECT "mbarrier.arrive.expect_tx.shared::cta.b64 _, [%0], %1;\n}" :: "r"(bar), "r"(bytes) : "memory"); }
__device__ __forceinline__ void w_arrive(uint32_t bar) { asm volatile(ELECT "mbarrier.arrive.shared::cta.b64 _, [%0];\n}" :: "r"(bar) : "memory"); }
__device__ __forceinline__ void tma_load_2d(uint32_t dst, const CUtensorMap* tm, uint32_t bar, int c0, int c1) {
  asm volatile(ELECT "cp.async.bulk.tensor.2d.shared::cluster.global.mbarrier::complete_tx::bytes [%0], [%1, {%3, %4}], [%2];\n}"
    :: "r"(dst), "l"(tm), "r"(bar), "r"(c0), "r"(c1) : "memory");
}
__device__ __forceinline__ void tma_load_2d_mc(uint32_t dst, const CUtensorMap* tm, uint32_t bar, int c0, int c1) {
  asm volatile(ELECT "cp.async.bulk.tensor.2d.shared::cluster.global.mbarrier::complete_tx::bytes.multicast::cluster [%0], [%1, {%3, %4}], [%2], %5;\n}"
    :: "r"(dst), "l"(tm), "r"(bar), "r"(c0), "r"(c1), "h"((uint16_t)3) : "memory");
}
__device__ __forceinline__ void tma_load_3d(uint32_t dst, const CUtensorMap* tm, uint32_t bar, int c0, int c1, int c2) {
  asm volatile(ELECT "cp.async.bulk.tensor.3d.shared::cluster.global.mbarrier::complete_tx::bytes [%0], [%1, {%3, %4, %5}], [%2];\n}"
    :: "r"(dst), "l"(tm), "r"(bar), "r"(c0), "r"(c1), "r"(c2) : "memory");
}
__device__ __forceinline__ void tma_load_3d_mc(uint32_t dst, const CUtensorMap* tm, uint32_t bar, int c0, int c1, int c2) {
  asm volatile(ELECT "cp.async.bulk.tensor.3d.shared::cluster.global.mbarrier::complete_tx::bytes.multicast::cluster [%0], [%1, {%3, %4, %5}], [%2], %6;\n}"
    :: "r"(dst), "l"(tm), "r"(bar), "r"(c0), "r"(c1), "r"(c2), "h"((uint16_t)3) : "memory");
}
__device__ __forceinline__ void bulk_load_mc(uint32_t dst, const void* src, uint32_t bar) {
  asm volatile(ELECT "cp.async.bulk.shared::cluster.global.mbarrier::complete_tx::bytes.multicast::cluster [%0], [%1], 16384, [%2], %3;\n}"
    :: "r"(dst), "l"(src), "r"(bar), "h"((uint16_t)3) : "memory");
}
__device__ __forceinline__ void bulk_load(uint32_t dst, const void* src, uint32_t bytes, uint32_t bar) {
  asm volatile(ELECT "cp.async.bulk.shared::cluster.global.mbarrier::complete_tx::bytes [%0], [%1], %2, [%3];\n}" :: "r"(dst), "l"(src), "r"(bytes), "r"(bar) : "memory");
}
__device__ __forceinline__ void tma_prefetch_2d(const CUtensorMap* tm, int c0, int c1) {
  asm volatile(ELECT "cp.async.bulk.prefetch.tensor.2d.L2.global [%0, {%1, %2}];\n}" :: "l"(tm), "r"(c0), "r"(c1) : "memory");
}
__device__ __forceinline__ void bulk_prefetch(const void* p, uint32_t bytes) {
  asm volatile(ELECT "cp.async.bulk.prefetch.L2.global [%0], %1;\n}" :: "l"(p), "r"(bytes) : "memory");
}
__device__ __forceinline__ void red_relaxed(unsigned int* p) { asm volatile("red.relaxed.gpu.global.add.u32 [%0], 1;" :: "l"(p) : "memory"); }
__device__ __forceinline__ void red_release(int idx) { asm volatile("red.release.gpu.global.add.u32 [%0], 1;" :: "l"(&g_x.cnt[idx]) : "memory"); }
__device__ __forceinline__ void prefetch_tmap(const CUtensorMap* tm) { asm volatile("prefetch.tensormap [%0];" :: "l"(tm) : "memory"); }
__device__ __forceinline__ void bar_sync(int id, int n) { asm volatile("bar.sync %0, %1;" :: "r"(id), "r"(n) : "memory"); }
__device__ __forceinline__ void bar_arrive(int id, int n) { asm volatile("bar.arrive %0, %1;" :: "r"(id), "r"(n) : "memory"); }
__device__ __forceinline__ void fence_async_smem() { asm volatile("fence.proxy.async.shared::cta;" ::: "memory"); }
__device__ __forceinline__ void fence_async_global() { asm volatile("fence.proxy.async.global;" ::: "memory"); }
__device__ __forceinline__ void fence_mbar_init() { asm volatile("fence.mbarrier_init.release.cluster;" ::: "memory"); }
__device__ __forceinline__ void cluster_arrive() { asm volatile("barrier.cluster.arrive.relaxed.aligned;" ::: "memory"); }
__device__ __forceinline__ void cluster_wait() { asm volatile("barrier.cluster.wait.aligned;" ::: "memory"); }
__device__ __forceinline__ uint32_t cluster_ctarank() { uint32_t r; asm volatile("mov.u32 %0, %%cluster_ctarank;" : "=r"(r)); return r; }
__device__ __forceinline__ void wgmma_fence() { asm volatile("wgmma.fence.sync.aligned;" ::: "memory"); }
__device__ __forceinline__ void wgmma_commit() { asm volatile("wgmma.commit_group.sync.aligned;" ::: "memory"); }
template<int N> __device__ __forceinline__ void wgmma_wait() { asm volatile("wgmma.wait_group.sync.aligned %0;" :: "n"(N) : "memory"); }
__device__ __forceinline__ float ex2(float x) { float y; asm("ex2.approx.ftz.f32 %0, %1;" : "=f"(y) : "f"(x)); return y; }
__device__ __forceinline__ float rcp_fast(float x) { float y; asm("rcp.approx.ftz.f32 %0, %1;" : "=f"(y) : "f"(x)); return y; }
__device__ __forceinline__ uint32_t pack_bf16(float lo, float hi) { uint32_t r; asm("cvt.rn.bf16x2.f32 %0, %1, %2;" : "=r"(r) : "f"(hi), "f"(lo)); return r; }
__device__ __forceinline__ float rbf(float x) { return __uint_as_float(pack_bf16(0.f, x)); }
__device__ __forceinline__ float bf_lo(uint32_t v) { return __uint_as_float(v << 16); }
__device__ __forceinline__ float bf_hi(uint32_t v) { return __uint_as_float(v & 0xffff0000u); }
__device__ __forceinline__ uint32_t add2(uint32_t a, uint32_t b) { uint32_t r; asm("add.rn.bf16x2 %0, %1, %2;" : "=r"(r) : "r"(a), "r"(b)); return r; }
__device__ __forceinline__ uint32_t mul2(uint32_t a, uint32_t b) { uint32_t r; asm("mul.rn.bf16x2 %0, %1, %2;" : "=r"(r) : "r"(a), "r"(b)); return r; }
__device__ __forceinline__ uint32_t fma2(uint32_t a, uint32_t b, uint32_t c) { uint32_t r; asm("fma.rn.bf16x2 %0, %1, %2, %3;" : "=r"(r) : "r"(a), "r"(b), "r"(c)); return r; }
__device__ __forceinline__ uint4 ldsm_x4_t(uint32_t addr) {
  uint4 v; asm volatile("ldmatrix.sync.aligned.m8n8.x4.trans.shared.b16 {%0, %1, %2, %3}, [%4];" : "=r"(v.x), "=r"(v.y), "=r"(v.z), "=r"(v.w) : "r"(addr) : "memory"); return v;
}
__device__ __forceinline__ uint4 ldsm_x4(uint32_t addr) {
  uint4 v; asm volatile("ldmatrix.sync.aligned.m8n8.x4.shared.b16 {%0, %1, %2, %3}, [%4];" : "=r"(v.x), "=r"(v.y), "=r"(v.z), "=r"(v.w) : "r"(addr) : "memory"); return v;
}
__device__ __forceinline__ void mma16816(float (&c)[4], const uint4& a, uint32_t b0, uint32_t b1) {
  asm("mma.sync.aligned.m16n8k16.row.col.f32.bf16.bf16.f32 {%0, %1, %2, %3}, {%4, %5, %6, %7}, {%8, %9}, {%0, %1, %2, %3};"
    : "+f"(c[0]), "+f"(c[1]), "+f"(c[2]), "+f"(c[3]) : "r"(a.x), "r"(a.y), "r"(a.z), "r"(a.w), "r"(b0), "r"(b1));
}
template<int N> __device__ __forceinline__ void fence_regs(float (&a)[N]) {
  #pragma unroll
  for (int i = 0; i < N; i++) asm volatile("" : "+f"(a[i]) :: "memory");
}
template<int N> __device__ __forceinline__ void fence_regs_u(uint32_t (&a)[N]) {
  #pragma unroll
  for (int i = 0; i < N; i++) asm volatile("" : "+r"(a[i]) :: "memory");
}
constexpr uint32_t SW128 = 0x40000040u, SW64 = 0x80000020u;
__device__ __forceinline__ uint32_t desc_lo(uint32_t addr, uint32_t lbo) { return ((addr & 0x3FFFF) >> 4) | ((lbo >> 4) << 16); }

template<int TB, int OA, int OB, uint32_t HA, uint32_t HB> __device__ __forceinline__ void wgmma_ss_n128(float (&d)[64], uint32_t da, uint32_t db, int sd) {
  asm volatile("{\n.reg .pred p;\n.reg .b32 ta, tb;\n.reg .b64 da, db;\nsetp.ne.b32 p, %66, 0;\nadd.u32 ta, %64, %68;\nadd.u32 tb, %65, %69;\nmov.b64 da, {ta, %70};\nmov.b64 db, {tb, %71};\n"
    "wgmma.mma_async.sync.aligned.m64n128k16.f32.bf16.bf16 "
    "{%0, %1, %2, %3, %4, %5, %6, %7, %8, %9, %10, %11, %12, %13, %14, %15, %16, %17, %18, %19, %20, %21, %22, %23, %24, %25, %26, %27, %28, %29, %30, %31, %32, %33, %34, %35, %36, %37, %38, %39, %40, %41, %42, %43, %44, %45, %46, %47, %48, %49, %50, %51, %52, %53, %54, %55, %56, %57, %58, %59, %60, %61, %62, %63}, da, db, p, 1, 1, 0, %67;\n}\n"
    : "+f"(d[0]), "+f"(d[1]), "+f"(d[2]), "+f"(d[3]), "+f"(d[4]), "+f"(d[5]), "+f"(d[6]), "+f"(d[7]), "+f"(d[8]), "+f"(d[9]), "+f"(d[10]), "+f"(d[11]), "+f"(d[12]), "+f"(d[13]), "+f"(d[14]), "+f"(d[15]), "+f"(d[16]), "+f"(d[17]), "+f"(d[18]), "+f"(d[19]), "+f"(d[20]), "+f"(d[21]), "+f"(d[22]), "+f"(d[23]), "+f"(d[24]), "+f"(d[25]), "+f"(d[26]), "+f"(d[27]), "+f"(d[28]), "+f"(d[29]), "+f"(d[30]), "+f"(d[31]), "+f"(d[32]), "+f"(d[33]), "+f"(d[34]), "+f"(d[35]), "+f"(d[36]), "+f"(d[37]), "+f"(d[38]), "+f"(d[39]), "+f"(d[40]), "+f"(d[41]), "+f"(d[42]), "+f"(d[43]), "+f"(d[44]), "+f"(d[45]), "+f"(d[46]), "+f"(d[47]), "+f"(d[48]), "+f"(d[49]), "+f"(d[50]), "+f"(d[51]), "+f"(d[52]), "+f"(d[53]), "+f"(d[54]), "+f"(d[55]), "+f"(d[56]), "+f"(d[57]), "+f"(d[58]), "+f"(d[59]), "+f"(d[60]), "+f"(d[61]), "+f"(d[62]), "+f"(d[63])
    : "r"(da), "r"(db), "r"(sd), "n"(TB), "n"(OA), "n"(OB), "n"(HA), "n"(HB));
}
template<int TB, int OB, uint32_t HB> __device__ __forceinline__ void wgmma_rs_n128(float (&d)[64], uint32_t a0, uint32_t a1, uint32_t a2, uint32_t a3, uint32_t db, int sd) {
  asm volatile("{\n.reg .pred p;\n.reg .b32 tb;\n.reg .b64 db;\nsetp.ne.b32 p, %69, 0;\nadd.u32 tb, %68, %71;\nmov.b64 db, {tb, %72};\n"
    "wgmma.mma_async.sync.aligned.m64n128k16.f32.bf16.bf16 "
    "{%0, %1, %2, %3, %4, %5, %6, %7, %8, %9, %10, %11, %12, %13, %14, %15, %16, %17, %18, %19, %20, %21, %22, %23, %24, %25, %26, %27, %28, %29, %30, %31, %32, %33, %34, %35, %36, %37, %38, %39, %40, %41, %42, %43, %44, %45, %46, %47, %48, %49, %50, %51, %52, %53, %54, %55, %56, %57, %58, %59, %60, %61, %62, %63}, {%64,%65,%66,%67}, db, p, 1, 1, %70;\n}\n"
    : "+f"(d[0]), "+f"(d[1]), "+f"(d[2]), "+f"(d[3]), "+f"(d[4]), "+f"(d[5]), "+f"(d[6]), "+f"(d[7]), "+f"(d[8]), "+f"(d[9]), "+f"(d[10]), "+f"(d[11]), "+f"(d[12]), "+f"(d[13]), "+f"(d[14]), "+f"(d[15]), "+f"(d[16]), "+f"(d[17]), "+f"(d[18]), "+f"(d[19]), "+f"(d[20]), "+f"(d[21]), "+f"(d[22]), "+f"(d[23]), "+f"(d[24]), "+f"(d[25]), "+f"(d[26]), "+f"(d[27]), "+f"(d[28]), "+f"(d[29]), "+f"(d[30]), "+f"(d[31]), "+f"(d[32]), "+f"(d[33]), "+f"(d[34]), "+f"(d[35]), "+f"(d[36]), "+f"(d[37]), "+f"(d[38]), "+f"(d[39]), "+f"(d[40]), "+f"(d[41]), "+f"(d[42]), "+f"(d[43]), "+f"(d[44]), "+f"(d[45]), "+f"(d[46]), "+f"(d[47]), "+f"(d[48]), "+f"(d[49]), "+f"(d[50]), "+f"(d[51]), "+f"(d[52]), "+f"(d[53]), "+f"(d[54]), "+f"(d[55]), "+f"(d[56]), "+f"(d[57]), "+f"(d[58]), "+f"(d[59]), "+f"(d[60]), "+f"(d[61]), "+f"(d[62]), "+f"(d[63])
    : "r"(a0), "r"(a1), "r"(a2), "r"(a3), "r"(db), "r"(sd), "n"(TB), "n"(OB), "n"(HB));
}
template<int TB, int OA, int OB, uint32_t HA, uint32_t HB> __device__ __forceinline__ void wgmma_ss_n64(float (&d)[32], uint32_t da, uint32_t db, int sd) {
  asm volatile("{\n.reg .pred p;\n.reg .b32 ta, tb;\n.reg .b64 da, db;\nsetp.ne.b32 p, %34, 0;\nadd.u32 ta, %32, %36;\nadd.u32 tb, %33, %37;\nmov.b64 da, {ta, %38};\nmov.b64 db, {tb, %39};\n"
    "wgmma.mma_async.sync.aligned.m64n64k16.f32.bf16.bf16 "
    "{%0, %1, %2, %3, %4, %5, %6, %7, %8, %9, %10, %11, %12, %13, %14, %15, %16, %17, %18, %19, %20, %21, %22, %23, %24, %25, %26, %27, %28, %29, %30, %31}, da, db, p, 1, 1, 0, %35;\n}\n"
    : "+f"(d[0]), "+f"(d[1]), "+f"(d[2]), "+f"(d[3]), "+f"(d[4]), "+f"(d[5]), "+f"(d[6]), "+f"(d[7]), "+f"(d[8]), "+f"(d[9]), "+f"(d[10]), "+f"(d[11]), "+f"(d[12]), "+f"(d[13]), "+f"(d[14]), "+f"(d[15]), "+f"(d[16]), "+f"(d[17]), "+f"(d[18]), "+f"(d[19]), "+f"(d[20]), "+f"(d[21]), "+f"(d[22]), "+f"(d[23]), "+f"(d[24]), "+f"(d[25]), "+f"(d[26]), "+f"(d[27]), "+f"(d[28]), "+f"(d[29]), "+f"(d[30]), "+f"(d[31])
    : "r"(da), "r"(db), "r"(sd), "n"(TB), "n"(OA), "n"(OB), "n"(HA), "n"(HB));
}
template<int TB, int OA, int OB, uint32_t HA, uint32_t HB> __device__ __forceinline__ void wgmma_ss_n128_new(float (&d)[64], uint32_t da, uint32_t db) {
  asm volatile("{\n.reg .pred p;\n.reg .b32 ta, tb;\n.reg .b64 da, db;\nsetp.ne.b32 p, %66, 0;\nadd.u32 ta, %64, %68;\nadd.u32 tb, %65, %69;\nmov.b64 da, {ta, %70};\nmov.b64 db, {tb, %71};\n"
    "wgmma.mma_async.sync.aligned.m64n128k16.f32.bf16.bf16 "
    "{%0, %1, %2, %3, %4, %5, %6, %7, %8, %9, %10, %11, %12, %13, %14, %15, %16, %17, %18, %19, %20, %21, %22, %23, %24, %25, %26, %27, %28, %29, %30, %31, %32, %33, %34, %35, %36, %37, %38, %39, %40, %41, %42, %43, %44, %45, %46, %47, %48, %49, %50, %51, %52, %53, %54, %55, %56, %57, %58, %59, %60, %61, %62, %63}, da, db, p, 1, 1, 0, %67;\n}\n"
    : "=f"(d[0]), "=f"(d[1]), "=f"(d[2]), "=f"(d[3]), "=f"(d[4]), "=f"(d[5]), "=f"(d[6]), "=f"(d[7]), "=f"(d[8]), "=f"(d[9]), "=f"(d[10]), "=f"(d[11]), "=f"(d[12]), "=f"(d[13]), "=f"(d[14]), "=f"(d[15]), "=f"(d[16]), "=f"(d[17]), "=f"(d[18]), "=f"(d[19]), "=f"(d[20]), "=f"(d[21]), "=f"(d[22]), "=f"(d[23]), "=f"(d[24]), "=f"(d[25]), "=f"(d[26]), "=f"(d[27]), "=f"(d[28]), "=f"(d[29]), "=f"(d[30]), "=f"(d[31]), "=f"(d[32]), "=f"(d[33]), "=f"(d[34]), "=f"(d[35]), "=f"(d[36]), "=f"(d[37]), "=f"(d[38]), "=f"(d[39]), "=f"(d[40]), "=f"(d[41]), "=f"(d[42]), "=f"(d[43]), "=f"(d[44]), "=f"(d[45]), "=f"(d[46]), "=f"(d[47]), "=f"(d[48]), "=f"(d[49]), "=f"(d[50]), "=f"(d[51]), "=f"(d[52]), "=f"(d[53]), "=f"(d[54]), "=f"(d[55]), "=f"(d[56]), "=f"(d[57]), "=f"(d[58]), "=f"(d[59]), "=f"(d[60]), "=f"(d[61]), "=f"(d[62]), "=f"(d[63])
    : "r"(da), "r"(db), "n"(0), "n"(TB), "n"(OA), "n"(OB), "n"(HA), "n"(HB));
}
template<int TB, int OA, int OB, uint32_t HA, uint32_t HB> __device__ __forceinline__ void wgmma_ss_n64_new(float (&d)[32], uint32_t da, uint32_t db) {
  asm volatile("{\n.reg .pred p;\n.reg .b32 ta, tb;\n.reg .b64 da, db;\nsetp.ne.b32 p, %34, 0;\nadd.u32 ta, %32, %36;\nadd.u32 tb, %33, %37;\nmov.b64 da, {ta, %38};\nmov.b64 db, {tb, %39};\n"
    "wgmma.mma_async.sync.aligned.m64n64k16.f32.bf16.bf16 "
    "{%0, %1, %2, %3, %4, %5, %6, %7, %8, %9, %10, %11, %12, %13, %14, %15, %16, %17, %18, %19, %20, %21, %22, %23, %24, %25, %26, %27, %28, %29, %30, %31}, da, db, p, 1, 1, 0, %35;\n}\n"
    : "=f"(d[0]), "=f"(d[1]), "=f"(d[2]), "=f"(d[3]), "=f"(d[4]), "=f"(d[5]), "=f"(d[6]), "=f"(d[7]), "=f"(d[8]), "=f"(d[9]), "=f"(d[10]), "=f"(d[11]), "=f"(d[12]), "=f"(d[13]), "=f"(d[14]), "=f"(d[15]), "=f"(d[16]), "=f"(d[17]), "=f"(d[18]), "=f"(d[19]), "=f"(d[20]), "=f"(d[21]), "=f"(d[22]), "=f"(d[23]), "=f"(d[24]), "=f"(d[25]), "=f"(d[26]), "=f"(d[27]), "=f"(d[28]), "=f"(d[29]), "=f"(d[30]), "=f"(d[31])
    : "r"(da), "r"(db), "n"(0), "n"(TB), "n"(OA), "n"(OB), "n"(HA), "n"(HB));
}
template<int OA, int OB = 0, uint32_t HA = SW128> __device__ __forceinline__ void kblock_n128(float (&d)[64], uint32_t da, uint32_t db, int sd) {
  constexpr int H = HA == SW128 ? 4 : 512;
  wgmma_ss_n128<1, OA, OB, HA, SW128>(d, da, db, sd); wgmma_ss_n128<1, OA + 2, OB + 128, HA, SW128>(d, da, db, 1);
  wgmma_ss_n128<1, OA + H, OB + 256, HA, SW128>(d, da, db, 1); wgmma_ss_n128<1, OA + H + 2, OB + 384, HA, SW128>(d, da, db, 1);
}

__device__ __forceinline__ float quad_sum(float v) {
  v += __shfl_xor_sync(0xffffffff, v, 1);
  v += __shfl_xor_sync(0xffffffff, v, 2);
  return v;
}
struct Row { uint32_t v[8]; };
template<class F> __device__ __forceinline__ Row load_row(const __nv_bfloat16* p, int lane, F ld) {
  const uint4 a = ld(reinterpret_cast<const uint4*>(p) + lane), b = ld(reinterpret_cast<const uint4*>(p) + 32 + lane);
  return Row{{a.x, a.y, a.z, a.w, b.x, b.y, b.z, b.w}};
}
__device__ __forceinline__ Row ldg_row(const __nv_bfloat16* p, int lane) { return load_row(p, lane, [](const uint4* q) { return __ldg(q); }); }
__device__ __forceinline__ Row ldca_row(const __nv_bfloat16* p, int lane) { return load_row(p, lane, [](const uint4* q) { return __ldca(q); }); }
__device__ __forceinline__ Row lds_row(uint32_t addr, int lane) {
  const uint4 a = lds_v4(addr + lane * 16), b = lds_v4(addr + 512 + lane * 16);
  return Row{{a.x, a.y, a.z, a.w, b.x, b.y, b.z, b.w}};
}
__device__ __forceinline__ void store_row(__nv_bfloat16* p, int lane, const Row& r) {
  stg_v4(p + lane * 8, r.v[0], r.v[1], r.v[2], r.v[3]); stg_v4(p + 256 + lane * 8, r.v[4], r.v[5], r.v[6], r.v[7]);
}
__device__ __forceinline__ Row fma_row(const Row& a, const Row& b, const Row& c) {
  Row r;
  #pragma unroll
  for (int i = 0; i < 8; i++) r.v[i] = fma2(a.v[i], b.v[i], c.v[i]);
  return r;
}
__device__ __forceinline__ Row add_row(const Row& a, const Row& b) {
  Row r;
  #pragma unroll
  for (int i = 0; i < 8; i++) r.v[i] = add2(a.v[i], b.v[i]);
  return r;
}
__device__ __forceinline__ Row one_plus(const Row& a) {
  Row r;
  #pragma unroll
  for (int i = 0; i < 8; i++) r.v[i] = add2(a.v[i], 0x3f803f80u);
  return r;
}
__device__ __forceinline__ float row_at(const Row& x, int i) { return (i & 1) ? bf_hi(x.v[i >> 1]) : bf_lo(x.v[i >> 1]); }
template<int N> __device__ __forceinline__ void warp_sums(float (&s)[N]) {
  #pragma unroll
  for (int o = 16; o > 0; o >>= 1) {
    #pragma unroll
    for (int k = 0; k < N; k++) s[k] += __shfl_xor_sync(0xffffffff, s[k], o);
  }
}
__device__ __forceinline__ void ln_stats(float& s1, float& s2) {
  s1 *= 1.f / DM;
  asm("rsqrt.approx.ftz.f32 %0, %1;" : "=f"(s2) : "f"(fmaxf(fmaf(-s1, s1, s2 * (1.f / DM)), 0.f) + 1e-5f));
}
__device__ __forceinline__ Row ln_apply(const Row& x, float mean, float f) {
  Row n;
  const float o = -mean * f;
  #pragma unroll
  for (int i = 0; i < 8; i++) n.v[i] = pack_bf16(fmaf(bf_lo(x.v[i]), f, o), fmaf(bf_hi(x.v[i]), f, o));
  return n;
}

constexpr int SM_Q = 6 * 32768, SM_BAR = 7 * 32768, SM_MAIL = SM_BAR + 640, SM_RED = SM_MAIL + 128, SM_H2 = SM_RED + 1024, SM_KEY = SM_H2 + 1024, SMEM = SM_KEY + 128;
constexpr int B_AF = 0, B_WF = 64, B_RF = 112, B_WE = 168, B_RE = 216, B_PUB = 272, B_RDY = 496;
constexpr int R_MOD = B_RDY, R_H1 = B_RDY + 8, R_ITEM = B_RDY + 16, R_NEAR = B_RDY + 48, R_CTX = B_RDY + 64;
constexpr int R_KEY = B_AF + 8, R_PART = B_AF + 32;
constexpr int NPUB = 14;
__device__ __forceinline__ uint32_t k_addrA(int kb) { return ((0x6310u >> ((kb >> 1) * 4)) & 15u) * 32768u + (kb & 1) * 16384u; }
__device__ __forceinline__ uint32_t k_addrW(int s) { return ((0x254u >> ((s >> 1) * 4)) & 15u) * 32768u + (s & 1) * 16384u; }

#define KORDER 0x3201
constexpr int KHEAD0 = ((KORDER >> 12) & 3) * 8;
constexpr int MAX_ITEMS = 4;
constexpr int MAX_STEPS = 10;
struct Sched {
  __nv_bfloat16 *kvc, *h1, *part;
  struct Pair {
    uint8_t oent[3 * MAX_STEPS + 6];
    uint8_t khead[4];
    uint8_t nitems, item[MAX_ITEMS];
    uint8_t otask, nsteps;
    uint8_t ochunk[MAX_STEPS][2];
  } pair[NGRID / 2];
};

__device__ __forceinline__ int ring_add(int e, int n) { e += n; return e >= 12 ? e - 12 : e; }
__device__ __forceinline__ int ring_slot(int e) { return e >= 6 ? e - 6 : e; }
__device__ __forceinline__ void ring_wait_full(uint32_t bars, int e) { mbar_wait(bars + B_RF + 8 * ring_slot(e), e >= 6); }

__device__ __forceinline__ void o_wait_full(uint32_t bars, uint32_t v) { mbar_wait(bars + B_RF + 8 * (v & 7), v >> 3); }

struct Ctx {
  uint32_t base, bars;
  uint32_t rel;
  bool rel1;
  int w, nev;
  const Sched* sched;
};
__device__ __forceinline__ void slot_release(const Ctx& x, int s, bool twice) {
  mbar_arrive_remote_if(x.rel + B_RE + 8 * s, twice ? (wg_tid() & 31) == 0 : x.rel1);
}
__device__ __forceinline__ void ring_release(const Ctx& x, int e, bool twice) { slot_release(x, ring_slot(e), twice); }
__device__ __forceinline__ void publish(Ctx& x, int idx) {
  const uint32_t n = x.w * NPUB + x.nev;
  const int t = wg_tid();
  if (t == 0) asm volatile("st.shared.u32 [%0], %1;" :: "r"(x.base + SM_MAIL + 4 * n), "r"(idx) : "memory");
  __syncwarp();
  if ((t & 31) == 0) mbar_arrive(x.bars + B_PUB + 8 * n);
  x.nev++;
}

template<int KK = 0> __device__ __forceinline__ void issue_qk(float (&S)[64], uint32_t dq, uint32_t dk) {
  constexpr int off = (KK >> 1) * 512 + (KK & 1) * 2;
  if constexpr (KK == 0) wgmma_ss_n128_new<0, 0, 0, SW64, SW64>(S, dq, dk); else wgmma_ss_n128<0, off, off, SW64, SW64>(S, dq, dk, 1);
  if constexpr (KK < 7) issue_qk<KK + 1>(S, dq, dk);
}
template<int KK = 0> __device__ __forceinline__ void issue_qk_half(float (&S)[32], uint32_t dq, uint32_t dk) {
  constexpr int off = (KK >> 1) * 512 + (KK & 1) * 2;
  if constexpr (KK == 0) wgmma_ss_n64_new<0, 0, 256, SW64, SW64>(S, dq, dk); else wgmma_ss_n64<0, off, off + 256, SW64, SW64>(S, dq, dk, 1);
  if constexpr (KK < 7) issue_qk_half<KK + 1>(S, dq, dk);
}
template<int NK, int KK = 0>
__device__ __forceinline__ void issue_pv(float (&O)[64], uint32_t (&P)[32], uint32_t dv, int accumulate) {
  wgmma_rs_n128<1, (KK + 8 - NK) * 64, SW64>(O, P[4*KK], P[4*KK+1], P[4*KK+2], P[4*KK+3], dv, accumulate);
  if constexpr (KK + 1 < NK) issue_pv<NK, KK + 1>(O, P, dv, 1);
}
template<int K0, int K1>
__device__ __forceinline__ void exp_pack(const float (&S)[64], uint32_t (&D)[32], float& s0, float& s1) {
  #pragma unroll
  for (int k = K0; k < K1; k++) {
    const float e0 = ex2(S[2*k]), e1 = ex2(S[2*k+1]);
    D[k] = pack_bf16(e0, e1);
    if (k & 1) s1 += e0 + e1; else s0 += e0 + e1;
  }
}
__device__ __forceinline__ int diag_limit() { const int t = wg_tid(); return 16 * (t >> 5) + ((t & 31) >> 2) - 2 * (t & 3); }
__device__ __forceinline__ void exp_pack_diag(const float (&S)[64], uint32_t (&D)[32], int t, float& s0, float& s1) {
  #pragma unroll
  for (int k = 0; k < 16; k++) {
    const int c = 8 * (k >> 1) - 8 * (k & 1);
    const float e0 = ex2((c <= t) ? S[2*k] : -INFINITY), e1 = ex2((c + 1 <= t) ? S[2*k+1] : -INFINITY);
    D[k] = pack_bf16(e0, e1);
    if (k & 1) s1 += e0 + e1; else s0 += e0 + e1;
  }
}
constexpr float SUM_HI = 1.8446744073709552e19f;
constexpr float SUM_LO = 5.421010862427522e-20f;

__device__ __forceinline__ void classic_tile(const float (&S)[64], uint32_t (&P)[32], bool fresh, bool half, bool was_classic, volatile float* mc,
                                             float& l0, float& l1, float& s0, float& s1, float& sc0, float& sc1) {
  const int tmask = diag_limit();
  float4 t[16];
  #pragma unroll
  for (int j = 0; j < 16; j++) t[j] = make_float4(S[4*j], S[4*j+1], S[4*j+2], S[4*j+3]);
  float mx0 = -INFINITY, mx1 = -INFINITY;
  #pragma unroll 1
  for (int j = 0; j < 16; j++) {
    float4 v = t[j];
    const int lim = !fresh ? 1000 : j < 8 ? tmask - 8 * j : half ? -1000 : 1000;
    v.x = 0 <= lim ? v.x : -INFINITY; v.y = 1 <= lim ? v.y : -INFINITY; v.z = -8 <= lim ? v.z : -INFINITY; v.w = -7 <= lim ? v.w : -INFINITY;
    t[j] = v;
    mx0 = fmaxf(mx0, fmaxf(v.x, v.y)); mx1 = fmaxf(mx1, fmaxf(v.z, v.w));
  }
  mx0 = fmaxf(mx0, __shfl_xor_sync(0xffffffff, mx0, 1));
  mx1 = fmaxf(mx1, __shfl_xor_sync(0xffffffff, mx1, 1));
  mx0 = fmaxf(mx0, __shfl_xor_sync(0xffffffff, mx0, 2));
  mx1 = fmaxf(mx1, __shfl_xor_sync(0xffffffff, mx1, 2));
  const float mc0 = was_classic ? mc[0] : 0.f, mc1 = was_classic ? mc[1] : 0.f;
  const float n0 = fresh ? -mx0 : fminf(mc0, -mx0), n1 = fresh ? -mx1 : fminf(mc1, -mx1);
  sc0 = ex2(n0 - mc0); sc1 = ex2(n1 - mc1);
  mc[0] = n0; mc[1] = n1;
  s0 = 0.f; s1 = 0.f;
  #pragma unroll 1
  for (int j = 0; j < 16; j++) {
    const float4 v = t[j];
    const float e0 = ex2(v.x + n0), e1 = ex2(v.y + n0), e2 = ex2(v.z + n1), e3 = ex2(v.w + n1);
    s0 += e0 + e1; s1 += e2 + e3;
    reinterpret_cast<uint2*>(t)[j] = make_uint2(pack_bf16(e0, e1), pack_bf16(e2, e3));
  }
  #pragma unroll
  for (int j = 0; j < 8; j++) { P[4*j] = __float_as_uint(t[j].x); P[4*j+1] = __float_as_uint(t[j].y); P[4*j+2] = __float_as_uint(t[j].z); P[4*j+3] = __float_as_uint(t[j].w); }
  if (!fresh) { l0 *= sc0; l1 *= sc1; }
}
__device__ __forceinline__ void pack_tile(const float (&A)[64], uint32_t (&D)[32], float f0, float f1) {
  #pragma unroll
  for (int j = 0; j < 16; j++) {
    D[8 * (j >> 2) + (j & 3)] = pack_bf16(A[4*j] * f0, A[4*j+1] * f0);
    D[8 * (j >> 2) + 4 + (j & 3)] = pack_bf16(A[4*j+2] * f1, A[4*j+3] * f1);
  }
}
__device__ __forceinline__ int piece0(int t) { return ((t >> 5) * 16 + ((t & 31) >> 2)) * 32 + (((t ^ (t >> 3)) & 3) << 3); }
__device__ __forceinline__ void store_tile(__nv_bfloat16* p, const uint32_t (&D)[32]) {
  #pragma unroll
  for (int i = 0; i < 8; i++) stg_v4(p + (i >> 2) * (SEQ * 64) + ((i >> 1) & 1) * 4096 + (i & 1) * 256, D[4*i], D[4*i+1], D[4*i+2], D[4*i+3]);
}

enum : int { PV_ACC = 0, PV_ZERO = 1, PV_HALF = 2, PV_NONE = 3 };
struct Att {
  float l0, l1, i0, i1;
  bool classic;
  volatile float* mc;
};
__device__ __forceinline__ void store_ctx(Ctx& x, int code, const uint32_t (&D)[32]) {
  store_tile(x.sched->kvc + ((size_t)(128 + (code >> 5) * 2) * SEQ + ((code >> 1) & 15) * 128) * 64 + (code & 1) * 2048 + piece0(wg_tid()), D);
  publish(x, C_CTX + (code >> 2));
}
__device__ __forceinline__ __nv_bfloat16* kv_tile(const Ctx& x, int code) {
  return x.sched->kvc + ((size_t)(x.w * 64 + (code >> 4) * 2) * SEQ + (code & 15) * 128) * 64 + piece0(wg_tid());
}
__device__ __forceinline__ void q_proj(Ctx& x, Att& a, int& e, int& sk, int& sv, int& en, int& sn, bool isY,
                                       const uint32_t (&PA)[32], const uint32_t (&PB)[32], int vtile, bool first) {
  float S[64];
  int ek = 0, s = sk, ps = 0, ph = e >= 6, kb = 0;
  uint32_t qa = 0;
  sv = en = sn = 0;
  if (isY) bar_sync(1 + x.w, 256);
  if (first) mbar_wait(x.bars + B_RF + 8 * s, ph);
  #pragma unroll 1
  while (true) {
    #pragma unroll 1
    do {
      wgmma_fence();
      kblock_n128<0>(S, desc_lo(x.base + x.w * 8192, 16) + s * 2048, desc_lo(x.base + 16384, 8192) + s * 2048, kb != 0);
      wgmma_commit();
      if (kb == 7 && !isY) bar_arrive(1 + (x.w ^ 1), 256);
      wgmma_wait<1>();
      mbar_arrive_remote_if(x.rel + B_RE + 8 * ps, x.rel1 && kb > 0);
      ps = s;
      if (++s == 6) { s = 0; ph ^= 1; }
      if (++kb == 8) break;
      mbar_wait(x.bars + B_RF + 8 * s, ph);
    } while (kb != 4);
    asm volatile("" : "+r"(vtile));
    if (kb == 8) break;
    a.i0 = rcp_fast(quad_sum(a.l0)); a.i1 = rcp_fast(quad_sum(a.l1));
    e = ring_add(e, 8); ek = ring_add(e, isY ? 0 : 2); en = ring_add(e, isY ? 2 : 4);
    sk = ring_slot(ek); sv = ring_slot(e) + 1; sn = ring_slot(en);
    qa = x.base + SM_Q + x.w * 4096 + piece0(wg_tid()) * 2;
    if (vtile >= 0) store_tile(kv_tile(x, vtile) + 2048, PA);
  }
  if (vtile >= 0) { store_tile(kv_tile(x, vtile), PB); publish(x, C_KV + (vtile >> 4)); }
  wgmma_wait<0>();
  fence_regs(S);
  slot_release(x, ps, false);
  const bool landed = isY && mbar_test2(x.bars + B_RF + 8 * sk, e >= 6);
  #pragma unroll
  for (int i = 0; i < 8; i++) {
    const int j = 4 * (i >> 1), o = 2 * (i & 1);
    sts_v4(qa + (i >> 1) * 8192 + (i & 1) * 512,
           pack_bf16(S[4*j+o], S[4*j+o+1]), pack_bf16(S[4*j+4+o], S[4*j+5+o]), pack_bf16(S[4*j+8+o], S[4*j+9+o]), pack_bf16(S[4*j+12+o], S[4*j+13+o]));
  }
  fence_async_smem();
  if (!landed) { mbar_wait(x.bars + B_RF + 8 * sk, ek >= 6); mbar_wait(x.bars + B_RF + 8 * sv, e >= 6); }
}

template<int KIND>
__device__ __forceinline__ void slot(Ctx& x, Att& a, int& e, int& sk, int sv, int en, int sn, float (&O)[64], uint32_t (&Pn)[32], uint32_t (&Po)[32],
                                     bool more, bool isY, bool half, int pv, int pend) {
  float S[64];
  const int w = x.w;
  const uint32_t dq = desc_lo(x.base + SM_Q + w * 4096, 16), dk = desc_lo(x.base, 16) + sk * 2048, dv = desc_lo(x.base, 8192) + sv * 2048;
  bar_sync(1 + w, 256);
  if (KIND == 2) {
    wgmma_fence();
    issue_qk(S, dq, dk); wgmma_commit();
    issue_pv<8>(O, Po, dv, 1); wgmma_commit();
    bar_arrive(1 + (w ^ 1), 256);
    wgmma_wait<1>();
  } else if (KIND == 0 && half) {
    float T[32];
    wgmma_fence(); issue_qk_half(T, dq, dk); wgmma_commit();
    if (pv == PV_NONE) { wgmma_fence(); wgmma_commit(); }
    else               { wgmma_fence(); issue_pv<8>(O, Po, dv, pv == PV_ACC); wgmma_commit(); }
    bar_arrive(1 + (w ^ 1), 256);
    wgmma_wait<1>();
    fence_regs(T);
    #pragma unroll
    for (int i = 0; i < 32; i++) { S[i] = T[i]; asm volatile("" : "=f"(S[32 + i])); }
  } else {
    wgmma_fence(); issue_qk(S, dq, dk); wgmma_commit();
    if (KIND == 1 && pend >= 0) { bar_arrive(1 + (w ^ 1), 256); pack_tile(O, Pn, a.i0, a.i1); store_ctx(x, pend, Pn); }
    if (KIND == 0 && pv == PV_NONE) { wgmma_fence(); wgmma_commit(); }
    else if (pv == PV_HALF)         { wgmma_fence(); issue_pv<4>(O, Po, dv, 0); wgmma_commit(); }
    else                            { wgmma_fence(); issue_pv<8>(O, Po, dv, pv == PV_ACC); wgmma_commit(); }
    if (KIND == 0 || pend < 0) bar_arrive(1 + (w ^ 1), 256);
    wgmma_wait<1>();
  }
  fence_regs(S);
  fence_regs_u(Pn);
  slot_release(x, sk, KIND == 0 && isY);
  const bool landed = mbar_test2(x.bars + B_RF + 8 * sn, en >= 6);
  float s0 = 0.f, s1 = 0.f;
  const bool was_classic = KIND != 0 && a.classic;
  if (KIND == 0) {
    a.l0 = 0.f; a.l1 = 0.f;
    if (!half) exp_pack<16, 32>(S, Pn, s0, s1);
    else {
      #pragma unroll
      for (int i = 16; i < 32; i++) asm volatile("" : "=r"(Pn[i]));
    }
    exp_pack_diag(S, Pn, diag_limit(), s0, s1);
    uint32_t b0 = __ballot_sync(0xffffffff, s0 >= SUM_LO), b1 = __ballot_sync(0xffffffff, s1 >= SUM_LO);
    b0 |= b0 >> 1; b0 |= b0 >> 2; b1 |= b1 >> 1; b1 |= b1 >> 2;
    a.classic = __any_sync(0xffffffff, !(s0 <= SUM_HI && s1 <= SUM_HI)) || (b0 & b1 & 0x11111111u) != 0x11111111u;
  } else {
    exp_pack<0, 32>(S, Pn, s0, s1);
    a.classic = __any_sync(0xffffffff, a.classic || !(s0 <= SUM_HI && s1 <= SUM_HI));
  }
  fence_regs_u(Pn);
  if (!landed) {
    mbar_wait(x.bars + B_RF + 8 * sn, en >= 6);
    if (more) mbar_wait(x.bars + B_RF + 8 * sn + 8, en >= 6);
  }
  wgmma_wait<0>();
  fence_regs(O);
  fence_regs_u(Po);
  slot_release(x, sv, KIND == 1 && isY && pv != PV_ACC);
  if (__builtin_expect(a.classic, 0)) {
    float sc0, sc1;
    classic_tile(S, Pn, KIND == 0, half, was_classic, a.mc, a.l0, a.l1, s0, s1, sc0, sc1);
    if (KIND != 0) {
      #pragma unroll
      for (int j = 0; j < 16; j++) { O[4*j] *= sc0; O[4*j+1] *= sc0; O[4*j+2] *= sc1; O[4*j+3] *= sc1; }
    }
  }
  a.l0 += s0; a.l1 += s1;
  e = en; sk = sn;
}

__device__ __forceinline__ int attention(Ctx& x, const uint8_t* items, int nitems, int rank, uint32_t (&PA)[32], uint32_t (&PB)[32], int vtile) {
  int e = 0, sk = 0;
  float O[64];
  Att a;
  volatile float mc[2];
  a.l0 = 1.f; a.l1 = 1.f; a.i0 = 0.f; a.i1 = 0.f; a.classic = false; a.mc = mc;
  int pv = PV_NONE, cur = -1;
  #pragma unroll 1
  for (int it = 0; ; it++) {
    const bool isY = (it & 1) == x.w;
    int pend = cur;
    if (it < nitems) {
      const bool half = isY == (rank != 0);
      int sv, en, sn;
      q_proj(x, a, e, sk, sv, en, sn, isY, PA, PB, vtile, it == 0);
      vtile = -1;
      const int item = items[it];
      cur = item * 4 + (isY ? 3 - rank : rank);
      int rem = 2 * (item & 7) + (isY ? 1 : 0);
      slot<0>(x, a, e, sk, sv, en, sn, O, PA, PB, rem > 0, isY, half, pv, -1);
      pv = half ? PV_HALF : PV_ZERO;
      #pragma unroll 1
      while (rem > 0) {
        slot<1>(x, a, e, sk, sk + 1, ring_add(e, 2), sk == 4 ? 0 : sk + 2, O, PB, PA, rem > 1, isY, false, pv, pend);
        pv = PV_ACC; pend = -1;
        if (rem == 1) break;
        rem -= 2;
        slot<2>(x, a, e, sk, sk + 1, ring_add(e, 2), sk == 4 ? 0 : sk + 2, O, PA, PB, rem > 0, false, false, 0, -1);
      }
      if (isY) continue;
    } else {
      slot_release(x, 6, false);
      const uint32_t dv = desc_lo(x.base, 8192) + sk * 2048;
      bar_sync(1 + x.w, 256);
      if (pv == PV_HALF) { wgmma_fence(); issue_pv<4>(O, PB, dv, 0); wgmma_commit(); }
      else { wgmma_fence(); issue_pv<8>(O, PB, dv, pv == PV_ACC); wgmma_commit(); }
      if (isY) bar_arrive(1 + (x.w ^ 1), 256);
      a.i0 = rcp_fast(quad_sum(a.l0)); a.i1 = rcp_fast(quad_sum(a.l1));
      ring_wait_full(x.bars, e);
      wgmma_wait<0>();
      fence_regs(O);
      fence_regs_u(PB);
      slot_release(x, sk, false);
    }
    if (pend >= 0) {
      pack_tile(O, PB, a.i0, a.i1);
      if (it == nitems) return pend;
      store_ctx(x, pend, PB);
    }
    #pragma unroll
    for (int i = 0; i < 32; i++) asm volatile("mov.b32 %0, %1;" : "=r"(PB[i]) : "r"(PA[i]));
  }
}

#define LN_AT 2
#define X_AT 6
#define PERT 0
#define CTX_T 3
#define PF_AT 5
#define PF_N 4
#define PF_MOE 3
constexpr float QSCALE = 0.08838834764831845f * 1.4426950408889634f;
__device__ __forceinline__ void mod_cta(Ctx& x, const __nv_bfloat16* cvec) {
  const int t = wg_tid(), ct = x.w * 128 + t;
  #pragma unroll 1
  for (int k = 0; k < 6; k++) slot_release(x, k, false);
  const uint32_t cv = __ldg(reinterpret_cast<const uint32_t*>(cvec) + ct);
  asm volatile("st.shared.u32 [%0], %1;" :: "r"(x.base + SM_H2 + ct * 4),
               "r"(pack_bf16(__fdividef(bf_lo(cv), 1.f + __expf(-bf_lo(cv))), __fdividef(bf_hi(cv), 1.f + __expf(-bf_hi(cv))))) : "memory");
  bar_sync(5, 256);
  float acc[64];
  int e = 0;
  #pragma unroll 1
  for (int g = 0; g < 24; g++) {
    uint32_t a[8];
    #pragma unroll
    for (int i = 0; i < 8; i++) a[i] = lds_u32(x.base + SM_H2 + (g & 7) * 128 + i * 16 + (t & 3) * 4);
    ring_wait_full(x.bars, e);
    const uint32_t db = desc_lo(x.base + x.w * 16384, 8192) + ring_slot(e) * 2048;
    wgmma_fence();
    wgmma_rs_n128<1, 0, SW128>(acc, a[0], a[0], a[1], a[1], db, g & 7);
    wgmma_rs_n128<1, 128, SW128>(acc, a[2], a[2], a[3], a[3], db, 1);
    wgmma_rs_n128<1, 256, SW128>(acc, a[4], a[4], a[5], a[5], db, 1);
    wgmma_rs_n128<1, 384, SW128>(acc, a[6], a[6], a[7], a[7], db, 1);
    wgmma_commit();
    wgmma_wait<0>();
    fence_regs(acc);
    ring_release(x, e, false);
    e = ring_add(e, 1);
    if ((g & 7) == 7) {
      float v[2][8];
      #pragma unroll
      for (int c = 0; c < 2; c++) {
        #pragma unroll
        for (int j = 0; j < 8; j++) v[c][j] = (t & 32) ? acc[4 * (j + 8) + c] : acc[4 * j + c];
        #pragma unroll
        for (int h = 4; h > 0; h >>= 1)
          #pragma unroll
          for (int j = 0; j < h; j++) v[c][j] = (t & (4 * h)) ? v[c][j + h] : v[c][j];
      }
      if (t < 64) reinterpret_cast<uint32_t*>(g_x.mod + (g >> 3) * 1024 + (blockIdx.x - NCTA) * 256 + x.w * 128)[t] = pack_bf16(v[0][0], v[1][0]);
      publish(x, g == 7 ? C_MOD : C_MOD2);
    }
  }
}

__global__ void __cluster_dims__(2, 1, 1) __launch_bounds__(384, 1)
k_fused(const __grid_constant__ CUtensorMap tmC, const __grid_constant__ CUtensorMap tmWq,
        const __grid_constant__ CUtensorMap tmWk, const __grid_constant__ CUtensorMap tmWv,
        const __grid_constant__ CUtensorMap tmWo, const __grid_constant__ CUtensorMap tmWg,
        const __grid_constant__ CUtensorMap tmWu, const __grid_constant__ CUtensorMap tmWd, const __grid_constant__ CUtensorMap tmWm,
        const __grid_constant__ Sched sched,
        const __nv_bfloat16* __restrict__ xin,
        const __nv_bfloat16* __restrict__ cvec, const __nv_bfloat16* __restrict__ w_o,
        const __nv_bfloat16* __restrict__ w_r, const __nv_bfloat16* __restrict__ w_gate, const __nv_bfloat16* __restrict__ w_up,
        const __nv_bfloat16* __restrict__ w_down, __nv_bfloat16* __restrict__ out) {
  extern __shared__ __align__(1024) uint8_t smem_raw[];
  const uint32_t base = smem_u32(smem_raw), bars = base + SM_BAR;
  const int warp = __shfl_sync(0xffffffff, threadIdx.x >> 5, 0), wg = warp >> 2;
  const int rank = cluster_ctarank(), p = blockIdx.x >> 1;
  const int mt = (p & 7) * 2 + rank;
  const bool spare = blockIdx.x >= NCTA;
  #pragma unroll
  for (int i = 0; i < PERT; i++) { uint32_t d; asm volatile("mov.u32 %0, %%laneid;" : "=r"(d)); (void)d; }
  {
    const int h0 = KHEAD0 + (p >> 3);
    if (warp == 11) { prefetch_tmap(&tmC); prefetch_tmap(&tmWk); }
    #pragma unroll 1
    for (int t = warp == 8 ? 0 : warp < 8 ? warp + 1 : warp == 11 ? 64 : warp; t < B_PUB / 8; t += (warp == 8 ? 64 : 10))
      w_mbar_init(bars + 8 * t, t < B_WE / 8 ? 1 : t < B_RE / 8 ? 2 : 4);
    fence_mbar_init();
    cluster_arrive();
    if (warp == 9) prefetch_tmap(&tmWv);
    if (wg == 2) bar_arrive(1, 256);
    if (warp == 8 && !spare) {
      #pragma unroll 1
      for (int kb = 0; kb < 8; kb++) {
        w_expect_tx(bars + B_AF + 8 * kb, 16384);
        tma_load_2d(base + k_addrA(kb), &tmC, bars + B_AF + 8 * kb, kb * 64, mt * 128);
        if (kb == 0) cluster_wait();
        if (kb < 6) {
          w_expect_tx(bars + B_WF + 8 * kb, 16384);
          tma_load_2d_mc(base + k_addrW(kb) + rank * 8192, &tmWk, bars + B_WF + 8 * kb, h0 * 128 + rank * 64, kb * 64);
        }
      }
    }
  }
  const Sched::Pair& sp = sched.pair[p];
  const int nitems = sp.nitems, nsteps = sp.nsteps;
  auto oent = [&](int k) -> uint32_t { return sp.oent[k]; };
  const int ot = sp.otask, m = (ot & 7) * 2 + rank, grp = m * 8 + (ot >> 3);

  if (wg == 0) {
    asm volatile("setmaxnreg.dec.sync.aligned.u32 24;");
    const int lane = threadIdx.x & 31;
    #pragma unroll 1
    for (int t = B_PUB / 8 + warp; t < 80; t += 4) w_mbar_init(bars + 8 * t, t < B_RDY / 8 ? 4 : 1);
    bar_sync(6, 128);
    bar_arrive(7, 256); bar_arrive(8, 256);
    cluster_wait();
    const unsigned int tag = ld_relaxed(&g_x.epoch) + 1;
    if (warp == 0) {
      if (!spare) {
        int s = 0, ph = 0;
        tma_prefetch_2d(&tmWv, sp.khead[0] * 128 + rank * 64, (p & 7) * 64);
        #pragma unroll 1
        for (int g = 6; g < 64; g++) {
          const int u = g >> 3, kb = g & 7;
          if (kb == 0 && u < 7) tma_prefetch_2d((u & 1) ? &tmWk : &tmWv, sp.khead[(u + 1) >> 1] * 128 + rank * 64, (p & 7) * 64);
          mbar_wait(bars + B_WE + 8 * s, ph);
          w_expect_tx(bars + B_WF + 8 * s, 16384);
          tma_load_2d_mc(base + k_addrW(s) + rank * 8192, (u & 1) ? &tmWv : &tmWk, bars + B_WF + 8 * s, sp.khead[u >> 1] * 128 + rank * 64, kb * 64);
          if (++s == 6) { s = 0; ph ^= 1; }
        }
      }
      int s = 0, ph = 0;
      auto next_entry = [&](int bytes) {
        mbar_wait(bars + B_RE + 8 * s, ph);
        w_expect_tx(bars + B_RF + 8 * s, bytes);
      };
      auto advance = [&]() { if (++s == 6) { s = 0; ph ^= 1; } };
      if (spare) {
        #pragma unroll 1
        for (int g = 0; g < 24; g++) {
          if (g == 8) mbar_wait(bars + R_MOD, 0);
          next_entry(32768);
          for (int k = 0; k < 2; k++) tma_load_3d(base + s * 32768 + k * 16384, &tmWm, bars + B_RF + 8 * s, 0, (g & 7) * 64, (g >> 3) * 16 + (blockIdx.x - NCTA) * 4 + k * 2);
          advance();
        }
      }
      mbar_wait(bars + R_H1, 0);
      fence_async_global();
      int vrow = -1;
      #pragma unroll 1
      for (int i = 0; i <= nitems; i++) {
        const int item = sp.item[i & (MAX_ITEMS - 1)], h = item >> 3, j = item & 7;
        if (i < nitems) {
          const int row0 = j * 256 + ((i & 1) ? rank : 3 - rank) * 64, row1 = j * 256 + ((i & 1) ? 3 - rank : rank) * 64;
          #pragma unroll 1
          for (int kb = 0; kb < 8; kb++) {
            next_entry(32768);
            tma_load_2d_mc(base + s * 32768 + 16384 + rank * 8192, &tmWq, bars + B_RF + 8 * s, h * 128 + rank * 64, kb * 64);
            bulk_load(base + s * 32768, sched.h1 + row0 * DM + kb * 4096, 8192, bars + B_RF + 8 * s);
            bulk_load(base + s * 32768 + 8192, sched.h1 + row1 * DM + kb * 4096, 8192, bars + B_RF + 8 * s);
            advance();
          }
          mbar_wait(bars + R_ITEM + 8 * i, 0);
          fence_async_global();
        }
        #pragma unroll 1
        for (int n = i < nitems ? 4 * j + 3 : 0; n >= 0; n--) {
          const int krow = (h * 2 + rank) * SEQ + (n >> 1) * 128;
          const int row = (n & 1) ? krow : vrow;
          if (i + 1 == nitems && n == min(4 * j + 3, 2 * PF_AT + 1)) w_arrive(bars + R_NEAR);
          next_entry(row >= 0 ? 32768 : 0);
          if (row >= 0) bulk_load_mc(base + s * 32768 + rank * 16384, sched.kvc + (size_t)row * 64, bars + B_RF + 8 * s);
          advance();
          if (!(n & 1)) vrow = krow + 64 * SEQ;
        }
      }
      if (!spare) {
      const int oc = ((ot >> 3) & 1) * 4 + rank * 2;
      auto o_next = [&](int k, int bytes) {
        const uint32_t v = oent(k); s = v & 7;
        mbar_wait(bars + B_RE + 8 * s, v >> 3);
        w_expect_tx(bars + B_RF + 8 * s, bytes);
      };
      #pragma unroll 1
      for (int i = 0; i < nsteps; i++) {
        const int c0 = sp.ochunk[i][0], c1 = sp.ochunk[i][1];
        const int pf = i - nsteps + PF_MOE;
        if (pf >= 0 && pf < 3)
          bulk_prefetch((pf == 0 ? w_gate : pf == 1 ? w_up : w_down) + (size_t)blockIdx.x * (DM * FF / NCTA), DM * FF / NCTA * 2);
        if (c0 < 64) { o_next(3 * i, 32768); tma_load_3d_mc(base + s * 32768 + rank * 16384, &tmWo, bars + B_RF + 8 * s, 0, c0 * 64, oc); }
        mbar_wait(bars + R_CTX + 8 * i, 0);
        fence_async_global();
        o_next(3 * i + 1, c0 < 64 ? 32768 : 16384);
        if (c0 < 64) bulk_load(base + s * 32768, sched.kvc + (size_t)((128 + c0) * SEQ + m * 128) * 64, 16384, bars + B_RF + 8 * s);
        bulk_load(base + s * 32768 + 16384, sched.kvc + (size_t)((128 + c1) * SEQ + m * 128) * 64, 16384, bars + B_RF + 8 * s);
        o_next(3 * i + 2, 32768);
        tma_load_3d_mc(base + s * 32768 + rank * 16384, &tmWo, bars + B_RF + 8 * s, 0, c1 * 64, oc);
      }
      const int f0 = (blockIdx.x < FF / 16 ? blockIdx.x : 0) * 16;
      o_next(3 * nsteps, 32768);
      tma_load_3d(base + s * 32768, &tmWd, bars + B_RF + 8 * s, 0, f0, 0);
      bulk_load(base + s * 32768 + 16384, xin + (size_t)grp * 16 * DM, 16384, bars + B_RF + 8 * s);
      o_next(3 * nsteps + 1, 32768);
      #pragma unroll 1
      for (int k = 0; k < 4; k++) tma_load_2d(base + s * 32768 + k * 8192, (k & 2) ? &tmWu : &tmWg, bars + B_RF + 8 * s, f0, (k & 1) * 256);
      #pragma unroll 1
      for (int k = 0; k < 4; k++) w_expect_tx(bars + R_PART + 8 * k, 16384);
      #pragma unroll 1
      for (int k = 2; k < 4; k++) mbar_wait(bars + B_RE + 8 * (oent(3 * nsteps + k) & 7), oent(3 * nsteps + k) >> 3);
      uint32_t todo = 0xff;
      #pragma unroll 1
      for (int n = 0; n < WAIT_LIM && todo; n++) {
        uint32_t now = __ballot_sync(0xffffffff, ld_acquire(&g_x.sent[grp][lane & 7]) == tag) & todo;
        todo &= ~now;
        if (now) fence_async_global();
        #pragma unroll 1
        for (; now; now &= now - 1) {
          const int q = __ffs(now) - 1;
          bulk_load(base + (oent(3 * nsteps + 2 + (q >> 2)) & 7) * 32768 + (q & 3) * 8192, sched.part + (grp * 8 + q) * 4096, 8192, bars + R_PART + 8 * (q >> 1));
        }
      }
      }
    } else if (warp < 3) {
      const int w = warp - 1, n1 = w * NPUB + (spare ? 3 : 5) + nitems;
      #pragma unroll 1
      for (int n = w * NPUB; n < n1; n++) {
        #pragma unroll 1
        for (int k = 0; k < 8 * WAIT_LIM; k++) { if (mbar_try(bars + B_PUB + 8 * n, 0)) break; }
        const uint32_t idx = lds_u32(base + SM_MAIL + 4 * n);
        fence_async_global();
        if (lane == 0 && idx < (unsigned)C_END) red_release(idx);
        __syncwarp();
      }
    } else {
      *reinterpret_cast<volatile uint32_t*>(smem_raw + SM_KEY + 48) = tag;
      if (!spare) { mbar_wait(bars + B_AF + 8 * X_AT, 0); bulk_prefetch(xin + (size_t)blockIdx.x * 16 * DM, 16 * DM * 2); }
      #pragma unroll 1
      for (int n = 0; n < 8 + nsteps; n++) {
        if (n == 2 + nitems) n = 7;
        int idx = n == 0 ? C_MOD : n == 1 ? C_H1 : C_MOD2, cnt = n == 0 ? 8 : n == 1 ? 256 : 16;
        if (n == 2) tma_prefetch_2d(&tmWq, (sp.item[0] >> 3) * 128 + rank * 64, (sp.item[0] & 7) * 64);
        if (n >= 2 && n < 7) { idx = C_KV + (sp.item[n - 2] >> 3); cnt = 32; }
        if (n >= 8) { const int c0 = sp.ochunk[n - 8][0], c1 = sp.ochunk[n - 8][1]; idx = C_CTX + (((lane & 1) && c0 < 64 ? c0 : c1) >> 1) * 8 + (ot & 7); cnt = 4; }
        wait_count_lazy(idx, cnt * tag);
        w_arrive(bars + B_RDY + 8 * n);
        if (n == 8 + PF_N - 1) {
          #pragma unroll 1
          for (int k = 0; k < 8 * WAIT_LIM; k++) { if (mbar_try(bars + R_NEAR, 0)) break; }
          bulk_prefetch(w_o + (size_t)blockIdx.x * (NH * DH * DM / NCTA), NH * DH * DM / NCTA * 2);
          #pragma unroll 1
          for (int k = 0; k < PF_N; k++) {
            const int cc = sp.ochunk[k][(ot >> 3) & 1];
            if (cc < 64) bulk_prefetch(sched.kvc + ((size_t)(128 + cc) * SEQ + m * 128) * 64, 16384);
          }
        }
      }
    }
    __syncwarp();
    cluster_arrive();
    if (!spare) {
      bar_sync(6, 128);
      asm volatile("setmaxnreg.inc.sync.aligned.u32 88;");
      const int pos = blockIdx.x * 4 + (lane & 1) * 2, col = (blockIdx.x >> 2) * 16 + (blockIdx.x & 3) * 2 + (lane & 1) * 8, src = threadIdx.x >> 1;
      uint32_t gbest = 0, hh = 0, gbf = 0;
      uint2 xx = make_uint2(0, 0);
      uint4 ya = make_uint4(0, 0, 0, 0), yb = make_uint4(0, tag, 0, tag);
      auto poll_y = [&]() {
        if (ya.y != tag || ya.w != tag) ya = ld_tagged2(&g_x.yll[src][pos]);
        if (yb.y != tag || yb.w != tag) yb = ld_tagged2(&g_x.yll[src + 64][pos]);
        return __all_sync(0xffffffff, ya.y == tag && ya.w == tag && yb.y == tag && yb.w == tag);
      };
      ya.y = tag - 1; if (src + 64 < FF / 16) yb.y = tag - 1;
      if (warp == 3) {
        gbf = __ldcg(reinterpret_cast<const uint32_t*>(g_x.mod + 5 * DM + col));
        uint32_t have = 0;
        uint2 k[4];
        #pragma unroll
        for (int i = 0; i < 4; i++) k[i] = make_uint2(0, tag - 1);
        #pragma unroll 1
        for (int n = 0; n < WAIT_LIM; n++) {
          #pragma unroll
          for (int i = 0; i < 4; i++) if (k[i].y != tag) k[i] = ld_tagged(&g_x.keys[i * 32 + lane][0]);
          if (gbest != have) {
            const int g = ((0xffffu - gbest) >> 4) & 127;
            uint4 hv[4];
            #pragma unroll
            for (int i = 0; i < 4; i++) hv[i] = ld_tagged2(&g_x.row[g][0][i * 64 + lane * 2]);
            xx = ld_tagged(&g_x.row[g][1][(col >> 8) * 128 + ((col >> 2) & 1) * 64 + ((col >> 3) & 31) * 2 + ((col >> 1) & 1)]);
            bool ok = xx.y == tag;
            #pragma unroll
            for (int i = 0; i < 4; i++) { ok = ok && hv[i].y == tag && hv[i].w == tag; reinterpret_cast<uint2*>(smem_raw + SM_H2)[(i >> 1) * 64 + lane * 2 + (i & 1)] = make_uint2(hv[i].x, hv[i].z); }
            if (lane == 0) *reinterpret_cast<uint32_t*>(smem_raw + SM_KEY + 32) = gbest;
            have = __all_sync(0xffffffff, ok) ? gbest : 0;
          }
          bool all = true;
          #pragma unroll
          for (int i = 0; i < 4; i++) { all = all && k[i].y == tag; gbest = max(gbest, k[i].y == tag ? k[i].x : 0u); }
          gbest = __reduce_max_sync(0xffffffff, gbest);
          if (__all_sync(0xffffffff, all) && gbest == have) break;
        }
        __syncwarp();
        w_arrive(bars + R_KEY);
        if (blockIdx.x == 0 && lane == 0) g_x.epoch = tag;
        hh = lds_u32(base + SM_H2 + col * 2);
      }
      const float rsel = rbf(__uint_as_float((((gbest & 0x80000000u) ? gbest & 0x7fffffffu : ~gbest) & 0xfffff000u) | 0x800u));
      const float rs = rbf(__fdividef(1.f, 1.f + __expf(-rsel)));
      bar_sync(9, 384);
      #pragma unroll 1
      for (int n = 0; n < WAIT_LIM; n++) { if (poll_y()) break; }
      float y0 = __uint_as_float(ya.x) + __uint_as_float(yb.x), y1 = __uint_as_float(ya.z) + __uint_as_float(yb.z);
      #pragma unroll
      for (int o = 2; o < 32; o <<= 1) { y0 += __shfl_xor_sync(0xffffffff, y0, o); y1 += __shfl_xor_sync(0xffffffff, y1, o); }
      float2* s_y = reinterpret_cast<float2*>(smem_raw + SM_KEY + 64);
      if (lane < 2) s_y[warp * 2 + lane] = make_float2(y0, y1);
      bar_sync(6, 128);
      if (warp == 3 && lane < 2) {
        y0 = 0.f; y1 = 0.f;
        #pragma unroll
        for (int i = 0; i < 4; i++) { y0 += reinterpret_cast<const float*>(s_y)[i * 4 + lane]; y1 += reinterpret_cast<const float*>(s_y)[i * 4 + 2 + lane]; }
        const float o0 = bf_lo(xx.x) + rbf(bf_lo(gbf) * rbf(bf_lo(hh) + rbf(rbf(y0) * rs)));
        const float o1 = bf_hi(xx.x) + rbf(bf_hi(gbf) * rbf(bf_hi(hh) + rbf(rbf(y1) * rs)));
        *reinterpret_cast<uint32_t*>(out + (size_t)((0xffffu - gbest) & (SEQ - 1)) * DM + col) = pack_bf16(o0, o1);
      }
    }
    __syncwarp();
    cluster_wait();
  } else {
    asm volatile("setmaxnreg.inc.sync.aligned.u32 240;");
    Ctx x;
    x.w = wg - 1; x.base = base; x.bars = bars; x.nev = 0; x.sched = &sched;
    const int w = x.w, warp4 = warp & 3;
    x.rel = mapa(bars, (warp4 & 1) ^ 1);
    x.rel1 = (threadIdx.x & 127) == 32 || (threadIdx.x & 127) == 64;
    if (warp != 8 || spare) cluster_wait();
    if (w == 1 || spare) bar_sync(7 + w, 256);
    uint32_t PA[32], PB[32];
    int vtile = -1;
    if (spare) {
      mod_cta(x, cvec);
    } else {
      const int lane = wg_tid() & 31;
      Row xn[2];
      float acc0[64], acc1[64];
      int s = 2 * w, ph = w;
      #pragma unroll 1
      for (int u = w; u < 8; u += 2) {
        bar_sync(1 + w, 256);
        int ps = 0;
        #pragma unroll 1
        for (int kb = 0; kb < 8; kb++) {
          if (u < 2) mbar_wait(bars + B_AF + 8 * kb, 0);
          mbar_wait(bars + B_WF + 8 * s, ph);
          const uint32_t da = desc_lo(base + k_addrA(kb), 16), dw = desc_lo(base + k_addrW(s), 8192);
          wgmma_fence();
          kblock_n128<0>(acc0, da, dw, kb != 0);
          kblock_n128<512>(acc1, da, dw, kb != 0);
          wgmma_commit();
          if (kb == 7) bar_arrive(1 + (w ^ 1), 256);
          if (kb > 0) {
            wgmma_wait<1>();
            mbar_arrive_remote_if(x.rel + B_WE + 8 * ps, x.rel1);
            if (u == 7 && !(kb & 1)) {
              ring_release(x, kb == 2 ? 0 : kb - 3, false);
              if (kb > 2) ring_release(x, kb - 2, false);
            }
          }
          ps = s;
          if (++s == 6) { s = 0; ph ^= 1; }
        }
        Row t[2];
        const int lrow = blockIdx.x * 16 + w * 8 + warp4 * 2;
        if (u == w) { t[0] = ldg_row(xin + (size_t)lrow * DM, lane); t[1] = ldg_row(xin + (size_t)(lrow + 1) * DM, lane); }
        if (u == LN_AT || u == LN_AT + 1) {
          mbar_wait(bars + R_MOD, 0);
          t[0] = ldca_row(g_x.mod, lane); t[1] = ldca_row(g_x.mod + DM, lane);
        }
        wgmma_wait<0>();
        fence_regs(acc0); fence_regs(acc1);
        mbar_arrive_remote_if(x.rel + B_WE + 8 * ps, x.rel1);
        if (u == 6) { for (int k = 0; k < 5; k++) ring_release(x, k, false); }
        if (u >= 6) ring_release(x, 5, false);
        if (u == 7) {
          pack_tile(acc0, PA, 1.f, 1.f); pack_tile(acc1, PB, 1.f, 1.f);
          vtile = sp.khead[3] * 16 + mt;
          break;
        }
        s += 2; ph ^= 1; if (s >= 6) { s -= 6; ph ^= 1; }
        if (u == 0) bar_sync(7, 256);
        const int tile = sp.khead[u >> 1] * 16 + mt;
        __nv_bfloat16* dst = kv_tile(x, tile);
        uint32_t D[32];
        pack_tile(acc0, D, 1.f, 1.f); store_tile(dst + 2048, D);
        pack_tile(acc1, D, 1.f, 1.f); store_tile(dst, D);
        if (u == w) {
          #pragma unroll 1
          for (int r = 0; r < 2; r++) {
            float st[2] = {0.f, 0.f};
            #pragma unroll
            for (int i = 0; i < 16; i++) { const float v = row_at(t[0], i); st[0] += v; st[1] = fmaf(v, v, st[1]); }
            warp_sums(st);
            const float mean = st[0] * (1.f / DM), var = fmaxf(fmaf(-mean, mean, st[1] * (1.f / DM)), 0.f);
            float sd; asm("sqrt.approx.ftz.f32 %0, %1;" : "=f"(sd) : "f"(rbf(rbf(var) + 1e-5f)));
            const float inv = rcp_fast(rbf(sd));
            const uint32_t nm = pack_bf16(-mean, -mean);
            xn[0] = xn[1];
            #pragma unroll
            for (int i = 0; i < 8; i++) { const uint32_t d = add2(t[0].v[i], nm); xn[1].v[i] = pack_bf16(bf_lo(d) * inv, bf_hi(d) * inv); }
            t[0] = t[1];
          }
        }
        if (u == LN_AT || u == LN_AT + 1) {
          #pragma unroll 1
          for (int r = lrow; r < lrow + 2; r++) {
            Row hr;
            #pragma unroll
            for (int i = 0; i < 8; i++) { const uint32_t h = add2(mul2(xn[0].v[i], add2(t[1].v[i], 0x3f803f80u)), t[0].v[i]); hr.v[i] = pack_bf16(bf_lo(h) * QSCALE, bf_hi(h) * QSCALE); }
            __nv_bfloat16* hp = sched.h1 + (r & ~63) * DM + (lane >> 3) * 4096 + (r & 63) * 64 + (((lane ^ r) & 7) << 3);
            stg_v4(hp, hr.v[0], hr.v[1], hr.v[2], hr.v[3]); stg_v4(hp + 4 * 4096, hr.v[4], hr.v[5], hr.v[6], hr.v[7]);
            xn[0] = xn[1];
          }
          publish(x, C_H1);
        }
        publish(x, C_KV + (tile >> 4));
      }
    }
    const int last = attention(x, sp.item, nitems, rank, PA, PB, vtile);
    const int lane = wg_tid() & 31, cw = w * 4 + warp4;
    const int row0 = grp * 16 + cw * 2;
    const bool moe_cta = blockIdx.x < FF / 16;
    if (spare) { store_ctx(x, last, PB); __syncwarp(); cluster_arrive(); cluster_wait(); return; }
    const int kl = 3 * nsteps - 3;
    uint2* const yp = &g_x.yll[blockIdx.x][cw * 64 + (lane & 3) * 16 + (lane >> 2) * 2];
    Row ga, sb, cb, gb, wr;
    unsigned int tag;
    {
      float accA[64], accB[64];
      const int t0 = oent(0) == oent(1);
      uint32_t pa = 0, pb = 0;
      #pragma unroll 1
      for (int t = t0; t < 2 * nsteps - 2; t++) {
        const uint32_t eb = oent(3 * (t >> 1) + 2 * (t & 1)), ea = oent(3 * (t >> 1) + 1);
        o_wait_full(bars, eb);
        o_wait_full(bars, ea);
        const uint32_t da = desc_lo(base + w * 4096, 16) + (ea & 7) * 2048 + (t & 1) * 1024, db = desc_lo(base, 8192) + (eb & 7) * 2048;
        wgmma_fence();
        kblock_n128<0, 0, SW64>(accA, da, db, t != t0); kblock_n128<0, 1024, SW64>(accB, da, db, t != t0);
        wgmma_commit();
        if (t == CTX_T) store_ctx(x, last, PB);
        if (t > t0) { wgmma_wait<1>(); slot_release(x, pb, false); if (!(t & 1)) slot_release(x, pa, false); }
        pa = ea & 7; pb = eb & 7;
      }
      const uint32_t e0 = oent(kl), ea = oent(kl + 1), eb = oent(kl + 2);
      const uint32_t da = desc_lo(base + w * 4096, 16) + (ea & 7) * 2048;
      const uint32_t db0 = desc_lo(base, 8192) + (e0 & 7) * 2048, db1 = desc_lo(base, 8192) + (eb & 7) * 2048;
      ga = ldca_row(g_x.mod + 2 * DM, lane); sb = ldca_row(g_x.mod + 3 * DM, lane); cb = ldca_row(g_x.mod + 4 * DM, lane); gb = ldca_row(g_x.mod + 5 * DM, lane);
      wr = ldca_row(w_r, lane);
      tag = lds_u32(base + SM_KEY + 48);
      if (moe_cta) st_tagged2(yp, 0, 0, 0);
      const bool lead = (nitems & 1) == w;
      o_wait_full(bars, e0);
      o_wait_full(bars, ea);
      o_wait_full(bars, eb);
      if (!lead) bar_sync(1, 256);
      wgmma_fence();
      kblock_n128<0, 0, SW64>(accA, da, db0, 1); kblock_n128<1024, 0, SW64>(accA, da, db1, 1);
      wgmma_commit();
      kblock_n128<0, 1024, SW64>(accB, da, db0, 1); kblock_n128<1024, 1024, SW64>(accB, da, db1, 1);
      wgmma_commit();
      if (lead) bar_arrive(1, 256);
      wgmma_wait<2>();
      slot_release(x, pa, false); slot_release(x, pb, false);
      __syncwarp();
      cluster_arrive();
      const uintptr_t dst = reinterpret_cast<uintptr_t>(sched.part + ((m * 8 + cw) * 8 + (ot >> 3)) * 4096 + lane * 8);
      const uint32_t even = ~lane & 1;
      auto send = [&](const float (&acc)[64], int h) {
        uint32_t D[32];
        pack_tile(acc, D, 1.f, 1.f);
        #pragma unroll
        for (int i = 0; i < 8; i++) stg_v4(reinterpret_cast<uint8_t*>(dst ^ ((h * 4 + (i >> 1)) << 4)) + (h * 8 + i) * 512, (D[4*i] & ~even) | (tag & even), D[4*i+1], D[4*i+2], D[4*i+3]);
      };
      wgmma_wait<1>();
      fence_regs(accA);
      send(accA, 0);
      o_wait_full(bars, eb);
      wgmma_wait<0>();
      fence_regs(accB);
      send(accB, 1);
      __syncwarp();
      if (lane == 0) red_relaxed(&g_x.sent[m * 8 + cw][ot >> 3]);
    }
    asm volatile("setmaxnreg.dec.sync.aligned.u32 208;");
    const uint32_t sD = base + (oent(kl + 3) & 7) * 32768, sW = base + (oent(kl + 4) & 7) * 32768;
    o_wait_full(bars, oent(kl + 3)); o_wait_full(bars, oent(kl + 4));
    Row x1[2];
    #pragma unroll
    for (int r = 0; r < 2; r++) x1[r] = lds_row(sD + 16384 + (cw * 2 + r) * 1024, lane);
    uint4 wgv[4], wuv[4], wdv[4];
    #pragma unroll
    for (int r = 0; r < 4; r++) {
      const uint32_t k = (lane & 7) + ((lane >> 4) << 3), h = (lane >> 3) & 1;
      wgv[r] = ldsm_x4_t(sW + (cw * 64 + r * 16 + k) * 32 + ((h ^ ((lane >> 2) & 1)) << 4));
      wuv[r] = ldsm_x4_t(sW + 16384 + (cw * 64 + r * 16 + k) * 32 + ((h ^ ((lane >> 2) & 1)) << 4));
      wdv[r] = ldsm_x4_t(sD + cw * 2048 + k * 128 + (((r * 2 + h) ^ (lane & 7)) << 4));
    }
    const Row cb1 = one_plus(cb);
    float u[16], ub[2] = {0.f, 0.f};
    #pragma unroll
    for (int i = 0; i < 16; i++) { u[i] = row_at(cb1, i) * row_at(wr, i); ub[0] += u[i]; ub[1] = fmaf(row_at(sb, i), row_at(wr, i), ub[1]); }
    warp_sums(ub);
    float st[6] = {0.f, 0.f, 0.f, 0.f, 0.f, 0.f};
    uint32_t key[2];
    {
      const uint32_t po = base + ((lane & 7) * 2 + (cw >> 2)) * 512 + (cw & 3) * 128;
      const uint32_t par = (lane & 3) == 0 ? tag & 1 : 0;
      Row av[2][2];
      #pragma unroll 1
      for (int n = 0; n < WAIT_LIM; n++) {
        uint32_t late = 0;
        #pragma unroll
        for (int k = 0; k < 4; k++) {
          mbar_wait(bars + R_PART + 8 * k, 1);
          late = (late & 7) * 2;
          uint32_t odd = 0;
          const uint32_t pa = po + (oent(kl + 5 + (k >> 1)) & 7) * 32768 + (k & 1) * 16384;
          #pragma unroll
          for (int r = 0; r < 2; r++) {
            const uint32_t sw = ((r * 4 + (lane >> 3)) ^ (lane & 7)) << 4;
            const uint4 lo = ldsm_x4(pa + sw), hi = ldsm_x4(pa + 8192 + sw);
            const Row v{{lo.x ^ par, lo.y, lo.z ^ par, lo.w, hi.x ^ par, hi.y, hi.z ^ par, hi.w}};
            odd |= v.v[0] | v.v[2] | v.v[4] | v.v[6];
            av[r][k >> 1] = (k & 1) ? add_row(av[r][k >> 1], v) : v;
          }
          late |= odd & 1;
        }
        late = __reduce_or_sync(0xffffffff, (lane & 3) == 0 ? late : 0);
        if (!late) break;
        #pragma unroll 1
        for (; late; late &= late - 1) {
          const int k = 4 - __ffs(late);
          const uint32_t off = (k & 1) * 16384 + ((lane >> 3) * 2 + (cw >> 2)) * 512 + (cw & 3) * 128 + (lane & 7) * 16;
          uint4 v[4];
          #pragma unroll
          for (int i = 0; i < 4; i++) v[i] = ld_tagged2(reinterpret_cast<const uint8_t*>(sched.part + (grp * 8 + (k >> 1) * 4) * 4096) + off + i * 4096);
          #pragma unroll
          for (int i = 0; i < 4; i++) sts_v4(base + (oent(kl + 5 + (k >> 1)) & 7) * 32768 + off + i * 4096, v[i].x, v[i].y, v[i].z, v[i].w);
        }
        __syncwarp();
      }
      #pragma unroll
      for (int r = 0; r < 2; r++) {
        x1[r] = fma_row(ga, add_row(av[r][0], av[r][1]), x1[r]);
        #pragma unroll
        for (int i = 0; i < 16; i++) { const float v = row_at(x1[r], i); st[3*r] += v; st[3*r+1] = fmaf(v, v, st[3*r+1]); st[3*r+2] = fmaf(v, u[i], st[3*r+2]); }
      }
      warp_sums(st);
      #pragma unroll
      for (int r = 0; r < 2; r++) {
        ln_stats(st[3*r], st[3*r+1]);
        const uint32_t rb = __float_as_uint(fmaf(st[3*r+1], fmaf(-st[3*r], ub[0], st[3*r+2]), ub[1]));
        key[r] = (((rb & 0x80000000u) ? ~rb : (rb | 0x80000000u)) & 0xfffff000u) | (0xfffu - (uint32_t)(row0 + r));
      }
    }
    float* s_red = reinterpret_cast<float*>(smem_raw + SM_RED);
    uint32_t* s_key = reinterpret_cast<uint32_t*>(smem_raw + SM_KEY);
    const int rb = key[1] > key[0];
    const uint32_t wbest = rb ? key[1] : key[0];
    if (lane == 0) s_key[cw] = wbest;
    bar_sync(5, 256);
    const uint32_t cbest = __reduce_max_sync(0xffffffff, s_key[lane & 7]);
    if (wbest == cbest && lane == 0) st_tagged(&g_x.keys[grp][0], cbest, tag);
    Row xb, xo;
    #pragma unroll
    for (int i = 0; i < 8; i++) { xb.v[i] = rb ? x1[1].v[i] : x1[0].v[i]; xo.v[i] = rb ? x1[0].v[i] : x1[1].v[i]; }
    const Row hb = fma_row(ln_apply(xb, rb ? st[3] : st[0], rb ? st[4] : st[1]), cb1, sb);
    if (wbest == cbest) {
      #pragma unroll
      for (int i = 0; i < 4; i++) st_tagged2(&g_x.row[grp][0][i * 64 + lane * 2], hb.v[2*i], hb.v[2*i+1], tag);
      #pragma unroll
      for (int i = 0; i < 4; i++) st_tagged2(&g_x.row[grp][1][i * 64 + lane * 2], xb.v[2*i], xb.v[2*i+1], tag);
    }
    const Row ob = fma_row(gb, hb, xb);
    if (wbest != cbest) store_row(out + (size_t)(row0 + rb) * DM, lane, ob);
    store_row(out + (size_t)(row0 + 1 - rb) * DM, lane, fma_row(gb, fma_row(ln_apply(xo, rb ? st[0] : st[3], rb ? st[1] : st[4]), cb1, sb), xo));
    mbar_wait(bars + R_KEY, 1);
    if (moe_cta) {
      float cg[4] = {0, 0, 0, 0}, cu[4] = {0, 0, 0, 0};
      #pragma unroll
      for (int r = 0; r < 4; r++) {
        const uint32_t b0 = lds_u32(base + SM_H2 + (cw * 64 + r * 16) * 2 + (lane & 3) * 4), b1 = lds_u32(base + SM_H2 + (cw * 64 + r * 16) * 2 + 16 + (lane & 3) * 4);
        mma16816(cg, wgv[r], b0, b1); mma16816(cu, wuv[r], b0, b1);
      }
      s_red[cw * 32 + (lane & 3) * 8 + (lane >> 2)] = (lane & 2) ? ((lane & 1) ? cu[2] : cu[0]) : ((lane & 1) ? cg[2] : cg[0]);
      bar_sync(5, 256);
      float g = 0.f;
      #pragma unroll
      for (int i = 0; i < 8; i++) g += s_red[i * 32 + lane];
      g = rbf(g);
      const float act = rbf(__fdividef(g, 1.f + __expf(-g))) * __shfl_down_sync(0xffffffff, g, 16);
      const uint32_t a2 = pack_bf16(act, __shfl_down_sync(0xffffffff, act, 1));
      const uint32_t b0 = __shfl_sync(0xffffffff, a2, (lane & 3) * 2), b1 = __shfl_sync(0xffffffff, a2, (lane & 3) * 2 + 8);
      float y0 = 0.f, y1 = 0.f;
      #pragma unroll
      for (int r = 0; r < 4; r++) {
        float c[4] = {0, 0, 0, 0};
        mma16816(c, wdv[r], b0, b1);
        if ((lane & 3) == r) { y0 = c[0]; y1 = c[2]; }
      }
      st_tagged2(yp, __float_as_uint(y0), __float_as_uint(y1), tag);
    }
    bar_arrive(9, 384);
    if (wbest == cbest && wbest != s_key[8]) store_row(out + (size_t)(row0 + rb) * DM, lane, ob);
    __syncwarp();
    cluster_wait();
  }
}

typedef CUresult (*EncodeFn)(CUtensorMap*, CUtensorMapDataType, cuuint32_t, void*, const cuuint64_t*, const cuuint64_t*, const cuuint32_t*,
                             const cuuint32_t*, CUtensorMapInterleave, CUtensorMapSwizzle, CUtensorMapL2promotion, CUtensorMapFloatOOBfill);

struct HostState {
  bool ready = false;
  EncodeFn encode = nullptr;
  CUtensorMap tmC, tmWq, tmWk, tmWv, tmWo, tmWg, tmWu, tmWd, tmWm;
  Sched sched;
};

void make_map(EncodeFn enc, CUtensorMap* m, const void* ptr, int rank, const cuuint64_t* dims, const cuuint64_t* strides, const cuuint32_t* box, bool wide = true) {
  const cuuint32_t es[3] = {1, 1, 1};
  enc(m, CU_TENSOR_MAP_DATA_TYPE_BFLOAT16, rank, const_cast<void*>(ptr), dims, strides, box, es, CU_TENSOR_MAP_INTERLEAVE_NONE,
      wide ? CU_TENSOR_MAP_SWIZZLE_128B : CU_TENSOR_MAP_SWIZZLE_32B, wide ? CU_TENSOR_MAP_L2_PROMOTION_L2_128B : CU_TENSOR_MAP_L2_PROMOTION_NONE, CU_TENSOR_MAP_FLOAT_OOB_FILL_NONE);
}
void make_2d(EncodeFn enc, CUtensorMap* m, const void* ptr, int rows, int cols, int box_rows) {
  const cuuint64_t dims[2] = {(cuuint64_t)cols, (cuuint64_t)rows}, strides[1] = {(cuuint64_t)cols * 2};
  const cuuint32_t box[2] = {64, (cuuint32_t)box_rows};
  make_map(enc, m, ptr, 2, dims, strides, box);
}
void make_3d(EncodeFn enc, CUtensorMap* m, const void* ptr, int rows, int chunks, size_t row_stride, size_t chunk_stride, int box_rows = 64, int box_chunks = 2) {
  const cuuint64_t dims[3] = {64, (cuuint64_t)rows, (cuuint64_t)chunks}, strides[2] = {row_stride, chunk_stride};
  const cuuint32_t box[3] = {64, (cuuint32_t)box_rows, (cuuint32_t)box_chunks};
  make_map(enc, m, ptr, 3, dims, strides, box);
}

void make_ffn(EncodeFn enc, CUtensorMap* m, const void* ptr) {
  const cuuint64_t dims[2] = {(cuuint64_t)FF, (cuuint64_t)DM}, strides[1] = {(cuuint64_t)FF * 2};
  const cuuint32_t box[2] = {16, 256};
  make_map(enc, m, ptr, 2, dims, strides, box, false);
}

#define SR 0x213312
#define SEED 12345
#define SPARE_N 3
void build_sched(Sched& s) {
  memset(&s, 0, sizeof(s));
  const int NP = NCTA / 2, korder[4] = {(KORDER >> 12) & 3, (KORDER >> 8) & 3, (KORDER >> 4) & 3, KORDER & 3};
  const int sround[4][2][3] = {{}, {{1}, {2}}, {{1, 2}, {1, 2}}, {{(SR >> 20) & 3, (SR >> 16) & 3, (SR >> 12) & 3}, {(SR >> 8) & 3, (SR >> 4) & 3, SR & 3}}};
  int jv[4][NP], used[4][8] = {};
  for (int r = 0; r < 4; r++) for (int p = 0; p < NP; p++) jv[r][p] = (r & 2) ? 7 - ((p + 4 * (r & 1)) & 7) : (p + 4 * (r & 1)) & 7;
  for (int q = 0; q < 2; q++) {
    s.pair[NP + q].nitems = SPARE_N;
    for (int i = 0; i < SPARE_N; i++) {
      const int r = sround[SPARE_N][q][i];
      s.pair[NP + q].item[i] = (uint8_t)((r * 8 + used[r][6]++) * 8 + 6);
      for (int p = 0; p < NP; p++) if (jv[r][p] == 6) { jv[r][p] = -2; break; }
    }
  }
  auto cost = [&](int p) {
    int u = 8 - ((p >> 4) < SPARE_N ? 21 : 22), z = 0, none = 0;
    for (int r = 0; r < 4; r++) { u += jv[r][p]; z += jv[r][p] == 0; none += jv[r][p] < 0; }
    return 4 * u * u + (z > 1) + 4 * (none > 1);
  };
  uint32_t rng = SEED;
  for (int it = 0; it < 2000000; it++) {
    if ((it & 255) == 0) { int t = 0; for (int p = 0; p < NP; p++) t += cost(p); if (t == 0) break; }
    rng = rng * 1664525u + 1013904223u;
    const int r = (rng >> 8) & 3, a = (rng >> 12) & 63, b = (rng >> 20) & 63, before = cost(a) + cost(b);
    if (r == 0) continue;
    int t = jv[r][a]; jv[r][a] = jv[r][b]; jv[r][b] = t;
    if (cost(a) + cost(b) > before) { jv[r][b] = jv[r][a]; jv[r][a] = t; }
  }
  int done[256];
  for (int p = 0; p < NP + 2; p++) {
    Sched::Pair& q = s.pair[p];
    if (p < NP) {
      for (int k = 0; k < 4; k++) q.khead[k] = (uint8_t)(korder[k] * 8 + (p >> 3));
      for (int r = 0; r < 4; r++) {
        if (jv[r][p] < 0) continue;
        q.item[q.nitems++] = (uint8_t)((r * 8 + used[r][jv[r][p]]++) * 8 + jv[r][p]);
      }
    }
    int t = p < NP ? 0 : -3, e = 1;
    for (int i = 0; i < q.nitems; i++) { t += (q.item[i] & 7) + 2; done[q.item[i]] = t + (i + 1 < q.nitems ? 2 : 0); e += 8 + 4 * ((q.item[i] & 7) + 1); }
    for (int k = 0; k < 3 * MAX_STEPS + 6; k++) {
      const int n = k > 0 ? k - (SPARE_N & 1) : 0, r = n % 7, f = (e + (r < 4 ? r : r - 1)) % 12;
      q.oent[k] = (uint8_t)((r == 4 ? 6 : f >= 6 ? f + 2 : f) ^ (((n / 7) & 1) << 3));
    }
  }
  for (int j = 0; j < 8; j++) {
    int order[NH], left[4];
    for (int h = 0; h < NH; h++) { int k = h; for (; k > 0 && done[order[k - 1] * 8 + j] < done[h * 8 + j]; k--) order[k] = order[k - 1]; order[k] = h; }
    for (int kq = 0; kq < 4; kq++) {
      left[kq] = SPARE_N == 0 ? 16 : kq < SPARE_N ? 20 - SPARE_N : 16 - SPARE_N;
      for (int nh = 0; nh < 2; nh++) { Sched::Pair& q = s.pair[kq * 16 + nh * 8 + j]; q.otask = (uint8_t)(kq * 16 + nh * 8 + j); q.nsteps = (uint8_t)((left[kq] + 1) / 2); q.ochunk[0][0] = 255; }
    }
    for (int n = 0, kq = 0, run = 0; n < 64; ) {
      if (left[kq] > 0 && run < 2) {
        const int pos = --left[kq] + (SPARE_N & 1);
        for (int nh = 0; nh < 2; nh++) s.pair[kq * 16 + nh * 8 + j].ochunk[pos >> 1][pos & 1] = (uint8_t)(order[n >> 1] * 2 + 1 - (n & 1));
        n++; run++;
      } else { kq = (kq + 1) & 3; run = 0; }
    }
  }
}

}

extern "C" void kernel_launch(void* const* d_in, const int* in_sizes, int n_in, void* d_out, int out_size) {
  (void)in_sizes; (void)n_in; (void)out_size;
  const __nv_bfloat16* x     = (const __nv_bfloat16*)d_in[0];
  const __nv_bfloat16* ckv   = (const __nv_bfloat16*)d_in[1];
  const __nv_bfloat16* w_q   = (const __nv_bfloat16*)d_in[2];
  const __nv_bfloat16* w_uk  = (const __nv_bfloat16*)d_in[3];
  const __nv_bfloat16* w_uv  = (const __nv_bfloat16*)d_in[4];
  const __nv_bfloat16* w_o   = (const __nv_bfloat16*)d_in[5];
  const __nv_bfloat16* w_r   = (const __nv_bfloat16*)d_in[7];
  const __nv_bfloat16* w_g   = (const __nv_bfloat16*)d_in[8];
  const __nv_bfloat16* w_u   = (const __nv_bfloat16*)d_in[9];
  const __nv_bfloat16* w_d   = (const __nv_bfloat16*)d_in[10];
  const __nv_bfloat16* cvec  = (const __nv_bfloat16*)d_in[11];
  const __nv_bfloat16* w_mod = (const __nv_bfloat16*)d_in[12];
  __nv_bfloat16* out = (__nv_bfloat16*)d_out;

  static HostState st;
  if (!st.ready) {
    void* fn = nullptr; cudaDriverEntryPointQueryResult qr;
    cudaGetDriverEntryPoint("cuTensorMapEncodeTiled", &fn, cudaEnableDefault, &qr);
    st.encode = (EncodeFn)fn;
    cudaFuncSetAttribute(k_fused, cudaFuncAttributeMaxDynamicSharedMemorySize, SMEM);
    build_sched(st.sched);
    void *p_kvc, *p_h1, *p_part;
    cudaGetSymbolAddress(&p_kvc, g_kvc); cudaGetSymbolAddress(&p_h1, g_h1); cudaGetSymbolAddress(&p_part, g_part);
    st.sched.kvc = (__nv_bfloat16*)p_kvc; st.sched.h1 = (__nv_bfloat16*)p_h1; st.sched.part = (__nv_bfloat16*)p_part;
    st.ready = true;
  }
  make_2d(st.encode, &st.tmC, ckv, SEQ, DM, 128);
  make_2d(st.encode, &st.tmWq, w_q, DM, NH * DH, 64);
  make_2d(st.encode, &st.tmWk, w_uk, DM, NH * DH, 64);
  make_2d(st.encode, &st.tmWv, w_uv, DM, NH * DH, 64);
  make_3d(st.encode, &st.tmWo, w_o, NH * DH, DM / 64, (size_t)DM * 2, 128);
  make_3d(st.encode, &st.tmWm, w_mod, DM, 6 * DM / 64, (size_t)6 * DM * 2, 128);
  make_3d(st.encode, &st.tmWd, w_d, FF, DM / 64, (size_t)DM * 2, 128, 16, 8);
  make_ffn(st.encode, &st.tmWg, w_g);
  make_ffn(st.encode, &st.tmWu, w_u);

  k_fused<<<NGRID, 384, SMEM, cudaStreamPerThread>>>(st.tmC, st.tmWq, st.tmWk, st.tmWv, st.tmWo, st.tmWg, st.tmWu, st.tmWd, st.tmWm, st.sched,
                                                     x, cvec, w_o, w_r, w_g, w_u, w_d, out);
}
```
